```python
import torch

def _softmax(x, axis=-1):
    return torch.softmax(x, dim=axis)

def _gelu(x):
    return torch.nn.functional.gelu(x, approximate='tanh')

def _silu(x):
    return torch.nn.functional.silu(x)

def _sigmoid(x):
    return torch.sigmoid(x)

def _layernorm(x, axis=-1, eps=1e-05):
    m = x.mean(dim=axis, keepdim=True)
    v = x.var(dim=axis, keepdim=True, unbiased=False)
    return (x - m) / torch.sqrt(v + eps)

def _scatter_add(tgt, idx, src, axis=0):
    return tgt.clone().index_add_(axis, idx, src)

def _segment_sum(src, seg, n):
    out = torch.zeros((n,) + src.shape[1:], dtype=src.dtype)
    return out.index_add_(0, seg, src)

def _pad(x, pw):
    flat = tuple((v for pair in reversed(pw) for v in pair))
    return torch.nn.functional.pad(x, flat)
kernel_name = 'interleave_layers__memory_aug_recurrent_mem_tr__ssm_conv_h3__prompt'

def setup_inputs():

    _w = lambda a: (lambda t: t.to(torch.bfloat16) if t.is_floating_point() else t)(torch.as_tensor(a))

    def _A_setup():
        B, S, Dm = (1, 2048, 640)
        H, Dh = (32, 128)
        M, seg = (8, 32)
        seg = min(seg, S)
        S = S // seg * seg
        return {'x': _w((lambda *s: torch.randn(*s, dtype=torch.bfloat16) * 0.05)(B, S, Dm)), 'mem0': _w((lambda *s: torch.randn(*s, dtype=torch.bfloat16) * 0.4)(B, M, Dm)), 'Wq': _w((lambda *s: torch.randn(*s, dtype=torch.bfloat16) * 1.6)(Dm, H, Dh) * Dm ** (-0.5)), 'Wk': _w((lambda *s: torch.randn(*s, dtype=torch.bfloat16) * 1.6)(Dm, H, Dh) * Dm ** (-0.5)), 'Wv': _w((lambda *s: torch.randn(*s, dtype=torch.bfloat16) * 0.4)(Dm, H, Dh) * Dm ** (-0.5)), 'Wo': _w((lambda *s: torch.randn(*s, dtype=torch.bfloat16) * 0.4)(H, Dh, Dm) * (H * Dh) ** (-0.5)), 'seg_len': seg}
    _A_in = _A_setup()

    def _B_setup():
        B, S, D = (1, 2048, 640)
        ks = 4
        return {'q': _w((lambda *s: torch.randn(*s, dtype=torch.bfloat16) * 0.05)(B, S, D)), 'k': _w((lambda *s: torch.randn(*s, dtype=torch.bfloat16) * 0.4)(B, S, D)), 'v': _w((lambda *s: torch.randn(*s, dtype=torch.bfloat16) * 0.4)(B, S, D)), 'shift_k': _w((lambda *s: torch.randn(*s, dtype=torch.bfloat16) * 0.4)(D, ks) * 0.5), 'ssm_k': _w((lambda *s: torch.randn(*s, dtype=torch.bfloat16) * 0.8)(D, S) * (1.0 / S ** 0.5)), 'ssm_D': _w((lambda *s: torch.randn(*s, dtype=torch.bfloat16) * 0.4)(D))}
    _B_in = _B_setup()
    return {'A_x': _A_in['x'], 'A_mem0': _A_in['mem0'], 'A_Wq': _A_in['Wq'], 'A_Wk': _A_in['Wk'], 'A_Wv': _A_in['Wv'], 'A_Wo': _A_in['Wo'], 'A_seg_len': _A_in['seg_len'], 'B_q': _B_in['q'], 'B_k': _B_in['k'], 'B_v': _B_in['v'], 'B_shift_k': _B_in['shift_k'], 'B_ssm_k': _B_in['ssm_k'], 'B_ssm_D': _B_in['ssm_D']}

def reference(A_x, A_mem0, A_Wq, A_Wk, A_Wv, A_Wo, A_seg_len, B_q, B_k, B_v, B_shift_k, B_ssm_k, B_ssm_D):

    def _A_ref(x, mem0, Wq, Wk, Wv, Wo, seg_len):
        B, S, Dm = x.shape
        H, Dh = (Wq.shape[1], Wq.shape[2])
        M = mem0.shape[1]
        scale = Dh ** (-0.5)
        n_seg = S // seg_len
        L = M + seg_len
        idx = torch.arange(L)
        mask = (idx[:, None] < M) | (idx[:, None] >= idx[None, :])
        mem = mem0
        outs = []
        for s in range(n_seg):
            xs = x[:, s * seg_len:(s + 1) * seg_len, :].clone()
            h = torch.concatenate([mem, xs], axis=1)
            q = torch.einsum('btd,dhe->bhte', h, Wq)
            k = torch.einsum('btd,dhe->bhte', h, Wk)
            v = torch.einsum('btd,dhe->bhte', h, Wv)
            scores = torch.einsum('bhqe,bhke->bhqk', q, k) * scale
            scores = torch.where(mask[None, None], scores, -1000000000.0)
            p = _softmax(scores, axis=-1)
            o = torch.einsum('bhqk,bhke->bhqe', p, v)
            o = torch.einsum('bhte,hed->btd', o, Wo)
            mem = o[:, :M, :].clone()
            outs.append(o[:, M:, :])
        return torch.concatenate(outs, axis=1)

    def _B_ref(q, k, v, shift_k, ssm_k, ssm_D):
        B, S, D = q.shape
        ks = shift_k.shape[-1]
        k_pad = _pad(k, ((0, 0), (ks - 1, 0), (0, 0)))
        k_shift = torch.zeros_like(k)
        for t in range(ks):
            k_shift = k_shift + k_pad[:, t:t + S, :] * shift_k[:, ks - 1 - t][None, None, :]
        kv = k_shift * v
        L = 2 * S
        kv_pad = _pad(kv, ((0, 0), (0, S), (0, 0)))
        kf_pad = _pad(ssm_k, ((0, 0), (0, S)))
        kv_f = (lambda x, axes=(-2, -1): torch.fft.rfft2(x.float(), dim=axes))(kv_pad[:, None, :, :], axes=(1, 2))
        kf_f = (lambda x, axes=(-2, -1): torch.fft.rfft2(x.float(), dim=axes))(kf_pad[:, None, :], axes=(1, 2))
        kf_f = (lambda x, *d: x.permute(*d))(kf_f, 1, 2, 0)
        y_f = kv_f * kf_f[None, :, :, :]
        y = (lambda x, s, axes=(-2, -1): torch.fft.irfft2(x, s=s, dim=axes).to(torch.bfloat16))(y_f, (1, L), axes=(1, 2))[:, 0, :S, :]
        y = y + kv * ssm_D[None, None, :]
        return q * y
    x = A_x
    x = x + _A_ref(_layernorm(x, axis=-1), A_mem0, A_Wq, A_Wk, A_Wv, A_Wo, A_seg_len)
    x = x + _B_ref(_layernorm(x, axis=-1), B_k, B_v, B_shift_k, B_ssm_k, B_ssm_D)
    x = x + _A_ref(_layernorm(x, axis=-1), A_mem0, A_Wq, A_Wk, A_Wv, A_Wo, A_seg_len)
    x = x + _B_ref(_layernorm(x, axis=-1), B_k, B_v, B_shift_k, B_ssm_k, B_ssm_D)
    return x
```

```cpp
#include <cuda_runtime.h>
#include <cuda_bf16.h>
#include <stdint.h>
#include <cuda.h>

typedef __nv_bfloat16 bf16;
namespace ws {
constexpr int S_LEN = 2048, DM = 640, NH = 32, DH = 128, HD = NH * DH, SEG = 32, NSEG = S_LEN / SEG;

__device__ __forceinline__ float bf2f(bf16 v) { return __bfloat162float(v); }
__device__ __forceinline__ float rbf(float v) { return __bfloat162float(__float2bfloat16_rn(v)); }
__device__ __forceinline__ uint32_t pack2(float a, float b) {
    __nv_bfloat162 t = __floats2bfloat162_rn(a, b);
    return *reinterpret_cast<uint32_t*>(&t);
}
__device__ __forceinline__ float blo(uint32_t v) { return __uint_as_float(v << 16); }
__device__ __forceinline__ float bhi(uint32_t v) { return __uint_as_float(v & 0xffff0000u); }
__device__ __forceinline__ uint32_t badd(uint32_t a, uint32_t b) { uint32_t r; asm("add.rn.bf16x2 %0, %1, %2;" : "=r"(r) : "r"(a), "r"(b)); return r; }
__device__ __forceinline__ uint32_t smem_u32(const void* p) { return (uint32_t)__cvta_generic_to_shared(p); }
__device__ __forceinline__ uint4 ldsm4(uint32_t a) {
    uint4 v;
    asm volatile("ldmatrix.sync.aligned.m8n8.x4.shared.b16 {%0,%1,%2,%3}, [%4];" : "=r"(v.x), "=r"(v.y), "=r"(v.z), "=r"(v.w) : "r"(a));
    return v;
}
__device__ __forceinline__ uint4 ldsm4t(uint32_t a) {
    uint4 v;
    asm volatile("ldmatrix.sync.aligned.m8n8.x4.trans.shared.b16 {%0,%1,%2,%3}, [%4];" : "=r"(v.x), "=r"(v.y), "=r"(v.z), "=r"(v.w) : "r"(a));
    return v;
}
__device__ __forceinline__ uint2 ldsm2t(uint32_t a) {
    uint2 v;
    asm volatile("ldmatrix.sync.aligned.m8n8.x2.trans.shared.b16 {%0,%1}, [%2];" : "=r"(v.x), "=r"(v.y) : "r"(a));
    return v;
}
__device__ __forceinline__ void stsm4(uint32_t a, uint32_t r0, uint32_t r1, uint32_t r2, uint32_t r3) {
    asm volatile("stmatrix.sync.aligned.m8n8.x4.shared.b16 [%0], {%1,%2,%3,%4};" ::"r"(a), "r"(r0), "r"(r1), "r"(r2), "r"(r3) : "memory");
}
__device__ __forceinline__ void stsm2(uint32_t a, uint32_t r0, uint32_t r1) {
    asm volatile("stmatrix.sync.aligned.m8n8.x2.shared.b16 [%0], {%1,%2};" ::"r"(a), "r"(r0), "r"(r1) : "memory");
}
__device__ __forceinline__ void stsm4t(uint32_t a, uint32_t r0, uint32_t r1, uint32_t r2, uint32_t r3) {
    asm volatile("stmatrix.sync.aligned.m8n8.x4.trans.shared.b16 [%0], {%1,%2,%3,%4};" ::"r"(a), "r"(r0), "r"(r1), "r"(r2), "r"(r3) : "memory");
}
__device__ __forceinline__ void mma16816(float* c, uint32_t a0, uint32_t a1, uint32_t a2, uint32_t a3, uint32_t b0, uint32_t b1) {
    asm("mma.sync.aligned.m16n8k16.row.col.f32.bf16.bf16.f32 {%0,%1,%2,%3}, {%4,%5,%6,%7}, {%8,%9}, {%0,%1,%2,%3};"
        : "+f"(c[0]), "+f"(c[1]), "+f"(c[2]), "+f"(c[3]) : "r"(a0), "r"(a1), "r"(a2), "r"(a3), "r"(b0), "r"(b1));
}
__device__ __forceinline__ void mmav(float* c, uint32_t a0, uint32_t a1, uint32_t a2, uint32_t a3, uint32_t b0, uint32_t b1) {
    asm volatile("mma.sync.aligned.m16n8k16.row.col.f32.bf16.bf16.f32 {%0,%1,%2,%3}, {%4,%5,%6,%7}, {%8,%9}, {%0,%1,%2,%3};"
        : "+f"(c[0]), "+f"(c[1]), "+f"(c[2]), "+f"(c[3]) : "r"(a0), "r"(a1), "r"(a2), "r"(a3), "r"(b0), "r"(b1));
}
__device__ __forceinline__ void mmau(float* c, const uint4& a, uint32_t b0, uint32_t b1) { mma16816(c, a.x, a.y, a.z, a.w, b0, b1); }
__device__ __forceinline__ void mma1688(float* c, uint32_t a0, uint32_t a1, uint32_t b0) {
    asm("mma.sync.aligned.m16n8k8.row.col.f32.bf16.bf16.f32 {%0,%1,%2,%3}, {%4,%5}, {%6}, {%0,%1,%2,%3};"
        : "+f"(c[0]), "+f"(c[1]), "+f"(c[2]), "+f"(c[3]) : "r"(a0), "r"(a1), "r"(b0));
}
__device__ __forceinline__ void mmav8(float* c, uint32_t a0, uint32_t a1, uint32_t b0) {
    asm volatile("mma.sync.aligned.m16n8k8.row.col.f32.bf16.bf16.f32 {%0,%1,%2,%3}, {%4,%5}, {%6}, {%0,%1,%2,%3};"
        : "+f"(c[0]), "+f"(c[1]), "+f"(c[2]), "+f"(c[3]) : "r"(a0), "r"(a1), "r"(b0));
}
__device__ __forceinline__ void cp_async16(uint32_t dst, const void* src) { asm volatile("cp.async.cg.shared.global [%0], [%1], 16;" ::"r"(dst), "l"(src)); }
__device__ __forceinline__ void cp_commit() { asm volatile("cp.async.commit_group;"); }
template <int N> __device__ __forceinline__ void cp_wait() { asm volatile("cp.async.wait_group %0;" ::"n"(N)); }
__device__ __forceinline__ uint4 lds128(uint32_t a) {
    uint4 v;
    asm volatile("ld.shared.v4.u32 {%0,%1,%2,%3}, [%4];" : "=r"(v.x), "=r"(v.y), "=r"(v.z), "=r"(v.w) : "r"(a));
    return v;
}
__device__ __forceinline__ uint2 lds64(uint32_t a) {
    uint2 v;
    asm volatile("ld.shared.v2.u32 {%0,%1}, [%2];" : "=r"(v.x), "=r"(v.y) : "r"(a));
    return v;
}
__device__ __forceinline__ uint32_t lds32(uint32_t a) { uint32_t v; asm volatile("ld.shared.u32 %0, [%1];" : "=r"(v) : "r"(a)); return v; }
__device__ __forceinline__ void sts32(uint32_t a, uint32_t x) { asm volatile("st.shared.u32 [%0], %1;" ::"r"(a), "r"(x) : "memory"); }
__device__ __forceinline__ void sts128(uint32_t a, uint32_t x, uint32_t y, uint32_t z, uint32_t w) {
    asm volatile("st.shared.v4.u32 [%0], {%1,%2,%3,%4};" ::"r"(a), "r"(x), "r"(y), "r"(z), "r"(w) : "memory");
}
__device__ __forceinline__ uint4 ld_relaxed_v4(const void* p) {
    uint4 v;
    asm volatile("ld.relaxed.gpu.global.v4.u32 {%0,%1,%2,%3}, [%4];" : "=r"(v.x), "=r"(v.y), "=r"(v.z), "=r"(v.w) : "l"(p) : "memory");
    return v;
}
__device__ __forceinline__ uint2 ld_relaxed_v2(const void* p) {
    uint2 v;
    asm volatile("ld.relaxed.gpu.global.v2.u32 {%0,%1}, [%2];" : "=r"(v.x), "=r"(v.y) : "l"(p) : "memory");
    return v;
}
__device__ __forceinline__ void st_relaxed_v4(void* p, uint32_t a, uint32_t b, uint32_t c, uint32_t d) {
    asm volatile("st.relaxed.gpu.global.v4.u32 [%0], {%1,%2,%3,%4};" ::"l"(p), "r"(a), "r"(b), "r"(c), "r"(d) : "memory");
}
__device__ __forceinline__ void st_relaxed_v2(void* p, uint32_t a, uint32_t b) {
    asm volatile("st.relaxed.gpu.global.v2.u32 [%0], {%1,%2};" ::"l"(p), "r"(a), "r"(b) : "memory");
}
__device__ __forceinline__ int ld_relaxed(const int* p) {
    int v;
    asm volatile("ld.relaxed.gpu.global.u32 %0, [%1];" : "=r"(v) : "l"(p) : "memory");
    return v;
}
__device__ __forceinline__ int ld_acquire(const int* p) {
    int v;
    asm volatile("ld.acquire.gpu.global.u32 %0, [%1];" : "=r"(v) : "l"(p) : "memory");
    return v;
}
__device__ __forceinline__ void red_release(int* p, int v) { asm volatile("red.release.gpu.global.add.u32 [%0], %1;" ::"l"(p), "r"(v) : "memory"); }
__device__ __forceinline__ void mbar_init(uint32_t bar, int count) { asm volatile("mbarrier.init.shared::cta.b64 [%0], %1;" ::"r"(bar), "r"(count)); }
__device__ __forceinline__ void mbar_expect_tx(uint32_t bar, uint32_t bytes) {
    asm volatile("mbarrier.arrive.expect_tx.shared::cta.b64 _, [%0], %1;" ::"r"(bar), "r"(bytes) : "memory");
}
__device__ __forceinline__ void mbar_arrive(uint32_t bar) { asm volatile("mbarrier.arrive.shared::cta.b64 _, [%0];" ::"r"(bar) : "memory"); }
__device__ __forceinline__ void mbar_arrive_cluster(uint32_t bar) { asm volatile("mbarrier.arrive.shared::cluster.b64 _, [%0];" ::"r"(bar) : "memory"); }
__device__ __forceinline__ void mwait(uint32_t bar, uint32_t parity) {
    asm volatile(
        "{\n.reg .pred P1;\n.reg .u32 cnt;\n"
        "mbarrier.try_wait.parity.shared::cta.b64 P1, [%0], %1;\n"
        "@P1 bra DONE;\n"
        "mov.u32 cnt, 0;\n"
        "LAB_WAIT:\n"
        "mbarrier.try_wait.parity.shared::cta.b64 P1, [%0], %1;\n"
        "@P1 bra DONE;\n"
        "add.u32 cnt, cnt, 1;\n"
        "setp.lt.u32 P1, cnt, 1000000;\n"
        "@P1 bra LAB_WAIT;\n"
        "trap;\n"
        "DONE:\n}\n" ::"r"(bar), "r"(parity) : "memory");
}
__device__ __forceinline__ uint32_t mtest(uint32_t bar, uint32_t parity) {
    uint32_t ok;
    asm volatile("{\n.reg .pred P1;\nmbarrier.test_wait.parity.shared::cta.b64 P1, [%1], %2;\nselp.u32 %0, 1, 0, P1;\n}\n" : "=r"(ok) : "r"(bar), "r"(parity) : "memory");
    return ok;
}
__device__ __forceinline__ uint32_t mapa(uint32_t addr, uint32_t rank) {
    uint32_t r;
    asm("mapa.shared::cluster.u32 %0, %1, %2;" : "=r"(r) : "r"(addr), "r"(rank));
    return r;
}
__device__ __forceinline__ void st_async_b32(uint32_t addr, uint32_t a, uint32_t bar) {
    asm volatile("st.async.weak.shared::cluster.mbarrier::complete_tx::bytes.b32 [%0], %1, [%2];" ::"r"(addr), "r"(a), "r"(bar) : "memory");
}
__device__ __forceinline__ void st_async_v2(uint32_t addr, uint32_t a, uint32_t b, uint32_t bar) {
    asm volatile("st.async.weak.shared::cluster.mbarrier::complete_tx::bytes.v2.b32 [%0], {%1,%2}, [%3];" ::"r"(addr), "r"(a), "r"(b), "r"(bar) : "memory");
}
__device__ __forceinline__ void st_async_v2_lt(uint32_t addr, uint32_t a, uint32_t b, uint32_t bar, uint32_t x, uint32_t lim) {
    asm volatile("{\n.reg .pred p;\nsetp.lt.u32 p, %4, %5;\n@p st.async.weak.shared::cluster.mbarrier::complete_tx::bytes.v2.b32 [%0], {%1,%2}, [%3];\n}"
                 ::"r"(addr), "r"(a), "r"(b), "r"(bar), "r"(x), "r"(lim) : "memory");
}
__device__ __forceinline__ void st_async_v4(uint32_t addr, uint32_t a, uint32_t b, uint32_t c, uint32_t d, uint32_t bar) {
    asm volatile("st.async.weak.shared::cluster.mbarrier::complete_tx::bytes.v4.b32 [%0], {%1,%2,%3,%4}, [%5];" ::"r"(addr), "r"(a), "r"(b), "r"(c), "r"(d), "r"(bar) : "memory");
}
__device__ __forceinline__ void cluster_arrive() { asm volatile("barrier.cluster.arrive.release.aligned;" ::: "memory"); }
__device__ __forceinline__ void cluster_wait() { asm volatile("barrier.cluster.wait.acquire.aligned;" ::: "memory"); }
__device__ __forceinline__ void named_bar(int id, int n) { asm volatile("bar.sync %0, %1;" ::"r"(id), "r"(n) : "memory"); }
__device__ __forceinline__ void named_arrive(int id, int n) { asm volatile("bar.arrive %0, %1;" ::"r"(id), "r"(n) : "memory"); }
__device__ __forceinline__ void fence_async_smem() { asm volatile("fence.proxy.async.shared::cta;" ::: "memory"); }
__device__ __forceinline__ void fence_async_global() { asm volatile("fence.proxy.async.global;" ::: "memory"); }
__device__ __forceinline__ void wg_fence() { asm volatile("wgmma.fence.sync.aligned;" ::: "memory"); }
__device__ __forceinline__ void wg_commit() { asm volatile("wgmma.commit_group.sync.aligned;" ::: "memory"); }
template <int N> __device__ __forceinline__ void wg_wait() { asm volatile("wgmma.wait_group.sync.aligned %0;" ::"n"(N) : "memory"); }
__device__ __forceinline__ uint64_t ndesc(uint32_t addr, uint32_t lbo, uint32_t sbo) {
    return (uint64_t)((addr & 0x3FFFF) >> 4) | ((uint64_t)(lbo >> 4) << 16) | ((uint64_t)(sbo >> 4) << 32);
}
__device__ __forceinline__ float ex2f(float x) { float y; asm("ex2.approx.ftz.f32 %0, %1;" : "=f"(y) : "f"(x)); return y; }
__device__ __forceinline__ float rcpf(float x) { float y; asm("rcp.approx.ftz.f32 %0, %1;" : "=f"(y) : "f"(x)); return y; }
__device__ __forceinline__ uint32_t clk32() { uint32_t c; asm volatile("mov.u32 %0, %clock;" : "=r"(c)); return c; }
__device__ __forceinline__ uint32_t opq(uint32_t x) { uint32_t y; asm volatile("mov.u32 %0, %1;" : "=r"(y) : "r"(x)); return y; }
__device__ __forceinline__ uint32_t rem(uint32_t addr, uint32_t rank) { return mapa(addr, rank); }
__device__ __forceinline__ uint64_t mkdesc(uint32_t lo, uint32_t hi) { uint64_t d; asm("mov.b64 %0, {%1,%2};" : "=l"(d) : "r"(lo), "r"(hi)); return d; }
__device__ __forceinline__ void delay(uint32_t n) { const uint32_t t0 = clk32(); while (__any_sync(0xffffffffu, clk32() - t0 < n)) {} }
#define UNI(x) __shfl_sync(0xffffffffu, (uint32_t)(x), 0)
__device__ __forceinline__ void wg_n16t(float* d, uint32_t a0, uint32_t a1, uint32_t a2, uint32_t a3, uint64_t db) {
    asm volatile("wgmma.mma_async.sync.aligned.m64n16k16.f32.bf16.bf16 {%0, %1, %2, %3, %4, %5, %6, %7}, {%8, %9, %10, %11}, %12, 1, 1, 1, 1;"
                 : "+f"(d[0]), "+f"(d[1]), "+f"(d[2]), "+f"(d[3]), "+f"(d[4]), "+f"(d[5]), "+f"(d[6]), "+f"(d[7]) : "r"(a0), "r"(a1), "r"(a2), "r"(a3), "l"(db));
}
__device__ __forceinline__ void wg_n16t_first(float* d, uint32_t a0, uint32_t a1, uint32_t a2, uint32_t a3, uint64_t db) {
    asm volatile("wgmma.mma_async.sync.aligned.m64n16k16.f32.bf16.bf16 {%0, %1, %2, %3, %4, %5, %6, %7}, {%8, %9, %10, %11}, %12, 0, 1, 1, 1;"
                 : "=f"(d[0]), "=f"(d[1]), "=f"(d[2]), "=f"(d[3]), "=f"(d[4]), "=f"(d[5]), "=f"(d[6]), "=f"(d[7]) : "r"(a0), "r"(a1), "r"(a2), "r"(a3), "l"(db));
}
__device__ __forceinline__ void wg_n32(float* d, uint32_t a0, uint32_t a1, uint32_t a2, uint32_t a3, uint64_t db) {
    asm volatile("wgmma.mma_async.sync.aligned.m64n32k16.f32.bf16.bf16 {%0, %1, %2, %3, %4, %5, %6, %7, %8, %9, %10, %11, %12, %13, %14, %15}, {%16, %17, %18, %19}, %20, 1, 1, 1, 0;"
                 : "+f"(d[0]), "+f"(d[1]), "+f"(d[2]), "+f"(d[3]), "+f"(d[4]), "+f"(d[5]), "+f"(d[6]), "+f"(d[7]), "+f"(d[8]), "+f"(d[9]), "+f"(d[10]), "+f"(d[11]), "+f"(d[12]), "+f"(d[13]), "+f"(d[14]), "+f"(d[15]) : "r"(a0), "r"(a1), "r"(a2), "r"(a3), "l"(db));
}
__device__ __forceinline__ void wg_n32_first(float* d, uint32_t a0, uint32_t a1, uint32_t a2, uint32_t a3, uint64_t db) {
    asm volatile("wgmma.mma_async.sync.aligned.m64n32k16.f32.bf16.bf16 {%0, %1, %2, %3, %4, %5, %6, %7, %8, %9, %10, %11, %12, %13, %14, %15}, {%16, %17, %18, %19}, %20, 0, 1, 1, 0;"
                 : "=f"(d[0]), "=f"(d[1]), "=f"(d[2]), "=f"(d[3]), "=f"(d[4]), "=f"(d[5]), "=f"(d[6]), "=f"(d[7]), "=f"(d[8]), "=f"(d[9]), "=f"(d[10]), "=f"(d[11]), "=f"(d[12]), "=f"(d[13]), "=f"(d[14]), "=f"(d[15]) : "r"(a0), "r"(a1), "r"(a2), "r"(a3), "l"(db));
}

__device__ __forceinline__ void wg_n16t_sfirst(float* d, uint64_t da, uint64_t db) {
    asm volatile("wgmma.mma_async.sync.aligned.m64n16k16.f32.bf16.bf16 {%0, %1, %2, %3, %4, %5, %6, %7}, %8, %9, 0, 1, 1, 1, 1;"
                 : "=f"(d[0]), "=f"(d[1]), "=f"(d[2]), "=f"(d[3]), "=f"(d[4]), "=f"(d[5]), "=f"(d[6]), "=f"(d[7]) : "l"(da), "l"(db));
}
__device__ __forceinline__ void wg_n32_sfirst(float* d, uint64_t da, uint64_t db) {
    asm volatile("wgmma.mma_async.sync.aligned.m64n32k16.f32.bf16.bf16 {%0, %1, %2, %3, %4, %5, %6, %7, %8, %9, %10, %11, %12, %13, %14, %15}, %16, %17, 0, 1, 1, 1, 0;"
                 : "=f"(d[0]), "=f"(d[1]), "=f"(d[2]), "=f"(d[3]), "=f"(d[4]), "=f"(d[5]), "=f"(d[6]), "=f"(d[7]), "=f"(d[8]), "=f"(d[9]), "=f"(d[10]), "=f"(d[11]), "=f"(d[12]), "=f"(d[13]), "=f"(d[14]), "=f"(d[15]) : "l"(da), "l"(db));
}

__device__ __forceinline__ void wg_n16t_s(float* d, uint64_t da, uint64_t db) {
    asm volatile("wgmma.mma_async.sync.aligned.m64n16k16.f32.bf16.bf16 {%0, %1, %2, %3, %4, %5, %6, %7}, %8, %9, 1, 1, 1, 1, 1;"
                 : "+f"(d[0]), "+f"(d[1]), "+f"(d[2]), "+f"(d[3]), "+f"(d[4]), "+f"(d[5]), "+f"(d[6]), "+f"(d[7]) : "l"(da), "l"(db));
}
__device__ __forceinline__ void wg_n64_sfirst(float* d, uint64_t da, uint64_t db) {
    asm volatile("wgmma.mma_async.sync.aligned.m64n64k16.f32.bf16.bf16 {%0, %1, %2, %3, %4, %5, %6, %7, %8, %9, %10, %11, %12, %13, %14, %15, %16, %17, %18, %19, %20, %21, %22, %23, %24, %25, %26, %27, %28, %29, %30, %31}, %32, %33, 0, 1, 1, 1, 0;"
                 : "=f"(d[0]), "=f"(d[1]), "=f"(d[2]), "=f"(d[3]), "=f"(d[4]), "=f"(d[5]), "=f"(d[6]), "=f"(d[7]), "=f"(d[8]), "=f"(d[9]), "=f"(d[10]), "=f"(d[11]), "=f"(d[12]), "=f"(d[13]), "=f"(d[14]), "=f"(d[15]), "=f"(d[16]), "=f"(d[17]), "=f"(d[18]), "=f"(d[19]), "=f"(d[20]), "=f"(d[21]), "=f"(d[22]), "=f"(d[23]), "=f"(d[24]), "=f"(d[25]), "=f"(d[26]), "=f"(d[27]), "=f"(d[28]), "=f"(d[29]), "=f"(d[30]), "=f"(d[31]) : "l"(da), "l"(db));
}
__device__ __forceinline__ void wg_n64_s(float* d, uint64_t da, uint64_t db) {
    asm volatile("wgmma.mma_async.sync.aligned.m64n64k16.f32.bf16.bf16 {%0, %1, %2, %3, %4, %5, %6, %7, %8, %9, %10, %11, %12, %13, %14, %15, %16, %17, %18, %19, %20, %21, %22, %23, %24, %25, %26, %27, %28, %29, %30, %31}, %32, %33, 1, 1, 1, 1, 0;"
                 : "+f"(d[0]), "+f"(d[1]), "+f"(d[2]), "+f"(d[3]), "+f"(d[4]), "+f"(d[5]), "+f"(d[6]), "+f"(d[7]), "+f"(d[8]), "+f"(d[9]), "+f"(d[10]), "+f"(d[11]), "+f"(d[12]), "+f"(d[13]), "+f"(d[14]), "+f"(d[15]), "+f"(d[16]), "+f"(d[17]), "+f"(d[18]), "+f"(d[19]), "+f"(d[20]), "+f"(d[21]), "+f"(d[22]), "+f"(d[23]), "+f"(d[24]), "+f"(d[25]), "+f"(d[26]), "+f"(d[27]), "+f"(d[28]), "+f"(d[29]), "+f"(d[30]), "+f"(d[31]) : "l"(da), "l"(db));
}
__device__ __forceinline__ void wg_n64(float* d, uint32_t a0, uint32_t a1, uint32_t a2, uint32_t a3, uint64_t db) {
    asm volatile("wgmma.mma_async.sync.aligned.m64n64k16.f32.bf16.bf16 {%0, %1, %2, %3, %4, %5, %6, %7, %8, %9, %10, %11, %12, %13, %14, %15, %16, %17, %18, %19, %20, %21, %22, %23, %24, %25, %26, %27, %28, %29, %30, %31}, {%32, %33, %34, %35}, %36, 1, 1, 1, 0;"
                 : "+f"(d[0]), "+f"(d[1]), "+f"(d[2]), "+f"(d[3]), "+f"(d[4]), "+f"(d[5]), "+f"(d[6]), "+f"(d[7]), "+f"(d[8]), "+f"(d[9]), "+f"(d[10]), "+f"(d[11]), "+f"(d[12]), "+f"(d[13]), "+f"(d[14]), "+f"(d[15]), "+f"(d[16]), "+f"(d[17]), "+f"(d[18]), "+f"(d[19]), "+f"(d[20]), "+f"(d[21]), "+f"(d[22]), "+f"(d[23]), "+f"(d[24]), "+f"(d[25]), "+f"(d[26]), "+f"(d[27]), "+f"(d[28]), "+f"(d[29]), "+f"(d[30]), "+f"(d[31]) : "r"(a0), "r"(a1), "r"(a2), "r"(a3), "l"(db));
}
__device__ __forceinline__ void wg_n64_first(float* d, uint32_t a0, uint32_t a1, uint32_t a2, uint32_t a3, uint64_t db) {
    asm volatile("wgmma.mma_async.sync.aligned.m64n64k16.f32.bf16.bf16 {%0, %1, %2, %3, %4, %5, %6, %7, %8, %9, %10, %11, %12, %13, %14, %15, %16, %17, %18, %19, %20, %21, %22, %23, %24, %25, %26, %27, %28, %29, %30, %31}, {%32, %33, %34, %35}, %36, 0, 1, 1, 0;"
                 : "=f"(d[0]), "=f"(d[1]), "=f"(d[2]), "=f"(d[3]), "=f"(d[4]), "=f"(d[5]), "=f"(d[6]), "=f"(d[7]), "=f"(d[8]), "=f"(d[9]), "=f"(d[10]), "=f"(d[11]), "=f"(d[12]), "=f"(d[13]), "=f"(d[14]), "=f"(d[15]), "=f"(d[16]), "=f"(d[17]), "=f"(d[18]), "=f"(d[19]), "=f"(d[20]), "=f"(d[21]), "=f"(d[22]), "=f"(d[23]), "=f"(d[24]), "=f"(d[25]), "=f"(d[26]), "=f"(d[27]), "=f"(d[28]), "=f"(d[29]), "=f"(d[30]), "=f"(d[31]) : "r"(a0), "r"(a1), "r"(a2), "r"(a3), "l"(db));
}

__device__ __forceinline__ void wg_n32t(float* d, uint32_t a0, uint32_t a1, uint32_t a2, uint32_t a3, uint64_t db) {
    asm volatile("wgmma.mma_async.sync.aligned.m64n32k16.f32.bf16.bf16 {%0, %1, %2, %3, %4, %5, %6, %7, %8, %9, %10, %11, %12, %13, %14, %15}, {%16, %17, %18, %19}, %20, 1, 1, 1, 1;"
                 : "+f"(d[0]), "+f"(d[1]), "+f"(d[2]), "+f"(d[3]), "+f"(d[4]), "+f"(d[5]), "+f"(d[6]), "+f"(d[7]), "+f"(d[8]), "+f"(d[9]), "+f"(d[10]), "+f"(d[11]), "+f"(d[12]), "+f"(d[13]), "+f"(d[14]), "+f"(d[15]) : "r"(a0), "r"(a1), "r"(a2), "r"(a3), "l"(db));
}
__device__ __forceinline__ void wg_n32t_first(float* d, uint32_t a0, uint32_t a1, uint32_t a2, uint32_t a3, uint64_t db) {
    asm volatile("wgmma.mma_async.sync.aligned.m64n32k16.f32.bf16.bf16 {%0, %1, %2, %3, %4, %5, %6, %7, %8, %9, %10, %11, %12, %13, %14, %15}, {%16, %17, %18, %19}, %20, 0, 1, 1, 1;"
                 : "=f"(d[0]), "=f"(d[1]), "=f"(d[2]), "=f"(d[3]), "=f"(d[4]), "=f"(d[5]), "=f"(d[6]), "=f"(d[7]), "=f"(d[8]), "=f"(d[9]), "=f"(d[10]), "=f"(d[11]), "=f"(d[12]), "=f"(d[13]), "=f"(d[14]), "=f"(d[15]) : "r"(a0), "r"(a1), "r"(a2), "r"(a3), "l"(db));
}
__device__ __forceinline__ void wg_n32t_sfirst(float* d, uint64_t da, uint64_t db) {
    asm volatile("wgmma.mma_async.sync.aligned.m64n32k16.f32.bf16.bf16 {%0, %1, %2, %3, %4, %5, %6, %7, %8, %9, %10, %11, %12, %13, %14, %15}, %16, %17, 0, 1, 1, 1, 1;"
                 : "=f"(d[0]), "=f"(d[1]), "=f"(d[2]), "=f"(d[3]), "=f"(d[4]), "=f"(d[5]), "=f"(d[6]), "=f"(d[7]), "=f"(d[8]), "=f"(d[9]), "=f"(d[10]), "=f"(d[11]), "=f"(d[12]), "=f"(d[13]), "=f"(d[14]), "=f"(d[15]) : "l"(da), "l"(db));
}
__device__ __forceinline__ void wg_n32t_s(float* d, uint64_t da, uint64_t db) {
    asm volatile("wgmma.mma_async.sync.aligned.m64n32k16.f32.bf16.bf16 {%0, %1, %2, %3, %4, %5, %6, %7, %8, %9, %10, %11, %12, %13, %14, %15}, %16, %17, 1, 1, 1, 1, 1;"
                 : "+f"(d[0]), "+f"(d[1]), "+f"(d[2]), "+f"(d[3]), "+f"(d[4]), "+f"(d[5]), "+f"(d[6]), "+f"(d[7]), "+f"(d[8]), "+f"(d[9]), "+f"(d[10]), "+f"(d[11]), "+f"(d[12]), "+f"(d[13]), "+f"(d[14]), "+f"(d[15]) : "l"(da), "l"(db));
}

}

namespace ws {
#define LAGT 4
constexpr int LAG = LAGT, NT = NSEG + LAG, NCL = 7;
#define P1A 26
#define P1C 22
#define XD 300
#define TPV_PAUSE 1
#define OT_LATE 1
#define H1_LATE 1
#define O_BULK 0
#define O_DLY 0
#define BP 0
#define REG_G 200
#define REG_T 72
#define REG_X 40
#define PDA 8
#define PDC 8
template <int V> struct IC { static constexpr int value = V; };
#define HBYTES 5120
#define POST_NS 40
#define OP_NS 40
#define LN0_AHEAD 8
constexpr int XRS = ((NT - 2) % 3 == 0) ? 4 : 3;
constexpr int O_H = 0, O_MEM = 81920, O_RED = 102400, O_BAR = 108800, O_TAB = O_BAR + 192, O_BT = O_TAB + 128, O_TR = 109312, O_X = O_TR + 2048;
constexpr int O_QRY = O_X, O_KEY = O_X + 10240, O_OBA = O_KEY + 10240, O_ST = O_OBA + 4096;
constexpr int O_VT = O_X, O_VM = O_VT + 32768, O_SM = O_VM + 4096, O_PB = O_SM + 3072;
constexpr int O_AS = 228352, O_WO = O_AS - 65536, HEAD_SMEM = O_AS + 4096, O_STG = 40960;
static_assert(O_ST + 2048 <= O_WO && O_PB + 10240 <= O_WO && O_AS % 1024 == 0 && O_STG + 163840 <= O_AS && HEAD_SMEM <= 232448, "smem");
constexpr int B_MEM = 0, B_RED = 64, B_SM = 88, B_ST = 96, B_OB = 104, B_HF = 112, B_HE = 128, B_OTF = 144, B_OTE = 160;

constexpr int F_H = 0, F_O = 128, F_P = 256, F_U = 384, F_CV = 388, NFLAG = 392;
__device__ int g_flags[NFLAG * 8];
#define FLG(i) (g_flags + (i) * 8)
__device__ uint4 g_ht[2 * NSEG * 2560];
__device__ uint4 g_ot[2 * NSEG * 256 * 64];
__device__ uint4 g_pt[2 * NSEG * 4 * 2560];
__device__ uint4 g_Y[80 * S_LEN];
__device__ uint4 g_U[DM * S_LEN / 8];
__device__ bf16 g_x[S_LEN * DM];
__device__ uint4 g_xc[4 * 16 * 3 * 8 * 32];
#define TS(i)
#define TV(i, v)

}

namespace ws {
__device__ __forceinline__ uint32_t bmul2(uint32_t a, uint32_t b) { uint32_t r; asm("mul.rn.bf16x2 %0, %1, %2;" : "=r"(r) : "r"(a), "r"(b)); return r; }
__device__ __forceinline__ void flag_wait(const int* f, int tgt, int ns) {
    int guard = 0;
    while (ld_acquire(f) < tgt) { if (++guard > 4000000) __trap(); __nanosleep(ns); }
}
template <int STRIDE> __device__ __forceinline__ void ld5(uint32_t* w, const void* p) {
#pragma unroll
    for (int r = 0; r < 5; r++) { const uint2 v = __ldcg(reinterpret_cast<const uint2*>(reinterpret_cast<const char*>(p) + r * STRIDE)); w[2 * r] = v.x; w[2 * r + 1] = v.y; }
}
template <int STRIDE> __device__ __forceinline__ void st5(void* p, const uint32_t* w) {
#pragma unroll
    for (int r = 0; r < 5; r++) *reinterpret_cast<uint2*>(reinterpret_cast<char*>(p) + r * STRIDE) = make_uint2(w[2 * r], w[2 * r + 1]);
}
__device__ __forceinline__ void ln_row(const uint32_t* x, uint32_t* y) {
    float s = 0.f;
#pragma unroll
    for (int i = 0; i < 10; i++) s += blo(x[i]) + bhi(x[i]);
#pragma unroll
    for (int o = 16; o > 0; o >>= 1) s += __shfl_xor_sync(0xffffffffu, s, o);
    const float mean = s * (1.0f / DM);
    float q = 0.f;
#pragma unroll
    for (int i = 0; i < 10; i++) { const float d0 = blo(x[i]) - mean, d1 = bhi(x[i]) - mean; q = fmaf(d0, d0, q); q = fmaf(d1, d1, q); }
#pragma unroll
    for (int o = 16; o > 0; o >>= 1) q += __shfl_xor_sync(0xffffffffu, q, o);
    const uint32_t nm = pack2(-mean, -mean);
    float sq;
    asm("sqrt.approx.ftz.f32 %0, %1;" : "=f"(sq) : "f"(rbf(rbf(q * (1.0f / DM)) + 1e-5f)));
    const float rd = rcpf(rbf(sq));
#pragma unroll
    for (int i = 0; i < 10; i++) { const uint32_t d = badd(x[i], nm); y[i] = pack2(blo(d) * rd, bhi(d) * rd); }
}
__device__ __forceinline__ void put_h(int l, int seg, int tok, int lane, const uint32_t* n) {
    st5<8192>(reinterpret_cast<char*>(g_ht + (l * NSEG + seg) * 2560) + (lane >> 2) * 1024 + (tok >> 3) * 256 + (lane & 2) * 64 + (tok & 7) * 16 + (lane & 1) * 8, n);
}
__device__ __forceinline__ void ln0_row(const bf16* x, int seg, int tok, int lane) {
    uint32_t v[10];
    ld5<256>(v, x + (size_t)(seg * SEG + tok) * DM + lane * 4);
    ln_row(v, v);
    put_h(0, seg, tok, lane, v);
    __syncwarp();
    if (lane == 0) red_release(FLG(F_H + seg), 1);
}
__device__ __forceinline__ void post_row(int l, int seg, int tok, int lane, const bf16* xin, bf16* xout) {
    uint32_t x[10], y[10], n[10];
    const int row = seg * SEG + tok;
    if ((seg & 15) == 0) flag_wait(FLG(F_CV + (seg >> 4)), 80, 100);
    ld5<16 * S_LEN * 16>(y, reinterpret_cast<const char*>(g_Y) + ((size_t)(lane >> 1) * S_LEN + row) * 16 + (lane & 1) * 8);
    if (l == 0) ld5<256>(x, xin + (size_t)row * DM + lane * 4);
    flag_wait(FLG(F_P + l * 64 + seg), 40, POST_NS);
    if (l) ld5<256>(x, xin + (size_t)row * DM + lane * 4);
    {
        const char* pp = reinterpret_cast<const char*>(g_pt + (l * NSEG + seg) * 10240) + (lane >> 4) * 4096 + tok * 128 +
                         ((((lane & 15) >> 1) ^ (((tok >> 3) << 1) | (tok & 1))) << 4) + (lane & 1) * 8;
        uint32_t a[10], b[10], c[10];
        ld5<8192>(a, pp); ld5<8192>(b, pp + 40960); ld5<8192>(c, pp + 81920); ld5<8192>(n, pp + 122880);
#pragma unroll
        for (int i = 0; i < 10; i++)
            x[i] = badd(x[i], pack2((blo(a[i]) + blo(b[i])) + (blo(c[i]) + blo(n[i])), (bhi(a[i]) + bhi(b[i])) + (bhi(c[i]) + bhi(n[i]))));
    }
    ln_row(x, n);
#pragma unroll
    for (int i = 0; i < 10; i++) x[i] = badd(x[i], bmul2(n[i], y[i]));
    st5<256>(xout + (size_t)row * DM + lane * 4, x);
    if (l == 0) {
        ln_row(x, n);
        put_h(1, seg, tok, lane, n);
        __syncwarp();
        if (lane == 0) red_release(FLG(F_H + 64 + seg), 1);
    }
}
__device__ __forceinline__ void u_unit(const bf16* Bk, const bf16* Bv, const bf16* shiftk, int unit, int lane) {
    const int t0 = (unit / 10) * 16, cp = (unit % 10) * 32 + lane;
    uint32_t kk[19], vv[16];
    const uint32_t* pk = reinterpret_cast<const uint32_t*>(Bk + (size_t)t0 * DM) + cp;
    const uint32_t* pv = reinterpret_cast<const uint32_t*>(Bv + (size_t)t0 * DM) + cp;
#pragma unroll
    for (int i = 0; i < 19; i++) kk[i] = (i >= 3 || t0 > 0) ? __ldg(pk + (i - 3) * (DM / 2)) : 0u;
#pragma unroll
    for (int i = 0; i < 16; i++) vv[i] = __ldg(pv + i * (DM / 2));
    const uint4 sh0 = __ldg(reinterpret_cast<const uint4*>(shiftk + cp * 8));
    const uint32_t s0 = __byte_perm(sh0.x, sh0.z, 0x5410), s1 = __byte_perm(sh0.x, sh0.z, 0x7632), s2 = __byte_perm(sh0.y, sh0.w, 0x5410), s3 = __byte_perm(sh0.y, sh0.w, 0x7632);
#pragma unroll
    for (int t = 0; t < 16; t++)
        vv[t] = bmul2(badd(badd(badd(bmul2(kk[t], s3), bmul2(kk[t + 1], s2)), bmul2(kk[t + 2], s1)), bmul2(kk[t + 3], s0)), vv[t]);
    uint4* d = g_U + (size_t)(cp * 2) * (S_LEN / 8) + (t0 >> 6) * 8;
    const int c0 = ((t0 ^ 48) & 63) >> 3, sw = (t0 >> 6) & 7;
#pragma unroll
    for (int c = 0; c < 2; c++) {
        const uint32_t sel = c ? 0x7632 : 0x5410;
#pragma unroll
        for (int hh = 0; hh < 2; hh++)
            d[c * (S_LEN / 8) + ((c0 + hh) ^ sw)] = make_uint4(__byte_perm(vv[15 - hh * 8], vv[14 - hh * 8], sel), __byte_perm(vv[13 - hh * 8], vv[12 - hh * 8], sel),
                                                              __byte_perm(vv[11 - hh * 8], vv[10 - hh * 8], sel), __byte_perm(vv[9 - hh * 8], vv[8 - hh * 8], sel));
    }
}
constexpr int CV_E = 4224, CV_W = 2 * 4096 + 3 * CV_E + 128, CV_HI = 111360, CV_Y = CV_HI + 4 * CV_W, CV_Z = CV_Y + 16384;
static_assert(4 * CV_W <= O_RED && CV_W % 128 == 0 && CV_Z + 128 <= HEAD_SMEM, "conv buffers");
__device__ __forceinline__ void conv_unit(uint32_t ub, uint32_t e0, uint32_t e1, uint32_t zrow, uint32_t yt, float Dv, int rg, int lane) {
    const int g = lane >> 2, tq = lane & 3;
    for (int i = lane; i < 64 * rg + 72; i += 32) {
        const uint4 v = lds128(e0 + i * 16);
        const uint32_t nx = lds32(e0 + i * 16 + 16);
        sts128(e1 + i * 16, __byte_perm(v.x, v.y, 0x5432), __byte_perm(v.y, v.z, 0x5432), __byte_perm(v.z, v.w, 0x5432), __byte_perm(v.w, nx, 0x5432));
    }
    __syncwarp();
    float acc[4][4];
#pragma unroll
    for (int i = 0; i < 16; i++) (&acc[0][0])[i] = 0.f;
    uint32_t wb = (g & 1) ? e0 + (1 + g + 2 * tq) * 2 : e1 + (g + 2 * tq) * 2;
    int row = 8 * rg + (lane & 7);
    auto ldb = [&](uint4& b0, uint4& b1) {
        const uint32_t x = row < 0 ? zrow : ub + row * 128 + (((lane >> 3) ^ (row & 7)) << 4);
        b0 = ldsm4(x); b1 = ldsm4(x ^ 64);
        row--;
    };
    uint32_t W[15], Wn[8];
    uint4 b0, b1, n0, n1;
#pragma unroll
    for (int i = 0; i < 15; i++) W[i] = lds32(wb + i * 16);
    ldb(b0, b1);
    const int nD = 8 * rg + 8;
#pragma unroll 2
    for (int D = 0; D < nD; D++) {
        wb += 128;
        ldb(n0, n1);
#pragma unroll
        for (int i = 0; i < 8; i++) Wn[i] = lds32(wb + 112 + i * 16);
#pragma unroll
        for (int ks = 0; ks < 4; ks++) {
            const uint32_t x0 = ks == 0 ? b0.x : (ks == 1 ? b0.z : (ks == 2 ? b1.x : b1.z)), x1 = ks == 0 ? b0.y : (ks == 1 ? b0.w : (ks == 2 ? b1.y : b1.w));
#pragma unroll
            for (int m = 0; m < 4; m++) mma16816(acc[m], W[2 * (m + ks)], W[2 * (m + ks) + 1], W[2 * (m + ks) + 1], W[2 * (m + ks) + 2], x0, x1);
        }
#pragma unroll
        for (int i = 0; i < 7; i++) W[i] = W[i + 8];
#pragma unroll
        for (int i = 0; i < 8; i++) W[i + 7] = Wn[i];
        b0 = n0; b1 = n1;
    }
#pragma unroll
    for (int m = 0; m < 4; m++)
#pragma unroll
        for (int i = 0; i < 4; i++) {
            const int pos = 16 * m + g + (i >> 1) * 8, blk = 2 * tq + (i & 1), ar = 8 * rg + blk, p = 63 - pos;
            unsigned short kv;
            asm volatile("ld.shared.u16 %0, [%1];" : "=h"(kv) : "r"(ub + ar * 128 + (((p >> 3) ^ (ar & 7)) << 4) + (p & 7) * 2));
            const float y = rbf(acc[m][i]) + rbf(__uint_as_float((uint32_t)kv << 16) * Dv);
            asm volatile("st.shared.u16 [%0], %1;" ::"r"(yt + (blk * 64 + pos) * 16), "h"((unsigned short)(pack2(y, y) & 0xffff)) : "memory");
        }
}
}

namespace ws {
struct HeadArgs { const bf16 *x, *mem0, *Wq, *Wk, *Wv, *Wo, *Bk, *Bv, *shiftk, *ssmk, *ssmD; bf16* out; int h_target; };

__global__ void __launch_bounds__(512, 1) head_kernel(const __grid_constant__ HeadArgs A) {
    extern __shared__ __align__(1024) unsigned char smem_raw[];
    const int tid = threadIdx.x, warp = __shfl_sync(0xffffffffu, tid >> 5, 0), lane = tid & 31;
    const int cq = blockIdx.x >> 4, r = blockIdx.x & 15;
    const int nh = cq < 4 ? 5 : 4, hi = r / 3, role = r - hi * 3;
    const bool head = r < 3 * nh;
    const int h = (cq < 4 ? 5 * cq : 4 * cq + 4) + hi;
    const uint32_t sb = smem_u32(smem_raw), bb = sb + O_BAR;
    asm volatile("griddepcontrol.launch_dependents;");
    const int sp = cq < 4 ? cq : 4 * cq + r - 24;
    if (tid == 0) {
        if ((sb & 0xFFFFFFu) != 1024) __trap();
        for (int i = 0; i < 13; i++) mbar_init(bb + i * 8, 1);
        mbar_init(bb + B_OB, 1); mbar_init(bb + B_OB + 64, 1);
        mbar_init(bb + B_HF, 1); mbar_init(bb + B_HF + 8, 1);
        mbar_init(bb + B_HE, 6 * nh);
        mbar_init(bb + B_OTF, head ? 4 : 8); mbar_init(bb + B_OTE, 1); mbar_init(bb + B_OTF + 8, 8); mbar_init(bb + B_OTE + 16, 1);
        asm volatile("fence.mbarrier_init.release.cluster;" ::: "memory");
        mbar_expect_tx(bb + B_RED, nh * 1280);
        mbar_expect_tx(bb + B_SM, 3072); mbar_expect_tx(bb + B_ST, role == 2 ? 5120 : 2048);
        if (role != 2) { mbar_expect_tx(bb + B_OB, 2048); mbar_expect_tx(bb + B_OB + 64, 2048); }
        mbar_expect_tx(bb + B_HF, 8 * HBYTES); mbar_expect_tx(bb + B_HF + 8, 8 * HBYTES);
    }
    if (warp < 8) {
        asm volatile("setmaxnreg.inc.sync.aligned.u32 %0;" ::"n"(REG_G));
        const int wg = warp >> 2, w4 = warp & 3;
        if (head) {
            const bf16* W = (role == 2 ? A.Wv + wg * 64 : (wg ? A.Wk : A.Wq) + role * 64) + h * DH;
            const uint32_t stg = sb + O_STG + wg * 81920;
            const int t7 = tid & 127;
#pragma unroll 8
            for (int i = 0; i < 40; i++) {
                const int row = i * 16 + (t7 >> 3), ch = t7 & 7;
                cp_async16(stg + row * 128 + ((ch ^ (row & 7)) << 4), W + (size_t)row * HD + ch * 8);
            }
            cp_commit();
        }
        cluster_arrive(); cluster_wait();
        if (head) {
            uint32_t wa[40][4];
            cp_wait<0>();
            named_bar(8 + wg, 128);
            {
                const uint32_t la = sb + O_STG + wg * 81920 + ((lane & 7) + (lane >> 4) * 8) * 128 + (((w4 * 2 + ((lane >> 3) & 1)) ^ (lane & 7)) << 4);
                { const uint4 v = lds128(sb + O_STG + wg * 81920 + (r >> 1) * 10240 + (tid & 127) * 16); sts128(sb + O_AS + wg * 2048 + (tid & 127) * 16, v.x, v.y, v.z, v.w); }
#pragma unroll
                for (int j = 1; j < 40; j++) {
                    const int kk = (((r >> 1) - j / 5) & 7) * 5 + j % 5;
                    const uint4 v = ldsm4t(la + kk * 2048);
                    wa[j][0] = v.x; wa[j][1] = v.y; wa[j][2] = v.z; wa[j][3] = v.w;
                }
            }
            named_bar(10, 384);
            for (int i = tid; i < 5120; i += 256) {
                const int j = i >> 7, kh = (i >> 6) & 1, ng = (i >> 5) & 1, kr = (i >> 2) & 7, u = (i >> 1) & 1;
                const int col = ((((r >> 1) - j / 5) & 7) * 5 + j % 5) * 16 + kh * 8 + kr, row = 4 * ng + 2 * u;
                const uint32_t lo = *reinterpret_cast<const unsigned short*>(A.mem0 + row * DM + col), hi16 = *reinterpret_cast<const unsigned short*>(A.mem0 + (row + 1) * DM + col);
                sts32(sb + O_MEM + i * 4, lo | hi16 << 16);
            }
            fence_async_smem();
            named_bar(11, 256);
            cluster_arrive();
            float acc[16];
            const uint32_t ep_q = role == 2 ? sb + O_VM + warp * 512 + (lane ^ ((lane >> 3) & 1)) * 16
                                            : sb + O_QRY + wg * 10240 + ((lane >> 1) & 1) * 5120 + (4 * (lane >> 4) + 2 * ((lane >> 2) & 1) + (lane & 1)) * 128 +
                                                  (((2 * w4 + ((lane >> 3) & 1)) ^ (4 * (lane >> 4) + 2 * ((lane >> 2) & 1) + (lane & 1)) ^ ((lane & 2) << 1)) << 4);
            const uint32_t ep_t = role == 2 ? sb + O_VT + warp * 1024 + lane * 16
                                            : sb + O_QRY + wg * 10240 + (8 + 8 * (lane >> 4) + (lane & 7)) * 128 + (((2 * w4 + ((lane >> 3) & 1)) ^ (lane & 7)) << 4);
                        const int pz = role == 2 ? P1C : P1A;
            const uint32_t ab = (1024 + O_AS + wg * 2048) >> 4;
            uint32_t ok = 1;
            auto token_gemm = [&](auto ll, const bool pause, const uint32_t vo, const uint32_t nbar, const uint32_t npar, const int t) {
                constexpr int l = decltype(ll)::value;
                constexpr uint32_t hb = ((1024 + O_H + l * 40960) >> 4) | (8u << 16);
                const uint32_t pr = opq(r >> 1);
                if (l) TS(15); else TS(14);
                wg_fence();
#pragma unroll
                for (int j = 0; j < 40; j++) {
                    const uint64_t db = mkdesc(hb + ((pr - j / 5) & 7) * 320 + (j % 5) * 64, 16);
                    if (j == 0) wg_n32_sfirst(acc, mkdesc(ab, 0x40000040u), db);
                    else wg_n32(acc, wa[j][0], wa[j][1], wa[j][2], wa[j][3], db);
                    if (l == 0 && (j + 1 == P1A || j + 1 == P1C)) {
                        if (pause && pz == j + 1) {
                            wg_commit();
                            if (role == 2) mwait(bb + B_OTE, vo >> 14);
                            wg_wait<0>();
                            named_arrive(3, 384);
                            named_bar(4, 384);
                            wg_fence();
                        }
                    }
                }
                wg_commit();
                ok = mtest(nbar, npar);
                wg_wait<0>();
                uint32_t pk[8];
#pragma unroll
                for (int i = 0; i < 8; i++) pk[i] = pack2(acc[2 * i], acc[2 * i + 1]);
                if (role == 2) {
                    sts128(ep_t + l * 8192 + vo, pk[0], pk[1], pk[2], pk[3]);
                    sts128(ep_t + l * 8192 + vo + 512, pk[4], pk[5], pk[6], pk[7]);
                } else {
                    stsm4t((ep_t ^ (l << 6)) + l * 5120, pk[0], pk[1], pk[2], pk[3]);
                    stsm4t((ep_t ^ (l << 6)) + l * 5120 + 2048, pk[4], pk[5], pk[6], pk[7]);
                }
                asm volatile("{\n.reg .pred p, q;\nsetp.eq.u32 p, %0, 0;\nsetp.eq.u32 q, %1, 0;\n"
                             "@p mbarrier.arrive.expect_tx.shared::cta.b64 _, [%2], %3;\n@q mbarrier.arrive.shared::cluster.b64 _, [%4];\n}"
                             ::"r"(tid), "r"(tid & 127), "r"(bb + B_HF + l * 8), "r"(8 * HBYTES), "r"(mapa(bb + B_HE, l)) : "memory");
            };
            mwait(bb + B_HF, 0);
            token_gemm(IC<0>{}, false, 0, bb + B_MEM, 1, -1);
            cluster_wait();
            named_arrive(13, 384);
#pragma unroll 1
            for (int t = 0; t < NT; t++) {
                TS(0);
                const uint32_t mp = (t & 1) ^ 1;
                const bool tg0 = t + 1 < NSEG, tg1 = t + 1 >= LAG;
                constexpr uint32_t mb = ((1024 + O_MEM) >> 4) | (16u << 16);
#pragma unroll
                for (int G = 0; G < 8; G++) {
                    if (!ok) mwait(bb + B_MEM + G * 8, mp);
                    ok = mtest(G < 7 ? bb + B_MEM + (G + 1) * 8 : bb + B_HF, mp);
                    if (G == 0) { TS(1); wg_fence(); }
                    if (G == 7) TS(2);
                    if (G == 1) TS(8); if (G == 2) TS(9); if (G == 3) TS(10); if (G == 4) TS(11); if (G == 5) TS(12); if (G == 6) TS(13);
#pragma unroll
                    for (int u = 0; u < 5; u++) {
                        const int j = G * 5 + u;
                        const uint64_t db = mkdesc(mb + j * 32, 8);
                        if (j == 0) wg_n16t_sfirst(acc, mkdesc(ab, 0x40000040u), db);
                        else wg_n16t(acc, wa[j][0], wa[j][1], wa[j][2], wa[j][3], db);
                    }
                    wg_commit();
                }
                if (role == 2 && t) named_bar(5, 384);
                wg_wait<0>();
                TS(3);
                if (role == 2) sts128(ep_q, pack2(acc[0], acc[1]), pack2(acc[2], acc[3]), pack2(acc[4], acc[5]), pack2(acc[6], acc[7]));
                else stsm4t(ep_q, pack2(acc[0], acc[1]), pack2(acc[2], acc[3]), pack2(acc[4], acc[5]), pack2(acc[6], acc[7]));
                named_arrive(1, 384);
                if (tid < 8) mbar_expect_tx(bb + B_MEM + tid * 8, 2560);
                if (t == NT - 1) break;
                if (tg0) {
                    if (!ok) mwait(bb + B_HF, mp);
                    if (role != 2) named_bar(2, 384);
                    token_gemm(IC<0>{}, true, mp * 16384, tg1 ? bb + B_HF + 8 : bb + B_MEM, tg1 ? (t + 1 - LAG) & 1 : mp ^ 1, t);
                } else {
                    if (role == 2) mwait(bb + B_OTE, mp); else named_bar(2, 384);
                    named_arrive(3, 384); named_bar(4, 384);
                    ok = 0;
                }
                TS(5);
                if (tg1) {
                    if (!ok) mwait(bb + B_HF + 8, (t + 1 - LAG) & 1);
                    token_gemm(IC<1>{}, false, mp * 16384, bb + B_MEM, mp ^ 1, t);
                }
                TS(6);
                named_arrive(13, 384);
            }
        } else {
            cluster_arrive();
            const uint32_t cb = sb + (warp < 4 ? warp * CV_W : CV_HI + (warp - 4) * CV_W), lb = bb + B_MEM + warp * 8;
            auto u_range = [&](int rg) {
#pragma unroll 1
                for (int u = rg * 320 + sp * 8 + warp; u < rg * 320 + 320; u += 128) u_unit(A.Bk, A.Bv, A.shiftk, u, lane);
                __syncwarp();
                if (lane == 0) red_release(FLG(F_U + rg), 1);
            };
            auto fetch = [&](int k) {
                const int rg = k / 5, ch = (sp * 5 + k - 5 * rg) * 8 + warp;
                if (k == 5 * rg) { flag_wait(FLG(F_U + rg), 128, 100); fence_async_global(); }
                if (lane == 0) {
                    const uint32_t nb = (rg + 1) * 1024;
                    mbar_expect_tx(lb, 2 * nb);
                    asm volatile("cp.async.bulk.shared::cluster.global.mbarrier::complete_tx::bytes [%0], [%1], %2, [%3];" ::"r"(cb + (k & 1) * 4096), "l"(g_U + ch * (S_LEN / 8)), "r"(nb), "r"(lb) : "memory");
                    asm volatile("cp.async.bulk.shared::cluster.global.mbarrier::complete_tx::bytes [%0], [%1], %2, [%3];" ::"r"(cb + 8192 + (k & 1) * CV_E + 128), "l"(A.ssmk + (size_t)ch * S_LEN), "r"(nb), "r"(lb) : "memory");
                }
                __syncwarp();
            };
            sts32(cb + 8192 + lane * 4, 0u); sts32(cb + 8192 + CV_E + lane * 4, 0u);
            if (warp == 0) sts32(sb + CV_Z + lane * 4, 0u);
            u_range(0);
            named_bar(8, 256);
            fetch(0);
#pragma unroll 1
            for (int k = 0; k < 20; k++) {
                const int rg = k / 5;
                const float Dv = bf2f(A.ssmD[(sp * 5 + k - 5 * rg) * 8 + warp]);
                mwait(lb, k & 1);
                if (k != 4 && k < 19) { fence_async_smem(); fetch(k + 1); }
                mwait(bb + B_OTE + (k & 1) * 16, ((k >> 1) & 1) ^ 1);
                conv_unit(cb + (k & 1) * 4096, cb + 8192 + (k & 1) * CV_E, cb + 8192 + 2 * CV_E + 64, sb + CV_Z, sb + CV_Y + (k & 1) * 8192 + warp * 2, Dv, rg, lane);
                fence_async_smem();
                __syncwarp();
                if (lane == 0) mbar_arrive(bb + B_OTF + (k & 1) * 8);
                if (k == 4) { u_range(1); u_range(2); u_range(3); fetch(5); }
            }
            cluster_wait();
        }
    } else if (warp < 12) {
        asm volatile("setmaxnreg.dec.sync.aligned.u32 %0;" ::"n"(REG_T));
        cluster_arrive(); cluster_wait();
        const int w = warp & 3, c = w >> 1, hh = w & 1;
        const uint32_t lane0 = __shfl_sync(0xffffffffu, tid & 31, tid & 31);
        if (head) {
            const int tile0 = role * 12, ntile = role == 2 ? 16 : 12;
            const uint32_t wo = sb + O_WO;
            named_bar(10, 384);
            for (int i = tid & 127; i < ntile * 256; i += 128) {
                const int ti = i >> 8, p = (i >> 1) & 127, ch = i & 1;
                const int ks = p >> 4, kh = (p >> 3) & 1, e8 = p & 7;
                const int dim = 64 * (ks >> 2) + 16 * (e8 >> 1) + 8 * (e8 & 1) + 2 * (ks & 3) + kh;
                cp_async16(wo + ti * 4096 + p * 32 + ((ch ^ ((p >> 2) & 1)) << 4), A.Wo + (size_t)(h * DH + dim) * DM + (tile0 + ti) * 16 + ch * 8);
            }
            cp_commit();
            if (lane < 8) {
                const int u = 2 * (tile0 + w + 4 * (lane >> 1)) + (lane & 1), ow = u / 5;
                sts32(sb + O_TAB + w * 32 + lane * 4, mapa(sb + O_RED + (u - 5 * ow) * 1280 + hi * 256, ow & 15));
            }
            cp_wait<0>();
            named_bar(7, 128);
            cluster_arrive(); cluster_wait();
            const uint32_t wo_a = wo + w * 4096 + ((lane >> 4) * 8 + (lane & 7)) * 32 + ((((lane >> 3) & 1) ^ ((lane >> 2) & 1)) << 4);
            const uint32_t ob_0 = sb + (role == 2 ? O_PB : O_OBA) + (lane >> 4) * 2048 + ((lane >> 3) & 1) * 128 + ((lane & 7) ^ ((lane >> 1) & 4)) * 16;
            const float cs = 0.08838834764831845f * 1.4426950408889634f;
            auto w_frag = [&](auto four, int i) {
                return ldsm4t(wo_a + (i < 16 || decltype(four)::value ? (i >> 4) * 32768 + (i & 1) * 16384 + ((i >> 1) & 7) * 512 : 32768 + (i & 1) * 2048 + ((i >> 1) & 7) * 512));
            };
            auto w_pre = [&](auto four, auto pd, uint4* wf) {
#pragma unroll
                for (int i = 0; i < decltype(pd)::value; i++) wf[i] = w_frag(four, i);
            };
            auto w_run = [&](auto four, auto pd, uint4* wf, int t, const uint32_t ob_a) {
                constexpr int FOUR = decltype(four)::value, PD = decltype(pd)::value, NF = FOUR ? 32 : 24;
                const uint32_t l8 = opq(lane0) * 8, rb = (bb + B_RED) & 0xFFFFFFu;
                uint4 ob = ldsm4(ob_a), on, o2;
#pragma unroll
                for (int p = 0; p < 2; p++) {
                    constexpr int dummy = 0; (void)dummy;
                    const bool split = p == 1 && !FOUR;
                    if (FOUR && p == 1) mwait(bb + B_ST, t & 1);
                    const int nk = split ? 4 : 8;
                    float d[4][4];
                    uint4 ta;
#pragma unroll
                    for (int i = 0; i < 16; i++) (&d[0][0])[i] = 0.f;
#pragma unroll
                    for (int ks = 0; ks < 8; ks++) {
                        if (ks >= nk) continue;
                        if (!FOUR && p == 0 && ks == 3) { mwait(bb + B_OB + 64, t & 1); TS(7); }
                        if (split) o2 = ldsm4(ob_a + (ks + 4) * 256);
                        if (ks + 1 < nk || p == 0) on = ldsm4(ob_a + ((ks + 1) & 7) * 256);
                        if (ks == nk - 2) ta = lds128(sb + O_TAB + w * 32 + p * 16);
#pragma unroll
                        for (int u = 0; u < 2; u++) {
                            const int i = p * 16 + ks * 2 + u;
                            const uint4& o = split && u ? o2 : ob;
                            mmav(d[2 * u], wf[i % PD].x, wf[i % PD].y, wf[i % PD].z, wf[i % PD].w, o.x, o.y);
                            mmav(d[2 * u + 1], wf[i % PD].x, wf[i % PD].y, wf[i % PD].z, wf[i % PD].w, o.z, o.w);
                            if (i + PD < NF) wf[i % PD] = w_frag(four, i + PD);
                        }
                        ob = on;
                    }
                    if (p) TS(10); else TS(8);
                    if (split) {
#pragma unroll
                        for (int i = 0; i < 4; i++) { d[0][i] += d[2][i]; d[1][i] += d[3][i]; }
                    }
                    st_async_v2(ta.x + l8, pack2(d[0][0], d[0][1]), pack2(d[1][0], d[1][1]), (ta.x & 0xFF000000u) | rb);
                    st_async_v2(ta.y + l8, pack2(d[0][2], d[0][3]), pack2(d[1][2], d[1][3]), (ta.y & 0xFF000000u) | rb);
                    if (!split) {
                        st_async_v2(ta.z + l8, pack2(d[2][0], d[2][1]), pack2(d[3][0], d[3][1]), (ta.z & 0xFF000000u) | rb);
                        st_async_v2(ta.w + l8, pack2(d[2][2], d[2][3]), pack2(d[3][2], d[3][3]), (ta.w & 0xFF000000u) | rb);
                    }
                }
            };
            if (role != 2) {
#pragma unroll 1
                for (int t = 0; t < NT; t++) {
                    const uint32_t lane = opq(lane0);
                    const uint32_t dc = mapa(sb, hi * 3 + 2), dp = mapa(sb, hi * 3 + (role ^ 1));
                    const uint32_t qa = sb + O_QRY + c * 5120 + (lane & 7) * 128;
                    const uint32_t sw = (((lane >> 3) ^ (lane & 7)) << 4) ^ (c << 6);
                    float s[10];
                    {
                        const uint32_t ka = qa + 10240;
                        const uint32_t kt = sb + O_KEY + c * 5120 + (lane & 15) * 128, kx = (((lane >> 4) ^ (lane & 7)) << 4) ^ (c << 6);
                        const uint32_t sd = dc + O_SM + role * 1536 + c * 768 + lane * 4, sbar = dc + O_BAR + B_SM;
                        named_bar(13, 384);
                        {
                            uint4 f[4];
#pragma unroll
                            for (int i = 0; i < 4; i++) f[i] = ldsm4(kt + 1024 + hh * 2048 + (kx ^ (i << 5) ^ (hh << 6)));
                            const uint32_t qh = qa + (sw ^ (hh << 6)), kh = kt + (kx ^ (hh << 6));
                            named_bar(1, 384);
                            const uint4 q0 = ldsm4(qh), g0 = ldsm4(kh), g1 = ldsm4(kh ^ 32), q1 = ldsm4(qh ^ 64);
                            float s0[4] = {0.f, 0.f, 0.f, 0.f}, s1[4] = {0.f, 0.f, 0.f, 0.f}, s2[4] = {0.f, 0.f, 0.f, 0.f}, s3[4] = {0.f, 0.f, 0.f, 0.f};
                            mmau(s0, f[0], q0.x, q0.y); mmau(s1, f[1], q0.z, q0.w);
                            mmau(s2, g0, q0.x, q0.y); mmau(s3, g1, q0.z, q0.w);
                            mmau(s0, f[2], q1.x, q1.y); mmau(s1, f[3], q1.z, q1.w);
                            st_async_b32(sd + hh * 128, pack2(s2[0] + s3[0], s2[1] + s3[1]), sbar);
                            st_async_b32(sd + 256 + hh * 256, pack2(s0[0] + s1[0], s0[1] + s1[1]), sbar);
                            st_async_b32(sd + 384 + hh * 256, pack2(s0[2] + s1[2], s0[3] + s1[3]), sbar);
                        }
                        uint4 m0 = ldsm4(ka + sw), m1 = ldsm4(ka + (sw ^ 64));
                        uint4 k0 = ldsm4(ka + (1 + 2 * hh) * 1024 + sw), k1 = ldsm4(ka + (1 + 2 * hh) * 1024 + (sw ^ 64));
                        uint4 k2 = ldsm4(ka + (2 + 2 * hh) * 1024 + sw), k3 = ldsm4(ka + (2 + 2 * hh) * 1024 + (sw ^ 64));
                        TS(1);
                        const uint32_t ta = sb + O_QRY + c * 5120 + (8 + 16 * hh + (lane & 15)) * 128;
                        uint4 a[4];
#pragma unroll
                        for (int i = 0; i < 4; i++) a[i] = ldsm4(ta + (kx ^ (i << 5)));
                        uint32_t st[5];
                        auto unit = [&](const uint4& b0, const uint4& b1, float& e0, float& e1, uint32_t& o) {
                            float s0[4] = {0.f, 0.f, 0.f, 0.f}, s1[4] = {0.f, 0.f, 0.f, 0.f};
                            mmav(s0, a[0].x, a[0].y, a[0].z, a[0].w, b0.x, b0.y); mmav(s1, a[1].x, a[1].y, a[1].z, a[1].w, b0.z, b0.w);
                            mmav(s0, a[2].x, a[2].y, a[2].z, a[2].w, b1.x, b1.y); mmav(s1, a[3].x, a[3].y, a[3].z, a[3].w, b1.z, b1.w);
                            const float u0 = s0[0] + s1[0], u1 = s0[1] + s1[1], u2 = s0[2] + s1[2], u3 = s0[3] + s1[3];
                            e0 = role ? u2 : u0; e1 = role ? u3 : u1;
                            o = role ? pack2(u0, u1) : pack2(u2, u3);
                        };
                        unit(m0, m1, s[0], s[1], st[0]);
                        if (hh) { m0 = ldsm4(ka + 1024 + sw); m1 = ldsm4(ka + 1024 + (sw ^ 64)); }
                        unit(k0, k1, s[2], s[3], st[1]);
                        if (hh) { k0 = ldsm4(ka + 2048 + sw); k1 = ldsm4(ka + 2048 + (sw ^ 64)); }
                        unit(k2, k3, s[4], s[5], st[2]);
                        const uint32_t td = dp + O_ST + c * 1024, tb = dp + O_BAR + B_ST;
                        if (hh == 0) {
                            s[6] = s[7] = s[8] = s[9] = -INFINITY;
                            st_async_v2(td + lane * 8, st[0], st[1], tb);
                            st_async_b32(td + 256 + lane * 4, st[2], tb);
                        } else {
                            unit(m0, m1, s[6], s[7], st[3]);
                            unit(k0, k1, s[8], s[9], st[4]);
                            st_async_v4(td + 384 + lane * 16, st[0], st[1], st[2], st[3], tb);
                            st_async_b32(td + 896 + lane * 4, st[4], tb);
                        }
                        if (t < NT - 1) named_arrive(2, 384);
                        const int lim = 8 * role + (int)(lane >> 2) - 2 * (int)(lane & 3);
                        if (lim < 0) s[2] = -INFINITY;
                        if (lim < 1) s[3] = -INFINITY;
                        if (lim < 8) s[4] = -INFINITY;
                        if (lim < 9) s[5] = -INFINITY;
                        TS(2);
                    }
                    {
                        mwait(bb + B_ST, t & 1);
                        const uint32_t sa = sb + O_ST + c * 1024;
                        if (hh == 0) {
                            const uint2 v = lds64(sa + lane * 8);
                            const uint32_t u = lds32(sa + 256 + lane * 4);
                            s[0] += blo(v.x); s[1] += bhi(v.x); s[2] += blo(v.y); s[3] += bhi(v.y); s[4] += blo(u); s[5] += bhi(u);
                        } else {
                            const uint4 v = lds128(sa + 384 + lane * 16);
                            const uint32_t u = lds32(sa + 896 + lane * 4);
                            s[0] += blo(v.x); s[1] += bhi(v.x); s[2] += blo(v.y); s[3] += bhi(v.y); s[4] += blo(v.z); s[5] += bhi(v.z);
                            s[6] += blo(v.w); s[7] += bhi(v.w); s[8] += blo(u); s[9] += bhi(u);
                        }
                        float mx = fmaxf(fmaxf(fmaxf(s[0], s[1]), fmaxf(s[2], s[3])), fmaxf(fmaxf(fmaxf(s[4], s[5]), fmaxf(s[6], s[7])), fmaxf(s[8], s[9])));
                        mx = fmaxf(mx, __shfl_xor_sync(0xffffffffu, mx, 1));
                        mx = fmaxf(mx, __shfl_xor_sync(0xffffffffu, mx, 2)) * -cs;
#pragma unroll
                        for (int i = 0; i < 10; i++) s[i] = ex2f(fmaf(s[i], cs, mx));
                        float sum = ((s[0] + s[1]) + (s[2] + s[3])) + ((s[4] + s[5]) + (s[6] + s[7])) + (s[8] + s[9]);
                        sum += __shfl_xor_sync(0xffffffffu, sum, 1);
                        sum += __shfl_xor_sync(0xffffffffu, sum, 2);
                        sum = rcpf(sum);
                        const uint32_t pd = dc + O_PB + (t & 1) * 5120 + c * 2560 + (2 * hh + role) * 128 + lane * 4;
#pragma unroll
                        for (int n = 0; n < 5; n++)
                            st_async_b32(pd + (n == 0 ? 0 : (n < 3 ? n * 512 + hh * 1024 : n * 512 - hh * 1024)), pack2(s[2 * n] * sum, s[2 * n + 1] * sum), dc + O_BAR + B_ST);
                        TS(6);
                        if (H1_LATE && r == 1 && t >= LAG - 1 && t < NT - 1) named_arrive(12, 160);
                    }
                    if (t == NT - 1) break;
                    uint4 wf[PDA];
                    w_pre(IC<0>{}, IC<PDA>{}, wf);
                    mwait(bb + B_OB, t & 1);
                    TS(3);
                    named_bar(3, 384);
                    w_run(IC<0>{}, IC<PDA>{}, wf, t, ob_0);
                    named_arrive(4, 384);
                    if (w == 0 && lane == 0) { mbar_expect_tx(bb + B_OB, 2048); mbar_expect_tx(bb + B_OB + 64, 2048); mbar_expect_tx(bb + B_ST, 2048); }
                    TS(5);
                }
            } else {
#pragma unroll 1
                for (int t = 0; t < NT; t++) {
                    const uint32_t lane = opq(lane0);
                    const int g = lane >> 2, tq = lane & 3;
                    const uint32_t vm_a = sb + O_VM + (g * 4 + 2 * (tq & 1) + (c ^ ((g >> 1) & 1))) * 16 + (tq >> 1) * 8;
                    const uint32_t vt_a = sb + O_VT + (t & 1) * 16384 + lane * 16;
                    named_bar(13, 384);
                    uint4 va[4][2];
#pragma unroll
                    for (int i = 0; i < 4; i++) {
                        va[i][0] = lds128(vt_a + c * 8192 + (4 * hh + i) * 1024);
                        va[i][1] = lds128(vt_a + c * 8192 + (4 * hh + i) * 1024 + 512);
                    }
                    const uint32_t sa = opq(sb + O_SM + c * 768 + 256 + lane * 16), sa2 = opq(sb + O_SM + c * 768 + (lane & 15) * 16 + (lane >> 4) * 1536), vm_b = opq(vm_a + hh * 2048);
                    named_bar(1, 384);
                    if (t < NT - 1) {
                        uint2 vm[4];
#pragma unroll
                        for (int i = 0; i < 4; i++) vm[i] = lds64(vm_b + i * 512);
                        mwait(bb + B_SM, t & 1);
                        TS(1);
                        const uint4 x0 = ldsm4t(sa), y0 = ldsm4t(sa + 1536), x1 = ldsm4t(sa2);
                        float s[10];
                        s[2] = blo(x0.x) + blo(y0.x); s[3] = bhi(x0.x) + bhi(y0.x); s[4] = blo(x0.y) + blo(y0.y); s[5] = bhi(x0.y) + bhi(y0.y);
                        s[6] = blo(x0.z) + blo(y0.z); s[7] = bhi(x0.z) + bhi(y0.z); s[8] = blo(x0.w) + blo(y0.w); s[9] = bhi(x0.w) + bhi(y0.w);
                        s[0] = (blo(x1.x) + blo(x1.y)) + (blo(x1.z) + blo(x1.w)); s[1] = (bhi(x1.x) + bhi(x1.y)) + (bhi(x1.z) + bhi(x1.w));
                        float mx = fmaxf(fmaxf(fmaxf(s[0], s[1]), fmaxf(s[2], s[3])), fmaxf(fmaxf(fmaxf(s[4], s[5]), fmaxf(s[6], s[7])), fmaxf(s[8], s[9])));
                        const float m1 = __shfl_xor_sync(0xffffffffu, mx, 1), m2 = __shfl_xor_sync(0xffffffffu, mx, 2), m3 = __shfl_xor_sync(0xffffffffu, mx, 3);
                        mx = fmaxf(fmaxf(mx, m1), fmaxf(m2, m3)) * -cs;
                        uint32_t pb[5];
#pragma unroll
                        for (int i = 0; i < 5; i++) pb[i] = pack2(ex2f(fmaf(s[2 * i], cs, mx)), ex2f(fmaf(s[2 * i + 1], cs, mx)));
                        TS(9);
                        named_bar(3, 384);
                        float o[5][4];
#pragma unroll
                        for (int i = 0; i < 20; i++) (&o[0][0])[i] = 0.f;
                        const uint32_t one2 = 0x3F803F80u;
                        float z[2][4] = {{0.f, 0.f, 0.f, 0.f}, {0.f, 0.f, 0.f, 0.f}};
                        mmav8(o[4], one2, one2, pb[0]);
                        mmav(z[0], one2, one2, one2, one2, pb[1], pb[2]);
                        mmav(z[1], one2, one2, one2, one2, pb[3], pb[4]);
#pragma unroll
                        for (int i = 0; i < 4; i++) mmav8(o[i], vm[i].x, vm[i].y, pb[0]);
#pragma unroll
                        for (int i = 0; i < 4; i++) mmav(o[i], va[i][0].x, va[i][0].y, va[i][0].z, va[i][0].w, pb[1], pb[2]);
#pragma unroll
                        for (int i = 0; i < 4; i++) mmav(o[i], va[i][1].x, va[i][1].y, va[i][1].z, va[i][1].w, pb[3], pb[4]);
                        o[4][0] += z[0][0] + z[1][0]; o[4][1] += z[0][1] + z[1][1];
                        uint4 wf[PDC];
                        w_pre(IC<1>{}, IC<PDC>{}, wf);
                        const float r0 = rcpf(o[4][0]), r1 = rcpf(o[4][1]);
                        const uint32_t oo = c * 2048 + hh * 1024 + g * 128 + tq * 16 + (g & 1) * 64;
                        uint32_t e0[4], e1[4];
#pragma unroll
                        for (int i = 0; i < 4; i++) { e0[i] = pack2(o[i][0] * r0, o[i][2] * r0); e1[i] = pack2(o[i][1] * r1, o[i][3] * r1); }
                        sts128(sb + O_PB + (~t & 1) * 5120 + oo, e0[0], e0[1], e0[2], e0[3]);
                        sts128(sb + O_PB + (~t & 1) * 5120 + (oo ^ 64), e1[0], e1[1], e1[2], e1[3]);
                        {
                            const uint32_t da = mapa(sb + O_OBA, r - 2) + oo, ba = mapa(bb + B_OB + hh * 64, r - 2);
                            st_async_v4(da, e0[0], e0[1], e0[2], e0[3], ba);
                            st_async_v4(da + 0x01000000u, e0[0], e0[1], e0[2], e0[3], ba + 0x01000000u);
                            st_async_v4(da ^ 64, e1[0], e1[1], e1[2], e1[3], ba);
                            st_async_v4((da ^ 64) + 0x01000000u, e1[0], e1[1], e1[2], e1[3], ba + 0x01000000u);
                        }
                        TS(3);
                        named_bar(7, 128);
                        w_run(IC<1>{}, IC<PDC>{}, wf, t, ob_0 + (~t & 1) * 5120);
                        TS(4);
                    } else { mwait(bb + B_SM, t & 1); mwait(bb + B_ST, t & 1); }
                    TS(5);
                    {
                        const uint32_t pa = sb + O_PB + (t & 1) * 5120 + c * 2560, pl = pa + (lane & 7) * 16 + ((lane >> 3) & 1) * 512 + (lane >> 4) * 128;
                        const uint4 p0 = ldsm4(pa + lane * 16), p1 = ldsm4(pl + 512), p2 = ldsm4(pl + 768), p3 = ldsm4(pl + 1792);
                        const uint32_t va_ = vt_a + c * 8192 + hh * 4096, oa = va_ - lane * 16 + g * 64 + ((tq ^ (g >> 1)) & 3) * 16;
                        float d[2][4][4];
#pragma unroll
                        for (int i = 0; i < 5; i++) {
                            if (i < 4) {
                                const uint2 a0 = lds64(vm_a + hh * 2048 + i * 512);
                                const uint4 a1 = lds128(va_ + i * 1024), a2 = lds128(va_ + i * 1024 + 512);
                                float (*e)[4] = d[i & 1];
#pragma unroll
                                for (int k = 0; k < 16; k++) (&e[0][0])[k] = 0.f;
                                mma16816(e[2], a2.x, a2.y, a2.z, a2.w, p3.x, p3.y); mma16816(e[3], a2.x, a2.y, a2.z, a2.w, p3.z, p3.w);
                                mma1688(e[0], a0.x, a0.y, p0.x); mma1688(e[1], a0.x, a0.y, p0.y); mma1688(e[2], a0.x, a0.y, p0.z); mma1688(e[3], a0.x, a0.y, p0.w);
                                mma16816(e[0], a1.x, a1.y, a1.z, a1.w, p1.x, p1.y); mma16816(e[1], a1.x, a1.y, a1.z, a1.w, p1.z, p1.w);
                                mma16816(e[2], a1.x, a1.y, a1.z, a1.w, p2.x, p2.y); mma16816(e[3], a1.x, a1.y, a1.z, a1.w, p2.z, p2.w);
                            }
                            if (i > 0) {
                                float (*e)[4] = d[(i - 1) & 1];
                                sts128(oa + (i - 1) * 1024, pack2(e[0][0], e[0][1]), pack2(e[1][0], e[1][1]), pack2(e[2][0], e[2][1]), pack2(e[3][0], e[3][1]));
                                sts128(oa + (i - 1) * 1024 + 512, pack2(e[0][2], e[0][3]), pack2(e[1][2], e[1][3]), pack2(e[2][2], e[2][3]), pack2(e[3][2], e[3][3]));
                            }
                        }
                    }
                    if (t < NT - 1) named_arrive(4, 384);
                    TS(6);
                    if (w == 0 && lane == 0) { mbar_expect_tx(bb + B_ST, 5120); mbar_expect_tx(bb + B_SM, 3072); }
                    fence_async_smem();
                    __syncwarp();
                    if (lane == 0) mbar_arrive(bb + B_OTF);
                    if (t < NT - 1) named_arrive(5, 384);
                }
            }
        } else {
            cluster_arrive();
            const int wi = sp * 4 + w, half = wi >> 5, tok = wi & 31;
#pragma unroll 1
            for (int s = half; s < LN0_AHEAD; s += 2) ln0_row(A.x, s, tok, lane);
#pragma unroll 1
            for (int k = 0; k < NT; k++) {
                if (half && k + LN0_AHEAD < NSEG) ln0_row(A.x, k + LN0_AHEAD, tok, lane);
                const int n = k - half * LAG;
                if (n >= 0 && n < NSEG) post_row(half, n, tok, lane, half ? g_x : A.x, half ? A.out : g_x);
            }
            cluster_wait();
        }
    } else {
        asm volatile("setmaxnreg.dec.sync.aligned.u32 %0;" ::"n"(REG_X));
        cluster_arrive(); cluster_wait();
        const int s = warp - 12;
        const uint32_t lane0 = __shfl_sync(0xffffffffu, tid & 31, tid & 31);
        if (s < 3) {
            cluster_arrive(); cluster_wait();
            int slot = 0;
            if (s == 0) {
                const uint32_t G = lane >> 1, d = ((r + 2 * G) & 15) ^ (lane & 1);
                const bool ok = lane < 16 && d < 3 * nh;
                const uint32_t pos = __popc(__ballot_sync(0xffffffffu, ok) & ((1u << lane) - 1u));
                if (ok) { sts32(sb + O_BT + pos * 8, (d << 24) + G * 2560); sts32(sb + O_BT + pos * 8 + 4, mapa(bb + B_MEM + G * 8, d)); }
            }
            named_bar(14, 96);
#pragma unroll 1
            for (int t = 0; t < NT - 1; t++) {
                const uint32_t lane = opq(lane0);
                const uint32_t ra = sb + O_RED + s * 2560 + lane * 8;
                uint4* xb = g_xc + ((slot * 16 + r) * 3 + s) * 256;
                uint32_t m0 = 0x80008000u, m1 = 0x80008000u;
                if (t < LAG && cq == 0) {
                    const bf16* mp = A.mem0 + 2 * (lane & 3) * DM + (5 * r + 2 * s) * 8 + (lane >> 2);
                    m0 = max(*reinterpret_cast<const unsigned short*>(mp) | (uint32_t)*reinterpret_cast<const unsigned short*>(mp + DM) << 16, 1u);
                    if (s < 2) m1 = max(*reinterpret_cast<const unsigned short*>(mp + 8) | (uint32_t)*reinterpret_cast<const unsigned short*>(mp + DM + 8) << 16, 1u);
                }
                const bool late = t >= LAG;
                auto sum5 = [](uint32_t a, uint32_t b, uint32_t c, uint32_t d, uint32_t e) { return max(badd(badd(badd(a, b), e), badd(c, d)), 1u); };
                auto sum7 = [](uint32_t a, uint32_t b, uint32_t c, uint32_t d, uint32_t e, uint32_t f, uint32_t h_) {
                    return badd(badd(badd(a, b), badd(c, d)), badd(badd(e, f), h_));
                };
                auto bcast = [&](auto two, const uint4& e0, uint32_t x0, uint32_t x1, uint32_t y0, uint32_t y1) {
                    const uint32_t aa = ((sb + O_MEM + (5 * (r & 1) + 2 * s) * 256) & 0xFFFFFFu) + (lane & 2) * 64 + (lane >> 2) * 16 + (lane & 1) * 8;
                    auto send = [&](uint32_t o, uint32_t bar) { st_async_v2(aa + o, x0, x1, bar); if (decltype(two)::value) st_async_v2(aa + o + 256, y0, y1, bar); };
                    const uint32_t tb0 = clk32();
                    auto pace = [&](int k) { if (BP) while (__any_sync(0xffffffffu, clk32() - tb0 < (uint32_t)(k * BP))) {} };
                    TS(8);
                    send(e0.x, e0.y); send(e0.z, e0.w);
                    TS(9);
                    uint4 e[5];
#pragma unroll
                    for (int i = 0; i < 5; i++) e[i] = lds128(sb + O_BT + 16 + i * 16);
#pragma unroll
                    for (int i = 0; i < 5; i++) { pace(i + 1); send(e[i].x, e[i].y); send(e[i].z, e[i].w); }
                    if (nh == 5) {
                        const uint4 f0 = lds128(sb + O_BT + 96);
                        const uint2 f1 = lds64(sb + O_BT + 112);
                        pace(6); send(f0.x, f0.y); send(f0.z, f0.w); pace(7); send(f1.x, f1.y);
                    }
                };
                mwait(bb + B_RED, t & 1);
                TS(0);
                int guard = 0;
                if (s < 2) {
                    uint2 p[5], q[5];
#pragma unroll
                    for (int i = 0; i < 5; i++) {
                        p[i] = i < 4 || nh == 5 ? lds64(ra + i * 256) : make_uint2(0, 0);
                        q[i] = i < 4 || nh == 5 ? lds64(ra + 1280 + i * 256) : make_uint2(0, 0);
                    }
                    const uint32_t u1 = sum5(p[0].y, p[1].y, p[2].y, p[3].y, p[4].y), u3 = sum5(q[0].y, q[1].y, q[2].y, q[3].y, q[4].y);
                    st_relaxed_v4(xb + cq * 32 + lane, sum5(p[0].x, p[1].x, p[2].x, p[3].x, p[4].x), late ? u1 : m0, sum5(q[0].x, q[1].x, q[2].x, q[3].x, q[4].x), late ? u3 : m1);
                    TS(1);
                    delay(XD);
                    uint4 x[NCL];
                    while (true) {
#pragma unroll
                        for (int k = 0; k < NCL; k++) x[k] = ld_relaxed_v4(xb + k * 32 + lane);
                        uint32_t mn = min(min(x[0].x, x[0].y), min(x[0].z, x[0].w));
#pragma unroll
                        for (int k = 1; k < NCL; k++) mn = min(min(mn, x[k].x), min(x[k].y, min(x[k].z, x[k].w)));
                        if (__all_sync(0xffffffffu, mn != 0)) break;
                        if (++guard > 2000000) __trap();
                    }
                    TS(2);
                    TV(4, guard);
                    const uint4 e0 = lds128(sb + O_BT);
                    bcast(IC<1>{}, e0, sum7(x[0].x, x[1].x, x[2].x, x[3].x, x[4].x, x[5].x, x[6].x), sum7(x[0].y, x[1].y, x[2].y, x[3].y, x[4].y, x[5].y, x[6].y),
                          sum7(x[0].z, x[1].z, x[2].z, x[3].z, x[4].z, x[5].z, x[6].z), sum7(x[0].w, x[1].w, x[2].w, x[3].w, x[4].w, x[5].w, x[6].w));
                } else {
                    uint2 p[5];
#pragma unroll
                    for (int i = 0; i < 5; i++) p[i] = i < 4 || nh == 5 ? lds64(ra + i * 256) : make_uint2(0, 0);
                    uint2* xh = reinterpret_cast<uint2*>(xb) + lane;
                    const uint32_t u1 = sum5(p[0].y, p[1].y, p[2].y, p[3].y, p[4].y);
                    st_relaxed_v2(xh + cq * 64, sum5(p[0].x, p[1].x, p[2].x, p[3].x, p[4].x), late ? u1 : m0);
                    if (lane == 0) mbar_expect_tx(bb + B_RED, nh * 1280);
                    TS(1);
                    delay(XD);
                    uint2 x[NCL];
                    while (true) {
#pragma unroll
                        for (int k = 0; k < NCL; k++) x[k] = ld_relaxed_v2(xh + k * 64);
                        uint32_t mn = min(x[0].x, x[0].y);
#pragma unroll
                        for (int k = 1; k < NCL; k++) mn = min(mn, min(x[k].x, x[k].y));
                        if (__all_sync(0xffffffffu, mn != 0)) break;
                        if (++guard > 2000000) __trap();
                    }
                    TS(2);
                    TV(4, guard);
                    const uint4 e0 = lds128(sb + O_BT);
                    bcast(IC<0>{}, e0, sum7(x[0].x, x[1].x, x[2].x, x[3].x, x[4].x, x[5].x, x[6].x), sum7(x[0].y, x[1].y, x[2].y, x[3].y, x[4].y, x[5].y, x[6].y), 0u, 0u);
                }
                TS(3);
                if (OT_LATE && head && role == 2) named_arrive(6, 128);
                slot = slot + 1 == XRS ? 0 : slot + 1;
                {
                    const int s2 = slot + 1 == XRS ? 0 : slot + 1;
                    uint4* zp = g_xc + ((s2 * 16 + r) * 3 + s) * 256 + cq * 32 + lane;
                    st_relaxed_v4(zp, 0, 0, 0, 0);
                    if (ld_relaxed_v4(zp).x) __trap();
                }
            }
        } else if (r < 2) {
            const uint16_t mask = (uint16_t)((1u << (3 * nh)) - 1u);
#pragma unroll 1
            for (int n = 0; n < NSEG; n++) {
                if (n == (r == 0 ? 1 : 0)) { cluster_arrive(); cluster_wait(); }
                int guard = 0;
                while (ld_acquire(FLG(F_H + r * 64 + n)) < A.h_target) { if (++guard > 2000000) __trap(); __nanosleep(40); }
                fence_async_global();
                if (H1_LATE && r == 1) named_bar(12, 160);
                if (n) mwait(bb + B_HE, (n - 1) & 1);
                if (lane < 8)
                    asm volatile("cp.async.bulk.shared::cluster.global.mbarrier::complete_tx::bytes.multicast::cluster [%0], [%1], %2, [%3], %4;" ::"r"(sb + O_H + r * 40960 + lane * 5120),
                                 "l"(g_ht + (r * NSEG + n) * 2560 + lane * 320), "r"(HBYTES), "r"(bb + B_HF + r * 8), "h"(mask) : "memory");
                __syncwarp();
            }
        } else {
            cluster_arrive(); cluster_wait();
            if (head && role == 2) {
#pragma unroll 1
                for (int t = 0; t < NT; t++) {
                    mwait(bb + B_OTF, t & 1);
                    if (OT_LATE && t < NT - 1) named_bar(6, 128);
                    const int l = lane & 1, n = t - l * LAG;
                    if (lane < 2 && n >= 0 && n < NSEG) {
                        asm volatile("cp.async.bulk.global.shared::cta.bulk_group [%0], [%1], %2;" ::"l"(g_ot + ((l * NSEG + n) * 256 + h * 8) * 64), "r"(sb + O_VT + (t & 1) * 16384 + l * 8192), "r"(8192) : "memory");
                        asm volatile("cp.async.bulk.commit_group;" ::: "memory");
                        asm volatile("cp.async.bulk.wait_group.read 0;" ::: "memory");
                    }
                    __syncwarp();
                    if (lane == 0) mbar_arrive(bb + B_OTE);
                    if (lane < 2 && n >= 0 && n < NSEG) {
                        asm volatile("cp.async.bulk.wait_group 0;" ::: "memory");
                        fence_async_global();
                        red_release(FLG(F_O + l * 64 + n) + (h >> 3), 1);
                    }
                    __syncwarp();
                }
            }
            if (!head && lane == 0) {
#pragma unroll 1
                for (int k = 0; k < 20; k++) {
                    const int rg = k / 5;
                    mwait(bb + B_OTF + (k & 1) * 8, (k >> 1) & 1);
                    asm volatile("cp.async.bulk.global.shared::cta.bulk_group [%0], [%1], %2;" ::"l"(g_Y + (sp * 5 + k - 5 * rg) * S_LEN + rg * 512), "r"(sb + CV_Y + (k & 1) * 8192), "r"(8192) : "memory");
                    asm volatile("cp.async.bulk.commit_group;" ::: "memory");
                    asm volatile("cp.async.bulk.wait_group 0;" ::: "memory");
                    mbar_arrive(bb + B_OTE + (k & 1) * 16);
                    fence_async_global();
                    red_release(FLG(F_CV + rg), 1);
                }
            }
            __syncwarp();
        }
    }
    cluster_arrive(); cluster_wait();
}
}

namespace ws {
constexpr int OP_SS = 17;
constexpr int P_RING = 0, P_AS = 131072, P_STG = P_AS + 2 * OP_SS * 2048, P_BAR = P_STG + 16384, OP_SMEM = P_BAR + 256;
constexpr int PB_FULL = 0, PB_EMPTY = 128, PB_SF = 144, PB_SE = 176;
static_assert(OP_SMEM <= 232448, "smem");

__global__ void __launch_bounds__(384, 1) op_kernel(const bf16* __restrict__ Wo) {
    extern __shared__ __align__(1024) unsigned char smem_raw[];
    const int tid = threadIdx.x, warp = __shfl_sync(0xffffffffu, tid >> 5, 0), lane = tid & 31;
    const int nb = blockIdx.x % 5, ks = blockIdx.x / 5;
    const uint32_t sb = smem_u32(smem_raw), bb = sb + P_BAR;
    if (tid == 0) {
        if ((sb & 0xFFFFFFu) != 1024) __trap();
        for (int i = 0; i < 16; i++) mbar_init(bb + PB_FULL + i * 8, 1);
        for (int i = 0; i < 2; i++) mbar_init(bb + PB_EMPTY + i * 8, 2);
        for (int i = 0; i < 4; i++) { mbar_init(bb + PB_SF + i * 8, 4); mbar_init(bb + PB_SE + i * 8, 1); }
        asm volatile("fence.mbarrier_init.release.cluster;" ::: "memory");
    }
    __syncthreads();
    if (warp < 4) {
        asm volatile("setmaxnreg.dec.sync.aligned.u32 40;");
        if (warp == 0) {
            named_bar(3, 288);
            uint32_t it = 0;
#pragma unroll 1
            for (int q = 0; q < 2 * NT; q++) {
                const int l = q & 1, n = (q >> 1) - l * LAG;
                if (n < 0 || n >= NSEG) continue;
                int guard = 0;
                while (ld_acquire(FLG(F_O + l * 64 + n) + ks) < 8) { if (++guard > 4000000) __trap(); __nanosleep(OP_NS); }
                fence_async_global();
                mwait(bb + PB_EMPTY + (it & 1) * 8, ((it >> 1) & 1) ^ 1);
                if (lane < 8) {
                    const uint32_t fb = bb + PB_FULL + ((it & 1) * 8 + lane) * 8;
                    mbar_expect_tx(fb, 8192);
                    asm volatile("cp.async.bulk.shared::cluster.global.mbarrier::complete_tx::bytes [%0], [%1], %2, [%3];" ::"r"(sb + P_RING + (it & 1) * 65536 + lane * 8192),
                                 "l"(g_ot + ((l * NSEG + n) * 256 + (ks * 8 + lane) * 8) * 64), "r"(8192), "r"(fb) : "memory");
                }
                __syncwarp();
                it++;
            }
        } else if (warp < 3 && lane == 0) {
            const int cw = warp - 1;
            uint32_t it = 0;
#pragma unroll 1
            for (int q = 0; q < 2 * NT; q++) {
                const int l = q & 1, n = (q >> 1) - l * LAG;
                if (n < 0 || n >= NSEG) continue;
                const uint32_t i = cw * 2 + (it & 1);
                mwait(bb + PB_SF + i * 8, (it >> 1) & 1);
                asm volatile("cp.async.bulk.global.shared::cta.bulk_group [%0], [%1], %2;" ::"l"(g_pt + (((l * NSEG + n) * 4 + ks) * 10 + nb * 2 + cw) * 256), "r"(sb + P_STG + i * 4096), "r"(4096) : "memory");
                asm volatile("cp.async.bulk.commit_group;" ::: "memory");
                asm volatile("cp.async.bulk.wait_group 0;" ::: "memory");
                mbar_arrive(bb + PB_SE + i * 8);
                fence_async_global();
                red_release(FLG(F_P + l * 64 + n), 1);
                it++;
            }
        }
    } else {
        asm volatile("setmaxnreg.inc.sync.aligned.u32 232;");
        const int cw = (warp >> 2) - 1, w4 = warp & 3, t7 = tid & 127;
        uint32_t wa[64 - OP_SS][4];
        {
            const bf16* W = Wo + (size_t)ks * 1024 * DM + nb * 128 + cw * 64 + (t7 & 7) * 8;
            const uint32_t so = (t7 >> 3) * 128 + (((t7 & 7) ^ ((t7 >> 3) & 7)) << 4);
            const uint32_t stg = sb + P_RING + cw * 65536;
            const uint32_t la = stg + ((lane & 7) + (lane >> 4) * 8) * 128 + (((w4 * 2 + ((lane >> 3) & 1)) ^ (lane & 7)) << 4);
#pragma unroll 4
            for (int i = 0; i < 32; i++) cp_async16(stg + i * 2048 + so, W + (size_t)((OP_SS + i) * 16 + (t7 >> 3)) * DM);
            cp_commit();
#pragma unroll 1
            for (int i = 0; i < OP_SS; i++) cp_async16(sb + P_AS + cw * OP_SS * 2048 + i * 2048 + so, W + (size_t)(i * 16 + (t7 >> 3)) * DM);
            cp_commit();
            cp_wait<1>();
            named_bar(1 + cw, 128);
#pragma unroll
            for (int j = 0; j < 32; j++) { const uint4 v = ldsm4t(la + j * 2048); wa[j][0] = v.x; wa[j][1] = v.y; wa[j][2] = v.z; wa[j][3] = v.w; }
            named_bar(1 + cw, 128);
#pragma unroll 1
            for (int i = 0; i < 32 - OP_SS; i++) cp_async16(stg + i * 2048 + so, W + (size_t)((OP_SS + 32 + i) * 16 + (t7 >> 3)) * DM);
            cp_commit();
            cp_wait<0>();
            named_bar(1 + cw, 128);
#pragma unroll
            for (int j = 0; j < 32 - OP_SS; j++) { const uint4 v = ldsm4t(la + j * 2048); wa[32 + j][0] = v.x; wa[32 + j][1] = v.y; wa[32 + j][2] = v.z; wa[32 + j][3] = v.w; }
            fence_async_smem();
            named_bar(3, 288);
        }
        const uint32_t ab = (1024 + P_AS + cw * OP_SS * 2048) >> 4;
        const int tk = 8 * ((lane & 7) >> 1) + 2 * (lane >> 4) + (lane & 1);
        const uint32_t ea = sb + P_STG + cw * 8192 + tk * 128 + (((2 * w4 + ((lane >> 3) & 1)) ^ (lane & 7)) << 4);
#pragma unroll 1
        for (uint32_t it = 0; it < 2 * NSEG; it++) {
            float acc[16];
            const uint32_t fb = bb + PB_FULL + (it & 1) * 64, par = (it >> 1) & 1;
            const uint32_t ob = opq(((1024 + P_RING) >> 4) + (it & 1) * 4096);
            uint32_t ok = 0;
#pragma unroll
            for (int j = 0; j < 64; j++) {
                if ((j & 7) == 0) {
                    if (j) wg_commit();
                    if (!ok) mwait(fb + j, par);
                    ok = j < 56 ? mtest(fb + j + 8, par) : mtest(bb + PB_SE + (cw * 2 + (it & 1)) * 8, par ^ 1);
                    if (j == 0) wg_fence();
                }
                const uint64_t db = mkdesc(ob + j * 64, 0x80000020u);
                if (j == 0) wg_n32t_sfirst(acc, mkdesc(ab, 0x40000040u), db);
                else if (j < OP_SS) wg_n32t_s(acc, mkdesc(ab + j * 128, 0x40000040u), db);
                else wg_n32t(acc, wa[j - OP_SS][0], wa[j - OP_SS][1], wa[j - OP_SS][2], wa[j - OP_SS][3], db);
            }
            wg_commit();
            if (!ok) mwait(bb + PB_SE + (cw * 2 + (it & 1)) * 8, par ^ 1);
            wg_wait<0>();
            if (t7 == 0) mbar_arrive(bb + PB_EMPTY + (it & 1) * 8);
            const uint32_t e = ea + (it & 1) * 4096;
            stsm4t(e, pack2(acc[0], acc[1]), pack2(acc[2], acc[3]), pack2(acc[4], acc[5]), pack2(acc[6], acc[7]));
            stsm4t(e + 512, pack2(acc[8], acc[9]), pack2(acc[10], acc[11]), pack2(acc[12], acc[13]), pack2(acc[14], acc[15]));
            fence_async_smem();
            __syncwarp();
            if (lane == 0) mbar_arrive(bb + PB_SF + (cw * 2 + (it & 1)) * 8);
        }
    }
}
}

namespace ws {
__global__ void reset_kernel() {
    const int i = blockIdx.x * blockDim.x + threadIdx.x;
    if (i < NFLAG * 2) reinterpret_cast<uint4*>(g_flags)[i] = make_uint4(0, 0, 0, 0);
    for (int k = i; k < 4 * 16 * 3 * 8 * 32; k += gridDim.x * blockDim.x) g_xc[k] = make_uint4(0, 0, 0, 0);
}
static void launch_all(void* const* d_in, void* d_out) {
    static bool inited = false;
    if (!inited) {
        inited = true;
        cudaFuncSetAttribute(head_kernel, cudaFuncAttributeMaxDynamicSharedMemorySize, HEAD_SMEM);
        cudaFuncSetAttribute(head_kernel, cudaFuncAttributeNonPortableClusterSizeAllowed, 1);
        cudaFuncSetAttribute(op_kernel, cudaFuncAttributeMaxDynamicSharedMemorySize, OP_SMEM);
    }
    HeadArgs A;
    A.x = (const bf16*)d_in[0]; A.mem0 = (const bf16*)d_in[1]; A.Wq = (const bf16*)d_in[2]; A.Wk = (const bf16*)d_in[3]; A.Wv = (const bf16*)d_in[4]; A.Wo = (const bf16*)d_in[5];
    A.Bk = (const bf16*)d_in[8]; A.Bv = (const bf16*)d_in[9]; A.shiftk = (const bf16*)d_in[10]; A.ssmk = (const bf16*)d_in[11]; A.ssmD = (const bf16*)d_in[12];
    A.out = (bf16*)d_out; A.h_target = 32;
    cudaStream_t s = cudaStreamPerThread;
    reset_kernel<<<48, 256, 0, s>>>();
    {
        cudaLaunchConfig_t cfg = {};
        cfg.gridDim = dim3(NCL * 16); cfg.blockDim = dim3(512); cfg.dynamicSmemBytes = HEAD_SMEM; cfg.stream = s;
        cudaLaunchAttribute at[1];
        at[0].id = cudaLaunchAttributeClusterDimension;
        at[0].val.clusterDim.x = 16; at[0].val.clusterDim.y = 1; at[0].val.clusterDim.z = 1;
        cfg.attrs = at; cfg.numAttrs = 1;
        cudaLaunchKernelEx(&cfg, head_kernel, A);
    }
    {
        cudaLaunchConfig_t cfg = {};
        cfg.gridDim = dim3(20); cfg.blockDim = dim3(384); cfg.dynamicSmemBytes = OP_SMEM; cfg.stream = s;
        cudaLaunchAttribute at[1];
        at[0].id = cudaLaunchAttributeProgrammaticStreamSerialization;
        at[0].val.programmaticStreamSerializationAllowed = 1;
        cfg.attrs = at; cfg.numAttrs = 1;
        cudaLaunchKernelEx(&cfg, op_kernel, A.Wo);
    }
}
}

extern "C" void kernel_launch(void* const* d_in, const int* in_sizes, int n_in, void* d_out, int out_size) {
    (void)in_sizes; (void)n_in; (void)out_size;
    ws::launch_all(d_in, d_out);
}
```

```cpp
#include <cuda_runtime.h>
#include <cuda_bf16.h>
#include <stdint.h>
#include <cuda.h>

typedef __nv_bfloat16 bf16;
namespace ws {
constexpr int S_LEN = 2048, DM = 640, NH = 32, DH = 128, HD = NH * DH, SEG = 32, NSEG = S_LEN / SEG;

__device__ __forceinline__ float bf2f(bf16 v) { return __bfloat162float(v); }
__device__ __forceinline__ float rbf(float v) { return __bfloat162float(__float2bfloat16_rn(v)); }
__device__ __forceinline__ uint32_t pack2(float a, float b) {
    __nv_bfloat162 t = __floats2bfloat162_rn(a, b);
    return *reinterpret_cast<uint32_t*>(&t);
}
__device__ __forceinline__ float blo(uint32_t v) { return __uint_as_float(v << 16); }
__device__ __forceinline__ float bhi(uint32_t v) { return __uint_as_float(v & 0xffff0000u); }
__device__ __forceinline__ uint32_t badd(uint32_t a, uint32_t b) { uint32_t r; asm("add.rn.bf16x2 %0, %1, %2;" : "=r"(r) : "r"(a), "r"(b)); return r; }
__device__ __forceinline__ uint32_t smem_u32(const void* p) { return (uint32_t)__cvta_generic_to_shared(p); }
__device__ __forceinline__ uint4 ldsm4(uint32_t a) {
    uint4 v;
    asm volatile("ldmatrix.sync.aligned.m8n8.x4.shared.b16 {%0,%1,%2,%3}, [%4];" : "=r"(v.x), "=r"(v.y), "=r"(v.z), "=r"(v.w) : "r"(a));
    return v;
}
__device__ __forceinline__ uint4 ldsm4t(uint32_t a) {
    uint4 v;
    asm volatile("ldmatrix.sync.aligned.m8n8.x4.trans.shared.b16 {%0,%1,%2,%3}, [%4];" : "=r"(v.x), "=r"(v.y), "=r"(v.z), "=r"(v.w) : "r"(a));
    return v;
}
__device__ __forceinline__ uint2 ldsm2t(uint32_t a) {
    uint2 v;
    asm volatile("ldmatrix.sync.aligned.m8n8.x2.trans.shared.b16 {%0,%1}, [%2];" : "=r"(v.x), "=r"(v.y) : "r"(a));
    return v;
}
__device__ __forceinline__ void stsm4(uint32_t a, uint32_t r0, uint32_t r1, uint32_t r2, uint32_t r3) {
    asm volatile("stmatrix.sync.aligned.m8n8.x4.shared.b16 [%0], {%1,%2,%3,%4};" ::"r"(a), "r"(r0), "r"(r1), "r"(r2), "r"(r3) : "memory");
}
__device__ __forceinline__ void stsm2(uint32_t a, uint32_t r0, uint32_t r1) {
    asm volatile("stmatrix.sync.aligned.m8n8.x2.shared.b16 [%0], {%1,%2};" ::"r"(a), "r"(r0), "r"(r1) : "memory");
}
__device__ __forceinline__ void stsm4t(uint32_t a, uint32_t r0, uint32_t r1, uint32_t r2, uint32_t r3) {
    asm volatile("stmatrix.sync.aligned.m8n8.x4.trans.shared.b16 [%0], {%1,%2,%3,%4};" ::"r"(a), "r"(r0), "r"(r1), "r"(r2), "r"(r3) : "memory");
}
__device__ __forceinline__ void mma16816(float* c, uint32_t a0, uint32_t a1, uint32_t a2, uint32_t a3, uint32_t b0, uint32_t b1) {
    asm("mma.sync.aligned.m16n8k16.row.col.f32.bf16.bf16.f32 {%0,%1,%2,%3}, {%4,%5,%6,%7}, {%8,%9}, {%0,%1,%2,%3};"
        : "+f"(c[0]), "+f"(c[1]), "+f"(c[2]), "+f"(c[3]) : "r"(a0), "r"(a1), "r"(a2), "r"(a3), "r"(b0), "r"(b1));
}
__device__ __forceinline__ void mmav(float* c, uint32_t a0, uint32_t a1, uint32_t a2, uint32_t a3, uint32_t b0, uint32_t b1) {
    asm volatile("mma.sync.aligned.m16n8k16.row.col.f32.bf16.bf16.f32 {%0,%1,%2,%3}, {%4,%5,%6,%7}, {%8,%9}, {%0,%1,%2,%3};"
        : "+f"(c[0]), "+f"(c[1]), "+f"(c[2]), "+f"(c[3]) : "r"(a0), "r"(a1), "r"(a2), "r"(a3), "r"(b0), "r"(b1));
}
__device__ __forceinline__ void mmau(float* c, const uint4& a, uint32_t b0, uint32_t b1) { mma16816(c, a.x, a.y, a.z, a.w, b0, b1); }
__device__ __forceinline__ void mma1688(float* c, uint32_t a0, uint32_t a1, uint32_t b0) {
    asm("mma.sync.aligned.m16n8k8.row.col.f32.bf16.bf16.f32 {%0,%1,%2,%3}, {%4,%5}, {%6}, {%0,%1,%2,%3};"
        : "+f"(c[0]), "+f"(c[1]), "+f"(c[2]), "+f"(c[3]) : "r"(a0), "r"(a1), "r"(b0));
}
__device__ __forceinline__ void mmav8(float* c, uint32_t a0, uint32_t a1, uint32_t b0) {
    asm volatile("mma.sync.aligned.m16n8k8.row.col.f32.bf16.bf16.f32 {%0,%1,%2,%3}, {%4,%5}, {%6}, {%0,%1,%2,%3};"
        : "+f"(c[0]), "+f"(c[1]), "+f"(c[2]), "+f"(c[3]) : "r"(a0), "r"(a1), "r"(b0));
}
__device__ __forceinline__ void cp_async16(uint32_t dst, const void* src) { asm volatile("cp.async.cg.shared.global [%0], [%1], 16;" ::"r"(dst), "l"(src)); }
__device__ __forceinline__ void cp_commit() { asm volatile("cp.async.commit_group;"); }
template <int N> __device__ __forceinline__ void cp_wait() { asm volatile("cp.async.wait_group %0;" ::"n"(N)); }
__device__ __forceinline__ uint4 lds128(uint32_t a) {
    uint4 v;
    asm volatile("ld.shared.v4.u32 {%0,%1,%2,%3}, [%4];" : "=r"(v.x), "=r"(v.y), "=r"(v.z), "=r"(v.w) : "r"(a));
    return v;
}
__device__ __forceinline__ uint2 lds64(uint32_t a) {
    uint2 v;
    asm volatile("ld.shared.v2.u32 {%0,%1}, [%2];" : "=r"(v.x), "=r"(v.y) : "r"(a));
    return v;
}
__device__ __forceinline__ uint32_t lds32(uint32_t a) { uint32_t v; asm volatile("ld.shared.u32 %0, [%1];" : "=r"(v) : "r"(a)); return v; }
__device__ __forceinline__ void sts32(uint32_t a, uint32_t x) { asm volatile("st.shared.u32 [%0], %1;" ::"r"(a), "r"(x) : "memory"); }
__device__ __forceinline__ void sts128(uint32_t a, uint32_t x, uint32_t y, uint32_t z, uint32_t w) {
    asm volatile("st.shared.v4.u32 [%0], {%1,%2,%3,%4};" ::"r"(a), "r"(x), "r"(y), "r"(z), "r"(w) : "memory");
}
__device__ __forceinline__ uint4 ld_relaxed_v4(const void* p) {
    uint4 v;
    asm volatile("ld.relaxed.gpu.global.v4.u32 {%0,%1,%2,%3}, [%4];" : "=r"(v.x), "=r"(v.y), "=r"(v.z), "=r"(v.w) : "l"(p) : "memory");
    return v;
}
__device__ __forceinline__ uint2 ld_relaxed_v2(const void* p) {
    uint2 v;
    asm volatile("ld.relaxed.gpu.global.v2.u32 {%0,%1}, [%2];" : "=r"(v.x), "=r"(v.y) : "l"(p) : "memory");
    return v;
}
__device__ __forceinline__ void ld7_relaxed(uint4* x, const void* p) {
    asm volatile("ld.relaxed.gpu.global.v4.u32 {%0,%1,%2,%3}, [%28 + 0];\nld.relaxed.gpu.global.v4.u32 {%4,%5,%6,%7}, [%28 + 512];\nld.relaxed.gpu.global.v4.u32 {%8,%9,%10,%11}, [%28 + 1024];\nld.relaxed.gpu.global.v4.u32 {%12,%13,%14,%15}, [%28 + 1536];\nld.relaxed.gpu.global.v4.u32 {%16,%17,%18,%19}, [%28 + 2048];\nld.relaxed.gpu.global.v4.u32 {%20,%21,%22,%23}, [%28 + 2560];\nld.relaxed.gpu.global.v4.u32 {%24,%25,%26,%27}, [%28 + 3072];\n" : "=r"(x[0].x), "=r"(x[0].y), "=r"(x[0].z), "=r"(x[0].w), "=r"(x[1].x), "=r"(x[1].y), "=r"(x[1].z), "=r"(x[1].w), "=r"(x[2].x), "=r"(x[2].y), "=r"(x[2].z), "=r"(x[2].w), "=r"(x[3].x), "=r"(x[3].y), "=r"(x[3].z), "=r"(x[3].w), "=r"(x[4].x), "=r"(x[4].y), "=r"(x[4].z), "=r"(x[4].w), "=r"(x[5].x), "=r"(x[5].y), "=r"(x[5].z), "=r"(x[5].w), "=r"(x[6].x), "=r"(x[6].y), "=r"(x[6].z), "=r"(x[6].w) : "l"(p) : "memory");
}
__device__ __forceinline__ void ld7_relaxed(uint2* x, const void* p) {
    asm volatile("ld.relaxed.gpu.global.v2.u32 {%0,%1}, [%14 + 0];\nld.relaxed.gpu.global.v2.u32 {%2,%3}, [%14 + 512];\nld.relaxed.gpu.global.v2.u32 {%4,%5}, [%14 + 1024];\nld.relaxed.gpu.global.v2.u32 {%6,%7}, [%14 + 1536];\nld.relaxed.gpu.global.v2.u32 {%8,%9}, [%14 + 2048];\nld.relaxed.gpu.global.v2.u32 {%10,%11}, [%14 + 2560];\nld.relaxed.gpu.global.v2.u32 {%12,%13}, [%14 + 3072];\n" : "=r"(x[0].x), "=r"(x[0].y), "=r"(x[1].x), "=r"(x[1].y), "=r"(x[2].x), "=r"(x[2].y), "=r"(x[3].x), "=r"(x[3].y), "=r"(x[4].x), "=r"(x[4].y), "=r"(x[5].x), "=r"(x[5].y), "=r"(x[6].x), "=r"(x[6].y) : "l"(p) : "memory");
}
__device__ __forceinline__ void st_relaxed_v4(void* p, uint32_t a, uint32_t b, uint32_t c, uint32_t d) {
    asm volatile("st.relaxed.gpu.global.v4.u32 [%0], {%1,%2,%3,%4};" ::"l"(p), "r"(a), "r"(b), "r"(c), "r"(d) : "memory");
}
__device__ __forceinline__ void st_relaxed_v2(void* p, uint32_t a, uint32_t b) {
    asm volatile("st.relaxed.gpu.global.v2.u32 [%0], {%1,%2};" ::"l"(p), "r"(a), "r"(b) : "memory");
}
__device__ __forceinline__ int ld_relaxed(const int* p) {
    int v;
    asm volatile("ld.relaxed.gpu.global.u32 %0, [%1];" : "=r"(v) : "l"(p) : "memory");
    return v;
}
__device__ __forceinline__ int ld_acquire(const int* p) {
    int v;
    asm volatile("ld.acquire.gpu.global.u32 %0, [%1];" : "=r"(v) : "l"(p) : "memory");
    return v;
}
__device__ __forceinline__ void red_release(int* p, int v) { asm volatile("red.release.gpu.global.add.u32 [%0], %1;" ::"l"(p), "r"(v) : "memory"); }
__device__ __forceinline__ void mbar_init(uint32_t bar, int count) { asm volatile("mbarrier.init.shared::cta.b64 [%0], %1;" ::"r"(bar), "r"(count)); }
__device__ __forceinline__ void mbar_expect_tx(uint32_t bar, uint32_t bytes) {
    asm volatile("mbarrier.arrive.expect_tx.shared::cta.b64 _, [%0], %1;" ::"r"(bar), "r"(bytes) : "memory");
}
__device__ __forceinline__ void mbar_arrive(uint32_t bar) { asm volatile("mbarrier.arrive.shared::cta.b64 _, [%0];" ::"r"(bar) : "memory"); }
__device__ __forceinline__ void mbar_arrive_cluster(uint32_t bar) { asm volatile("mbarrier.arrive.shared::cluster.b64 _, [%0];" ::"r"(bar) : "memory"); }
__device__ __forceinline__ void mwait(uint32_t bar, uint32_t parity) {
    asm volatile(
        "{\n.reg .pred P1;\n.reg .u32 cnt;\n"
        "mbarrier.try_wait.parity.shared::cta.b64 P1, [%0], %1;\n"
        "@P1 bra DONE;\n"
        "mov.u32 cnt, 0;\n"
        "LAB_WAIT:\n"
        "mbarrier.try_wait.parity.shared::cta.b64 P1, [%0], %1;\n"
        "@P1 bra DONE;\n"
        "add.u32 cnt, cnt, 1;\n"
        "setp.lt.u32 P1, cnt, 1000000;\n"
        "@P1 bra LAB_WAIT;\n"
        "trap;\n"
        "DONE:\n}\n" ::"r"(bar), "r"(parity) : "memory");
}
__device__ __forceinline__ uint32_t mtest(uint32_t bar, uint32_t parity) {
    uint32_t ok;
    asm volatile("{\n.reg .pred P1;\nmbarrier.test_wait.parity.shared::cta.b64 P1, [%1], %2;\nselp.u32 %0, 1, 0, P1;\n}\n" : "=r"(ok) : "r"(bar), "r"(parity) : "memory");
    return ok;
}
__device__ __forceinline__ uint32_t mapa(uint32_t addr, uint32_t rank) {
    uint32_t r;
    asm("mapa.shared::cluster.u32 %0, %1, %2;" : "=r"(r) : "r"(addr), "r"(rank));
    return r;
}
__device__ __forceinline__ void st_async_b32(uint32_t addr, uint32_t a, uint32_t bar) {
    asm volatile("st.async.weak.shared::cluster.mbarrier::complete_tx::bytes.b32 [%0], %1, [%2];" ::"r"(addr), "r"(a), "r"(bar) : "memory");
}
__device__ __forceinline__ void st_async_v2(uint32_t addr, uint32_t a, uint32_t b, uint32_t bar) {
    asm volatile("st.async.weak.shared::cluster.mbarrier::complete_tx::bytes.v2.b32 [%0], {%1,%2}, [%3];" ::"r"(addr), "r"(a), "r"(b), "r"(bar) : "memory");
}
__device__ __forceinline__ void st_async_v2_lt(uint32_t addr, uint32_t a, uint32_t b, uint32_t bar, uint32_t x, uint32_t lim) {
    asm volatile("{\n.reg .pred p;\nsetp.lt.u32 p, %4, %5;\n@p st.async.weak.shared::cluster.mbarrier::complete_tx::bytes.v2.b32 [%0], {%1,%2}, [%3];\n}"
                 ::"r"(addr), "r"(a), "r"(b), "r"(bar), "r"(x), "r"(lim) : "memory");
}
__device__ __forceinline__ void st_async_v4(uint32_t addr, uint32_t a, uint32_t b, uint32_t c, uint32_t d, uint32_t bar) {
    asm volatile("st.async.weak.shared::cluster.mbarrier::complete_tx::bytes.v4.b32 [%0], {%1,%2,%3,%4}, [%5];" ::"r"(addr), "r"(a), "r"(b), "r"(c), "r"(d), "r"(bar) : "memory");
}
__device__ __forceinline__ void cluster_arrive() { asm volatile("barrier.cluster.arrive.release.aligned;" ::: "memory"); }
__device__ __forceinline__ void cluster_arrive_relaxed() { asm volatile("barrier.cluster.arrive.relaxed.aligned;" ::: "memory"); }
__device__ __forceinline__ void prefetch_l2(const void* p, uint32_t bytes) { asm volatile("cp.async.bulk.prefetch.L2.global [%0], %1;" ::"l"(p), "r"(bytes) : "memory"); }
__device__ __forceinline__ void cluster_wait() { asm volatile("barrier.cluster.wait.acquire.aligned;" ::: "memory"); }
__device__ __forceinline__ void named_bar(int id, int n) { asm volatile("bar.sync %0, %1;" ::"r"(id), "r"(n) : "memory"); }
__device__ __forceinline__ void named_arrive(int id, int n) { asm volatile("bar.arrive %0, %1;" ::"r"(id), "r"(n) : "memory"); }
__device__ __forceinline__ void fence_async_smem() { asm volatile("fence.proxy.async.shared::cta;" ::: "memory"); }
__device__ __forceinline__ void fence_async_global() { asm volatile("fence.proxy.async.global;" ::: "memory"); }
__device__ __forceinline__ void wg_fence() { asm volatile("wgmma.fence.sync.aligned;" ::: "memory"); }
__device__ __forceinline__ void wg_commit() { asm volatile("wgmma.commit_group.sync.aligned;" ::: "memory"); }
template <int N> __device__ __forceinline__ void wg_wait() { asm volatile("wgmma.wait_group.sync.aligned %0;" ::"n"(N) : "memory"); }
__device__ __forceinline__ uint64_t ndesc(uint32_t addr, uint32_t lbo, uint32_t sbo) {
    return (uint64_t)((addr & 0x3FFFF) >> 4) | ((uint64_t)(lbo >> 4) << 16) | ((uint64_t)(sbo >> 4) << 32);
}
__device__ __forceinline__ float ex2f(float x) { float y; asm("ex2.approx.ftz.f32 %0, %1;" : "=f"(y) : "f"(x)); return y; }
__device__ __forceinline__ float rcpf(float x) { float y; asm("rcp.approx.ftz.f32 %0, %1;" : "=f"(y) : "f"(x)); return y; }
__device__ __forceinline__ uint32_t clk32() { uint32_t c; asm volatile("mov.u32 %0, %clock;" : "=r"(c)); return c; }
__device__ __forceinline__ uint32_t opq(uint32_t x) { uint32_t y; asm volatile("mov.u32 %0, %1;" : "=r"(y) : "r"(x)); return y; }
__device__ __forceinline__ uint32_t rem(uint32_t addr, uint32_t rank) { return mapa(addr, rank); }
__device__ __forceinline__ uint64_t mkdesc(uint32_t lo, uint32_t hi) { uint64_t d; asm("mov.b64 %0, {%1,%2};" : "=l"(d) : "r"(lo), "r"(hi)); return d; }
__device__ __forceinline__ void delay(uint32_t n) { const uint32_t t0 = clk32(); while (__any_sync(0xffffffffu, clk32() - t0 < n)) {} }
#define UNI(x) __shfl_sync(0xffffffffu, (uint32_t)(x), 0)
__device__ __forceinline__ void wg_n16t(float* d, uint32_t a0, uint32_t a1, uint32_t a2, uint32_t a3, uint64_t db) {
    asm volatile("wgmma.mma_async.sync.aligned.m64n16k16.f32.bf16.bf16 {%0, %1, %2, %3, %4, %5, %6, %7}, {%8, %9, %10, %11}, %12, 1, 1, 1, 1;"
                 : "+f"(d[0]), "+f"(d[1]), "+f"(d[2]), "+f"(d[3]), "+f"(d[4]), "+f"(d[5]), "+f"(d[6]), "+f"(d[7]) : "r"(a0), "r"(a1), "r"(a2), "r"(a3), "l"(db));
}
__device__ __forceinline__ void wg_n16t_first(float* d, uint32_t a0, uint32_t a1, uint32_t a2, uint32_t a3, uint64_t db) {
    asm volatile("wgmma.mma_async.sync.aligned.m64n16k16.f32.bf16.bf16 {%0, %1, %2, %3, %4, %5, %6, %7}, {%8, %9, %10, %11}, %12, 0, 1, 1, 1;"
                 : "=f"(d[0]), "=f"(d[1]), "=f"(d[2]), "=f"(d[3]), "=f"(d[4]), "=f"(d[5]), "=f"(d[6]), "=f"(d[7]) : "r"(a0), "r"(a1), "r"(a2), "r"(a3), "l"(db));
}
__device__ __forceinline__ void wg_n32(float* d, uint32_t a0, uint32_t a1, uint32_t a2, uint32_t a3, uint64_t db) {
    asm volatile("wgmma.mma_async.sync.aligned.m64n32k16.f32.bf16.bf16 {%0, %1, %2, %3, %4, %5, %6, %7, %8, %9, %10, %11, %12, %13, %14, %15}, {%16, %17, %18, %19}, %20, 1, 1, 1, 0;"
                 : "+f"(d[0]), "+f"(d[1]), "+f"(d[2]), "+f"(d[3]), "+f"(d[4]), "+f"(d[5]), "+f"(d[6]), "+f"(d[7]), "+f"(d[8]), "+f"(d[9]), "+f"(d[10]), "+f"(d[11]), "+f"(d[12]), "+f"(d[13]), "+f"(d[14]), "+f"(d[15]) : "r"(a0), "r"(a1), "r"(a2), "r"(a3), "l"(db));
}
__device__ __forceinline__ void wg_n32_first(float* d, uint32_t a0, uint32_t a1, uint32_t a2, uint32_t a3, uint64_t db) {
    asm volatile("wgmma.mma_async.sync.aligned.m64n32k16.f32.bf16.bf16 {%0, %1, %2, %3, %4, %5, %6, %7, %8, %9, %10, %11, %12, %13, %14, %15}, {%16, %17, %18, %19}, %20, 0, 1, 1, 0;"
                 : "=f"(d[0]), "=f"(d[1]), "=f"(d[2]), "=f"(d[3]), "=f"(d[4]), "=f"(d[5]), "=f"(d[6]), "=f"(d[7]), "=f"(d[8]), "=f"(d[9]), "=f"(d[10]), "=f"(d[11]), "=f"(d[12]), "=f"(d[13]), "=f"(d[14]), "=f"(d[15]) : "r"(a0), "r"(a1), "r"(a2), "r"(a3), "l"(db));
}

__device__ __forceinline__ void wg_n16t_sfirst(float* d, uint64_t da, uint64_t db) {
    asm volatile("wgmma.mma_async.sync.aligned.m64n16k16.f32.bf16.bf16 {%0, %1, %2, %3, %4, %5, %6, %7}, %8, %9, 0, 1, 1, 1, 1;"
                 : "=f"(d[0]), "=f"(d[1]), "=f"(d[2]), "=f"(d[3]), "=f"(d[4]), "=f"(d[5]), "=f"(d[6]), "=f"(d[7]) : "l"(da), "l"(db));
}
__device__ __forceinline__ void wg_n32_sfirst(float* d, uint64_t da, uint64_t db) {
    asm volatile("wgmma.mma_async.sync.aligned.m64n32k16.f32.bf16.bf16 {%0, %1, %2, %3, %4, %5, %6, %7, %8, %9, %10, %11, %12, %13, %14, %15}, %16, %17, 0, 1, 1, 1, 0;"
                 : "=f"(d[0]), "=f"(d[1]), "=f"(d[2]), "=f"(d[3]), "=f"(d[4]), "=f"(d[5]), "=f"(d[6]), "=f"(d[7]), "=f"(d[8]), "=f"(d[9]), "=f"(d[10]), "=f"(d[11]), "=f"(d[12]), "=f"(d[13]), "=f"(d[14]), "=f"(d[15]) : "l"(da), "l"(db));
}

__device__ __forceinline__ void wg_n16t_s(float* d, uint64_t da, uint64_t db) {
    asm volatile("wgmma.mma_async.sync.aligned.m64n16k16.f32.bf16.bf16 {%0, %1, %2, %3, %4, %5, %6, %7}, %8, %9, 1, 1, 1, 1, 1;"
                 : "+f"(d[0]), "+f"(d[1]), "+f"(d[2]), "+f"(d[3]), "+f"(d[4]), "+f"(d[5]), "+f"(d[6]), "+f"(d[7]) : "l"(da), "l"(db));
}
__device__ __forceinline__ void wg_n64_sfirst(float* d, uint64_t da, uint64_t db) {
    asm volatile("wgmma.mma_async.sync.aligned.m64n64k16.f32.bf16.bf16 {%0, %1, %2, %3, %4, %5, %6, %7, %8, %9, %10, %11, %12, %13, %14, %15, %16, %17, %18, %19, %20, %21, %22, %23, %24, %25, %26, %27, %28, %29, %30, %31}, %32, %33, 0, 1, 1, 1, 0;"
                 : "=f"(d[0]), "=f"(d[1]), "=f"(d[2]), "=f"(d[3]), "=f"(d[4]), "=f"(d[5]), "=f"(d[6]), "=f"(d[7]), "=f"(d[8]), "=f"(d[9]), "=f"(d[10]), "=f"(d[11]), "=f"(d[12]), "=f"(d[13]), "=f"(d[14]), "=f"(d[15]), "=f"(d[16]), "=f"(d[17]), "=f"(d[18]), "=f"(d[19]), "=f"(d[20]), "=f"(d[21]), "=f"(d[22]), "=f"(d[23]), "=f"(d[24]), "=f"(d[25]), "=f"(d[26]), "=f"(d[27]), "=f"(d[28]), "=f"(d[29]), "=f"(d[30]), "=f"(d[31]) : "l"(da), "l"(db));
}
__device__ __forceinline__ void wg_n64_s(float* d, uint64_t da, uint64_t db) {
    asm volatile("wgmma.mma_async.sync.aligned.m64n64k16.f32.bf16.bf16 {%0, %1, %2, %3, %4, %5, %6, %7, %8, %9, %10, %11, %12, %13, %14, %15, %16, %17, %18, %19, %20, %21, %22, %23, %24, %25, %26, %27, %28, %29, %30, %31}, %32, %33, 1, 1, 1, 1, 0;"
                 : "+f"(d[0]), "+f"(d[1]), "+f"(d[2]), "+f"(d[3]), "+f"(d[4]), "+f"(d[5]), "+f"(d[6]), "+f"(d[7]), "+f"(d[8]), "+f"(d[9]), "+f"(d[10]), "+f"(d[11]), "+f"(d[12]), "+f"(d[13]), "+f"(d[14]), "+f"(d[15]), "+f"(d[16]), "+f"(d[17]), "+f"(d[18]), "+f"(d[19]), "+f"(d[20]), "+f"(d[21]), "+f"(d[22]), "+f"(d[23]), "+f"(d[24]), "+f"(d[25]), "+f"(d[26]), "+f"(d[27]), "+f"(d[28]), "+f"(d[29]), "+f"(d[30]), "+f"(d[31]) : "l"(da), "l"(db));
}
__device__ __forceinline__ void wg_n64(float* d, uint32_t a0, uint32_t a1, uint32_t a2, uint32_t a3, uint64_t db) {
    asm volatile("wgmma.mma_async.sync.aligned.m64n64k16.f32.bf16.bf16 {%0, %1, %2, %3, %4, %5, %6, %7, %8, %9, %10, %11, %12, %13, %14, %15, %16, %17, %18, %19, %20, %21, %22, %23, %24, %25, %26, %27, %28, %29, %30, %31}, {%32, %33, %34, %35}, %36, 1, 1, 1, 0;"
                 : "+f"(d[0]), "+f"(d[1]), "+f"(d[2]), "+f"(d[3]), "+f"(d[4]), "+f"(d[5]), "+f"(d[6]), "+f"(d[7]), "+f"(d[8]), "+f"(d[9]), "+f"(d[10]), "+f"(d[11]), "+f"(d[12]), "+f"(d[13]), "+f"(d[14]), "+f"(d[15]), "+f"(d[16]), "+f"(d[17]), "+f"(d[18]), "+f"(d[19]), "+f"(d[20]), "+f"(d[21]), "+f"(d[22]), "+f"(d[23]), "+f"(d[24]), "+f"(d[25]), "+f"(d[26]), "+f"(d[27]), "+f"(d[28]), "+f"(d[29]), "+f"(d[30]), "+f"(d[31]) : "r"(a0), "r"(a1), "r"(a2), "r"(a3), "l"(db));
}
__device__ __forceinline__ void wg_n64_first(float* d, uint32_t a0, uint32_t a1, uint32_t a2, uint32_t a3, uint64_t db) {
    asm volatile("wgmma.mma_async.sync.aligned.m64n64k16.f32.bf16.bf16 {%0, %1, %2, %3, %4, %5, %6, %7, %8, %9, %10, %11, %12, %13, %14, %15, %16, %17, %18, %19, %20, %21, %22, %23, %24, %25, %26, %27, %28, %29, %30, %31}, {%32, %33, %34, %35}, %36, 0, 1, 1, 0;"
                 : "=f"(d[0]), "=f"(d[1]), "=f"(d[2]), "=f"(d[3]), "=f"(d[4]), "=f"(d[5]), "=f"(d[6]), "=f"(d[7]), "=f"(d[8]), "=f"(d[9]), "=f"(d[10]), "=f"(d[11]), "=f"(d[12]), "=f"(d[13]), "=f"(d[14]), "=f"(d[15]), "=f"(d[16]), "=f"(d[17]), "=f"(d[18]), "=f"(d[19]), "=f"(d[20]), "=f"(d[21]), "=f"(d[22]), "=f"(d[23]), "=f"(d[24]), "=f"(d[25]), "=f"(d[26]), "=f"(d[27]), "=f"(d[28]), "=f"(d[29]), "=f"(d[30]), "=f"(d[31]) : "r"(a0), "r"(a1), "r"(a2), "r"(a3), "l"(db));
}

__device__ __forceinline__ void wg_n32t(float* d, uint32_t a0, uint32_t a1, uint32_t a2, uint32_t a3, uint64_t db) {
    asm volatile("wgmma.mma_async.sync.aligned.m64n32k16.f32.bf16.bf16 {%0, %1, %2, %3, %4, %5, %6, %7, %8, %9, %10, %11, %12, %13, %14, %15}, {%16, %17, %18, %19}, %20, 1, 1, 1, 1;"
                 : "+f"(d[0]), "+f"(d[1]), "+f"(d[2]), "+f"(d[3]), "+f"(d[4]), "+f"(d[5]), "+f"(d[6]), "+f"(d[7]), "+f"(d[8]), "+f"(d[9]), "+f"(d[10]), "+f"(d[11]), "+f"(d[12]), "+f"(d[13]), "+f"(d[14]), "+f"(d[15]) : "r"(a0), "r"(a1), "r"(a2), "r"(a3), "l"(db));
}
__device__ __forceinline__ void wg_n32t_first(float* d, uint32_t a0, uint32_t a1, uint32_t a2, uint32_t a3, uint64_t db) {
    asm volatile("wgmma.mma_async.sync.aligned.m64n32k16.f32.bf16.bf16 {%0, %1, %2, %3, %4, %5, %6, %7, %8, %9, %10, %11, %12, %13, %14, %15}, {%16, %17, %18, %19}, %20, 0, 1, 1, 1;"
                 : "=f"(d[0]), "=f"(d[1]), "=f"(d[2]), "=f"(d[3]), "=f"(d[4]), "=f"(d[5]), "=f"(d[6]), "=f"(d[7]), "=f"(d[8]), "=f"(d[9]), "=f"(d[10]), "=f"(d[11]), "=f"(d[12]), "=f"(d[13]), "=f"(d[14]), "=f"(d[15]) : "r"(a0), "r"(a1), "r"(a2), "r"(a3), "l"(db));
}
__device__ __forceinline__ void wg_n32t_sfirst(float* d, uint64_t da, uint64_t db) {
    asm volatile("wgmma.mma_async.sync.aligned.m64n32k16.f32.bf16.bf16 {%0, %1, %2, %3, %4, %5, %6, %7, %8, %9, %10, %11, %12, %13, %14, %15}, %16, %17, 0, 1, 1, 1, 1;"
                 : "=f"(d[0]), "=f"(d[1]), "=f"(d[2]), "=f"(d[3]), "=f"(d[4]), "=f"(d[5]), "=f"(d[6]), "=f"(d[7]), "=f"(d[8]), "=f"(d[9]), "=f"(d[10]), "=f"(d[11]), "=f"(d[12]), "=f"(d[13]), "=f"(d[14]), "=f"(d[15]) : "l"(da), "l"(db));
}
__device__ __forceinline__ void wg_n32t_s(float* d, uint64_t da, uint64_t db) {
    asm volatile("wgmma.mma_async.sync.aligned.m64n32k16.f32.bf16.bf16 {%0, %1, %2, %3, %4, %5, %6, %7, %8, %9, %10, %11, %12, %13, %14, %15}, %16, %17, 1, 1, 1, 1, 1;"
                 : "+f"(d[0]), "+f"(d[1]), "+f"(d[2]), "+f"(d[3]), "+f"(d[4]), "+f"(d[5]), "+f"(d[6]), "+f"(d[7]), "+f"(d[8]), "+f"(d[9]), "+f"(d[10]), "+f"(d[11]), "+f"(d[12]), "+f"(d[13]), "+f"(d[14]), "+f"(d[15]) : "l"(da), "l"(db));
}

}

namespace ws {
#define LAGT 4
constexpr int LAG = LAGT, NT = NSEG + LAG, NCL = 7;
#define P1A 26
#define P1C 22
#define XD 300
#define TPV_PAUSE 1
#define OT_LATE 1
#define H1_LATE 1
#define O_BULK 0
#define O_DLY 0
#define BP 0
#define REG_G 200
#define REG_T 72
#define REG_X 40
#define PDA 8
#define PDC 8
template <int V> struct IC { static constexpr int value = V; };
#define HBYTES 5120
#define POST_NS 40
#define OP_NS 40
#define LN0_AHEAD 8
#define PRE_PDL 0
#define PRE_PF 0
#define OP_LATE 0
#define G_DLY 0
#define QUIET 0
constexpr int NB4 = QUIET ? 480 : 384;
#define TG_STEPS 40
#define NO_X 0
#define WTA 4
constexpr int WTC = 10 - 2 * WTA;
constexpr int XRS = ((NT - 2) % 3 == 0) ? 4 : 3;
constexpr int O_H = 0, O_MEM = 81920, O_RED = 102400, O_BAR = 108800, O_TAB = O_BAR + 192, O_BT = O_TAB + 128, O_TR = 109312, O_X = O_TR + 2048;
constexpr int O_QRY = O_X, O_KEY = O_X + 10240, O_OBA = O_KEY + 10240, O_ST = O_OBA + 4096;
constexpr int O_VT = O_X, O_VM = O_VT + 32768, O_SM = O_VM + 4096, O_PB = O_SM + 3072;
constexpr int O_AS = 228352, O_WO = O_AS - 65536, HEAD_SMEM = O_AS + 4096, O_STG = 40960;
static_assert(O_ST + 4096 <= O_WO && O_PB + 10240 <= O_WO && O_AS % 1024 == 0 && O_STG + 163840 <= O_AS && HEAD_SMEM <= 232448, "smem");
constexpr int B_MEM = 0, B_RED = 64, B_SM = 88, B_ST = 96, B_OB = 104, B_HF = 112, B_HE = 128, B_OTF = 144, B_OTE = 160;

constexpr int F_H = 0, F_O = 128, F_P = 256, F_U = 384, F_CV = 388, NFLAG = 396;
__device__ int g_flags[NFLAG * 8];
#define FLG(i) (g_flags + (i) * 8)
__device__ uint4 g_ht[2 * NSEG * 2560];
__device__ uint4 g_ot[2 * NSEG * 256 * 64];
__device__ uint4 g_pt[2 * NSEG * 4 * 2560];
__device__ uint4 g_Y[80 * S_LEN];
__device__ uint4 g_U[DM * S_LEN / 8];
__device__ bf16 g_x[S_LEN * DM];
__device__ uint4 g_xc[4 * 16 * 3 * 8 * 32];
#define GT(cond, i)
#define SC(cond, i)
#define SD(x)
#define TS(i)
#define TV(i, v)

}

namespace ws {
__device__ __forceinline__ uint32_t bmul2(uint32_t a, uint32_t b) { uint32_t r; asm("mul.rn.bf16x2 %0, %1, %2;" : "=r"(r) : "r"(a), "r"(b)); return r; }
__device__ __forceinline__ uint32_t bmax2(uint32_t a, uint32_t b) { uint32_t r; asm("max.bf16x2 %0, %1, %2;" : "=r"(r) : "r"(a), "r"(b)); return r; }
__device__ __forceinline__ void flag_wait(const int* f, int tgt, int ns) {
    int guard = 0;
    while (ld_acquire(f) < tgt) { if (++guard > 4000000) __trap(); __nanosleep(ns); }
}
template <int STRIDE> __device__ __forceinline__ void ld5(uint32_t* w, const void* p) {
#pragma unroll
    for (int r = 0; r < 5; r++) { const uint2 v = __ldcg(reinterpret_cast<const uint2*>(reinterpret_cast<const char*>(p) + r * STRIDE)); w[2 * r] = v.x; w[2 * r + 1] = v.y; }
}
template <int STRIDE> __device__ __forceinline__ void st5(void* p, const uint32_t* w) {
#pragma unroll
    for (int r = 0; r < 5; r++) *reinterpret_cast<uint2*>(reinterpret_cast<char*>(p) + r * STRIDE) = make_uint2(w[2 * r], w[2 * r + 1]);
}
__device__ __forceinline__ void ln_row(const uint32_t* x, uint32_t* y) {
    const float c = blo(__shfl_sync(0xffffffffu, x[0], 0));
    float s0 = 0.f, s1 = 0.f, q0 = 0.f, q1 = 0.f;
#pragma unroll
    for (int i = 0; i < 10; i++) { const float d0 = blo(x[i]) - c, d1 = bhi(x[i]) - c; s0 += d0; s1 += d1; q0 = fmaf(d0, d0, q0); q1 = fmaf(d1, d1, q1); }
    float s = s0 + s1, q = q0 + q1;
#pragma unroll
    for (int o = 16; o > 0; o >>= 1) { s += __shfl_xor_sync(0xffffffffu, s, o); q += __shfl_xor_sync(0xffffffffu, q, o); }
    s *= 1.0f / DM;
    const float mean = c + s;
    q = fmaxf(fmaf(q, 1.0f / DM, -s * s), 0.f);
    const uint32_t nm = pack2(-mean, -mean);
    float sq;
    asm("sqrt.approx.ftz.f32 %0, %1;" : "=f"(sq) : "f"(rbf(rbf(q) + 1e-5f)));
    const float rd = rcpf(rbf(sq));
#pragma unroll
    for (int i = 0; i < 10; i++) { const uint32_t d = badd(x[i], nm); y[i] = pack2(blo(d) * rd, bhi(d) * rd); }
}
__device__ __forceinline__ void put_h(int l, int seg, int tok, int lane, const uint32_t* n) {
    st5<8192>(reinterpret_cast<char*>(g_ht + (l * NSEG + seg) * 2560) + (lane >> 2) * 1024 + tok * 32 + (((lane & 3) * 8) ^ ((tok & 4) << 2)), n);
}
__device__ __forceinline__ void ln0_row(const bf16* x, int seg, int tok, int lane) {
    uint32_t v[10];
    ld5<256>(v, x + (size_t)(seg * SEG + tok) * DM + lane * 4);
    ln_row(v, v);
    put_h(0, seg, tok, lane, v);
    __syncwarp();
    if (lane == 0) red_release(FLG(F_H + seg), 1);
}
__device__ __forceinline__ void post_row(int l, int seg, int tok, int lane, const bf16* xin, bf16* xout, bool dry) {
    uint32_t x[10], y[10], n[10];
    const int row = seg * SEG + tok;
    SC(tr, tb);
    if ((seg & 15) == 0 || seg == 8) flag_wait(FLG(F_CV + (seg >> 4) + (seg >= 8)), dry ? 0 : 80, 100);
    SC(tr, tb + 1);
    ld5<16 * S_LEN * 16>(y, reinterpret_cast<const char*>(g_Y) + ((size_t)(lane >> 1) * S_LEN + row) * 16 + (lane & 1) * 8);
    if (l == 0) ld5<256>(x, xin + (size_t)row * DM + lane * 4);
    flag_wait(FLG(F_P + l * 64 + seg), dry ? 0 : 40, POST_NS);
    SC(tr, tb + 2);
    if (l) ld5<256>(x, xin + (size_t)row * DM + lane * 4);
    {
        const char* pp = reinterpret_cast<const char*>(g_pt + (l * NSEG + seg) * 10240) + (lane >> 4) * 4096 + tok * 128 +
                         ((((lane & 15) >> 1) ^ (((tok >> 3) << 1) | (tok & 1))) << 4) + (lane & 1) * 8;
        uint32_t a[10], b[10], c[10];
        ld5<8192>(a, pp); ld5<8192>(b, pp + 40960); ld5<8192>(c, pp + 81920); ld5<8192>(n, pp + 122880);
#pragma unroll
        for (int i = 0; i < 10; i++)
            x[i] = badd(x[i], pack2((blo(a[i]) + blo(b[i])) + (blo(c[i]) + blo(n[i])), (bhi(a[i]) + bhi(b[i])) + (bhi(c[i]) + bhi(n[i]))));
    }
    SC(tr && x[0] != 0x12345, tb + 3);
    ln_row(x, n);
#pragma unroll
    for (int i = 0; i < 10; i++) x[i] = badd(x[i], bmul2(n[i], y[i]));
    SC(tr && x[0] != 0x12345, tb + 4);
    if (!dry) st5<256>(xout + (size_t)row * DM + lane * 4, x);
    if (l == 0) {
        ln_row(x, n);
        SC(tr && n[0] != 0x12345, tb + 5);
        if (!dry) put_h(1, seg, tok, lane, n);
        __syncwarp();
        if (lane == 0) red_release(FLG(F_H + 64 + seg), dry ? 0 : 1);
        SC(tr, tb + 6);
    }
}
__device__ __forceinline__ void u_half(const bf16* Bk, const bf16* Bv, const bf16* shiftk, int unit, int lane) {
    const int odd = lane & 1, t0 = (unit / 20) * 16 + odd * 8, cp = (unit % 20) * 16 + (lane >> 1);
    uint32_t kk[11], vv[8];
    const uint32_t* pk = reinterpret_cast<const uint32_t*>(Bk + (size_t)t0 * DM) + cp;
    const uint32_t* pv = reinterpret_cast<const uint32_t*>(Bv + (size_t)t0 * DM) + cp;
#pragma unroll
    for (int i = 0; i < 11; i++) kk[i] = (i >= 3 || t0 > 0) ? __ldg(pk + (i - 3) * (DM / 2)) : 0u;
#pragma unroll
    for (int i = 0; i < 8; i++) vv[i] = __ldg(pv + i * (DM / 2));
    const uint4 sh0 = __ldg(reinterpret_cast<const uint4*>(shiftk + cp * 8));
    const uint32_t s0 = __byte_perm(sh0.x, sh0.z, 0x5410), s1 = __byte_perm(sh0.x, sh0.z, 0x7632), s2 = __byte_perm(sh0.y, sh0.w, 0x5410), s3 = __byte_perm(sh0.y, sh0.w, 0x7632);
#pragma unroll
    for (int t = 0; t < 8; t++)
        vv[t] = bmul2(badd(badd(badd(bmul2(kk[t], s3), bmul2(kk[t + 1], s2)), bmul2(kk[t + 2], s1)), bmul2(kk[t + 3], s0)), vv[t]);
    uint4* d = g_U + (size_t)(cp * 2) * (S_LEN / 8) + (t0 >> 6) * 8 + ((((t0 ^ 56) & 63) >> 3) ^ ((t0 >> 6) & 7));
#pragma unroll
    for (int c = 0; c < 2; c++) {
        const uint32_t sel = c ? 0x7632 : 0x5410;
        d[c * (S_LEN / 8)] = make_uint4(__byte_perm(vv[7], vv[6], sel), __byte_perm(vv[5], vv[4], sel), __byte_perm(vv[3], vv[2], sel), __byte_perm(vv[1], vv[0], sel));
    }
}
constexpr int CV_E = 4224, CV_W = 2 * 4096 + 3 * CV_E + 128, CV_HI = 111360, CV_Y = CV_HI + 4 * CV_W, CV_T = CV_Y + 16384, CV_Z = CV_T + 16384;
static_assert(4 * CV_W <= O_RED && CV_W % 128 == 0 && CV_Z + 128 <= HEAD_SMEM, "conv buffers");
__device__ __forceinline__ void conv_unit(uint32_t ub, uint32_t e0, uint32_t e1, uint32_t zrow, uint32_t tt, uint32_t Dv, int rg, int nq, int lane, uint32_t zero, int tb) {
    const int g7 = 7 - (lane >> 2), tq = lane & 3;
    SC(tb >= 0, tb + 3);
    for (int i = lane; i < 64 * rg + 72; i += 32) {
        const uint4 v = lds128(e0 + i * 16);
        const uint32_t nx = lds32(e0 + i * 16 + 16);
        sts128(e1 + i * 16, __byte_perm(v.x, v.y, 0x5432), __byte_perm(v.y, v.z, 0x5432), __byte_perm(v.z, v.w, 0x5432), __byte_perm(v.w, nx, 0x5432));
    }
    __syncwarp();
    SC(tb >= 0, tb + 4);
    float acc[4][4];
#pragma unroll
    for (int i = 0; i < 16; i++) (&acc[0][0])[i] = 0.f;
    uint32_t wb = (g7 & 1) ? e0 + (1 + g7 + 2 * tq) * 2 : e1 + (g7 + 2 * tq) * 2;
    int row = 8 * rg + (lane & 7);
    auto ldb = [&](uint4* b) {
        const uint32_t x = row < 0 ? zrow : ub + row * 128 + (((lane >> 3) ^ (row & 7)) << 4);
        b[0] = ldsm4(x); b[1] = ldsm4(x ^ 64);
        row--;
    };
    uint4 Q[16], b[2][2];
    Q[15].w = lds32(wb);
    auto ldq = [&](int q, int o) { Q[q].y = lds32(wb + o * 32 + 16); Q[q].w = lds32(wb + o * 32 + 32); };
    auto cpq = [&](int q) { Q[q].x = Q[(q + 15) & 15].w + zero; Q[q].z = Q[q].y + zero; };
#pragma unroll
    for (int q = 0; q < 11; q++) ldq(q, q);
#pragma unroll
    for (int q = 0; q < 7; q++) cpq(q);
    ldb(b[0]);
#pragma unroll 1
    for (int D0 = nq; D0 > 0; D0--) {
#pragma unroll
        for (int d = 0; d < 4; d++) {
            ldb(b[(d + 1) & 1]);
#pragma unroll
            for (int q = 11; q < 15; q++) ldq((4 * d + q) & 15, 4 * d + q);
#pragma unroll
            for (int ks = 0; ks < 4; ks++) {
                const uint4& bb_ = b[d & 1][ks >> 1];
#pragma unroll
                for (int m = 0; m < 4; m++) {
                    const uint4& a = Q[(4 * d + m + ks) & 15];
                    mmav(acc[m], a.x, a.y, a.z, a.w, (ks & 1) ? bb_.z : bb_.x, (ks & 1) ? bb_.w : bb_.y);
                }
                cpq((4 * d + 7 + ks) & 15);
            }
        }
        wb += 512;
    }
    SC(tb >= 0 && acc[0][0] != 1.2345f, tb + 5);
    const uint32_t ua = ub + (8 * rg + (lane & 7)) * 128 + (((lane >> 3) ^ (lane & 7)) << 4);
    const uint4 u0 = ldsm4t(ua), u1 = ldsm4t(ua ^ 64);
    auto y = [&](int m, int hf, uint32_t u) { return badd(pack2(acc[m][2 * hf], acc[m][2 * hf + 1]), bmul2(u, Dv)); };
    stsm4t(tt, y(0, 0, u1.w), y(0, 1, u1.z), y(1, 0, u1.y), y(1, 1, u1.x));
    stsm4t(tt ^ 64, y(2, 0, u0.w), y(2, 1, u0.z), y(3, 0, u0.y), y(3, 1, u0.x));
}
}

namespace ws {
struct HeadArgs { const bf16 *x, *mem0, *Wq, *Wk, *Wv, *Wo, *Bk, *Bv, *shiftk, *ssmk, *ssmD; bf16* out; int h_target; };

__global__ void __launch_bounds__(512, 1) head_kernel(const __grid_constant__ HeadArgs A) {
    extern __shared__ __align__(1024) unsigned char smem_raw[];
    const int tid = threadIdx.x, warp = __shfl_sync(0xffffffffu, tid >> 5, 0), lane = tid & 31;
    const int cq = blockIdx.x >> 4, r = blockIdx.x & 15;
    const int nh = cq < 4 ? 5 : 4, hi = r / 3, role = r - hi * 3;
    const bool head = r < 3 * nh;
    const int h = (cq < 4 ? 5 * cq : 4 * cq + 4) + hi;
    const uint32_t sb = smem_u32(smem_raw), bb = sb + O_BAR;
    GT(tid == 0, 1);
    const int sp = cq < 4 ? cq : 4 * cq + r - 24;
    if (tid == 0) {
        if ((sb & 0xFFFFFFu) != 1024) __trap();
        for (int i = 0; i < 13; i++) mbar_init(bb + i * 8, 1);
        mbar_init(bb + B_OB, 1); mbar_init(bb + B_OB + 64, 1);
        mbar_init(bb + B_HF, 1); mbar_init(bb + B_HF + 8, 1);
        mbar_init(bb + B_HE, 6 * nh);
        mbar_init(bb + B_OTF, head ? 4 : 8); mbar_init(bb + B_OTE, 1); mbar_init(bb + B_OTF + 8, 8); mbar_init(bb + B_OTE + 16, 1);
        asm volatile("fence.mbarrier_init.release.cluster;" ::: "memory");
        mbar_expect_tx(bb + B_RED, nh * 1280);
        mbar_expect_tx(bb + B_SM, 3072); mbar_expect_tx(bb + B_ST, role == 2 ? 5120 : 4096);
        if (role != 2) { mbar_expect_tx(bb + B_OB, 2048); mbar_expect_tx(bb + B_OB + 64, 2048); }
        mbar_expect_tx(bb + B_HF, 8 * HBYTES); mbar_expect_tx(bb + B_HF + 8, 8 * HBYTES);
    }
    asm volatile("griddepcontrol.launch_dependents;");
    __syncwarp();
    cluster_arrive_relaxed();
    if (warp < 8) {
        asm volatile("setmaxnreg.inc.sync.aligned.u32 %0;" ::"n"(REG_G));
        const int wg = warp >> 2, w4 = warp & 3;
        if (head) {
            const bf16* W = (role == 2 ? A.Wv + wg * 64 : (wg ? A.Wk : A.Wq) + role * 64) + h * DH;
            const uint32_t stg = sb + O_STG + wg * 81920;
            const int t7 = tid & 127;
            if (G_DLY) delay(G_DLY);
#pragma unroll 8
            for (int i = 0; i < 40; i++) {
                const int row = i * 16 + (t7 >> 3), ch = t7 & 7;
                cp_async16(stg + row * 128 + ((ch ^ (row & 7)) << 4), W + (size_t)row * HD + ch * 8);
            }
            cp_commit();
        }
        if (head) {
            cluster_wait();
            uint32_t wa[40][4];
            cp_wait<0>();
            named_bar(8 + wg, 128);
            {
                const uint32_t la = sb + O_STG + wg * 81920 + ((lane & 7) + (lane >> 4) * 8) * 128 + (((w4 * 2 + ((lane >> 3) & 1)) ^ (lane & 7)) << 4);
                { const uint4 v = lds128(sb + O_STG + wg * 81920 + (r >> 1) * 10240 + (tid & 127) * 16); sts128(sb + O_AS + wg * 2048 + (tid & 127) * 16, v.x, v.y, v.z, v.w); }
#pragma unroll
                for (int j = 1; j < 40; j++) {
                    const int kk = (((r >> 1) - j / 5) & 7) * 5 + j % 5;
                    const uint4 v = ldsm4t(la + kk * 2048);
                    wa[j][0] = v.x; wa[j][1] = v.y; wa[j][2] = v.z; wa[j][3] = v.w;
                }
            }
            named_bar(10, 384);
            GT(tid == 0, 2);
            fence_async_smem();
            named_bar(8 + wg, 128);
            cluster_arrive_relaxed();
            float acc[16];
            const uint32_t ep_q = role == 2 ? sb + O_VM + warp * 512 + (lane ^ ((lane >> 3) & 1)) * 16
                                            : sb + O_QRY + wg * 10240 + ((lane >> 1) & 1) * 5120 + (4 * (lane >> 4) + 2 * ((lane >> 2) & 1) + (lane & 1)) * 128 +
                                                  (((2 * w4 + ((lane >> 3) & 1)) ^ (4 * (lane >> 4) + 2 * ((lane >> 2) & 1) + (lane & 1)) ^ ((lane & 2) << 1)) << 4);
            const uint32_t ep_t = role == 2 ? sb + O_VT + warp * 1024 + lane * 16
                                            : sb + O_QRY + wg * 10240 + (8 + 8 * (lane >> 4) + (lane & 7)) * 128 + (((2 * w4 + ((lane >> 3) & 1)) ^ (lane & 7)) << 4);
                        const int pz = role == 2 ? P1C : P1A;
            const uint32_t ab = (1024 + O_AS + wg * 2048) >> 4;
            uint32_t ok = 1;
            auto token_gemm = [&](auto ll, const bool pause, const uint32_t vo, const uint32_t nbar, const uint32_t npar, const int t) {
                constexpr int l = decltype(ll)::value;
                constexpr uint32_t hb = ((1024 + O_H + l * 40960) >> 4) | (1u << 16);
                const uint32_t pr = opq(r >> 1);
                if (l) TS(15); else TS(14);
                wg_fence();
#pragma unroll
                for (int j = 0; j < 40; j++) {
                    const uint64_t db = mkdesc(hb + ((pr - j / 5) & 7) * 320 + (j % 5) * 64, 0xC0000010u);
                    if (j == 0) wg_n32_sfirst(acc, mkdesc(ab, 0x40000040u), db);
                    else if (j < TG_STEPS) wg_n32(acc, wa[j][0], wa[j][1], wa[j][2], wa[j][3], db);
                    if (l == 0 && (j + 1 == P1A || j + 1 == P1C)) {
                        if (pause && pz == j + 1) {
                            wg_commit();
                            if (role == 2) mwait(bb + B_OTE, vo >> 14);
                            wg_wait<0>();
                            named_arrive(3, 384);
                            named_bar(4, NB4);
                            wg_fence();
                        }
                    }
                }
                wg_commit();
                ok = mtest(nbar, npar);
                wg_wait<0>();
                uint32_t pk[8];
#pragma unroll
                for (int i = 0; i < 8; i++) pk[i] = pack2(acc[2 * i], acc[2 * i + 1]);
                if (role == 2) {
                    sts128(ep_t + l * 8192 + vo, pk[0], pk[1], pk[2], pk[3]);
                    sts128(ep_t + l * 8192 + vo + 512, pk[4], pk[5], pk[6], pk[7]);
                } else {
                    stsm4t((ep_t ^ (l << 6)) + l * 5120, pk[0], pk[1], pk[2], pk[3]);
                    stsm4t((ep_t ^ (l << 6)) + l * 5120 + 2048, pk[4], pk[5], pk[6], pk[7]);
                }
                asm volatile("{\n.reg .pred p, q;\nsetp.eq.u32 p, %0, 0;\nsetp.eq.u32 q, %1, 0;\n"
                             "@p mbarrier.arrive.expect_tx.shared::cta.b64 _, [%2], %3;\n@q mbarrier.arrive.shared::cluster.b64 _, [%4];\n}"
                             ::"r"(tid), "r"(tid & 127), "r"(bb + B_HF + l * 8), "r"(8 * HBYTES), "r"(mapa(bb + B_HE, l)) : "memory");
            };
            mwait(bb + B_HF, 0);
            token_gemm(IC<0>{}, false, 0, bb + B_MEM, 1, -1);
            named_bar(11, 384);
            cluster_wait();
            named_arrive(13, 384);
#pragma unroll 1
            for (int t = 0; t < NT; t++) {
                GT(tid == 0 && blockIdx.x == 98, 100 + t);
                TS(0);
                const uint32_t mp = (t & 1) ^ 1;
                const bool tg0 = t + 1 < NSEG, tg1 = t + 1 >= LAG;
                constexpr uint32_t mb = ((1024 + O_MEM) >> 4) | (16u << 16);
#pragma unroll
                for (int G = 0; G < 8; G++) {
                    if (!ok) mwait(bb + B_MEM + G * 8, mp);
                    ok = mtest(G < 7 ? bb + B_MEM + (G + 1) * 8 : bb + B_HF, mp);
                    if (G == 0) { TS(1); wg_fence(); }
                    if (G == 7) TS(2);
                    if (G == 1) TS(8); if (G == 2) TS(9); if (G == 3) TS(10); if (G == 4) TS(11); if (G == 5) TS(12); if (G == 6) TS(13);
#pragma unroll
                    for (int u = 0; u < 5; u++) {
                        const int j = G * 5 + u;
                        const uint64_t db = mkdesc(mb + j * 32, 8);
                        if (j == 0) wg_n16t_sfirst(acc, mkdesc(ab, 0x40000040u), db);
                        else wg_n16t(acc, wa[j][0], wa[j][1], wa[j][2], wa[j][3], db);
                    }
                    wg_commit();
                }
                if (role == 2 && t) named_bar(5, 384);
                wg_wait<0>();
                TS(3);
                if (role == 2) sts128(ep_q, pack2(acc[0], acc[1]), pack2(acc[2], acc[3]), pack2(acc[4], acc[5]), pack2(acc[6], acc[7]));
                else stsm4t(ep_q, pack2(acc[0], acc[1]), pack2(acc[2], acc[3]), pack2(acc[4], acc[5]), pack2(acc[6], acc[7]));
                named_arrive(1, 384);
                if (tid < 8) mbar_expect_tx(bb + B_MEM + tid * 8, 2560);
                if (t == NT - 1) break;
                if (tg0) {
                    if (!ok) mwait(bb + B_HF, mp);
                    if (role != 2) named_bar(2, 384);
                    token_gemm(IC<0>{}, true, mp * 16384, tg1 ? bb + B_HF + 8 : bb + B_MEM, tg1 ? (t + 1 - LAG) & 1 : mp ^ 1, t);
                } else {
                    if (role == 2) mwait(bb + B_OTE, mp); else named_bar(2, 384);
                    named_arrive(3, 384); named_bar(4, NB4);
                    ok = 0;
                }
                TS(5);
                if (tg1) {
                    if (!ok) mwait(bb + B_HF + 8, (t + 1 - LAG) & 1);
                    token_gemm(IC<1>{}, false, mp * 16384, bb + B_MEM, mp ^ 1, t);
                }
                TS(6);
                named_arrive(13, 384);
            }
        } else {
            cluster_wait(); cluster_arrive_relaxed();
            const uint32_t cb = sb + (warp < 4 ? warp * CV_W : CV_HI + (warp - 4) * CV_W), lb = bb + B_MEM + warp * 8;
            auto fetch = [&](int k) {
                const int ps = k / 5, rg = ps ? ps - 1 : 0, ch = (sp * 5 + k - 5 * ps) * 8 + warp;
                if (k == 5 * ps) { flag_wait(FLG(F_U + rg), rg ? 20 : 336, 100); fence_async_global(); }
                if (lane == 0) {
                    const uint32_t nb = (rg + 1) * 1024;
                    mbar_expect_tx(lb, 2 * nb);
                    asm volatile("cp.async.bulk.shared::cluster.global.mbarrier::complete_tx::bytes [%0], [%1], %2, [%3];" ::"r"(cb + (k & 1) * 4096), "l"(g_U + ch * (S_LEN / 8)), "r"(nb), "r"(lb) : "memory");
                    asm volatile("cp.async.bulk.shared::cluster.global.mbarrier::complete_tx::bytes [%0], [%1], %2, [%3];" ::"r"(cb + 8192 + (k & 1) * CV_E + 128), "l"(A.ssmk + (size_t)ch * S_LEN), "r"(nb), "r"(lb) : "memory");
                }
                __syncwarp();
            };
            sts32(cb + 8192 + lane * 4, 0u); sts32(cb + 8192 + CV_E + lane * 4, 0u);
            if (warp == 0) sts32(sb + CV_Z + lane * 4, 0u);
            uint32_t dv = 0;
            if (lane < 5) {
                prefetch_l2(A.ssmk + (size_t)((sp * 5 + lane) * 8 + warp) * S_LEN, 1024);
                dv = *reinterpret_cast<const unsigned short*>(A.ssmD + (sp * 5 + lane) * 8 + warp) * 0x10001u;
            }
            named_bar(8, 256);
#pragma unroll 1
            for (int k = -1; k < 25; k++) {
                const int ps = k < 0 ? 0 : k / 5, rg = ps ? ps - 1 : 0;
                const uint32_t Dv = __shfl_sync(0xffffffffu, dv, k - 5 * ps);
                const int tb = sp == 0 && tid == 0 && k >= -1 && k < 7 ? 72 + k * 8 : -1;
                SC(tb >= 0, tb);
                if (k >= 0) {
                    mwait(lb, k & 1);
                    SC(tb >= 0, tb + 1);
                    if (k < 24) { fence_async_smem(); fetch(k + 1); }
                    SC(tb >= 0, tb + 2);
                }
                const uint32_t tt = sb + CV_T + (k & 1) * 8192;
                conv_unit(cb + (k & 1) * 4096, cb + 8192 + (k & 1) * CV_E, cb + 8192 + 2 * CV_E + 64, sb + CV_Z,
                          tt + warp * 1024 + (lane & 7) * 128 + (((lane >> 3) ^ (lane & 7) ^ warp) & 7) * 16, Dv, rg, ps ? 2 * ps : 1, lane, (uint32_t)A.h_target >> 8, tb);
                if (k >= 0) mwait(bb + B_OTE + (k & 1) * 16, ((k >> 1) & 1) ^ 1);
                named_bar(8, 256);
                {
                    const uint32_t la = tt + (lane & 7) * 1024 + warp * 128 + (((lane >> 3) ^ (lane & 7) ^ warp) & 7) * 16;
                    const uint4 v0 = ldsm4t(la), v1 = ldsm4t(la ^ 64);
                    const uint32_t ya = sb + CV_Y + (k & 1) * 8192 + (warp * 64 + (lane >> 3) * 8 + 7 - (lane & 7)) * 16;
                    stsm4(ya, v0.x, v0.y, v0.z, v0.w);
                    stsm4(ya + 512, v1.x, v1.y, v1.z, v1.w);
                }
                SC(tb >= 0, tb + 6);
                fence_async_smem();
                __syncwarp();
                if (k >= 0 && lane == 0) mbar_arrive(bb + B_OTF + (k & 1) * 8);
                if (k < 0) fetch(0);
                if (k < 0 && lane < 5) prefetch_l2(A.ssmk + (size_t)((sp * 5 + lane) * 8 + warp) * S_LEN + 512, 3072);
            }
            cluster_wait();
        }
    } else if (warp < 12) {
        asm volatile("setmaxnreg.dec.sync.aligned.u32 %0;" ::"n"(REG_T));
        const int w = warp & 3, c = w >> 1, hh = w & 1;
        const uint32_t lane0 = __shfl_sync(0xffffffffu, tid & 31, tid & 31);
        if (head) {
            const int tile0 = role * 4 * WTA, ntile = role == 2 ? 4 * WTC : 4 * WTA;
            const uint32_t wo = sb + O_WO;
            uint32_t mi[5][4];
#pragma unroll
            for (int i = 0; i < 5; i++)
#pragma unroll
                for (int q = 0; q < 4; q++) {
                    const unsigned short* mp = reinterpret_cast<const unsigned short*>(A.mem0) + 2 * q * DM + i * 128 + (tid & 127);
                    mi[i][q] = mp[0] | (uint32_t)mp[DM] << 16;
                }
            cluster_wait();
            named_bar(10, 384);
#pragma unroll
            for (int i = 0; i < 5; i++) {
                const int col = i * 128 + (tid & 127), kk = col >> 4, pr = (kk * 13) >> 6;
                const uint32_t ma = sb + O_MEM + ((((r >> 1) - pr) & 7) * 5 + kk - 5 * pr) * 512 + (col & 8) * 32 + (col & 7) * 16;
                sts128(ma, mi[i][0], mi[i][0], mi[i][1], mi[i][1]);
                sts128(ma + 128, mi[i][2], mi[i][2], mi[i][3], mi[i][3]);
            }
            fence_async_smem();
            named_arrive(11, 384);
            for (int i = tid & 127; i < ntile * 256; i += 128) {
                const int ti = i >> 8, p = (i >> 1) & 127, ch = i & 1;
                const int ks = p >> 4, kh = (p >> 3) & 1, e8 = p & 7;
                const int dim = 64 * (ks >> 2) + 16 * (e8 >> 1) + 8 * (e8 & 1) + 2 * (ks & 3) + kh;
                cp_async16(wo + ti * 4096 + p * 32 + ((ch ^ ((p >> 2) & 1)) << 4), A.Wo + (size_t)(h * DH + dim) * DM + (tile0 + ti) * 16 + ch * 8);
            }
            cp_commit();
            if (lane < 8) {
                const int u = 2 * (tile0 + w + 4 * (lane >> 1)) + (lane & 1), ow = u / 5;
                const int sl = u - 5 * ow;
                sts32(sb + O_TAB + w * 32 + lane * 4, mapa(sb + O_RED + (sl >> 1) * 2560 + (sl & 1) * 256 + hi * (sl < 4 ? 512 : 256), ow & 15));
            }
            cluster_arrive_relaxed(); cluster_wait();
            cp_wait<0>();
            named_bar(7, 128);
            const uint32_t wo_a = wo + w * 4096 + ((lane >> 4) * 8 + (lane & 7)) * 32 + ((((lane >> 3) & 1) ^ ((lane >> 2) & 1)) << 4);
            const uint32_t ob_0 = sb + (role == 2 ? O_PB : O_OBA) + (lane >> 4) * 2048 + ((lane >> 3) & 1) * 128 + ((lane & 7) ^ ((lane >> 1) & 4)) * 16;
            const float cs = 0.08838834764831845f * 1.4426950408889634f;
            auto w_frag = [&](auto four, int i) {
                return ldsm4t(wo_a + (i < 16 || decltype(four)::value == 4 ? (i >> 4) * 32768 + (i & 1) * 16384 + ((i >> 1) & 7) * 512 : 32768 + (i & 1) * 2048 + ((i >> 1) & 7) * 512));
            };
            auto w_pre = [&](auto four, auto pd, uint4* wf) {
#pragma unroll
                for (int i = 0; i < decltype(pd)::value; i++) wf[i] = w_frag(four, i);
            };
            auto w_run = [&](auto four, auto pd, auto rem_, uint4* wf, int t, const uint32_t ob_a, auto&& before_last) {
                constexpr int NTL = decltype(four)::value, PD = decltype(pd)::value, NF = 8 * NTL, NP = NTL > 2 ? 2 : 1;
                constexpr bool REMOTE = decltype(rem_)::value;
                const uint32_t ln = opq(lane0), l8 = (ln & 2) * 64 + (ln >> 2) * 16 + (ln & 1) * 8, rb = (bb + B_RED) & 0xFFFFFFu;
                uint4 ob = ldsm4(ob_a), on, o2;
#pragma unroll
                for (int p = 0; p < NP; p++) {
                    const bool split = p == 1 && NTL == 3;
                    if (!REMOTE && p == 1) mwait(bb + B_ST, t & 1);
                    const int nk = split ? 4 : 8;
                    float d[4][4];
                    uint4 ta;
#pragma unroll
                    for (int i = 0; i < 16; i++) (&d[0][0])[i] = 0.f;
#pragma unroll
                    for (int ks = 0; ks < 8; ks++) {
                        if (ks >= nk) continue;
                        if (REMOTE && p == 0 && ks == 3) { mwait(bb + B_OB + 64, t & 1); TS(7); }
                        if (split) o2 = ldsm4(ob_a + (ks + 4) * 256);
                        if (ks + 1 < nk || p + 1 < NP) on = ldsm4(ob_a + ((ks + 1) & 7) * 256);
                        if (ks == nk - 2) ta = lds128(sb + O_TAB + w * 32 + p * 16);
#pragma unroll
                        for (int u = 0; u < 2; u++) {
                            const int i = p * 16 + ks * 2 + u;
                            const uint4& o = split && u ? o2 : ob;
                            mmav(d[2 * u], wf[i % PD].x, wf[i % PD].y, wf[i % PD].z, wf[i % PD].w, o.x, o.y);
                            mmav(d[2 * u + 1], wf[i % PD].x, wf[i % PD].y, wf[i % PD].z, wf[i % PD].w, o.z, o.w);
                            if (i + PD < NF) wf[i % PD] = w_frag(four, i + PD);
                        }
                        ob = on;
                    }
                    if (p) TS(10); else TS(8);
                    if (p == NP - 1) before_last();
                    if (split) {
#pragma unroll
                        for (int i = 0; i < 4; i++) { d[0][i] += d[2][i]; d[1][i] += d[3][i]; }
                    }
                    st_async_v2(ta.x + l8, pack2(d[0][0], d[0][1]), pack2(d[1][0], d[1][1]), (ta.x & 0xFF000000u) | rb);
                    st_async_v2(ta.y + l8, pack2(d[0][2], d[0][3]), pack2(d[1][2], d[1][3]), (ta.y & 0xFF000000u) | rb);
                    if (!split) {
                        st_async_v2(ta.z + l8, pack2(d[2][0], d[2][1]), pack2(d[3][0], d[3][1]), (ta.z & 0xFF000000u) | rb);
                        st_async_v2(ta.w + l8, pack2(d[2][2], d[2][3]), pack2(d[3][2], d[3][3]), (ta.w & 0xFF000000u) | rb);
                    }
                }
            };
            if (role != 2) {
#pragma unroll 1
                for (int t = 0; t < NT; t++) {
                    const uint32_t lane = opq(lane0);
                    const uint32_t dc = mapa(sb, hi * 3 + 2), dp = mapa(sb, hi * 3 + (role ^ 1));
                    const uint32_t qa = sb + O_QRY + c * 5120 + (lane & 7) * 128;
                    const uint32_t sw = (((lane >> 3) ^ (lane & 7)) << 4) ^ (c << 6);
                    float s[10];
                    {
                        const uint32_t ka = qa + 10240;
                        const uint32_t kt = sb + O_KEY + c * 5120 + (lane & 15) * 128, kx = (((lane >> 4) ^ (lane & 7)) << 4) ^ (c << 6);
                        const uint32_t sd = dc + O_SM + role * 1536 + c * 768 + lane * 4, sbar = dc + O_BAR + B_SM;
                        const uint32_t ta = sb + O_QRY + c * 5120 + (8 + 16 * hh + (lane & 15)) * 128;
                        uint4 a[4], f[4];
                        float st[10];
                        auto unit = [&](const uint4& b0, const uint4& b1, int n) {
                            float s0[4] = {0.f, 0.f, 0.f, 0.f}, s1[4] = {0.f, 0.f, 0.f, 0.f};
                            mmav(s0, a[0].x, a[0].y, a[0].z, a[0].w, b0.x, b0.y); mmav(s1, a[1].x, a[1].y, a[1].z, a[1].w, b0.z, b0.w);
                            mmav(s0, a[2].x, a[2].y, a[2].z, a[2].w, b1.x, b1.y); mmav(s1, a[3].x, a[3].y, a[3].z, a[3].w, b1.z, b1.w);
                            const float u0 = s0[0] + s1[0], u1 = s0[1] + s1[1], u2 = s0[2] + s1[2], u3 = s0[3] + s1[3];
                            s[2 * n] = role ? u2 : u0; s[2 * n + 1] = role ? u3 : u1;
                            st[2 * n] = role ? u0 : u2; st[2 * n + 1] = role ? u1 : u3;
                        };
                        named_bar(13, 384);
#pragma unroll
                        for (int i = 0; i < 4; i++) f[i] = ldsm4(kt + 1024 + hh * 2048 + (kx ^ (i << 5) ^ (hh << 6)));
#pragma unroll
                        for (int i = 0; i < 4; i++) a[i] = ldsm4(ta + (kx ^ (i << 5)));
                        uint4 k0 = ldsm4(ka + (1 + 2 * hh) * 1024 + sw), k1 = ldsm4(ka + (1 + 2 * hh) * 1024 + (sw ^ 64)), k2, k3;
                        {
                            const uint32_t qh = qa + (sw ^ (hh << 6)), kh = kt + (kx ^ (hh << 6));
                            named_bar(1, 384);
                            const uint4 q0 = ldsm4(qh), g0 = ldsm4(kh), g1 = ldsm4(kh ^ 32), q1 = ldsm4(qh ^ 64);
                            float s0[4] = {0.f, 0.f, 0.f, 0.f}, s1[4] = {0.f, 0.f, 0.f, 0.f}, s2[4] = {0.f, 0.f, 0.f, 0.f}, s3[4] = {0.f, 0.f, 0.f, 0.f};
                            mmav(s0, f[0].x, f[0].y, f[0].z, f[0].w, q0.x, q0.y); mmav(s1, f[1].x, f[1].y, f[1].z, f[1].w, q0.z, q0.w);
                            mmav(s2, g0.x, g0.y, g0.z, g0.w, q0.x, q0.y); mmav(s3, g1.x, g1.y, g1.z, g1.w, q0.z, q0.w);
                            mmav(s0, f[2].x, f[2].y, f[2].z, f[2].w, q1.x, q1.y); mmav(s1, f[3].x, f[3].y, f[3].z, f[3].w, q1.z, q1.w);
                            st_async_b32(sd + hh * 128, pack2(s2[0] + s3[0], s2[1] + s3[1]), sbar);
                            st_async_b32(sd + 256 + hh * 256, pack2(s0[0] + s1[0], s0[1] + s1[1]), sbar);
                            st_async_b32(sd + 384 + hh * 256, pack2(s0[2] + s1[2], s0[3] + s1[3]), sbar);
                        }
                        TS(1);
                        k2 = ldsm4(ka + (2 + 2 * hh) * 1024 + sw); k3 = ldsm4(ka + (2 + 2 * hh) * 1024 + (sw ^ 64));
                        f[0] = ldsm4(ka + sw); f[1] = ldsm4(ka + (sw ^ 64));
                        unit(k0, k1, 1);
                        if (hh) { k0 = ldsm4(ka + 1024 + sw); k1 = ldsm4(ka + 1024 + (sw ^ 64)); f[2] = ldsm4(ka + 2048 + sw); f[3] = ldsm4(ka + 2048 + (sw ^ 64)); }
                        unit(k2, k3, 2);
                        unit(f[0], f[1], 0);
                        if (hh) {
                            unit(k0, k1, 3);
                            unit(f[2], f[3], 4);
                        } else s[6] = s[7] = s[8] = s[9] = -INFINITY;
                        const uint32_t td = dp + O_ST + c * 2048 + hh * 768, tb = dp + O_BAR + B_ST;
                        auto fu = [](float x) { return __float_as_uint(x); };
                        st_async_v4(td + lane * 16, fu(st[0]), fu(st[1]), fu(st[2]), fu(st[3]), tb);
                        if (hh == 0) st_async_v2(td + 512 + lane * 8, fu(st[4]), fu(st[5]), tb);
                        else {
                            st_async_v4(td + 512 + lane * 16, fu(st[4]), fu(st[5]), fu(st[6]), fu(st[7]), tb);
                            st_async_v2(td + 1024 + lane * 8, fu(st[8]), fu(st[9]), tb);
                        }
                        if (t < NT - 1) named_arrive(2, 384);
                        {
                            const int lim = 8 * role + (int)(lane >> 2) - 2 * (int)(lane & 3);
                            if (lim < 0) s[2] = -INFINITY;
                            if (lim < 1) s[3] = -INFINITY;
                            if (lim < 8) s[4] = -INFINITY;
                            if (lim < 9) s[5] = -INFINITY;
                        }
                        TS(2);
                    }
                    {
                        mwait(bb + B_ST, t & 1);
                        const uint32_t sa = sb + O_ST + c * 2048 + hh * 768;
                        auto uf = [](uint32_t x) { return __uint_as_float(x); };
                        { const uint4 v = lds128(sa + lane * 16); s[0] += uf(v.x); s[1] += uf(v.y); s[2] += uf(v.z); s[3] += uf(v.w); }
                        if (hh == 0) {
                            const uint2 u = lds64(sa + 512 + lane * 8);
                            s[4] += uf(u.x); s[5] += uf(u.y);
                        } else {
                            const uint4 v = lds128(sa + 512 + lane * 16);
                            const uint2 u = lds64(sa + 1024 + lane * 8);
                            s[4] += uf(v.x); s[5] += uf(v.y); s[6] += uf(v.z); s[7] += uf(v.w); s[8] += uf(u.x); s[9] += uf(u.y);
                        }
                        uint32_t z[5];
#pragma unroll
                        for (int n = 0; n < 5; n++) { const uint32_t u = pack2(s[2 * n], s[2 * n + 1]); z[n] = pack2(blo(u) * 0.08838834764831845f, bhi(u) * 0.08838834764831845f); }
                        uint32_t zm = bmax2(bmax2(bmax2(z[0], z[1]), bmax2(z[2], z[3])), z[4]);
                        zm = bmax2(zm, __shfl_xor_sync(0xffffffffu, zm, 1));
                        zm = bmax2(zm, __shfl_xor_sync(0xffffffffu, zm, 2));
                        const float l2e = 1.4426950408889634f, mx = fmaxf(blo(zm), bhi(zm)) * -l2e;
#pragma unroll
                        for (int n = 0; n < 5; n++) { s[2 * n] = ex2f(fmaf(blo(z[n]), l2e, mx)); s[2 * n + 1] = ex2f(fmaf(bhi(z[n]), l2e, mx)); }
                        float sum = ((s[0] + s[1]) + (s[2] + s[3])) + ((s[4] + s[5]) + (s[6] + s[7])) + (s[8] + s[9]);
                        sum += __shfl_xor_sync(0xffffffffu, sum, 1);
                        sum += __shfl_xor_sync(0xffffffffu, sum, 2);
                        sum = rcpf(sum);
                        const uint32_t pd = dc + O_PB + (t & 1) * 5120 + c * 2560 + (2 * hh + role) * 128 + lane * 4;
#pragma unroll
                        for (int n = 0; n < 5; n++)
                            st_async_b32(pd + (n == 0 ? 0 : (n < 3 ? n * 512 + hh * 1024 : n * 512 - hh * 1024)), pack2(s[2 * n] * sum, s[2 * n + 1] * sum), dc + O_BAR + B_ST);
                        TS(6);
                        if (H1_LATE && r == 1 && t >= LAG - 1 && t < NT - 1) named_arrive(12, 160);
                    }
                    if (t == NT - 1) break;
                    uint4 wf[PDA];
                    w_pre(IC<WTA>{}, IC<PDA>{}, wf);
                    mwait(bb + B_OB, t & 1);
                    TS(3);
                    named_bar(3, 384);
                    w_run(IC<WTA>{}, IC<PDA>{}, IC<1>{}, wf, t, ob_0, []() {});
                    named_arrive(4, NB4);
                    if (w == 0 && lane == 0) { mbar_expect_tx(bb + B_OB, 2048); mbar_expect_tx(bb + B_OB + 64, 2048); mbar_expect_tx(bb + B_ST, 4096); }
                    TS(5);
                }
            } else {
#pragma unroll 1
                for (int t = 0; t < NT; t++) {
                    const uint32_t lane = opq(lane0);
                    const int g = lane >> 2, tq = lane & 3;
                    const uint32_t vm_a = sb + O_VM + (g * 4 + 2 * (tq & 1) + (c ^ ((g >> 1) & 1))) * 16 + (tq >> 1) * 8;
                    const uint32_t vt_a = sb + O_VT + (t & 1) * 16384 + lane * 16;
                    named_bar(13, 384);
                    uint4 va[4][2];
#pragma unroll
                    for (int i = 0; i < 4; i++) {
                        va[i][0] = lds128(vt_a + c * 8192 + (4 * hh + i) * 1024);
                        va[i][1] = lds128(vt_a + c * 8192 + (4 * hh + i) * 1024 + 512);
                    }
                    const uint32_t sa = opq(sb + O_SM + c * 768 + 256 + lane * 16), sa2 = opq(sb + O_SM + c * 768 + (lane & 15) * 16 + (lane >> 4) * 1536), vm_b = opq(vm_a + hh * 2048);
                    named_bar(1, 384);
                    if (t < NT - 1) {
                        uint2 vm[4];
#pragma unroll
                        for (int i = 0; i < 4; i++) vm[i] = lds64(vm_b + i * 512);
                        mwait(bb + B_SM, t & 1);
                        TS(1);
                        const uint4 x0 = ldsm4t(sa), y0 = ldsm4t(sa + 1536), x1 = ldsm4t(sa2);
                        float s[10];
                        s[2] = blo(x0.x) + blo(y0.x); s[3] = bhi(x0.x) + bhi(y0.x); s[4] = blo(x0.y) + blo(y0.y); s[5] = bhi(x0.y) + bhi(y0.y);
                        s[6] = blo(x0.z) + blo(y0.z); s[7] = bhi(x0.z) + bhi(y0.z); s[8] = blo(x0.w) + blo(y0.w); s[9] = bhi(x0.w) + bhi(y0.w);
                        s[0] = (blo(x1.x) + blo(x1.y)) + (blo(x1.z) + blo(x1.w)); s[1] = (bhi(x1.x) + bhi(x1.y)) + (bhi(x1.z) + bhi(x1.w));
                        float mx = fmaxf(fmaxf(fmaxf(s[0], s[1]), fmaxf(s[2], s[3])), fmaxf(fmaxf(fmaxf(s[4], s[5]), fmaxf(s[6], s[7])), fmaxf(s[8], s[9])));
                        const float m1 = __shfl_xor_sync(0xffffffffu, mx, 1), m2 = __shfl_xor_sync(0xffffffffu, mx, 2), m3 = __shfl_xor_sync(0xffffffffu, mx, 3);
                        mx = fmaxf(fmaxf(mx, m1), fmaxf(m2, m3)) * -cs;
                        uint32_t pb[5];
#pragma unroll
                        for (int i = 0; i < 5; i++) pb[i] = pack2(ex2f(fmaf(s[2 * i], cs, mx)), ex2f(fmaf(s[2 * i + 1], cs, mx)));
                        TS(9);
                        named_bar(3, 384);
                        float o[5][4];
#pragma unroll
                        for (int i = 0; i < 20; i++) (&o[0][0])[i] = 0.f;
                        const uint32_t one2 = 0x3F803F80u;
                        float z[2][4] = {{0.f, 0.f, 0.f, 0.f}, {0.f, 0.f, 0.f, 0.f}};
                        mmav8(o[4], one2, one2, pb[0]);
                        mmav(z[0], one2, one2, one2, one2, pb[1], pb[2]);
                        mmav(z[1], one2, one2, one2, one2, pb[3], pb[4]);
#pragma unroll
                        for (int i = 0; i < 4; i++) mmav8(o[i], vm[i].x, vm[i].y, pb[0]);
#pragma unroll
                        for (int i = 0; i < 4; i++) mmav(o[i], va[i][0].x, va[i][0].y, va[i][0].z, va[i][0].w, pb[1], pb[2]);
#pragma unroll
                        for (int i = 0; i < 4; i++) mmav(o[i], va[i][1].x, va[i][1].y, va[i][1].z, va[i][1].w, pb[3], pb[4]);
                        o[4][0] += z[0][0] + z[1][0]; o[4][1] += z[0][1] + z[1][1];
                        uint4 wf[PDC];
                        w_pre(IC<WTC>{}, IC<PDC>{}, wf);
                        const float r0 = rcpf(o[4][0]), r1 = rcpf(o[4][1]);
                        const uint32_t oo = c * 2048 + hh * 1024 + g * 128 + tq * 16 + (g & 1) * 64;
                        uint32_t e0[4], e1[4];
#pragma unroll
                        for (int i = 0; i < 4; i++) { e0[i] = pack2(o[i][0] * r0, o[i][2] * r0); e1[i] = pack2(o[i][1] * r1, o[i][3] * r1); }
                        sts128(sb + O_PB + (~t & 1) * 5120 + oo, e0[0], e0[1], e0[2], e0[3]);
                        sts128(sb + O_PB + (~t & 1) * 5120 + (oo ^ 64), e1[0], e1[1], e1[2], e1[3]);
                        {
                            const uint32_t da = mapa(sb + O_OBA, r - 2) + oo, ba = mapa(bb + B_OB + hh * 64, r - 2);
                            st_async_v4(da, e0[0], e0[1], e0[2], e0[3], ba);
                            st_async_v4(da + 0x01000000u, e0[0], e0[1], e0[2], e0[3], ba + 0x01000000u);
                            st_async_v4(da ^ 64, e1[0], e1[1], e1[2], e1[3], ba);
                            st_async_v4((da ^ 64) + 0x01000000u, e1[0], e1[1], e1[2], e1[3], ba + 0x01000000u);
                        }
                        TS(3);
                        named_bar(7, 128);
                        w_run(IC<WTC>{}, IC<PDC>{}, IC<0>{}, wf, t, ob_0 + (~t & 1) * 5120, []() {});
                        if (WTC == 2) mwait(bb + B_ST, t & 1);
                        TS(4);
                    } else { mwait(bb + B_SM, t & 1); mwait(bb + B_ST, t & 1); }
                    TS(5);
                    {
                        const uint32_t pa = sb + O_PB + (t & 1) * 5120 + c * 2560, pl = pa + (lane & 7) * 16 + ((lane >> 3) & 1) * 512 + (lane >> 4) * 128;
                        const uint4 p0 = ldsm4(pa + lane * 16), p1 = ldsm4(pl + 512), p2 = ldsm4(pl + 768), p3 = ldsm4(pl + 1792);
                        const uint32_t va_ = vt_a + c * 8192 + hh * 4096, oa = va_ - lane * 16 + g * 64 + ((tq ^ (g >> 1)) & 3) * 16;
                        float d[2][4][4];
#pragma unroll
                        for (int i = 0; i < 5; i++) {
                            if (i < 4) {
                                const uint2 a0 = lds64(vm_a + hh * 2048 + i * 512);
                                const uint4 a1 = lds128(va_ + i * 1024), a2 = lds128(va_ + i * 1024 + 512);
                                float (*e)[4] = d[i & 1];
#pragma unroll
                                for (int k = 0; k < 16; k++) (&e[0][0])[k] = 0.f;
                                mma16816(e[2], a2.x, a2.y, a2.z, a2.w, p3.x, p3.y); mma16816(e[3], a2.x, a2.y, a2.z, a2.w, p3.z, p3.w);
                                mma1688(e[0], a0.x, a0.y, p0.x); mma1688(e[1], a0.x, a0.y, p0.y); mma1688(e[2], a0.x, a0.y, p0.z); mma1688(e[3], a0.x, a0.y, p0.w);
                                mma16816(e[0], a1.x, a1.y, a1.z, a1.w, p1.x, p1.y); mma16816(e[1], a1.x, a1.y, a1.z, a1.w, p1.z, p1.w);
                                mma16816(e[2], a1.x, a1.y, a1.z, a1.w, p2.x, p2.y); mma16816(e[3], a1.x, a1.y, a1.z, a1.w, p2.z, p2.w);
                            }
                            if (i > 0) {
                                float (*e)[4] = d[(i - 1) & 1];
                                sts128(oa + (i - 1) * 1024, pack2(e[0][0], e[0][1]), pack2(e[1][0], e[1][1]), pack2(e[2][0], e[2][1]), pack2(e[3][0], e[3][1]));
                                sts128(oa + (i - 1) * 1024 + 512, pack2(e[0][2], e[0][3]), pack2(e[1][2], e[1][3]), pack2(e[2][2], e[2][3]), pack2(e[3][2], e[3][3]));
                            }
                        }
                    }
                    if (t < NT - 1) named_arrive(4, NB4);
                    TS(6);
                    if (w == 0 && lane == 0) { mbar_expect_tx(bb + B_ST, 5120); mbar_expect_tx(bb + B_SM, 3072); }
                    fence_async_smem();
                    __syncwarp();
                    if (lane == 0) mbar_arrive(bb + B_OTF);
                    if (t < NT - 1) named_arrive(5, 384);
                }
            }
        } else {
            cluster_wait(); cluster_arrive_relaxed();
            const int wi = sp * 4 + w, half = wi >> 5, tok = wi & 31;
            if (lane < LN0_AHEAD / 2) prefetch_l2(A.x + (size_t)((half + 2 * lane) * SEG + tok) * DM, 1280);
#pragma unroll 1
            for (int k = -LN0_AHEAD / 2; k < NT; k++) {
                const int s0 = k < 0 ? 2 * k + LN0_AHEAD + half : (half ? k + LN0_AHEAD : NSEG);
                if (s0 < NSEG) { ln0_row(A.x, s0, tok, lane); GT(lane == 0 && k < 0, 30 + s0); }
                const int n = k - half * LAG;
                if (k == -LN0_AHEAD / 2 + 1 || (n >= 0 && n < NSEG && k >= 0)) {
                    post_row(half, k < 0 ? 0 : n, tok, lane, half ? g_x : A.x, half ? A.out : g_x, k < 0);
                    GT(lane == 0 && (n & 3) == 0 && k >= 0, 460 + half * 16 + (n >> 2)); GT(lane == 0 && n == 63 && half, 40);
                }
            }
            cluster_wait();
        }
    } else {
        asm volatile("setmaxnreg.dec.sync.aligned.u32 %0;" ::"n"(REG_X));
        cluster_wait();
        const int s = warp - 12;
        const uint32_t lane0 = __shfl_sync(0xffffffffu, tid & 31, tid & 31);
        if (s < 3) {
            cluster_arrive_relaxed();
#pragma unroll 1
            for (int u = blockIdx.x * 3 + s; u < 640; u += 336) u_half(A.Bk, A.Bv, A.shiftk, u, lane);
            __syncwarp();
            if (lane == 0) red_release(FLG(F_U), 1);
            GT(lane == 0, 4);
            cluster_wait();
            int slot = 0;
            if (s == 0) {
                const uint32_t G = lane >> 1, d = ((r + 2 * G) & 15) ^ (lane & 1);
                const bool ok = lane < 16 && d < 3 * nh;
                const uint32_t pos = __popc(__ballot_sync(0xffffffffu, ok) & ((1u << lane) - 1u));
                if (ok) { sts32(sb + O_BT + pos * 8, (d << 24) + G * 2560); sts32(sb + O_BT + pos * 8 + 4, mapa(bb + B_MEM + G * 8, d)); }
            }
            named_bar(14, 96);
#pragma unroll 1
            for (int t = 0; t < NT - 1; t++) {
                const uint32_t lane = opq(lane0);
                uint32_t m0 = 0x80008000u, m1 = 0x80008000u;
                if (t < LAG && cq == 0) {
                    const uint32_t ch = s < 2 ? lane : lane >> 1;
                    const unsigned short* mp = reinterpret_cast<const unsigned short*>(A.mem0) + (((ch >> 3) & 1) * 4 + (s < 2 ? 0 : (lane & 1) * 2)) * DM + (5 * r + 2 * s + (ch >> 4)) * 8 + (ch & 7);
                    m0 = max(mp[0] | (uint32_t)mp[DM] << 16, 1u);
                    if (s < 2) m1 = max(mp[2 * DM] | (uint32_t)mp[3 * DM] << 16, 1u);
                }
                const bool late = t >= LAG;
                auto sum5 = [](uint32_t a, uint32_t b, uint32_t c, uint32_t d, uint32_t e) { return max(badd(badd(badd(a, b), e), badd(c, d)), 1u); };
                auto sum7 = [](uint32_t a, uint32_t b, uint32_t c, uint32_t d, uint32_t e, uint32_t f, uint32_t h_) {
                    return badd(badd(badd(a, b), badd(c, d)), badd(badd(e, f), h_));
                };
                auto min3 = [](uint32_t a, uint32_t b, uint32_t c) { return min(min(a, b), c); };
                auto bcast = [&](auto two, const uint32_t aa, uint32_t x0, uint32_t x1, uint32_t x2, uint32_t x3) {
                    auto send = [&](uint32_t o, uint32_t bar) { if (decltype(two)::value) st_async_v4(aa + o, x0, x1, x2, x3, bar); else st_async_v2(aa + o, x0, x1, bar); };
                    const uint32_t tb0 = clk32();
                    auto pace = [&](int k) { if (BP) while (__any_sync(0xffffffffu, clk32() - tb0 < (uint32_t)(k * BP))) {} };
                    uint4 e[6];
                    e[0] = lds128(sb + O_BT);
                    TS(8);
                    send(e[0].x, e[0].y); send(e[0].z, e[0].w);
                    TS(9);
#pragma unroll
                    for (int i = 1; i < 6; i++) e[i] = lds128(sb + O_BT + i * 16);
#pragma unroll
                    for (int i = 1; i < 6; i++) { pace(i); send(e[i].x, e[i].y); send(e[i].z, e[i].w); }
                    if (nh == 5) {
                        const uint4 f0 = lds128(sb + O_BT + 96);
                        const uint2 f1 = lds64(sb + O_BT + 112);
                        pace(6); send(f0.x, f0.y); send(f0.z, f0.w); pace(7); send(f1.x, f1.y);
                    }
                };
                const uint32_t ma = (sb + O_MEM + (5 * (r & 1) + 2 * s) * 256) & 0xFFFFFFu;
                int guard = 0;
                if (s < 2) {
                    const uint32_t ra = sb + O_RED + s * 2560 + lane * 16;
                    uint4* xb = g_xc + ((slot * 16 + r) * 3 + s) * 256 + lane;
                    uint4* xo = xb + cq * 32;
                    mwait(bb + B_RED, t & 1);
                    TS(0);
                    uint4 p[5];
#pragma unroll
                    for (int i = 0; i < 5; i++) p[i] = i < 4 || nh == 5 ? lds128(ra + i * 512) : make_uint4(0, 0, 0, 0);
                    const uint32_t u1 = sum5(p[0].y, p[1].y, p[2].y, p[3].y, p[4].y), u3 = sum5(p[0].w, p[1].w, p[2].w, p[3].w, p[4].w);
                    st_relaxed_v4(xo, sum5(p[0].x, p[1].x, p[2].x, p[3].x, p[4].x), late ? u1 : m0, sum5(p[0].z, p[1].z, p[2].z, p[3].z, p[4].z), late ? u3 : m1);
                    TS(1);
                    if (QUIET && head) named_arrive(4, NB4);
                    delay(XD);
                    uint4 x[NCL];
                    while (true) {
                        ld7_relaxed(x, xb);
                        const uint32_t mn = min3(min3(min3(x[0].x, x[0].y, x[0].z), min3(x[0].w, x[1].x, x[1].y), min3(x[1].z, x[1].w, x[2].x)),
                                                 min3(min3(x[2].y, x[2].z, x[2].w), min3(x[3].x, x[3].y, x[3].z), min3(x[3].w, x[4].x, x[4].y)),
                                                 min3(min3(x[4].z, x[4].w, x[5].x), min3(x[5].y, x[5].z, x[5].w), min(min3(x[6].x, x[6].y, x[6].z), x[6].w)));
                        if (NO_X || __all_sync(0xffffffffu, mn != 0)) break;
                        if (++guard > 2000000) __trap();
                    }
                    TS(2);
                    TV(4, guard);
                    bcast(IC<1>{}, ma + lane * 16, sum7(x[0].x, x[1].x, x[2].x, x[3].x, x[4].x, x[5].x, x[6].x), sum7(x[0].y, x[1].y, x[2].y, x[3].y, x[4].y, x[5].y, x[6].y),
                          sum7(x[0].z, x[1].z, x[2].z, x[3].z, x[4].z, x[5].z, x[6].z), sum7(x[0].w, x[1].w, x[2].w, x[3].w, x[4].w, x[5].w, x[6].w));
                } else {
                    const uint32_t ra = sb + O_RED + 5120 + lane * 8;
                    uint2* xb = reinterpret_cast<uint2*>(g_xc + ((slot * 16 + r) * 3 + 2) * 256) + lane;
                    uint2* xo = xb + cq * 64;
                    mwait(bb + B_RED, t & 1);
                    TS(0);
                    uint2 p[5];
#pragma unroll
                    for (int i = 0; i < 5; i++) p[i] = i < 4 || nh == 5 ? lds64(ra + i * 256) : make_uint2(0, 0);
                    const uint32_t u1 = sum5(p[0].y, p[1].y, p[2].y, p[3].y, p[4].y);
                    st_relaxed_v2(xo, sum5(p[0].x, p[1].x, p[2].x, p[3].x, p[4].x), late ? u1 : m0);
                    if (lane == 0) mbar_expect_tx(bb + B_RED, nh * 1280);
                    TS(1);
                    if (QUIET && head) named_arrive(4, NB4);
                    delay(XD);
                    uint32_t y0, y1;
                    while (true) {
                        uint2 x[NCL];
                        ld7_relaxed(x, xb);
                        const uint32_t mn = min3(min3(min3(x[0].x, x[0].y, x[1].x), min3(x[1].y, x[2].x, x[2].y), min3(x[3].x, x[3].y, x[4].x)), min3(x[4].y, x[5].x, x[5].y), min(x[6].x, x[6].y));
                        y0 = sum7(x[0].x, x[1].x, x[2].x, x[3].x, x[4].x, x[5].x, x[6].x); y1 = sum7(x[0].y, x[1].y, x[2].y, x[3].y, x[4].y, x[5].y, x[6].y);
                        if (NO_X || __all_sync(0xffffffffu, mn != 0)) break;
                        if (++guard > 2000000) __trap();
                    }
                    TS(2);
                    TV(4, guard);
                    bcast(IC<0>{}, ma + lane * 8, y0, y1, 0u, 0u);
                }
                TS(3);
                if (OT_LATE && head && role == 2) named_arrive(6, 128);
                slot = slot + 1 == XRS ? 0 : slot + 1;
                {
                    const int s2 = slot + 1 == XRS ? 0 : slot + 1;
                    uint4* zp = g_xc + ((s2 * 16 + r) * 3 + s) * 256 + cq * 32 + lane;
                    st_relaxed_v4(zp, 0, 0, 0, 0);
                    if (ld_relaxed_v4(zp).x) __trap();
                }
            }
        } else if (r < 2) {
            const uint16_t mask = (uint16_t)((1u << (3 * nh)) - 1u);
#pragma unroll 1
            for (int n = 0; n < NSEG; n++) {
                if (n == (r == 0 ? 1 : 0)) { cluster_arrive(); cluster_wait(); }
                int guard = 0;
                while (ld_acquire(FLG(F_H + r * 64 + n)) < A.h_target) { if (++guard > 2000000) __trap(); __nanosleep(40); }
                fence_async_global();
                if (H1_LATE && r == 1) named_bar(12, 160);
                if (n) mwait(bb + B_HE, (n - 1) & 1);
                if (lane < 8)
                    asm volatile("cp.async.bulk.shared::cluster.global.mbarrier::complete_tx::bytes.multicast::cluster [%0], [%1], %2, [%3], %4;" ::"r"(sb + O_H + r * 40960 + lane * 5120),
                                 "l"(g_ht + (r * NSEG + n) * 2560 + lane * 320), "r"(HBYTES), "r"(bb + B_HF + r * 8), "h"(mask) : "memory");
                __syncwarp();
            }
        } else {
            cluster_arrive(); cluster_wait();
            if (head && role == 2) {
#pragma unroll 1
                for (int t = 0; t < NT; t++) {
                    mwait(bb + B_OTF, t & 1);
                    if (OT_LATE && t < NT - 1) named_bar(6, 128);
                    const int l = lane & 1, n = t - l * LAG;
                    if (lane < 2 && n >= 0 && n < NSEG) {
                        asm volatile("cp.async.bulk.global.shared::cta.bulk_group [%0], [%1], %2;" ::"l"(g_ot + ((l * NSEG + n) * 256 + h * 8) * 64), "r"(sb + O_VT + (t & 1) * 16384 + l * 8192), "r"(8192) : "memory");
                        asm volatile("cp.async.bulk.commit_group;" ::: "memory");
                        asm volatile("cp.async.bulk.wait_group.read 0;" ::: "memory");
                    }
                    __syncwarp();
                    if (lane == 0) mbar_arrive(bb + B_OTE);
                    if (lane < 2 && n >= 0 && n < NSEG) {
                        asm volatile("cp.async.bulk.wait_group 0;" ::: "memory");
                        fence_async_global();
                        red_release(FLG(F_O + l * 64 + n) + (h >> 3), 1);
                        GT(true, 200 + l * 64 + n);
                    }
                    __syncwarp();
                }
            }
            if (!head && lane == 0) {
#pragma unroll 1
                for (int k = 0; k < 25; k++) {
                    const int rg = k / 5, r0 = rg == 1 ? 256 : 0;
                    mwait(bb + B_OTF + (k & 1) * 8, (k >> 1) & 1);
                    asm volatile("cp.async.bulk.global.shared::cta.bulk_group [%0], [%1], %2;" ::"l"(g_Y + (sp * 5 + k - 5 * rg) * S_LEN + (rg ? rg - 1 : 0) * 512 + r0),
                                 "r"(sb + CV_Y + (k & 1) * 8192 + r0 * 16), "r"(rg < 2 ? 4096 : 8192) : "memory");
                    asm volatile("cp.async.bulk.commit_group;" ::: "memory");
                    asm volatile("cp.async.bulk.wait_group 0;" ::: "memory");
                    mbar_arrive(bb + B_OTE + (k & 1) * 16);
                    fence_async_global();
                    red_release(FLG(F_CV + rg), 1);
                    GT(true, 50 + k);
                }
            }
            __syncwarp();
        }
    }
    cluster_arrive(); cluster_wait();
}
}

namespace ws {
constexpr int OP_SS = 17;
constexpr int P_RING = 0, P_AS = 131072, P_STG = P_AS + 2 * OP_SS * 2048, P_BAR = P_STG + 16384, OP_SMEM = P_BAR + 256;
constexpr int PB_FULL = 0, PB_EMPTY = 128, PB_SF = 144, PB_SE = 176;
static_assert(OP_SMEM <= 232448, "smem");

__global__ void __launch_bounds__(384, 1) op_kernel(const bf16* __restrict__ Wo, const bf16* __restrict__ Bk, const bf16* __restrict__ Bv, const bf16* __restrict__ shiftk) {
    extern __shared__ __align__(1024) unsigned char smem_raw[];
    const int tid = threadIdx.x, warp = __shfl_sync(0xffffffffu, tid >> 5, 0), lane = tid & 31;
    const int nb = blockIdx.x % 5, ks = blockIdx.x / 5;
    const uint32_t sb = smem_u32(smem_raw), bb = sb + P_BAR;
    if (tid == 0) {
        if ((sb & 0xFFFFFFu) != 1024) __trap();
        for (int i = 0; i < 16; i++) mbar_init(bb + PB_FULL + i * 8, 1);
        for (int i = 0; i < 2; i++) mbar_init(bb + PB_EMPTY + i * 8, 2);
        for (int i = 0; i < 4; i++) { mbar_init(bb + PB_SF + i * 8, 4); mbar_init(bb + PB_SE + i * 8, 1); }
        asm volatile("fence.mbarrier_init.release.cluster;" ::: "memory");
    }
    GT(tid == 0, 8);
    if (OP_LATE && tid == 0) flag_wait(FLG(F_H), 32, 200);
    __syncthreads();
    if (warp < 4) {
        asm volatile("setmaxnreg.dec.sync.aligned.u32 40;");
        if (warp == 0) {
            named_bar(3, 288);
            GT(lane == 0, 3);
            uint32_t it = 0;
#pragma unroll 1
            for (int q = 0; q < 2 * NT; q++) {
                const int l = q & 1, n = (q >> 1) - l * LAG;
                if (n < 0 || n >= NSEG) continue;
                int guard = 0;
                while (ld_acquire(FLG(F_O + l * 64 + n) + ks) < 8) { if (++guard > 4000000) __trap(); __nanosleep(OP_NS); }
                fence_async_global();
                mwait(bb + PB_EMPTY + (it & 1) * 8, ((it >> 1) & 1) ^ 1);
                if (lane < 8) {
                    const uint32_t fb = bb + PB_FULL + ((it & 1) * 8 + lane) * 8;
                    mbar_expect_tx(fb, 8192);
                    asm volatile("cp.async.bulk.shared::cluster.global.mbarrier::complete_tx::bytes [%0], [%1], %2, [%3];" ::"r"(sb + P_RING + (it & 1) * 65536 + lane * 8192),
                                 "l"(g_ot + ((l * NSEG + n) * 256 + (ks * 8 + lane) * 8) * 64), "r"(8192), "r"(fb) : "memory");
                }
                __syncwarp();
                it++;
            }
        } else if (warp == 3) {
#pragma unroll 1
            for (int rg = 1; rg < 4; rg++) {
#pragma unroll 1
                for (int u = rg * 640 + blockIdx.x; u < rg * 640 + 640; u += 20) u_half(Bk, Bv, shiftk, u, lane);
                __syncwarp();
                if (lane == 0) red_release(FLG(F_U + rg), 1);
                GT(lane == 0, 4 + rg);
            }
        } else if (lane == 0) {
            const int cw = warp - 1;
            uint32_t it = 0;
#pragma unroll 1
            for (int q = 0; q < 2 * NT; q++) {
                const int l = q & 1, n = (q >> 1) - l * LAG;
                if (n < 0 || n >= NSEG) continue;
                const uint32_t i = cw * 2 + (it & 1);
                mwait(bb + PB_SF + i * 8, (it >> 1) & 1);
                asm volatile("cp.async.bulk.global.shared::cta.bulk_group [%0], [%1], %2;" ::"l"(g_pt + (((l * NSEG + n) * 4 + ks) * 10 + nb * 2 + cw) * 256), "r"(sb + P_STG + i * 4096), "r"(4096) : "memory");
                asm volatile("cp.async.bulk.commit_group;" ::: "memory");
                asm volatile("cp.async.bulk.wait_group 0;" ::: "memory");
                mbar_arrive(bb + PB_SE + i * 8);
                fence_async_global();
                red_release(FLG(F_P + l * 64 + n), 1);
                GT(true, 330 + l * 64 + n);
                it++;
            }
        }
    } else {
        asm volatile("setmaxnreg.inc.sync.aligned.u32 232;");
        const int cw = (warp >> 2) - 1, w4 = warp & 3, t7 = tid & 127;
        uint32_t wa[64 - OP_SS][4];
        {
            const bf16* W = Wo + (size_t)ks * 1024 * DM + nb * 128 + cw * 64 + (t7 & 7) * 8;
            const uint32_t so = (t7 >> 3) * 128 + (((t7 & 7) ^ ((t7 >> 3) & 7)) << 4);
            const uint32_t stg = sb + P_RING + cw * 65536;
            const uint32_t la = stg + ((lane & 7) + (lane >> 4) * 8) * 128 + (((w4 * 2 + ((lane >> 3) & 1)) ^ (lane & 7)) << 4);
#pragma unroll 4
            for (int i = 0; i < 32; i++) cp_async16(stg + i * 2048 + so, W + (size_t)((OP_SS + i) * 16 + (t7 >> 3)) * DM);
            cp_commit();
#pragma unroll 1
            for (int i = 0; i < OP_SS; i++) cp_async16(sb + P_AS + cw * OP_SS * 2048 + i * 2048 + so, W + (size_t)(i * 16 + (t7 >> 3)) * DM);
            cp_commit();
            cp_wait<1>();
            named_bar(1 + cw, 128);
#pragma unroll
            for (int j = 0; j < 32; j++) { const uint4 v = ldsm4t(la + j * 2048); wa[j][0] = v.x; wa[j][1] = v.y; wa[j][2] = v.z; wa[j][3] = v.w; }
            named_bar(1 + cw, 128);
#pragma unroll 1
            for (int i = 0; i < 32 - OP_SS; i++) cp_async16(stg + i * 2048 + so, W + (size_t)((OP_SS + 32 + i) * 16 + (t7 >> 3)) * DM);
            cp_commit();
            cp_wait<0>();
            named_bar(1 + cw, 128);
#pragma unroll
            for (int j = 0; j < 32 - OP_SS; j++) { const uint4 v = ldsm4t(la + j * 2048); wa[32 + j][0] = v.x; wa[32 + j][1] = v.y; wa[32 + j][2] = v.z; wa[32 + j][3] = v.w; }
            fence_async_smem();
            named_bar(3, 288);
        }
        const uint32_t ab = (1024 + P_AS + cw * OP_SS * 2048) >> 4;
        const int tk = 8 * ((lane & 7) >> 1) + 2 * (lane >> 4) + (lane & 1);
        const uint32_t ea = sb + P_STG + cw * 8192 + tk * 128 + (((2 * w4 + ((lane >> 3) & 1)) ^ (lane & 7)) << 4);
#pragma unroll 1
        for (uint32_t it = 0; it < 2 * NSEG; it++) {
            float acc[16];
            const uint32_t fb = bb + PB_FULL + (it & 1) * 64, par = (it >> 1) & 1;
            const uint32_t ob = opq(((1024 + P_RING) >> 4) + (it & 1) * 4096);
            uint32_t ok = 0;
#pragma unroll
            for (int j = 0; j < 64; j++) {
                if ((j & 7) == 0) {
                    if (j) wg_commit();
                    if (!ok) mwait(fb + j, par);
                    ok = j < 56 ? mtest(fb + j + 8, par) : mtest(bb + PB_SE + (cw * 2 + (it & 1)) * 8, par ^ 1);
                    if (j == 0) wg_fence();
                }
                const uint64_t db = mkdesc(ob + j * 64, 0x80000020u);
                if (j == 0) wg_n32t_sfirst(acc, mkdesc(ab, 0x40000040u), db);
                else if (j < OP_SS) wg_n32t_s(acc, mkdesc(ab + j * 128, 0x40000040u), db);
                else wg_n32t(acc, wa[j - OP_SS][0], wa[j - OP_SS][1], wa[j - OP_SS][2], wa[j - OP_SS][3], db);
            }
            wg_commit();
            if (!ok) mwait(bb + PB_SE + (cw * 2 + (it & 1)) * 8, par ^ 1);
            wg_wait<0>();
            if (t7 == 0) mbar_arrive(bb + PB_EMPTY + (it & 1) * 8);
            const uint32_t e = ea + (it & 1) * 4096;
            stsm4t(e, pack2(acc[0], acc[1]), pack2(acc[2], acc[3]), pack2(acc[4], acc[5]), pack2(acc[6], acc[7]));
            stsm4t(e + 512, pack2(acc[8], acc[9]), pack2(acc[10], acc[11]), pack2(acc[12], acc[13]), pack2(acc[14], acc[15]));
            fence_async_smem();
            __syncwarp();
            if (lane == 0) mbar_arrive(bb + PB_SF + (cw * 2 + (it & 1)) * 8);
        }
    }
}
}

namespace ws {
__global__ void __launch_bounds__(128) reset_kernel(const __grid_constant__ HeadArgs A) {
    const int i = blockIdx.x * 128 + threadIdx.x;
    if (i < NFLAG * 2) reinterpret_cast<uint4*>(g_flags)[i] = make_uint4(0, 0, 0, 0);
    if (i < 4 * 16 * 3 * 8 * 32 / 4) for (int k = 0; k < 4; k++) g_xc[k * (16 * 3 * 8 * 32) + i] = make_uint4(0, 0, 0, 0);
}
static void launch_all(void* const* d_in, void* d_out) {
    static bool inited = false;
    if (!inited) {
        inited = true;
        cudaFuncSetAttribute(head_kernel, cudaFuncAttributeMaxDynamicSharedMemorySize, HEAD_SMEM);
        cudaFuncSetAttribute(head_kernel, cudaFuncAttributeNonPortableClusterSizeAllowed, 1);
        cudaFuncSetAttribute(op_kernel, cudaFuncAttributeMaxDynamicSharedMemorySize, OP_SMEM);
    }
    HeadArgs A;
    A.x = (const bf16*)d_in[0]; A.mem0 = (const bf16*)d_in[1]; A.Wq = (const bf16*)d_in[2]; A.Wk = (const bf16*)d_in[3]; A.Wv = (const bf16*)d_in[4]; A.Wo = (const bf16*)d_in[5];
    A.Bk = (const bf16*)d_in[8]; A.Bv = (const bf16*)d_in[9]; A.shiftk = (const bf16*)d_in[10]; A.ssmk = (const bf16*)d_in[11]; A.ssmD = (const bf16*)d_in[12];
    A.out = (bf16*)d_out; A.h_target = 32;
    cudaStream_t s = cudaStreamPerThread;
    reset_kernel<<<128, 128, 0, s>>>(A);
    {
        cudaLaunchConfig_t cfg = {};
        cfg.gridDim = dim3(NCL * 16); cfg.blockDim = dim3(512); cfg.dynamicSmemBytes = HEAD_SMEM; cfg.stream = s;
        cudaLaunchAttribute at[2];
        at[0].id = cudaLaunchAttributeClusterDimension;
        at[0].val.clusterDim.x = 16; at[0].val.clusterDim.y = 1; at[0].val.clusterDim.z = 1;
        at[1].id = cudaLaunchAttributeProgrammaticStreamSerialization;
        at[1].val.programmaticStreamSerializationAllowed = 1;
        cfg.attrs = at; cfg.numAttrs = PRE_PDL ? 2 : 1;
        cudaLaunchKernelEx(&cfg, head_kernel, A);
    }
    {
        cudaLaunchConfig_t cfg = {};
        cfg.gridDim = dim3(20); cfg.blockDim = dim3(384); cfg.dynamicSmemBytes = OP_SMEM; cfg.stream = s;
        cudaLaunchAttribute at[1];
        at[0].id = cudaLaunchAttributeProgrammaticStreamSerialization;
        at[0].val.programmaticStreamSerializationAllowed = 1;
        cfg.attrs = at; cfg.numAttrs = 1;
        cudaLaunchKernelEx(&cfg, op_kernel, A.Wo, A.Bk, A.Bv, A.shiftk);
    }
}
}

extern "C" void kernel_launch(void* const* d_in, const int* in_sizes, int n_in, void* d_out, int out_size) {
    (void)in_sizes; (void)n_in; (void)out_size;
    ws::launch_all(d_in, d_out);
}
```

```cpp
#include <cuda_runtime.h>
#include <cuda_bf16.h>
#include <stdint.h>
#include <cuda.h>

typedef __nv_bfloat16 bf16;
namespace ws {
constexpr int S_LEN = 2048, DM = 640, NH = 32, DH = 128, HD = NH * DH, SEG = 32, NSEG = S_LEN / SEG;

__device__ __forceinline__ float bf2f(bf16 v) { return __bfloat162float(v); }
__device__ __forceinline__ float rbf(float v) { return __bfloat162float(__float2bfloat16_rn(v)); }
__device__ __forceinline__ uint32_t pack2(float a, float b) {
    __nv_bfloat162 t = __floats2bfloat162_rn(a, b);
    return *reinterpret_cast<uint32_t*>(&t);
}
__device__ __forceinline__ float blo(uint32_t v) { return __uint_as_float(v << 16); }
__device__ __forceinline__ float bhi(uint32_t v) { return __uint_as_float(v & 0xffff0000u); }
__device__ __forceinline__ uint32_t badd(uint32_t a, uint32_t b) { uint32_t r; asm("add.rn.bf16x2 %0, %1, %2;" : "=r"(r) : "r"(a), "r"(b)); return r; }
__device__ __forceinline__ uint32_t smem_u32(const void* p) { return (uint32_t)__cvta_generic_to_shared(p); }
__device__ __forceinline__ uint4 ldsm4(uint32_t a) {
    uint4 v;
    asm volatile("ldmatrix.sync.aligned.m8n8.x4.shared.b16 {%0,%1,%2,%3}, [%4];" : "=r"(v.x), "=r"(v.y), "=r"(v.z), "=r"(v.w) : "r"(a));
    return v;
}
__device__ __forceinline__ uint4 ldsm4t(uint32_t a) {
    uint4 v;
    asm volatile("ldmatrix.sync.aligned.m8n8.x4.trans.shared.b16 {%0,%1,%2,%3}, [%4];" : "=r"(v.x), "=r"(v.y), "=r"(v.z), "=r"(v.w) : "r"(a));
    return v;
}
__device__ __forceinline__ uint2 ldsm2t(uint32_t a) {
    uint2 v;
    asm volatile("ldmatrix.sync.aligned.m8n8.x2.trans.shared.b16 {%0,%1}, [%2];" : "=r"(v.x), "=r"(v.y) : "r"(a));
    return v;
}
__device__ __forceinline__ void stsm4(uint32_t a, uint32_t r0, uint32_t r1, uint32_t r2, uint32_t r3) {
    asm volatile("stmatrix.sync.aligned.m8n8.x4.shared.b16 [%0], {%1,%2,%3,%4};" ::"r"(a), "r"(r0), "r"(r1), "r"(r2), "r"(r3) : "memory");
}
__device__ __forceinline__ void stsm2(uint32_t a, uint32_t r0, uint32_t r1) {
    asm volatile("stmatrix.sync.aligned.m8n8.x2.shared.b16 [%0], {%1,%2};" ::"r"(a), "r"(r0), "r"(r1) : "memory");
}
__device__ __forceinline__ void stsm4t(uint32_t a, uint32_t r0, uint32_t r1, uint32_t r2, uint32_t r3) {
    asm volatile("stmatrix.sync.aligned.m8n8.x4.trans.shared.b16 [%0], {%1,%2,%3,%4};" ::"r"(a), "r"(r0), "r"(r1), "r"(r2), "r"(r3) : "memory");
}
__device__ __forceinline__ void mma16816(float* c, uint32_t a0, uint32_t a1, uint32_t a2, uint32_t a3, uint32_t b0, uint32_t b1) {
    asm("mma.sync.aligned.m16n8k16.row.col.f32.bf16.bf16.f32 {%0,%1,%2,%3}, {%4,%5,%6,%7}, {%8,%9}, {%0,%1,%2,%3};"
        : "+f"(c[0]), "+f"(c[1]), "+f"(c[2]), "+f"(c[3]) : "r"(a0), "r"(a1), "r"(a2), "r"(a3), "r"(b0), "r"(b1));
}
__device__ __forceinline__ void mmav(float* c, uint32_t a0, uint32_t a1, uint32_t a2, uint32_t a3, uint32_t b0, uint32_t b1) {
    asm volatile("mma.sync.aligned.m16n8k16.row.col.f32.bf16.bf16.f32 {%0,%1,%2,%3}, {%4,%5,%6,%7}, {%8,%9}, {%0,%1,%2,%3};"
        : "+f"(c[0]), "+f"(c[1]), "+f"(c[2]), "+f"(c[3]) : "r"(a0), "r"(a1), "r"(a2), "r"(a3), "r"(b0), "r"(b1));
}
__device__ __forceinline__ void mmau(float* c, const uint4& a, uint32_t b0, uint32_t b1) { mma16816(c, a.x, a.y, a.z, a.w, b0, b1); }
__device__ __forceinline__ void mma1688(float* c, uint32_t a0, uint32_t a1, uint32_t b0) {
    asm("mma.sync.aligned.m16n8k8.row.col.f32.bf16.bf16.f32 {%0,%1,%2,%3}, {%4,%5}, {%6}, {%0,%1,%2,%3};"
        : "+f"(c[0]), "+f"(c[1]), "+f"(c[2]), "+f"(c[3]) : "r"(a0), "r"(a1), "r"(b0));
}
__device__ __forceinline__ void mmav8(float* c, uint32_t a0, uint32_t a1, uint32_t b0) {
    asm volatile("mma.sync.aligned.m16n8k8.row.col.f32.bf16.bf16.f32 {%0,%1,%2,%3}, {%4,%5}, {%6}, {%0,%1,%2,%3};"
        : "+f"(c[0]), "+f"(c[1]), "+f"(c[2]), "+f"(c[3]) : "r"(a0), "r"(a1), "r"(b0));
}
__device__ __forceinline__ void cp_async16(uint32_t dst, const void* src) { asm volatile("cp.async.cg.shared.global [%0], [%1], 16;" ::"r"(dst), "l"(src)); }
__device__ __forceinline__ void cp_commit() { asm volatile("cp.async.commit_group;"); }
template <int N> __device__ __forceinline__ void cp_wait() { asm volatile("cp.async.wait_group %0;" ::"n"(N)); }
__device__ __forceinline__ uint4 lds128(uint32_t a) {
    uint4 v;
    asm volatile("ld.shared.v4.u32 {%0,%1,%2,%3}, [%4];" : "=r"(v.x), "=r"(v.y), "=r"(v.z), "=r"(v.w) : "r"(a));
    return v;
}
__device__ __forceinline__ uint2 lds64(uint32_t a) {
    uint2 v;
    asm volatile("ld.shared.v2.u32 {%0,%1}, [%2];" : "=r"(v.x), "=r"(v.y) : "r"(a));
    return v;
}
__device__ __forceinline__ uint32_t lds32(uint32_t a) { uint32_t v; asm volatile("ld.shared.u32 %0, [%1];" : "=r"(v) : "r"(a)); return v; }
__device__ __forceinline__ void sts32(uint32_t a, uint32_t x) { asm volatile("st.shared.u32 [%0], %1;" ::"r"(a), "r"(x) : "memory"); }
__device__ __forceinline__ void sts64(uint32_t a, uint32_t x, uint32_t y) { asm volatile("st.shared.v2.u32 [%0], {%1,%2};" ::"r"(a), "r"(x), "r"(y) : "memory"); }
__device__ __forceinline__ void sts128(uint32_t a, uint32_t x, uint32_t y, uint32_t z, uint32_t w) {
    asm volatile("st.shared.v4.u32 [%0], {%1,%2,%3,%4};" ::"r"(a), "r"(x), "r"(y), "r"(z), "r"(w) : "memory");
}
__device__ __forceinline__ uint4 ld_relaxed_v4(const void* p) {
    uint4 v;
    asm volatile("ld.relaxed.gpu.global.v4.u32 {%0,%1,%2,%3}, [%4];" : "=r"(v.x), "=r"(v.y), "=r"(v.z), "=r"(v.w) : "l"(p) : "memory");
    return v;
}
__device__ __forceinline__ uint2 ld_relaxed_v2(const void* p) {
    uint2 v;
    asm volatile("ld.relaxed.gpu.global.v2.u32 {%0,%1}, [%2];" : "=r"(v.x), "=r"(v.y) : "l"(p) : "memory");
    return v;
}
__device__ __forceinline__ void ld7_relaxed(uint4* x, const void* p) {
    asm volatile("ld.relaxed.gpu.global.v4.u32 {%0,%1,%2,%3}, [%28 + 0];\nld.relaxed.gpu.global.v4.u32 {%4,%5,%6,%7}, [%28 + 512];\nld.relaxed.gpu.global.v4.u32 {%8,%9,%10,%11}, [%28 + 1024];\nld.relaxed.gpu.global.v4.u32 {%12,%13,%14,%15}, [%28 + 1536];\nld.relaxed.gpu.global.v4.u32 {%16,%17,%18,%19}, [%28 + 2048];\nld.relaxed.gpu.global.v4.u32 {%20,%21,%22,%23}, [%28 + 2560];\nld.relaxed.gpu.global.v4.u32 {%24,%25,%26,%27}, [%28 + 3072];\n" : "=r"(x[0].x), "=r"(x[0].y), "=r"(x[0].z), "=r"(x[0].w), "=r"(x[1].x), "=r"(x[1].y), "=r"(x[1].z), "=r"(x[1].w), "=r"(x[2].x), "=r"(x[2].y), "=r"(x[2].z), "=r"(x[2].w), "=r"(x[3].x), "=r"(x[3].y), "=r"(x[3].z), "=r"(x[3].w), "=r"(x[4].x), "=r"(x[4].y), "=r"(x[4].z), "=r"(x[4].w), "=r"(x[5].x), "=r"(x[5].y), "=r"(x[5].z), "=r"(x[5].w), "=r"(x[6].x), "=r"(x[6].y), "=r"(x[6].z), "=r"(x[6].w) : "l"(p) : "memory");
}
__device__ __forceinline__ void ld7_relaxed(uint2* x, const void* p) {
    asm volatile("ld.relaxed.gpu.global.v2.u32 {%0,%1}, [%14 + 0];\nld.relaxed.gpu.global.v2.u32 {%2,%3}, [%14 + 512];\nld.relaxed.gpu.global.v2.u32 {%4,%5}, [%14 + 1024];\nld.relaxed.gpu.global.v2.u32 {%6,%7}, [%14 + 1536];\nld.relaxed.gpu.global.v2.u32 {%8,%9}, [%14 + 2048];\nld.relaxed.gpu.global.v2.u32 {%10,%11}, [%14 + 2560];\nld.relaxed.gpu.global.v2.u32 {%12,%13}, [%14 + 3072];\n" : "=r"(x[0].x), "=r"(x[0].y), "=r"(x[1].x), "=r"(x[1].y), "=r"(x[2].x), "=r"(x[2].y), "=r"(x[3].x), "=r"(x[3].y), "=r"(x[4].x), "=r"(x[4].y), "=r"(x[5].x), "=r"(x[5].y), "=r"(x[6].x), "=r"(x[6].y) : "l"(p) : "memory");
}
__device__ __forceinline__ void st_relaxed_v4(void* p, uint32_t a, uint32_t b, uint32_t c, uint32_t d) {
    asm volatile("st.relaxed.gpu.global.v4.u32 [%0], {%1,%2,%3,%4};" ::"l"(p), "r"(a), "r"(b), "r"(c), "r"(d) : "memory");
}
__device__ __forceinline__ void st_relaxed_v2(void* p, uint32_t a, uint32_t b) {
    asm volatile("st.relaxed.gpu.global.v2.u32 [%0], {%1,%2};" ::"l"(p), "r"(a), "r"(b) : "memory");
}
__device__ __forceinline__ int ld_relaxed(const int* p) {
    int v;
    asm volatile("ld.relaxed.gpu.global.u32 %0, [%1];" : "=r"(v) : "l"(p) : "memory");
    return v;
}
__device__ __forceinline__ int ld_acquire(const int* p) {
    int v;
    asm volatile("ld.acquire.gpu.global.u32 %0, [%1];" : "=r"(v) : "l"(p) : "memory");
    return v;
}
__device__ __forceinline__ void red_release(int* p, int v) { asm volatile("red.release.gpu.global.add.u32 [%0], %1;" ::"l"(p), "r"(v) : "memory"); }
__device__ __forceinline__ void mbar_init(uint32_t bar, int count) { asm volatile("mbarrier.init.shared::cta.b64 [%0], %1;" ::"r"(bar), "r"(count)); }
__device__ __forceinline__ void mbar_expect_tx(uint32_t bar, uint32_t bytes) {
    asm volatile("mbarrier.arrive.expect_tx.shared::cta.b64 _, [%0], %1;" ::"r"(bar), "r"(bytes) : "memory");
}
__device__ __forceinline__ void mbar_arrive(uint32_t bar) { asm volatile("mbarrier.arrive.shared::cta.b64 _, [%0];" ::"r"(bar) : "memory"); }
__device__ __forceinline__ void mbar_arrive_cluster(uint32_t bar) { asm volatile("mbarrier.arrive.shared::cluster.b64 _, [%0];" ::"r"(bar) : "memory"); }
__device__ __forceinline__ bool mtry(uint32_t bar, uint32_t parity) {
    uint32_t ok;
    asm volatile("{\n.reg .pred P1;\nmbarrier.try_wait.parity.shared::cta.b64 P1, [%1], %2;\nselp.u32 %0, 1, 0, P1;\n}\n" : "=r"(ok) : "r"(bar), "r"(parity) : "memory");
    return ok != 0;
}
__device__ __forceinline__ void mslow(uint32_t bar, uint32_t parity) {
    asm volatile(
        "{\n.reg .pred P1;\n.reg .u32 cnt;\n"
        "mov.u32 cnt, 0;\n"
        "LAB_WAIT:\n"
        "mbarrier.try_wait.parity.shared::cta.b64 P1, [%0], %1;\n"
        "@P1 bra DONE;\n"
        "add.u32 cnt, cnt, 1;\n"
        "setp.lt.u32 P1, cnt, 1000000;\n"
        "@P1 bra LAB_WAIT;\n"
        "trap;\n"
        "DONE:\n}\n" ::"r"(bar), "r"(parity) : "memory");
}
__device__ __forceinline__ void mwait(uint32_t bar, uint32_t parity) {
    asm volatile(
        "{\n.reg .pred P1, P2;\n.reg .u32 cnt;\n"
        "mov.u32 cnt, 0;\n"
        "LAB_WAIT:\n"
        "mbarrier.try_wait.parity.shared::cta.b64 P1, [%0], %1;\n"
        "add.u32 cnt, cnt, 1;\n"
        "setp.gt.u32 P2, cnt, 1000000;\n"
        "@P2 trap;\n"
        "@!P1 bra LAB_WAIT;\n"
        "}\n" ::"r"(bar), "r"(parity) : "memory");
}
__device__ __forceinline__ uint32_t mtest(uint32_t bar, uint32_t parity) {
    uint32_t ok;
    asm volatile("{\n.reg .pred P1;\nmbarrier.test_wait.parity.shared::cta.b64 P1, [%1], %2;\nselp.u32 %0, 1, 0, P1;\n}\n" : "=r"(ok) : "r"(bar), "r"(parity) : "memory");
    return ok;
}
__device__ __forceinline__ uint32_t mapa(uint32_t addr, uint32_t rank) {
    uint32_t r;
    asm("mapa.shared::cluster.u32 %0, %1, %2;" : "=r"(r) : "r"(addr), "r"(rank));
    return r;
}
__device__ __forceinline__ void st_async_b32(uint32_t addr, uint32_t a, uint32_t bar) {
    asm volatile("st.async.weak.shared::cluster.mbarrier::complete_tx::bytes.b32 [%0], %1, [%2];" ::"r"(addr), "r"(a), "r"(bar) : "memory");
}
__device__ __forceinline__ void st_async_v2(uint32_t addr, uint32_t a, uint32_t b, uint32_t bar) {
    asm volatile("st.async.weak.shared::cluster.mbarrier::complete_tx::bytes.v2.b32 [%0], {%1,%2}, [%3];" ::"r"(addr), "r"(a), "r"(b), "r"(bar) : "memory");
}
__device__ __forceinline__ void st_async_v2_lt(uint32_t addr, uint32_t a, uint32_t b, uint32_t bar, uint32_t x, uint32_t lim) {
    asm volatile("{\n.reg .pred p;\nsetp.lt.u32 p, %4, %5;\n@p st.async.weak.shared::cluster.mbarrier::complete_tx::bytes.v2.b32 [%0], {%1,%2}, [%3];\n}"
                 ::"r"(addr), "r"(a), "r"(b), "r"(bar), "r"(x), "r"(lim) : "memory");
}
__device__ __forceinline__ void st_async_v4(uint32_t addr, uint32_t a, uint32_t b, uint32_t c, uint32_t d, uint32_t bar) {
    asm volatile("st.async.weak.shared::cluster.mbarrier::complete_tx::bytes.v4.b32 [%0], {%1,%2,%3,%4}, [%5];" ::"r"(addr), "r"(a), "r"(b), "r"(c), "r"(d), "r"(bar) : "memory");
}
__device__ __forceinline__ void cluster_arrive() { asm volatile("barrier.cluster.arrive.release.aligned;" ::: "memory"); }
__device__ __forceinline__ void cluster_arrive_relaxed() { asm volatile("barrier.cluster.arrive.relaxed.aligned;" ::: "memory"); }
__device__ __forceinline__ void prefetch_l2(const void* p, uint32_t bytes) { asm volatile("cp.async.bulk.prefetch.L2.global [%0], %1;" ::"l"(p), "r"(bytes) : "memory"); }
__device__ __forceinline__ void cluster_wait() { asm volatile("barrier.cluster.wait.acquire.aligned;" ::: "memory"); }
__device__ __forceinline__ void named_bar(int id, int n) { asm volatile("bar.sync %0, %1;" ::"r"(id), "r"(n) : "memory"); }
__device__ __forceinline__ void named_arrive(int id, int n) { asm volatile("bar.arrive %0, %1;" ::"r"(id), "r"(n) : "memory"); }
__device__ __forceinline__ void fence_async_smem() { asm volatile("fence.proxy.async.shared::cta;" ::: "memory"); }
__device__ __forceinline__ void fence_async_global() { asm volatile("fence.proxy.async.global;" ::: "memory"); }
__device__ __forceinline__ void wg_fence() { asm volatile("wgmma.fence.sync.aligned;" ::: "memory"); }
__device__ __forceinline__ void wg_commit() { asm volatile("wgmma.commit_group.sync.aligned;" ::: "memory"); }
template <int N> __device__ __forceinline__ void wg_wait() { asm volatile("wgmma.wait_group.sync.aligned %0;" ::"n"(N) : "memory"); }
__device__ __forceinline__ uint64_t ndesc(uint32_t addr, uint32_t lbo, uint32_t sbo) {
    return (uint64_t)((addr & 0x3FFFF) >> 4) | ((uint64_t)(lbo >> 4) << 16) | ((uint64_t)(sbo >> 4) << 32);
}
__device__ __forceinline__ float ex2f(float x) { float y; asm("ex2.approx.ftz.f32 %0, %1;" : "=f"(y) : "f"(x)); return y; }
__device__ __forceinline__ float rcpf(float x) { float y; asm("rcp.approx.ftz.f32 %0, %1;" : "=f"(y) : "f"(x)); return y; }
__device__ __forceinline__ uint32_t clk32() { uint32_t c; asm volatile("mov.u32 %0, %clock;" : "=r"(c)); return c; }
__device__ __forceinline__ uint32_t opq(uint32_t x) { uint32_t y; asm volatile("mov.u32 %0, %1;" : "=r"(y) : "r"(x)); return y; }
__device__ __forceinline__ uint32_t rem(uint32_t addr, uint32_t rank) { return mapa(addr, rank); }
__device__ __forceinline__ uint64_t mkdesc(uint32_t lo, uint32_t hi) { uint64_t d; asm("mov.b64 %0, {%1,%2};" : "=l"(d) : "r"(lo), "r"(hi)); return d; }
__device__ __forceinline__ void delay(uint32_t n) {
    asm volatile("{\n.reg .pred P;\n.reg .u32 a, b;\nmov.u32 a, %clock;\nadd.u32 a, a, %0;\nDL:\nmov.u32 b, %clock;\nsub.u32 b, b, a;\nsetp.lt.s32 P, b, 0;\n@P bra.uni DL;\n}" ::"r"(n) : "memory");
}
#define UNI(x) __shfl_sync(0xffffffffu, (uint32_t)(x), 0)
__device__ __forceinline__ void wg_n16t(float* d, uint32_t a0, uint32_t a1, uint32_t a2, uint32_t a3, uint64_t db) {
    asm volatile("wgmma.mma_async.sync.aligned.m64n16k16.f32.bf16.bf16 {%0, %1, %2, %3, %4, %5, %6, %7}, {%8, %9, %10, %11}, %12, 1, 1, 1, 1;"
                 : "+f"(d[0]), "+f"(d[1]), "+f"(d[2]), "+f"(d[3]), "+f"(d[4]), "+f"(d[5]), "+f"(d[6]), "+f"(d[7]) : "r"(a0), "r"(a1), "r"(a2), "r"(a3), "l"(db));
}
__device__ __forceinline__ void wg_n16t_first(float* d, uint32_t a0, uint32_t a1, uint32_t a2, uint32_t a3, uint64_t db) {
    asm volatile("wgmma.mma_async.sync.aligned.m64n16k16.f32.bf16.bf16 {%0, %1, %2, %3, %4, %5, %6, %7}, {%8, %9, %10, %11}, %12, 0, 1, 1, 1;"
                 : "=f"(d[0]), "=f"(d[1]), "=f"(d[2]), "=f"(d[3]), "=f"(d[4]), "=f"(d[5]), "=f"(d[6]), "=f"(d[7]) : "r"(a0), "r"(a1), "r"(a2), "r"(a3), "l"(db));
}
__device__ __forceinline__ void wg_n32(float* d, uint32_t a0, uint32_t a1, uint32_t a2, uint32_t a3, uint64_t db) {
    asm volatile("wgmma.mma_async.sync.aligned.m64n32k16.f32.bf16.bf16 {%0, %1, %2, %3, %4, %5, %6, %7, %8, %9, %10, %11, %12, %13, %14, %15}, {%16, %17, %18, %19}, %20, 1, 1, 1, 0;"
                 : "+f"(d[0]), "+f"(d[1]), "+f"(d[2]), "+f"(d[3]), "+f"(d[4]), "+f"(d[5]), "+f"(d[6]), "+f"(d[7]), "+f"(d[8]), "+f"(d[9]), "+f"(d[10]), "+f"(d[11]), "+f"(d[12]), "+f"(d[13]), "+f"(d[14]), "+f"(d[15]) : "r"(a0), "r"(a1), "r"(a2), "r"(a3), "l"(db));
}
__device__ __forceinline__ void wg_n32_first(float* d, uint32_t a0, uint32_t a1, uint32_t a2, uint32_t a3, uint64_t db) {
    asm volatile("wgmma.mma_async.sync.aligned.m64n32k16.f32.bf16.bf16 {%0, %1, %2, %3, %4, %5, %6, %7, %8, %9, %10, %11, %12, %13, %14, %15}, {%16, %17, %18, %19}, %20, 0, 1, 1, 0;"
                 : "=f"(d[0]), "=f"(d[1]), "=f"(d[2]), "=f"(d[3]), "=f"(d[4]), "=f"(d[5]), "=f"(d[6]), "=f"(d[7]), "=f"(d[8]), "=f"(d[9]), "=f"(d[10]), "=f"(d[11]), "=f"(d[12]), "=f"(d[13]), "=f"(d[14]), "=f"(d[15]) : "r"(a0), "r"(a1), "r"(a2), "r"(a3), "l"(db));
}

__device__ __forceinline__ void wg_n16t_sfirst(float* d, uint64_t da, uint64_t db) {
    asm volatile("wgmma.mma_async.sync.aligned.m64n16k16.f32.bf16.bf16 {%0, %1, %2, %3, %4, %5, %6, %7}, %8, %9, 0, 1, 1, 1, 1;"
                 : "=f"(d[0]), "=f"(d[1]), "=f"(d[2]), "=f"(d[3]), "=f"(d[4]), "=f"(d[5]), "=f"(d[6]), "=f"(d[7]) : "l"(da), "l"(db));
}
__device__ __forceinline__ void wg_n32_sfirst(float* d, uint64_t da, uint64_t db) {
    asm volatile("wgmma.mma_async.sync.aligned.m64n32k16.f32.bf16.bf16 {%0, %1, %2, %3, %4, %5, %6, %7, %8, %9, %10, %11, %12, %13, %14, %15}, %16, %17, 0, 1, 1, 1, 0;"
                 : "=f"(d[0]), "=f"(d[1]), "=f"(d[2]), "=f"(d[3]), "=f"(d[4]), "=f"(d[5]), "=f"(d[6]), "=f"(d[7]), "=f"(d[8]), "=f"(d[9]), "=f"(d[10]), "=f"(d[11]), "=f"(d[12]), "=f"(d[13]), "=f"(d[14]), "=f"(d[15]) : "l"(da), "l"(db));
}

__device__ __forceinline__ void wg_n16t_s(float* d, uint64_t da, uint64_t db) {
    asm volatile("wgmma.mma_async.sync.aligned.m64n16k16.f32.bf16.bf16 {%0, %1, %2, %3, %4, %5, %6, %7}, %8, %9, 1, 1, 1, 1, 1;"
                 : "+f"(d[0]), "+f"(d[1]), "+f"(d[2]), "+f"(d[3]), "+f"(d[4]), "+f"(d[5]), "+f"(d[6]), "+f"(d[7]) : "l"(da), "l"(db));
}
__device__ __forceinline__ void wg_n64_sfirst(float* d, uint64_t da, uint64_t db) {
    asm volatile("wgmma.mma_async.sync.aligned.m64n64k16.f32.bf16.bf16 {%0, %1, %2, %3, %4, %5, %6, %7, %8, %9, %10, %11, %12, %13, %14, %15, %16, %17, %18, %19, %20, %21, %22, %23, %24, %25, %26, %27, %28, %29, %30, %31}, %32, %33, 0, 1, 1, 1, 0;"
                 : "=f"(d[0]), "=f"(d[1]), "=f"(d[2]), "=f"(d[3]), "=f"(d[4]), "=f"(d[5]), "=f"(d[6]), "=f"(d[7]), "=f"(d[8]), "=f"(d[9]), "=f"(d[10]), "=f"(d[11]), "=f"(d[12]), "=f"(d[13]), "=f"(d[14]), "=f"(d[15]), "=f"(d[16]), "=f"(d[17]), "=f"(d[18]), "=f"(d[19]), "=f"(d[20]), "=f"(d[21]), "=f"(d[22]), "=f"(d[23]), "=f"(d[24]), "=f"(d[25]), "=f"(d[26]), "=f"(d[27]), "=f"(d[28]), "=f"(d[29]), "=f"(d[30]), "=f"(d[31]) : "l"(da), "l"(db));
}
__device__ __forceinline__ void wg_n64_s(float* d, uint64_t da, uint64_t db) {
    asm volatile("wgmma.mma_async.sync.aligned.m64n64k16.f32.bf16.bf16 {%0, %1, %2, %3, %4, %5, %6, %7, %8, %9, %10, %11, %12, %13, %14, %15, %16, %17, %18, %19, %20, %21, %22, %23, %24, %25, %26, %27, %28, %29, %30, %31}, %32, %33, 1, 1, 1, 1, 0;"
                 : "+f"(d[0]), "+f"(d[1]), "+f"(d[2]), "+f"(d[3]), "+f"(d[4]), "+f"(d[5]), "+f"(d[6]), "+f"(d[7]), "+f"(d[8]), "+f"(d[9]), "+f"(d[10]), "+f"(d[11]), "+f"(d[12]), "+f"(d[13]), "+f"(d[14]), "+f"(d[15]), "+f"(d[16]), "+f"(d[17]), "+f"(d[18]), "+f"(d[19]), "+f"(d[20]), "+f"(d[21]), "+f"(d[22]), "+f"(d[23]), "+f"(d[24]), "+f"(d[25]), "+f"(d[26]), "+f"(d[27]), "+f"(d[28]), "+f"(d[29]), "+f"(d[30]), "+f"(d[31]) : "l"(da), "l"(db));
}
__device__ __forceinline__ void wg_n64(float* d, uint32_t a0, uint32_t a1, uint32_t a2, uint32_t a3, uint64_t db) {
    asm volatile("wgmma.mma_async.sync.aligned.m64n64k16.f32.bf16.bf16 {%0, %1, %2, %3, %4, %5, %6, %7, %8, %9, %10, %11, %12, %13, %14, %15, %16, %17, %18, %19, %20, %21, %22, %23, %24, %25, %26, %27, %28, %29, %30, %31}, {%32, %33, %34, %35}, %36, 1, 1, 1, 0;"
                 : "+f"(d[0]), "+f"(d[1]), "+f"(d[2]), "+f"(d[3]), "+f"(d[4]), "+f"(d[5]), "+f"(d[6]), "+f"(d[7]), "+f"(d[8]), "+f"(d[9]), "+f"(d[10]), "+f"(d[11]), "+f"(d[12]), "+f"(d[13]), "+f"(d[14]), "+f"(d[15]), "+f"(d[16]), "+f"(d[17]), "+f"(d[18]), "+f"(d[19]), "+f"(d[20]), "+f"(d[21]), "+f"(d[22]), "+f"(d[23]), "+f"(d[24]), "+f"(d[25]), "+f"(d[26]), "+f"(d[27]), "+f"(d[28]), "+f"(d[29]), "+f"(d[30]), "+f"(d[31]) : "r"(a0), "r"(a1), "r"(a2), "r"(a3), "l"(db));
}
__device__ __forceinline__ void wg_n64_first(float* d, uint32_t a0, uint32_t a1, uint32_t a2, uint32_t a3, uint64_t db) {
    asm volatile("wgmma.mma_async.sync.aligned.m64n64k16.f32.bf16.bf16 {%0, %1, %2, %3, %4, %5, %6, %7, %8, %9, %10, %11, %12, %13, %14, %15, %16, %17, %18, %19, %20, %21, %22, %23, %24, %25, %26, %27, %28, %29, %30, %31}, {%32, %33, %34, %35}, %36, 0, 1, 1, 0;"
                 : "=f"(d[0]), "=f"(d[1]), "=f"(d[2]), "=f"(d[3]), "=f"(d[4]), "=f"(d[5]), "=f"(d[6]), "=f"(d[7]), "=f"(d[8]), "=f"(d[9]), "=f"(d[10]), "=f"(d[11]), "=f"(d[12]), "=f"(d[13]), "=f"(d[14]), "=f"(d[15]), "=f"(d[16]), "=f"(d[17]), "=f"(d[18]), "=f"(d[19]), "=f"(d[20]), "=f"(d[21]), "=f"(d[22]), "=f"(d[23]), "=f"(d[24]), "=f"(d[25]), "=f"(d[26]), "=f"(d[27]), "=f"(d[28]), "=f"(d[29]), "=f"(d[30]), "=f"(d[31]) : "r"(a0), "r"(a1), "r"(a2), "r"(a3), "l"(db));
}

__device__ __forceinline__ void wg_n32t(float* d, uint32_t a0, uint32_t a1, uint32_t a2, uint32_t a3, uint64_t db) {
    asm volatile("wgmma.mma_async.sync.aligned.m64n32k16.f32.bf16.bf16 {%0, %1, %2, %3, %4, %5, %6, %7, %8, %9, %10, %11, %12, %13, %14, %15}, {%16, %17, %18, %19}, %20, 1, 1, 1, 1;"
                 : "+f"(d[0]), "+f"(d[1]), "+f"(d[2]), "+f"(d[3]), "+f"(d[4]), "+f"(d[5]), "+f"(d[6]), "+f"(d[7]), "+f"(d[8]), "+f"(d[9]), "+f"(d[10]), "+f"(d[11]), "+f"(d[12]), "+f"(d[13]), "+f"(d[14]), "+f"(d[15]) : "r"(a0), "r"(a1), "r"(a2), "r"(a3), "l"(db));
}
__device__ __forceinline__ void wg_n32t_first(float* d, uint32_t a0, uint32_t a1, uint32_t a2, uint32_t a3, uint64_t db) {
    asm volatile("wgmma.mma_async.sync.aligned.m64n32k16.f32.bf16.bf16 {%0, %1, %2, %3, %4, %5, %6, %7, %8, %9, %10, %11, %12, %13, %14, %15}, {%16, %17, %18, %19}, %20, 0, 1, 1, 1;"
                 : "=f"(d[0]), "=f"(d[1]), "=f"(d[2]), "=f"(d[3]), "=f"(d[4]), "=f"(d[5]), "=f"(d[6]), "=f"(d[7]), "=f"(d[8]), "=f"(d[9]), "=f"(d[10]), "=f"(d[11]), "=f"(d[12]), "=f"(d[13]), "=f"(d[14]), "=f"(d[15]) : "r"(a0), "r"(a1), "r"(a2), "r"(a3), "l"(db));
}
__device__ __forceinline__ void wg_n32t_sfirst(float* d, uint64_t da, uint64_t db) {
    asm volatile("wgmma.mma_async.sync.aligned.m64n32k16.f32.bf16.bf16 {%0, %1, %2, %3, %4, %5, %6, %7, %8, %9, %10, %11, %12, %13, %14, %15}, %16, %17, 0, 1, 1, 1, 1;"
                 : "=f"(d[0]), "=f"(d[1]), "=f"(d[2]), "=f"(d[3]), "=f"(d[4]), "=f"(d[5]), "=f"(d[6]), "=f"(d[7]), "=f"(d[8]), "=f"(d[9]), "=f"(d[10]), "=f"(d[11]), "=f"(d[12]), "=f"(d[13]), "=f"(d[14]), "=f"(d[15]) : "l"(da), "l"(db));
}
__device__ __forceinline__ void wg_n32t_s(float* d, uint64_t da, uint64_t db) {
    asm volatile("wgmma.mma_async.sync.aligned.m64n32k16.f32.bf16.bf16 {%0, %1, %2, %3, %4, %5, %6, %7, %8, %9, %10, %11, %12, %13, %14, %15}, %16, %17, 1, 1, 1, 1, 1;"
                 : "+f"(d[0]), "+f"(d[1]), "+f"(d[2]), "+f"(d[3]), "+f"(d[4]), "+f"(d[5]), "+f"(d[6]), "+f"(d[7]), "+f"(d[8]), "+f"(d[9]), "+f"(d[10]), "+f"(d[11]), "+f"(d[12]), "+f"(d[13]), "+f"(d[14]), "+f"(d[15]) : "l"(da), "l"(db));
}

}

namespace ws {
#define LAGT 4
constexpr int LAG = LAGT, NT = NSEG + LAG, NCL = 7;
#define P1A 26
#define P1C 10
#define XD 300
#define TPV_PAUSE 1
#define OT_LATE 1
#define H1_LATE 1
#define O_BULK 0
#define O_DLY 0
#define BP 0
#define REG_G 200
#define REG_T 72
#define REG_X 40
#define PDA 8
#define PDC 8
template <int V> struct IC { static constexpr int value = V; };
#define HBYTES 5120
#define POST_NS 40
#define OP_NS 40
#define LN0_AHEAD 8
#define PRE_PDL 0
#define PRE_PF 0
#define OP_LATE 0
#define G_DLY 0
#define QUIET 0
constexpr int NB4 = QUIET ? 480 : 384;
#define TG_STEPS 40
#define NO_X 0
#define WTA 4
constexpr int WTC = 10 - 2 * WTA;
#define WR 4
#define OBK 2
#define TPVW 1
#define OBRES 0
#define O0_EARLY 1
#define BNS 0
#define SKEW 0
#define XS 250
constexpr int XRS = (NT - 2) % 3 >= 2 ? 3 : ((NT - 2) % 4 >= 2 ? 4 : 5);
static_assert((NT - 2) % XRS >= 2, "ring");
constexpr int O_H = 0, O_MEM = 81920, O_RED = 102400, O_BAR = 110080, O_TAB = O_BAR + 192, O_BT = O_TAB + 128, O_TR = O_BAR + 512, O_X = O_TR + 1024;
constexpr int O_QRY = O_X, O_KEY = O_X + 10240, O_OBA = O_KEY + 10240, O_ST = O_OBA + 4096;
constexpr int O_VT = O_X, O_VM = O_VT + 32768, O_SM = O_VM + 4096, O_PB = O_SM + 3072;
constexpr int O_AS = 228352, O_WO = O_AS - 65536, HEAD_SMEM = O_AS + 4096, O_STG = 40960;
static_assert(O_ST + 8192 <= O_WO && O_PB + 10240 <= O_WO && O_AS % 1024 == 0 && O_STG + 163840 <= O_AS && HEAD_SMEM <= 232448, "smem");
constexpr int B_MEM = 0, B_RED = 64, B_SM = 88, B_ST = 96, B_OB = 104, B_HF = 112, B_HE = 128, B_OTF = 144, B_OTE = 160;

constexpr int F_H = 0, F_O = 128, F_P = 256, F_U = 384, F_CV = 392, NFLAG = 400;
__device__ int g_flags[NFLAG * 8];
#define FLG(i) (g_flags + (i) * 8)
__device__ uint4 g_ht[2 * NSEG * 2560];
__device__ uint4 g_ot[2 * NSEG * 256 * 64];
__device__ uint4 g_pt[2 * NSEG * 4 * 2560];
__device__ uint4 g_Y[80 * S_LEN];
__device__ uint4 g_U[DM * S_LEN / 8];
__device__ bf16 g_x[S_LEN * DM];
__device__ int g_epoch;
__device__ uint4 g_xc[5 * 16 * 3 * 8 * 32];
#define GT(cond, i)
#define SC(cond, i)
#define SD(x)
#define TS(i)
#define TV(i, v)

}

namespace ws {
__device__ __forceinline__ uint32_t bmul2(uint32_t a, uint32_t b) { uint32_t r; asm("mul.rn.bf16x2 %0, %1, %2;" : "=r"(r) : "r"(a), "r"(b)); return r; }
__device__ __forceinline__ uint32_t bmax2(uint32_t a, uint32_t b) { uint32_t r; asm("max.bf16x2 %0, %1, %2;" : "=r"(r) : "r"(a), "r"(b)); return r; }
__device__ __forceinline__ void flag_wait(const int* f, int tgt, int ns) {
    int guard = 0;
    while (ld_relaxed(f) < tgt) { if (++guard > 4000000) __trap(); __nanosleep(ns); }
}
template <int STRIDE> __device__ __forceinline__ void ld5(uint32_t* w, const void* p) {
#pragma unroll
    for (int r = 0; r < 5; r++) { const uint2 v = __ldcg(reinterpret_cast<const uint2*>(reinterpret_cast<const char*>(p) + r * STRIDE)); w[2 * r] = v.x; w[2 * r + 1] = v.y; }
}
template <int STRIDE> __device__ __forceinline__ void st5(void* p, const uint32_t* w) {
#pragma unroll
    for (int r = 0; r < 5; r++) *reinterpret_cast<uint2*>(reinterpret_cast<char*>(p) + r * STRIDE) = make_uint2(w[2 * r], w[2 * r + 1]);
}
__device__ __forceinline__ void ln_row(const uint32_t* x, uint32_t* y) {
    const float c = blo(__shfl_sync(0xffffffffu, x[0], 0));
    float s0 = 0.f, s1 = 0.f, q0 = 0.f, q1 = 0.f;
#pragma unroll
    for (int i = 0; i < 10; i++) { const float d0 = blo(x[i]) - c, d1 = bhi(x[i]) - c; s0 += d0; s1 += d1; q0 = fmaf(d0, d0, q0); q1 = fmaf(d1, d1, q1); }
    float s = s0 + s1, q = q0 + q1;
#pragma unroll
    for (int o = 16; o > 0; o >>= 1) { s += __shfl_xor_sync(0xffffffffu, s, o); q += __shfl_xor_sync(0xffffffffu, q, o); }
    s *= 1.0f / DM;
    const float mean = c + s;
    q = fmaxf(fmaf(q, 1.0f / DM, -s * s), 0.f);
    const uint32_t nm = pack2(-mean, -mean);
    float sq;
    asm("sqrt.approx.ftz.f32 %0, %1;" : "=f"(sq) : "f"(rbf(rbf(q) + 1e-5f)));
    const float rd = rcpf(rbf(sq));
#pragma unroll
    for (int i = 0; i < 10; i++) { const uint32_t d = badd(x[i], nm); y[i] = pack2(blo(d) * rd, bhi(d) * rd); }
}
__device__ __forceinline__ void put_h(int l, int seg, int tok, int lane, const uint32_t* n) {
    st5<8192>(reinterpret_cast<char*>(g_ht + (l * NSEG + seg) * 2560) + (lane >> 2) * 1024 + tok * 32 + (((lane & 3) * 8) ^ ((tok & 4) << 2)), n);
}
__device__ __forceinline__ void ln0_row(const bf16* x, int seg, int tok, int lane) {
    uint32_t v[10];
    ld5<256>(v, x + (size_t)(seg * SEG + tok) * DM + lane * 4);
    ln_row(v, v);
    put_h(0, seg, tok, lane, v);
    __syncwarp();
    if (lane == 0) red_release(FLG(F_H + seg), 1);
}
__device__ __forceinline__ void post_row(int l, int seg, int tok, int lane, const bf16* xin, bf16* xout, int ep) {
    const bool dry = ep == 0;
    uint32_t x[10], y[10], n[10];
    const int row = seg * SEG + tok;
    SC(tr, tb);
    const bool first = seg == 0;
    if (seg == 8 || ((seg & 15) == 0 && seg)) flag_wait(FLG(F_CV + (seg >> 4) + 1), 80 * ep, 50);
    const char* yp = reinterpret_cast<const char*>(g_Y) + ((size_t)(lane >> 1) * S_LEN + row) * 16 + (lane & 1) * 8;
    SC(tr, tb + 1);
    if (!first) ld5<16 * S_LEN * 16>(y, yp);
    if (l == 0) ld5<256>(x, xin + (size_t)row * DM + lane * 4);
    flag_wait(FLG(F_P + l * 64 + seg), 40 * ep, POST_NS);
    SC(tr, tb + 2);
    if (l) ld5<256>(x, xin + (size_t)row * DM + lane * 4);
    {
        const char* pp = reinterpret_cast<const char*>(g_pt + (l * NSEG + seg) * 10240) + (lane >> 4) * 4096 + tok * 128 +
                         ((((lane & 15) >> 1) ^ (((tok >> 3) << 1) | (tok & 1))) << 4) + (lane & 1) * 8;
        uint32_t a[10], b[10], c[10];
        ld5<8192>(a, pp); ld5<8192>(b, pp + 40960); ld5<8192>(c, pp + 81920); ld5<8192>(n, pp + 122880);
#pragma unroll
        for (int i = 0; i < 10; i++)
            x[i] = badd(x[i], pack2((blo(a[i]) + blo(b[i])) + (blo(c[i]) + blo(n[i])), (bhi(a[i]) + bhi(b[i])) + (bhi(c[i]) + bhi(n[i]))));
    }
    SC(tr && x[0] != 0x12345, tb + 3);
    if (first) { flag_wait(FLG(F_CV), 80 * ep, 50); ld5<16 * S_LEN * 16>(y, yp); }
    ln_row(x, n);
#pragma unroll
    for (int i = 0; i < 10; i++) x[i] = badd(x[i], bmul2(n[i], y[i]));
    SC(tr && x[0] != 0x12345, tb + 4);
    if (!dry) st5<256>(xout + (size_t)row * DM + lane * 4, x);
    if (l == 0) {
        ln_row(x, n);
        SC(tr && n[0] != 0x12345, tb + 5);
        if (!dry) put_h(1, seg, tok, lane, n);
        __syncwarp();
        if (lane == 0) red_release(FLG(F_H + 64 + seg), dry ? 0 : 1);
        SC(tr, tb + 6);
    }
}
__device__ __forceinline__ void u_half(const bf16* Bk, const bf16* Bv, const bf16* shiftk, int unit, int lane) {
    const int odd = lane & 1, t0 = (unit / 20) * 16 + odd * 8, cp = (unit % 20) * 16 + (lane >> 1);
    uint32_t kk[11], vv[8];
    const uint32_t* pk = reinterpret_cast<const uint32_t*>(Bk + (size_t)t0 * DM) + cp;
    const uint32_t* pv = reinterpret_cast<const uint32_t*>(Bv + (size_t)t0 * DM) + cp;
#pragma unroll
    for (int i = 0; i < 11; i++) kk[i] = (i >= 3 || t0 > 0) ? __ldg(pk + (i - 3) * (DM / 2)) : 0u;
#pragma unroll
    for (int i = 0; i < 8; i++) vv[i] = __ldg(pv + i * (DM / 2));
    const uint4 sh0 = __ldg(reinterpret_cast<const uint4*>(shiftk + cp * 8));
    const uint32_t s0 = __byte_perm(sh0.x, sh0.z, 0x5410), s1 = __byte_perm(sh0.x, sh0.z, 0x7632), s2 = __byte_perm(sh0.y, sh0.w, 0x5410), s3 = __byte_perm(sh0.y, sh0.w, 0x7632);
#pragma unroll
    for (int t = 0; t < 8; t++)
        vv[t] = bmul2(badd(badd(badd(bmul2(kk[t], s3), bmul2(kk[t + 1], s2)), bmul2(kk[t + 2], s1)), bmul2(kk[t + 3], s0)), vv[t]);
    uint4* d = g_U + (size_t)(cp * 2) * (S_LEN / 8) + (t0 >> 6) * 8 + ((((t0 ^ 56) & 63) >> 3) ^ ((t0 >> 6) & 7));
#pragma unroll
    for (int c = 0; c < 2; c++) {
        const uint32_t sel = c ? 0x7632 : 0x5410;
        d[c * (S_LEN / 8)] = make_uint4(__byte_perm(vv[7], vv[6], sel), __byte_perm(vv[5], vv[4], sel), __byte_perm(vv[3], vv[2], sel), __byte_perm(vv[1], vv[0], sel));
    }
}
constexpr int CV_E = 4224, CV_W = 2 * 4096 + 3 * CV_E + 128, CV_HI = O_X, CV_Y = CV_HI + 4 * CV_W, CV_T = CV_Y + 16384, CV_Z = CV_T + 16384;
static_assert(4 * CV_W <= O_RED && CV_W % 128 == 0 && CV_Z + 128 <= HEAD_SMEM, "conv buffers");
__device__ __forceinline__ void conv_unit(uint32_t ub, uint32_t e0, uint32_t e1, uint32_t zrow, uint32_t tt, uint32_t Dv, int rg, int nq, int lane, uint32_t zero, int tb) {
    const int g7 = 7 - (lane >> 2), tq = lane & 3;
    SC(tb >= 0, tb + 3);
    for (int i = lane; i < 32 * nq + 8; i += 32) {
        const uint4 v = lds128(e0 + i * 16);
        const uint32_t nx = lds32(e0 + i * 16 + 16);
        sts128(e1 + i * 16, __byte_perm(v.x, v.y, 0x5432), __byte_perm(v.y, v.z, 0x5432), __byte_perm(v.z, v.w, 0x5432), __byte_perm(v.w, nx, 0x5432));
    }
    __syncwarp();
    SC(tb >= 0, tb + 4);
    float acc[4][4];
#pragma unroll
    for (int i = 0; i < 16; i++) (&acc[0][0])[i] = 0.f;
    uint32_t wb = (g7 & 1) ? e0 + (1 + g7 + 2 * tq) * 2 : e1 + (g7 + 2 * tq) * 2;
    int row = 8 * rg + (lane & 7);
    auto ldb = [&](uint4* b) {
        const uint32_t x = row < 0 ? zrow : ub + row * 128 + (((lane >> 3) ^ (row & 7)) << 4);
        b[0] = ldsm4(x); b[1] = ldsm4(x ^ 64);
        row--;
    };
    uint4 Q[16], b[2][2];
    Q[15].w = lds32(wb);
    auto ldq = [&](int q, int o) { Q[q].y = lds32(wb + o * 32 + 16); Q[q].w = lds32(wb + o * 32 + 32); };
    auto cpq = [&](int q) { Q[q].x = Q[(q + 15) & 15].w + zero; Q[q].z = Q[q].y + zero; };
#pragma unroll
    for (int q = 0; q < 11; q++) ldq(q, q);
#pragma unroll
    for (int q = 0; q < 7; q++) cpq(q);
    ldb(b[0]);
#pragma unroll 1
    for (int D0 = nq; D0 > 0; D0--) {
#pragma unroll
        for (int d = 0; d < 4; d++) {
            ldb(b[(d + 1) & 1]);
#pragma unroll
            for (int q = 11; q < 15; q++) ldq((4 * d + q) & 15, 4 * d + q);
#pragma unroll
            for (int ks = 0; ks < 4; ks++) {
                const uint4& bb_ = b[d & 1][ks >> 1];
#pragma unroll
                for (int m = 0; m < 4; m++) {
                    const uint4& a = Q[(4 * d + m + ks) & 15];
                    mmav(acc[m], a.x, a.y, a.z, a.w, (ks & 1) ? bb_.z : bb_.x, (ks & 1) ? bb_.w : bb_.y);
                }
                cpq((4 * d + 7 + ks) & 15);
            }
        }
        wb += 512;
    }
    SC(tb >= 0 && acc[0][0] != 1.2345f, tb + 5);
    const uint32_t ua = ub + (8 * rg + (lane & 7)) * 128 + (((lane >> 3) ^ (lane & 7)) << 4);
    const uint4 u0 = ldsm4t(ua), u1 = ldsm4t(ua ^ 64);
    auto y = [&](int m, int hf, uint32_t u) { return badd(pack2(acc[m][2 * hf], acc[m][2 * hf + 1]), bmul2(u, Dv)); };
    stsm4t(tt, y(0, 0, u1.w), y(0, 1, u1.z), y(1, 0, u1.y), y(1, 1, u1.x));
    stsm4t(tt ^ 64, y(2, 0, u0.w), y(2, 1, u0.z), y(3, 0, u0.y), y(3, 1, u0.x));
}
}

namespace ws {
struct HeadArgs { const bf16 *x, *mem0, *Wq, *Wk, *Wv, *Wo, *Bk, *Bv, *shiftk, *ssmk, *ssmD; bf16* out; int h_target; };

__global__ void __launch_bounds__(512, 1) head_kernel(const __grid_constant__ HeadArgs A) {
    extern __shared__ __align__(1024) unsigned char smem_raw[];
    const int tid = threadIdx.x, warp = __shfl_sync(0xffffffffu, tid >> 5, 0), lane = tid & 31;
    const int cq = blockIdx.x >> 4, r = blockIdx.x & 15;
    const int nh = cq < 4 ? 5 : 4, hi = r / 3, role = r - hi * 3;
    const bool head = r < 3 * nh;
    const int h = (cq < 4 ? 5 * cq : 4 * cq + 4) + hi;
    const uint32_t sb = smem_u32(smem_raw), bb = sb + O_BAR;
    GT(tid == 0, 1);
    const int sp = cq < 4 ? cq : 4 * cq + r - 24;
    if (tid == 0) {
        if ((sb & 0xFFFFFFu) != 1024) __trap();
        for (int i = 0; i < 12; i++) mbar_init(bb + i * 8, 1);
        mbar_init(bb + B_ST, role == 2 ? 1 : 5);
        mbar_init(bb + B_OB, 1); mbar_init(bb + B_OB + 64, 1);
        mbar_init(bb + B_HF, 1); mbar_init(bb + B_HF + 8, 1);
        mbar_init(bb + B_HE, 6 * nh);
        mbar_init(bb + B_OTF, head ? 4 : 8); mbar_init(bb + B_OTE, 1); mbar_init(bb + B_OTF + 8, head ? 4 : 8); mbar_init(bb + B_OTE + 16, 1);
        asm volatile("fence.mbarrier_init.release.cluster;" ::: "memory");
        mbar_expect_tx(bb + B_RED, nh * 1280);
        mbar_expect_tx(bb + B_SM, 3072); mbar_expect_tx(bb + B_ST, role == 2 ? 5120 : 4096);
        if (role != 2) { mbar_expect_tx(bb + B_OB, 2048); mbar_expect_tx(bb + B_OB + 64, 2048); }
        mbar_expect_tx(bb + B_HF, 8 * HBYTES); mbar_expect_tx(bb + B_HF + 8, 8 * HBYTES);
    }
    asm volatile("griddepcontrol.launch_dependents;");
    __syncwarp();
    cluster_arrive_relaxed();
    if (warp < 8) {
        asm volatile("setmaxnreg.inc.sync.aligned.u32 %0;" ::"n"(REG_G));
        const int wg = warp >> 2, w4 = warp & 3;
        if (head) {
            const bf16* W = (role == 2 ? A.Wv + wg * 64 : (wg ? A.Wk : A.Wq) + role * 64) + h * DH;
            const uint32_t stg = sb + O_STG + wg * 81920;
            const int t7 = tid & 127;
            if (G_DLY) delay(G_DLY);
#pragma unroll 8
            for (int i = 0; i < 40; i++) {
                const int row = i * 16 + (t7 >> 3), ch = t7 & 7;
                cp_async16(stg + row * 128 + ((ch ^ (row & 7)) << 4), W + (size_t)row * HD + ch * 8);
            }
            cp_commit();
        }
        if (head) {
            cluster_wait();
            uint32_t wa[40][4];
            cp_wait<0>();
            named_bar(8 + wg, 128);
            {
                const uint32_t la = sb + O_STG + wg * 81920 + ((lane & 7) + (lane >> 4) * 8) * 128 + (((w4 * 2 + ((lane >> 3) & 1)) ^ (lane & 7)) << 4);
                { const uint4 v = lds128(sb + O_STG + wg * 81920 + (r >> 1) * 10240 + (tid & 127) * 16); sts128(sb + O_AS + wg * 2048 + (tid & 127) * 16, v.x, v.y, v.z, v.w); }
#pragma unroll
                for (int j = 1; j < 40; j++) {
                    const int kk = (((r >> 1) - j / 5) & 7) * 5 + j % 5;
                    const uint4 v = ldsm4t(la + kk * 2048);
                    wa[j][0] = v.x; wa[j][1] = v.y; wa[j][2] = v.z; wa[j][3] = v.w;
                }
            }
            named_bar(10, 384);
            GT(tid == 0, 2);
            fence_async_smem();
            named_bar(8 + wg, 128);
            cluster_arrive_relaxed();
            float acc[16];
            const uint32_t ep_q = role == 2 ? sb + O_VM + warp * 512 + (lane ^ ((lane >> 3) & 1)) * 16
                                            : sb + O_QRY + wg * 10240 + ((lane >> 1) & 1) * 5120 + (4 * (lane >> 4) + 2 * ((lane >> 2) & 1) + (lane & 1)) * 128 +
                                                  (((2 * w4 + ((lane >> 3) & 1)) ^ (4 * (lane >> 4) + 2 * ((lane >> 2) & 1) + (lane & 1)) ^ ((lane & 2) << 1)) << 4);
            const uint32_t ep_t = role == 2 ? sb + O_VT + warp * 1024 + lane * 16
                                            : sb + O_QRY + wg * 10240 + (8 + 8 * (lane >> 4) + (lane & 7)) * 128 + (((2 * w4 + ((lane >> 3) & 1)) ^ (lane & 7)) << 4);
                        const int pz = role == 2 ? P1C : P1A;
            const uint32_t ab = (1024 + O_AS + wg * 2048) >> 4;
            uint32_t ok = 1;
            const uint32_t tidk = __shfl_sync(0xffffffffu, tid, lane);
            auto token_gemm = [&](auto ll, const bool pause, const uint32_t vo, const uint32_t nbar, const uint32_t npar, const int t) {
                constexpr int l = decltype(ll)::value;
                constexpr uint32_t hb = ((1024 + O_H + l * 40960) >> 4) | (1u << 16);
                const uint32_t pr = opq(r >> 1);
                if (l) TS(15); else TS(14);
                wg_fence();
#pragma unroll
                for (int j = 0; j < 40; j++) {
                    const uint64_t db = mkdesc(hb + ((pr - j / 5) & 7) * 320 + (j % 5) * 64, 0xC0000010u);
                    if (j == 0) wg_n32_sfirst(acc, mkdesc(ab, 0x40000040u), db);
                    else if (j < TG_STEPS) wg_n32(acc, wa[j][0], wa[j][1], wa[j][2], wa[j][3], db);
                    if (l == 0 && (j + 1 == P1A || j + 1 == P1C)) {
                        if (pause && pz == j + 1) {
                            wg_commit();
                            if (role == 2) mwait(bb + B_OTE, vo >> 14);
                            wg_wait<0>();
                            named_arrive(3, 384);
                            named_bar(4, NB4);
                            if (SKEW && wg) delay(SKEW);
                            wg_fence();
                        }
                    }
                }
                wg_commit();
                ok = mtest(nbar, npar);
                wg_wait<0>();
                uint32_t pk[8];
#pragma unroll
                for (int i = 0; i < 8; i++) pk[i] = pack2(acc[2 * i], acc[2 * i + 1]);
                if (role == 2) {
                    sts128(ep_t + l * 8192 + vo, pk[0], pk[1], pk[2], pk[3]);
                    sts128(ep_t + l * 8192 + vo + 512, pk[4], pk[5], pk[6], pk[7]);
                } else {
                    stsm4t((ep_t ^ (l << 6)) + l * 5120, pk[0], pk[1], pk[2], pk[3]);
                    stsm4t((ep_t ^ (l << 6)) + l * 5120 + 2048, pk[4], pk[5], pk[6], pk[7]);
                }
                asm volatile("{\n.reg .pred p, q;\nsetp.eq.u32 p, %0, 0;\nsetp.eq.u32 q, %1, 0;\n"
                             "@p mbarrier.arrive.expect_tx.shared::cta.b64 _, [%2], %3;\n@q mbarrier.arrive.shared::cluster.b64 _, [%4];\n}"
                             ::"r"(tidk), "r"(tidk & 127), "r"(bb + B_HF + l * 8), "r"(8 * HBYTES), "r"(mapa(bb + B_HE, l)) : "memory");
            };
            mwait(bb + B_HF, 0);
            token_gemm(IC<0>{}, false, 0, bb + B_MEM, 1, -1);
            named_bar(11, 384);
            cluster_wait();
            named_arrive(13, 384);
#pragma unroll 1
            for (int t = 0; t < NT; t++) {
                GT(tid == 0 && blockIdx.x == 98, 100 + t);
                TS(0);
                const uint32_t mp = (t & 1) ^ 1;
                const bool tg0 = t + 1 < NSEG, tg1 = t + 1 >= LAG;
                constexpr uint32_t mb = ((1024 + O_MEM) >> 4) | (16u << 16);
#pragma unroll
                for (int G = 0; G < 8; G++) {
                    if (__builtin_expect(!ok, 0)) mwait(bb + B_MEM + G * 8, mp);
                    ok = mtest(G < 7 ? bb + B_MEM + (G + 1) * 8 : bb + B_HF, mp);
                    if (G == 0) { TS(1); wg_fence(); }
                    if (G == 7) TS(2);
                    if (G == 1) TS(8); if (G == 2) TS(9); if (G == 3) TS(10); if (G == 4) TS(11); if (G == 5) TS(12); if (G == 6) TS(13);
#pragma unroll
                    for (int u = 0; u < 5; u++) {
                        const int j = G * 5 + u;
                        const uint64_t db = mkdesc(mb + j * 32, 8);
                        if (j == 0) wg_n16t_sfirst(acc, mkdesc(ab, 0x40000040u), db);
                        else wg_n16t(acc, wa[j][0], wa[j][1], wa[j][2], wa[j][3], db);
                    }
                    wg_commit();
                }
                if (role == 2 && t) named_bar(5, 384);
                wg_wait<0>();
                TS(3);
                if (role == 2) sts128(ep_q, pack2(acc[0], acc[1]), pack2(acc[2], acc[3]), pack2(acc[4], acc[5]), pack2(acc[6], acc[7]));
                else stsm4t(ep_q, pack2(acc[0], acc[1]), pack2(acc[2], acc[3]), pack2(acc[4], acc[5]), pack2(acc[6], acc[7]));
                named_arrive(1, 384);
                if (tidk < 8) mbar_expect_tx(bb + B_MEM + tidk * 8, 2560);
                if (t == NT - 1) break;
                if (tg0) {
                    if (__builtin_expect(!ok, 0)) mwait(bb + B_HF, mp);
                    if (role != 2) named_bar(2, 384);
                    token_gemm(IC<0>{}, true, mp * 16384, tg1 ? bb + B_HF + 8 : bb + B_MEM, tg1 ? (t + 1 - LAG) & 1 : mp ^ 1, t);
                } else {
                    if (role == 2) mwait(bb + B_OTE, mp); else named_bar(2, 384);
                    named_arrive(3, 384); named_bar(4, NB4);
                    ok = 0;
                }
                TS(5);
                if (tg1) {
                    if (__builtin_expect(!ok, 0)) mwait(bb + B_HF + 8, (t + 1 - LAG) & 1);
                    token_gemm(IC<1>{}, false, mp * 16384, bb + B_MEM, mp ^ 1, t);
                }
                TS(6);
                named_arrive(13, 384);
            }
        } else {
            cluster_wait(); cluster_arrive_relaxed();
            const int ep = ld_relaxed(&g_epoch) + 1;
            const uint32_t cb = sb + (warp < 4 ? warp * CV_W : CV_HI + (warp - 4) * CV_W), lb = bb + B_MEM + warp * 8;
            auto fetch = [&](int k) {
                const int ps = k / 5, rg = ps ? ps - 1 : 0, ch = (sp * 5 + k - 5 * ps) * 8 + warp;
                if (k == 5 * ps) { flag_wait(FLG(F_U + ps), (ps > 1 ? 20 : 320) * ep, 50); fence_async_global(); }
                if (lane == 0) {
                    const uint32_t nb = ps ? ps * 1024 : 512;
                    mbar_expect_tx(lb, 2 * nb);
                    asm volatile("cp.async.bulk.shared::cluster.global.mbarrier::complete_tx::bytes [%0], [%1], %2, [%3];" ::"r"(cb + (k & 1) * 4096), "l"(g_U + ch * (S_LEN / 8)), "r"(nb), "r"(lb) : "memory");
                    asm volatile("cp.async.bulk.shared::cluster.global.mbarrier::complete_tx::bytes [%0], [%1], %2, [%3];" ::"r"(cb + 8192 + (k & 1) * CV_E + 128), "l"(A.ssmk + (size_t)ch * S_LEN), "r"(nb), "r"(lb) : "memory");
                }
                __syncwarp();
            };
            sts32(cb + 8192 + lane * 4, 0u); sts32(cb + 8192 + CV_E + lane * 4, 0u);
            if (warp == 0) sts32(sb + CV_Z + lane * 4, 0u);
            uint32_t dv = 0;
            if (lane < 5) {
                prefetch_l2(A.ssmk + (size_t)((sp * 5 + lane) * 8 + warp) * S_LEN, 1024);
                dv = *reinterpret_cast<const unsigned short*>(A.ssmD + (sp * 5 + lane) * 8 + warp) * 0x10001u;
            }
            named_bar(8, 256);
#pragma unroll 1
            for (int k = -1; k < 25; k++) {
                const int ps = k < 0 ? 0 : k / 5, rg = ps ? ps - 1 : 0;
                const uint32_t Dv = __shfl_sync(0xffffffffu, dv, k - 5 * ps);
                const int tb = sp == 0 && tid == 0 && k >= -1 && k < 7 ? 72 + k * 8 : -1;
                SC(tb >= 0, tb);
                if (k >= 0) {
                    mwait(lb, k & 1);
                    SC(tb >= 0, tb + 1);
                    if (k - 5 * ps < 4) { fence_async_smem(); fetch(k + 1); }
                    SC(tb >= 0, tb + 2);
                }
                const uint32_t tt = sb + CV_T + (k & 1) * 8192;
                conv_unit(cb + (k & 1) * 4096, cb + 8192 + (k & 1) * CV_E, cb + 8192 + 2 * CV_E + 64, sb + CV_Z,
                          tt + warp * 1024 + (lane & 7) * 128 + (((lane >> 3) ^ (lane & 7) ^ warp) & 7) * 16, Dv, rg, ps ? 2 * ps : 1, lane, (uint32_t)A.h_target >> 8, tb);
                if (k >= 0) mwait(bb + B_OTE + (k & 1) * 16, ((k >> 1) & 1) ^ 1);
                named_bar(8, 256);
                {
                    const uint32_t la = tt + (lane & 7) * 1024 + warp * 128 + (((lane >> 3) ^ (lane & 7) ^ warp) & 7) * 16;
                    const uint4 v0 = ldsm4t(la), v1 = ldsm4t(la ^ 64);
                    const uint32_t ya = sb + CV_Y + (k & 1) * 8192 + (warp * 64 + (lane >> 3) * 8 + 7 - (lane & 7)) * 16;
                    stsm4(ya, v0.x, v0.y, v0.z, v0.w);
                    stsm4(ya + 512, v1.x, v1.y, v1.z, v1.w);
                }
                SC(tb >= 0, tb + 6);
                fence_async_smem();
                __syncwarp();
                if (k >= 0 && lane == 0) mbar_arrive(bb + B_OTF + (k & 1) * 8);
                if (k < 0 || (k - 5 * ps == 4 && k < 24)) fetch(k + 1);
                if (k < 0 && lane < 5) prefetch_l2(A.ssmk + (size_t)((sp * 5 + lane) * 8 + warp) * S_LEN + 512, 3072);
            }
            cluster_wait();
        }
    } else if (warp < 12) {
        asm volatile("setmaxnreg.dec.sync.aligned.u32 %0;" ::"n"(REG_T));
        const int w = warp & 3, c = w >> 1, hh = w & 1;
        const uint32_t lane0 = __shfl_sync(0xffffffffu, tid & 31, tid & 31);
        if (head) {
            const int tile0 = role * 4 * WTA, ntile = role == 2 ? 4 * WTC : 4 * WTA;
            const uint32_t wo = sb + O_WO;
            uint32_t mi[5][4];
#pragma unroll
            for (int i = 0; i < 5; i++)
#pragma unroll
                for (int q = 0; q < 4; q++) {
                    const unsigned short* mp = reinterpret_cast<const unsigned short*>(A.mem0) + 2 * q * DM + i * 128 + (tid & 127);
                    mi[i][q] = mp[0] | (uint32_t)mp[DM] << 16;
                }
            cluster_wait();
            named_bar(10, 384);
#pragma unroll
            for (int i = 0; i < 5; i++) {
                const int col = i * 128 + (tid & 127), kk = col >> 4, pr = (kk * 13) >> 6;
                const uint32_t ma = sb + O_MEM + ((((r >> 1) - pr) & 7) * 5 + kk - 5 * pr) * 512 + (col & 8) * 32 + (col & 7) * 16;
                sts128(ma, mi[i][0], mi[i][0], mi[i][1], mi[i][1]);
                sts128(ma + 128, mi[i][2], mi[i][2], mi[i][3], mi[i][3]);
            }
            fence_async_smem();
            named_arrive(11, 384);
            for (int i = tid & 127; i < ntile * 256; i += 128) {
                const int ti = i >> 8, p = (i >> 1) & 127, ch = i & 1;
                const int ks = p >> 4, kh = (p >> 3) & 1, e8 = p & 7;
                const int dim = 64 * (ks >> 2) + 16 * (e8 >> 1) + 8 * (e8 & 1) + 2 * (ks & 3) + kh;
                cp_async16(wo + ti * 4096 + p * 32 + ((ch ^ ((p >> 2) & 1)) << 4), A.Wo + (size_t)(h * DH + dim) * DM + (tile0 + ti) * 16 + ch * 8);
            }
            cp_commit();
            if (lane < 8) {
                const int u = 2 * (tile0 + w + 4 * (lane >> 1)) + (lane & 1), ow = u / 5;
                const int sl = u - 5 * ow;
                sts32(sb + O_TAB + w * 32 + lane * 4, mapa(sb + O_RED + (sl >> 1) * 2560 + (sl & 1) * 256 + hi * (sl < 4 ? 512 : 256), ow & 15));
            }
            cluster_arrive_relaxed(); cluster_wait();
            cp_wait<0>();
            named_bar(7, 128);
            const uint32_t wo_a = wo + w * 4096 + ((lane >> 4) * 8 + (lane & 7)) * 32 + ((((lane >> 3) & 1) ^ ((lane >> 2) & 1)) << 4);
            const uint32_t ob_0 = sb + (role == 2 ? O_PB : O_OBA) + (lane >> 4) * 2048 + ((lane >> 3) & 1) * 128 + ((lane & 7) ^ ((lane >> 1) & 4)) * 16;
            const float cs = 0.08838834764831845f * 1.4426950408889634f;
            auto w_frag = [&](auto four, int i) {
                return ldsm4t(wo_a + (i < 16 || decltype(four)::value == 4 ? (i >> 4) * 32768 + (i & 1) * 16384 + ((i >> 1) & 7) * 512 : 32768 + (i & 1) * 2048 + ((i >> 1) & 7) * 512));
            };
            auto w_pre = [&](auto four, auto pd, uint4* wf) {
#pragma unroll
                for (int i = 0; i < decltype(pd)::value; i++) wf[i] = w_frag(four, i);
            };
            auto w_run = [&](auto four, auto pd, auto rem_, uint4* wf, int t, const uint32_t ob_a, auto&& before_last) {
                constexpr int NTL = decltype(four)::value, PD = decltype(pd)::value, NF = 8 * NTL, NP = NTL > 2 ? 2 : 1;
                constexpr bool REMOTE = decltype(rem_)::value;
                const uint32_t ln = opq(lane0), l8 = (ln & 2) * 64 + (ln >> 2) * 16 + (ln & 1) * 8, rb = (bb + B_RED) & 0xFFFFFFu;
                uint4 ob = ldsm4(ob_a), on, o2;
#pragma unroll
                for (int p = 0; p < NP; p++) {
                    const bool split = p == 1 && NTL == 3;
                    if (!REMOTE && !TPVW && p == 1) mwait(bb + B_ST, t & 1);
                    const int nk = split ? 4 : 8;
                    float d[4][4];
                    uint4 ta;
#pragma unroll
                    for (int i = 0; i < 16; i++) (&d[0][0])[i] = 0.f;
#pragma unroll
                    for (int ks = 0; ks < 8; ks++) {
                        if (ks >= nk) continue;
                        if (REMOTE && p == 0 && ks == 3) { mwait(bb + B_OB + 64, t & 1); TS(7); }
                        if (split) o2 = ldsm4(ob_a + (ks + 4) * 256);
                        if (ks + 1 < nk || p + 1 < NP) on = ldsm4(ob_a + ((ks + 1) & 7) * 256);
                        if (ks == nk - 2) ta = lds128(sb + O_TAB + w * 32 + p * 16);
#pragma unroll
                        for (int u = 0; u < 2; u++) {
                            const int i = p * 16 + ks * 2 + u;
                            const uint4& o = split && u ? o2 : ob;
                            mmav(d[2 * u], wf[i % PD].x, wf[i % PD].y, wf[i % PD].z, wf[i % PD].w, o.x, o.y);
                            mmav(d[2 * u + 1], wf[i % PD].x, wf[i % PD].y, wf[i % PD].z, wf[i % PD].w, o.z, o.w);
                            if (i + PD < NF) wf[i % PD] = w_frag(four, i + PD);
                        }
                        ob = on;
                    }
                    if (p) TS(10); else TS(8);
                    if (p == NP - 1) before_last();
                    if (split) {
#pragma unroll
                        for (int i = 0; i < 4; i++) { d[0][i] += d[2][i]; d[1][i] += d[3][i]; }
                    }
                    st_async_v2(ta.x + l8, pack2(d[0][0], d[0][1]), pack2(d[1][0], d[1][1]), (ta.x & 0xFF000000u) | rb);
                    st_async_v2(ta.y + l8, pack2(d[0][2], d[0][3]), pack2(d[1][2], d[1][3]), (ta.y & 0xFF000000u) | rb);
                    if (!split) {
                        st_async_v2(ta.z + l8, pack2(d[2][0], d[2][1]), pack2(d[3][0], d[3][1]), (ta.z & 0xFF000000u) | rb);
                        st_async_v2(ta.w + l8, pack2(d[2][2], d[2][3]), pack2(d[3][2], d[3][3]), (ta.w & 0xFF000000u) | rb);
                    }
                }
            };
            if (role != 2) {
#pragma unroll 1
                for (int t = 0; t < NT; t++) {
                    const uint32_t lane = opq(lane0);
                    const uint32_t dc = mapa(sb, hi * 3 + 2), dp = mapa(sb, hi * 3 + (role ^ 1));
                    const uint32_t qa = sb + O_QRY + c * 5120 + (lane & 7) * 128;
                    const uint32_t sw = (((lane >> 3) ^ (lane & 7)) << 4) ^ (c << 6);
                    {
                        const uint32_t ka = qa + 10240;
                        const uint32_t kt = sb + O_KEY + c * 5120 + (lane & 15) * 128, kx = (((lane >> 4) ^ (lane & 7)) << 4) ^ (c << 6);
                        const uint32_t sd = dc + O_SM + role * 1536 + c * 768 + lane * 4, sbar = dc + O_BAR + B_SM;
                        const uint32_t ta = sb + O_QRY + c * 5120 + (8 + 16 * hh + ((lane & 15) ^ (role * 8))) * 128;
                        uint4 a[4], f[4];
                        named_bar(13, 384);
#pragma unroll
                        for (int i = 0; i < 4; i++) f[i] = ldsm4(kt + 1024 + hh * 2048 + (kx ^ (i << 5) ^ (hh << 6)));
#pragma unroll
                        for (int i = 0; i < 4; i++) a[i] = ldsm4(ta + (kx ^ (i << 5)));
                        const uint32_t kd = ka + (1 + 2 * hh) * 1024 + sw;
                        uint4 k[5];
                        k[1] = ldsm4(kd); k[2] = ldsm4(kd + 1024);
                        {
                            const uint32_t qh = qa + (sw ^ (hh << 6)), kh = kt + (kx ^ (hh << 6));
                            named_bar(1, 384);
                            const uint4 q0 = ldsm4(qh), g0 = ldsm4(kh), g1 = ldsm4(kh ^ 32), q1 = ldsm4(qh ^ 64);
                            float s0[4] = {0.f, 0.f, 0.f, 0.f}, s1[4] = {0.f, 0.f, 0.f, 0.f}, s2[4] = {0.f, 0.f, 0.f, 0.f}, s3[4] = {0.f, 0.f, 0.f, 0.f};
                            mmav(s0, f[0].x, f[0].y, f[0].z, f[0].w, q0.x, q0.y); mmav(s1, f[1].x, f[1].y, f[1].z, f[1].w, q0.z, q0.w);
                            mmav(s2, g0.x, g0.y, g0.z, g0.w, q0.x, q0.y); mmav(s3, g1.x, g1.y, g1.z, g1.w, q0.z, q0.w);
                            mmav(s0, f[2].x, f[2].y, f[2].z, f[2].w, q1.x, q1.y); mmav(s1, f[3].x, f[3].y, f[3].z, f[3].w, q1.z, q1.w);
                            k[0] = ldsm4(ka + sw); k[3] = ldsm4(ka + 1024 + sw); k[4] = ldsm4(ka + 2048 + sw);
                            st_async_b32(sd + hh * 128, pack2(s2[0] + s3[0], s2[1] + s3[1]), sbar);
                            st_async_b32(sd + 256 + hh * 256, pack2(s0[0] + s1[0], s0[1] + s1[1]), sbar);
                            st_async_b32(sd + 384 + hh * 256, pack2(s0[2] + s1[2], s0[3] + s1[3]), sbar);
                        }
                        TS(1);
                        float u[5][4];
#pragma unroll
                        for (int i = 0; i < 20; i++) (&u[0][0])[i] = 0.f;
                        auto half = [&](auto nn, const uint4& a0, const uint4& a1, bool more) {
                            constexpr int NU = decltype(nn)::value;
                            constexpr int ord[5] = {1, 2, 0, 3, 4};
#pragma unroll
                            for (int i = 0; i < NU; i++) mmav(u[ord[i]], a0.x, a0.y, a0.z, a0.w, k[ord[i]].x, k[ord[i]].y);
#pragma unroll
                            for (int i = 0; i < NU; i++) {
                                const int n = ord[i];
                                mmav(u[n], a1.x, a1.y, a1.z, a1.w, k[n].z, k[n].w);
                                if (more) k[n] = ldsm4(((n == 0 ? ka + sw : (n < 3 ? kd + (n - 1) * 1024 : ka + (n - 2) * 1024 + sw))) ^ 64);
                            }
                        };
                        auto fu = [](float x) { return __float_as_uint(x); };
                        const uint32_t so = O_ST + c * 2048 + hh * 768, td = dp + so, tb = dp + O_BAR + B_ST, lo = sb + so + 4096;
                        if (hh) {
                            half(IC<5>{}, a[0], a[1], true); half(IC<5>{}, a[2], a[3], false);
                            st_async_v4(td + lane * 16, fu(u[0][2]), fu(u[0][3]), fu(u[1][2]), fu(u[1][3]), tb);
                            st_async_v4(td + 512 + lane * 16, fu(u[2][2]), fu(u[2][3]), fu(u[3][2]), fu(u[3][3]), tb);
                            st_async_v2(td + 1024 + lane * 8, fu(u[4][2]), fu(u[4][3]), tb);
                            sts128(lo + lane * 16, fu(u[0][0]), fu(u[0][1]), fu(u[1][0]), fu(u[1][1]));
                            sts128(lo + 512 + lane * 16, fu(u[2][0]), fu(u[2][1]), fu(u[3][0]), fu(u[3][1]));
                            sts64(lo + 1024 + lane * 8, fu(u[4][0]), fu(u[4][1]));
                        } else {
                            half(IC<3>{}, a[0], a[1], true); half(IC<3>{}, a[2], a[3], false);
                            st_async_v4(td + lane * 16, fu(u[0][2]), fu(u[0][3]), fu(u[1][2]), fu(u[1][3]), tb);
                            st_async_v2(td + 512 + lane * 8, fu(u[2][2]), fu(u[2][3]), tb);
                            sts128(lo + lane * 16, fu(u[0][0]), fu(u[0][1]), fu(u[1][0]), fu(u[1][1]));
                            sts64(lo + 512 + lane * 8, fu(u[2][0]), fu(u[2][1]));
                        }
                        if (t < NT - 1) named_arrive(2, 384);
                        __syncwarp();
                        if (lane == 0) mbar_arrive(bb + B_ST);
                        TS(2);
                    }
                    if (t == NT - 1) break;
                    uint4 wf[PDA];
                    w_pre(IC<WTA>{}, IC<PDA>{}, wf);
                    mwait(bb + B_OB, t & 1);
                    TS(3);
                    named_bar(3, 384);
                    w_run(IC<WTA>{}, IC<PDA>{}, IC<1>{}, wf, t, ob_0, []() {});
                    named_arrive(4, NB4);
                    if (w == 0 && lane == 0) { mbar_expect_tx(bb + B_OB, 2048); mbar_expect_tx(bb + B_OB + 64, 2048); }
                    TS(5);
                }
            } else {
#pragma unroll 1
                for (int t = 0; t < NT; t++) {
                    const uint32_t lane = opq(lane0);
                    const int g = lane >> 2, tq = lane & 3;
                    const uint32_t vm_a = sb + O_VM + (g * 4 + 2 * (tq & 1) + (c ^ ((g >> 1) & 1))) * 16 + (tq >> 1) * 8;
                    const uint32_t vt_a = sb + O_VT + (t & 1) * 16384 + lane * 16;
                    named_bar(13, 384);
                    uint4 va[4][2];
#pragma unroll
                    for (int i = 0; i < 4; i++) {
                        va[i][0] = lds128(vt_a + c * 8192 + (4 * hh + i) * 1024);
                        va[i][1] = lds128(vt_a + c * 8192 + (4 * hh + i) * 1024 + 512);
                    }
                    const uint32_t sa = opq(sb + O_SM + c * 768 + 256 + lane * 16), sa2 = opq(sb + O_SM + c * 768 + (lane & 15) * 16 + (lane >> 4) * 1536), vm_b = opq(vm_a + hh * 2048);
                    named_bar(1, 384);
                    if (__builtin_expect(t < NT - 1, 1)) {
                        uint2 vm[4];
#pragma unroll
                        for (int i = 0; i < 4; i++) vm[i] = lds64(vm_b + i * 512);
                        mwait(bb + B_SM, t & 1);
                        TS(1);
                        const uint4 x0 = ldsm4t(sa), y0 = ldsm4t(sa + 1536), x1 = ldsm4t(sa2);
                        float s[10];
                        s[2] = blo(x0.x) + blo(y0.x); s[3] = bhi(x0.x) + bhi(y0.x); s[4] = blo(x0.y) + blo(y0.y); s[5] = bhi(x0.y) + bhi(y0.y);
                        s[6] = blo(x0.z) + blo(y0.z); s[7] = bhi(x0.z) + bhi(y0.z); s[8] = blo(x0.w) + blo(y0.w); s[9] = bhi(x0.w) + bhi(y0.w);
                        s[0] = (blo(x1.x) + blo(x1.y)) + (blo(x1.z) + blo(x1.w)); s[1] = (bhi(x1.x) + bhi(x1.y)) + (bhi(x1.z) + bhi(x1.w));
                        float mx = fmaxf(fmaxf(fmaxf(s[0], s[1]), fmaxf(s[2], s[3])), fmaxf(fmaxf(fmaxf(s[4], s[5]), fmaxf(s[6], s[7])), fmaxf(s[8], s[9])));
                        const float m1 = __shfl_xor_sync(0xffffffffu, mx, 1), m2 = __shfl_xor_sync(0xffffffffu, mx, 2), m3 = __shfl_xor_sync(0xffffffffu, mx, 3);
                        mx = fmaxf(fmaxf(mx, m1), fmaxf(m2, m3)) * -cs;
                        uint32_t pb[5];
#pragma unroll
                        for (int i = 0; i < 5; i++) pb[i] = pack2(ex2f(fmaf(s[2 * i], cs, mx)), ex2f(fmaf(s[2 * i + 1], cs, mx)));
                        TS(9);
                        named_bar(3, 384);
                        float o[5][4];
#pragma unroll
                        for (int i = 0; i < 20; i++) (&o[0][0])[i] = 0.f;
                        const uint32_t one2 = 0x3F803F80u;
                        float z[2][4] = {{0.f, 0.f, 0.f, 0.f}, {0.f, 0.f, 0.f, 0.f}};
                        mmav8(o[4], one2, one2, pb[0]);
                        mmav(z[0], one2, one2, one2, one2, pb[1], pb[2]);
                        mmav(z[1], one2, one2, one2, one2, pb[3], pb[4]);
#pragma unroll
                        for (int i = 0; i < 4; i++) mmav8(o[i], vm[i].x, vm[i].y, pb[0]);
#pragma unroll
                        for (int i = 0; i < 4; i++) mmav(o[i], va[i][0].x, va[i][0].y, va[i][0].z, va[i][0].w, pb[1], pb[2]);
#pragma unroll
                        for (int i = 0; i < 4; i++) mmav(o[i], va[i][1].x, va[i][1].y, va[i][1].z, va[i][1].w, pb[3], pb[4]);
                        o[4][0] += z[0][0] + z[1][0]; o[4][1] += z[0][1] + z[1][1];
                        uint4 wf[PDC];
                        w_pre(IC<WTC>{}, IC<PDC>{}, wf);
                        const float r0 = rcpf(o[4][0]), r1 = rcpf(o[4][1]);
                        const uint32_t oo = c * 2048 + hh * 1024 + g * 128 + tq * 16 + (g & 1) * 64;
                        uint32_t e0[4], e1[4];
#pragma unroll
                        for (int i = 0; i < 4; i++) { e0[i] = pack2(o[i][0] * r0, o[i][2] * r0); e1[i] = pack2(o[i][1] * r1, o[i][3] * r1); }
                        sts128(sb + O_PB + (~t & 1) * 5120 + oo, e0[0], e0[1], e0[2], e0[3]);
                        sts128(sb + O_PB + (~t & 1) * 5120 + (oo ^ 64), e1[0], e1[1], e1[2], e1[3]);
                        {
                            const uint32_t da = mapa(sb + O_OBA, r - 2) + oo, ba = mapa(bb + B_OB + hh * 64, r - 2);
                            if (O_DLY) { named_bar(7, 128); if (hh) delay(O_DLY); }
                            st_async_v4(da, e0[0], e0[1], e0[2], e0[3], ba);
                            st_async_v4(da + 0x01000000u, e0[0], e0[1], e0[2], e0[3], ba + 0x01000000u);
                            st_async_v4(da ^ 64, e1[0], e1[1], e1[2], e1[3], ba);
                            st_async_v4((da ^ 64) + 0x01000000u, e1[0], e1[1], e1[2], e1[3], ba + 0x01000000u);
                        }
                        TS(3);
                        if (!O_DLY) named_bar(7, 128);
                        w_run(IC<WTC>{}, IC<PDC>{}, IC<0>{}, wf, t, ob_0 + (~t & 1) * 5120, []() {});
                        if (TPVW) named_arrive(4, NB4);
                        if (WTC == 2 || TPVW) mwait(bb + B_ST, t & 1);
                        TS(4);
                    } else { mwait(bb + B_SM, t & 1); mwait(bb + B_ST, t & 1); }
                    TS(5);
                    fence_async_smem();
#pragma unroll 1
                    for (int l = t < NSEG ? 0 : 1; l < (t >= LAG ? 2 : 1); l++) {
                        const uint32_t pb_ = ((1024 + O_PB) >> 4) + (t & 1) * 320 + l * 160;
                        const uint32_t va_ = vt_a + l * 8192 + w * 1024, oa = va_ - lane * 16 + g * 64 + ((tq ^ (g >> 1)) & 3) * 16, vl = (vm_a ^ ((l ^ c) << 4)) + w * 512;
                        float d[2][16];
#pragma unroll
                        for (int mt = 0; mt < 2; mt++) {
                            const uint2 a0 = lds64(vl + mt * 2048);
                            const uint4 a1 = lds128(va_ + mt * 4096), a2 = lds128(va_ + mt * 4096 + 512);
                            wg_fence();
                            wg_n32_first(d[mt], a0.x, a0.y, 0u, 0u, mkdesc(pb_, 8));
                            wg_n32(d[mt], a1.x, a1.y, a1.z, a1.w, mkdesc(pb_ + 32 + (32u << 16), 8));
                            wg_n32(d[mt], a2.x, a2.y, a2.z, a2.w, mkdesc(pb_ + 96 + (32u << 16), 8));
                            wg_commit();
                            if (mt == 0) wg_wait<0>();
                        }
#pragma unroll
                        for (int mt = 0; mt < 2; mt++) {
                            if (mt) wg_wait<0>();
                            sts128(oa + mt * 4096, pack2(d[mt][0], d[mt][1]), pack2(d[mt][4], d[mt][5]), pack2(d[mt][8], d[mt][9]), pack2(d[mt][12], d[mt][13]));
                            sts128(oa + mt * 4096 + 512, pack2(d[mt][2], d[mt][3]), pack2(d[mt][6], d[mt][7]), pack2(d[mt][10], d[mt][11]), pack2(d[mt][14], d[mt][15]));
                        }
                        if (O0_EARLY && l == 0) {
                            fence_async_smem();
                            __syncwarp();
                            if (lane == 0) mbar_arrive(bb + B_OTF + 8);
                        }
                    }
                    TS(6);
                    if (w == 0 && lane == 0) { mbar_expect_tx(bb + B_ST, 5120); mbar_expect_tx(bb + B_SM, 3072); }
                    fence_async_smem();
                    __syncwarp();
                    if (lane == 0) mbar_arrive(bb + B_OTF);
                    if (t < NT - 1) named_arrive(5, 384);
                }
            }
        } else {
            cluster_wait(); cluster_arrive_relaxed();
            const int wi = sp * 4 + w, half = wi >> 5, tok = wi & 31, ep = ld_relaxed(&g_epoch) + 1;
            if (lane < LN0_AHEAD / 2) prefetch_l2(A.x + (size_t)((half + 2 * lane) * SEG + tok) * DM, 1280);
#pragma unroll 1
            for (int k = -LN0_AHEAD / 2; k < NT; k++) {
                const int s0 = k < 0 ? 2 * k + LN0_AHEAD + half : (half ? k + LN0_AHEAD : NSEG);
                if (s0 < NSEG) { ln0_row(A.x, s0, tok, lane); GT(lane == 0 && k < 0, 30 + s0); }
                const int n = k - half * LAG;
                if (k == -LN0_AHEAD / 2 + 1 || (n >= 0 && n < NSEG && k >= 0)) {
                    post_row(half, k < 0 ? 0 : n, tok, lane, half ? g_x : A.x, half ? A.out : g_x, k < 0 ? 0 : ep);
                    GT(lane == 0 && (n & 3) == 0 && k >= 0, 460 + half * 16 + (n >> 2)); GT(lane == 0 && n == 63 && half, 40);
                }
            }
            cluster_wait();
        }
    } else {
        asm volatile("setmaxnreg.dec.sync.aligned.u32 %0;" ::"n"(REG_X));
        cluster_wait();
        const int s = warp - 12;
        const uint32_t lane0 = __shfl_sync(0xffffffffu, tid & 31, tid & 31);
        if (s < 3) {
            cluster_arrive_relaxed();
            if (blockIdx.x * 3 + s < 320) {
#pragma unroll 1
                for (int i = 0; i < 2; i++) {
                    u_half(A.Bk, A.Bv, A.shiftk, blockIdx.x * 3 + s + i * 320, lane);
                    __syncwarp();
                    if (lane == 0) red_release(FLG(F_U + i), 1);
                    GT(lane == 0 && i == 0, 4);
                }
            }
            cluster_wait();
            constexpr uint32_t XSLOT = 16 * 3 * 4096;
            uint32_t xo_ = (r * 3 + s) * 4096;
            if (s == 0) {
                const uint32_t G = lane >> 1, d = ((r + 2 * G) & 15) ^ (lane & 1);
                const bool ok = lane < 16 && d < 3 * nh;
                const uint32_t pos = __popc(__ballot_sync(0xffffffffu, ok) & ((1u << lane) - 1u));
                if (ok) { sts32(sb + O_BT + pos * 8, (d << 24) + G * 2560); sts32(sb + O_BT + pos * 8 + 4, mapa(bb + B_MEM + G * 8, d)); }
            }
            named_bar(14, 96);
#pragma unroll 1
            for (int t = 0; t < NT; t++) {
                const uint32_t lane = opq(lane0);
                if (head && role != 2) {
                    auto soft = [&](auto uu, auto vv, int c0, int hh) {
                        constexpr int U = decltype(uu)::value, NV = decltype(vv)::value;
                        const uint32_t dc = mapa(sb, hi * 3 + 2), sa = sb + O_ST + c0 * 2048 + hh * 768;
                        const uint32_t pd = dc + O_PB + (t & 1) * 5120 + c0 * 2560 + (2 * hh + role) * 128 + lane * 4, pbar = dc + O_BAR + B_ST;
                        const int lim = 8 * role + (int)(lane >> 2) - 2 * (int)(lane & 3);
                        auto uf = [](uint32_t x) { return __uint_as_float(x); };
                        mwait(bb + B_ST, t & 1);
                        uint32_t z[U][NV];
                        auto zz = [](float x, float y) { const uint32_t w = pack2(x, y); return pack2(blo(w) * 0.08838834764831845f, bhi(w) * 0.08838834764831845f); };
#pragma unroll
                        for (int i = 0; i < U; i++) {
                            const uint4 v = lds128(sa + i * 2048 + lane * 16), w = lds128(sa + i * 2048 + 4096 + lane * 16);
                            z[i][0] = zz(uf(v.x) + uf(w.x), uf(v.y) + uf(w.y));
                            z[i][1] = zz(lim < 0 ? -INFINITY : uf(v.z) + uf(w.z), lim < 1 ? -INFINITY : uf(v.w) + uf(w.w));
                            if (NV == 3) {
                                const uint2 x = lds64(sa + i * 2048 + 512 + lane * 8), y = lds64(sa + i * 2048 + 4608 + lane * 8);
                                z[i][2] = zz(lim < 8 ? -INFINITY : uf(x.x) + uf(y.x), lim < 9 ? -INFINITY : uf(x.y) + uf(y.y));
                            } else {
                                const uint4 x = lds128(sa + 512 + lane * 16), y = lds128(sa + 4608 + lane * 16);
                                const uint2 p = lds64(sa + 1024 + lane * 8), q = lds64(sa + 5120 + lane * 8);
                                z[i][2] = zz(lim < 8 ? -INFINITY : uf(x.x) + uf(y.x), lim < 9 ? -INFINITY : uf(x.y) + uf(y.y));
                                z[i][NV - 2] = zz(uf(x.z) + uf(y.z), uf(x.w) + uf(y.w));
                                z[i][NV - 1] = zz(uf(p.x) + uf(q.x), uf(p.y) + uf(q.y));
                            }
                        }
                        const float l2e = 1.4426950408889634f;
                        float e[U][2 * NV], sum[U];
#pragma unroll
                        for (int i = 0; i < U; i++) {
                            uint32_t zm = bmax2(bmax2(z[i][0], z[i][1]), z[i][2]);
                            if (NV == 5) zm = bmax2(zm, bmax2(z[i][NV - 2], z[i][NV - 1]));
                            zm = bmax2(zm, __shfl_xor_sync(0xffffffffu, zm, 1));
                            zm = bmax2(zm, __shfl_xor_sync(0xffffffffu, zm, 2));
                            const float mx = fmaxf(blo(zm), bhi(zm)) * -l2e;
                            sum[i] = 0.f;
#pragma unroll
                            for (int n = 0; n < NV; n++) { e[i][2 * n] = ex2f(fmaf(blo(z[i][n]), l2e, mx)); e[i][2 * n + 1] = ex2f(fmaf(bhi(z[i][n]), l2e, mx)); }
                            sum[i] = ((e[i][0] + e[i][1]) + (e[i][2] + e[i][3])) + (e[i][4] + e[i][5]);
                            if (NV == 5) sum[i] += (e[i][2 * NV - 4] + e[i][2 * NV - 3]) + (e[i][2 * NV - 2] + e[i][2 * NV - 1]);
                            sum[i] += __shfl_xor_sync(0xffffffffu, sum[i], 1);
                            sum[i] += __shfl_xor_sync(0xffffffffu, sum[i], 2);
                            sum[i] = rcpf(sum[i]);
                        }
#pragma unroll
                        for (int i = 0; i < U; i++)
#pragma unroll
                            for (int n = 0; n < 5; n++)
                                st_async_b32(pd + i * 2560 + (n == 0 ? 0 : (NV == 3 ? n : (n < 3 ? n + 2 : n - 2)) * 512), n < NV ? pack2(e[i][2 * n] * sum[i], e[i][2 * n + 1] * sum[i]) : 0u, pbar);
                    };
                    if (s < 2) soft(IC<1>{}, IC<5>{}, s, 1); else soft(IC<2>{}, IC<3>{}, 0, 0);
                    TS(12);
                    named_bar(14, 96);
                    if (s == 0 && lane == 0) mbar_expect_tx(bb + B_ST, 4096);
                    if (H1_LATE && r == 1 && s == 0 && t >= LAG - 1 && t < NT - 1) named_arrive(12, 64);
                }
                if (t == NT - 1) break;
                uint32_t m0 = 0x80008000u, m1 = 0x80008000u;
                if (t < LAG && cq == 0) {
                    const uint32_t ch = s < 2 ? lane : lane >> 1;
                    const unsigned short* mp = reinterpret_cast<const unsigned short*>(A.mem0) + (((ch >> 3) & 1) * 4 + (s < 2 ? 0 : (lane & 1) * 2)) * DM + (5 * r + 2 * s + (ch >> 4)) * 8 + (ch & 7);
                    m0 = max(mp[0] | (uint32_t)mp[DM] << 16, 1u);
                    if (s < 2) m1 = max(mp[2 * DM] | (uint32_t)mp[3 * DM] << 16, 1u);
                }
                const bool late = t >= LAG;
                auto sum5 = [](uint32_t a, uint32_t b, uint32_t c, uint32_t d, uint32_t e) { return max(badd(badd(badd(a, b), e), badd(c, d)), 1u); };
                auto sum7 = [](uint32_t a, uint32_t b, uint32_t c, uint32_t d, uint32_t e, uint32_t f, uint32_t h_) {
                    return badd(badd(badd(a, b), badd(c, d)), badd(badd(e, f), h_));
                };
                auto min3 = [](uint32_t a, uint32_t b, uint32_t c) { return min(min(a, b), c); };
                auto bcast = [&](auto two, const uint32_t aa, uint32_t x0, uint32_t x1, uint32_t x2, uint32_t x3) {
                    auto send = [&](uint32_t o, uint32_t bar) { if (decltype(two)::value) st_async_v4(aa + o, x0, x1, x2, x3, bar); else st_async_v2(aa + o, x0, x1, bar); };
                    const uint32_t tb0 = clk32();
                    auto pace = [&](int k) { if (BP) while (__any_sync(0xffffffffu, clk32() - tb0 < (uint32_t)(k * BP))) {} };
                    uint4 e[6];
                    e[0] = lds128(sb + O_BT);
                    TS(8);
                    send(e[0].x, e[0].y); send(e[0].z, e[0].w);
                    TS(9);
                    if (BNS) __nanosleep(BNS);
#pragma unroll
                    for (int i = 1; i < 6; i++) e[i] = lds128(sb + O_BT + i * 16);
#pragma unroll
                    for (int i = 1; i < 6; i++) { pace(i); send(e[i].x, e[i].y); send(e[i].z, e[i].w); }
                    if (nh == 5) {
                        const uint4 f0 = lds128(sb + O_BT + 96);
                        const uint2 f1 = lds64(sb + O_BT + 112);
                        pace(6); send(f0.x, f0.y); send(f0.z, f0.w); pace(7); send(f1.x, f1.y);
                    }
                };
                const uint32_t ma = (sb + O_MEM + (5 * (r & 1) + 2 * s) * 256) & 0xFFFFFFu;
                int guard = 0;
                if (s < 2) {
                    const uint32_t ra = sb + O_RED + s * 2560 + lane * 16;
                    uint4* xb = reinterpret_cast<uint4*>(reinterpret_cast<char*>(g_xc) + xo_ + lane * 16);
                    uint4* xo = xb + cq * 32;
                    mwait(bb + B_RED, t & 1);
                    TS(0);
                    uint4 p[5];
#pragma unroll
                    for (int i = 0; i < 5; i++) p[i] = i < 4 || nh == 5 ? lds128(ra + i * 512) : make_uint4(0, 0, 0, 0);
                    const uint32_t u1 = sum5(p[0].y, p[1].y, p[2].y, p[3].y, p[4].y), u3 = sum5(p[0].w, p[1].w, p[2].w, p[3].w, p[4].w);
                    st_relaxed_v4(xo, sum5(p[0].x, p[1].x, p[2].x, p[3].x, p[4].x), late ? u1 : m0, sum5(p[0].z, p[1].z, p[2].z, p[3].z, p[4].z), late ? u3 : m1);
                    TS(1);
                    if (QUIET && head) named_arrive(4, NB4);
                    delay(XD);
                    uint4 x[NCL];
                    while (true) {
                        ld7_relaxed(x, xb);
                        const uint32_t mn = min3(min3(min3(x[0].x, x[0].y, x[0].z), min3(x[0].w, x[1].x, x[1].y), min3(x[1].z, x[1].w, x[2].x)),
                                                 min3(min3(x[2].y, x[2].z, x[2].w), min3(x[3].x, x[3].y, x[3].z), min3(x[3].w, x[4].x, x[4].y)),
                                                 min3(min3(x[4].z, x[4].w, x[5].x), min3(x[5].y, x[5].z, x[5].w), min(min3(x[6].x, x[6].y, x[6].z), x[6].w)));
                        if (NO_X || __all_sync(0xffffffffu, mn != 0)) break;
                        if (++guard > 2000000) __trap();
                    }
                    TS(2);
                    TV(4, guard);
                    bcast(IC<1>{}, ma + lane * 16, sum7(x[0].x, x[1].x, x[2].x, x[3].x, x[4].x, x[5].x, x[6].x), sum7(x[0].y, x[1].y, x[2].y, x[3].y, x[4].y, x[5].y, x[6].y),
                          sum7(x[0].z, x[1].z, x[2].z, x[3].z, x[4].z, x[5].z, x[6].z), sum7(x[0].w, x[1].w, x[2].w, x[3].w, x[4].w, x[5].w, x[6].w));
                } else {
                    const uint32_t ra = sb + O_RED + 5120 + lane * 8;
                    uint2* xb = reinterpret_cast<uint2*>(reinterpret_cast<char*>(g_xc) + xo_ + lane * 8);
                    uint2* xo = xb + cq * 64;
                    mwait(bb + B_RED, t & 1);
                    TS(0);
                    uint2 p[5];
#pragma unroll
                    for (int i = 0; i < 5; i++) p[i] = i < 4 || nh == 5 ? lds64(ra + i * 256) : make_uint2(0, 0);
                    const uint32_t u1 = sum5(p[0].y, p[1].y, p[2].y, p[3].y, p[4].y);
                    st_relaxed_v2(xo, sum5(p[0].x, p[1].x, p[2].x, p[3].x, p[4].x), late ? u1 : m0);
                    if (lane == 0) mbar_expect_tx(bb + B_RED, nh * 1280);
                    TS(1);
                    if (QUIET && head) named_arrive(4, NB4);
                    delay(XD);
                    uint32_t y0, y1;
                    while (true) {
                        uint2 x[NCL];
                        ld7_relaxed(x, xb);
                        const uint32_t mn = min3(min3(min3(x[0].x, x[0].y, x[1].x), min3(x[1].y, x[2].x, x[2].y), min3(x[3].x, x[3].y, x[4].x)), min3(x[4].y, x[5].x, x[5].y), min(x[6].x, x[6].y));
                        y0 = sum7(x[0].x, x[1].x, x[2].x, x[3].x, x[4].x, x[5].x, x[6].x); y1 = sum7(x[0].y, x[1].y, x[2].y, x[3].y, x[4].y, x[5].y, x[6].y);
                        if (NO_X || __all_sync(0xffffffffu, mn != 0)) break;
                        if (++guard > 2000000) __trap();
                    }
                    TS(2);
                    TV(4, guard);
                    bcast(IC<0>{}, ma + lane * 8, y0, y1, 0u, 0u);
                }
                TS(3);
                if (OT_LATE && head && role == 2) named_arrive(6, 128);
                xo_ += XSLOT; if (xo_ >= XRS * XSLOT) xo_ -= XRS * XSLOT;
                {
                    const uint32_t zo = xo_ + XSLOT >= XRS * XSLOT ? xo_ + XSLOT - XRS * XSLOT : xo_ + XSLOT;
                    char* zp = reinterpret_cast<char*>(g_xc) + zo + cq * 512 + lane * 16;
                    st_relaxed_v4(zp, 0, 0, 0, 0);
                    if (ld_relaxed_v4(zp).x) __trap();
                }
            }
            st_relaxed_v4(g_xc + (r * 3 + s) * 256 + cq * 32 + lane0, 0, 0, 0, 0);
            st_relaxed_v4(g_xc + ((16 + r) * 3 + s) * 256 + cq * 32 + lane0, 0, 0, 0, 0);
        } else if (r < 2) {
            const uint16_t mask = (uint16_t)((1u << (3 * nh)) - 1u);
            const int htgt = A.h_target * (ld_relaxed(&g_epoch) + 1);
#pragma unroll 1
            for (int n = 0; n < NSEG; n++) {
                if (n == (r == 0 ? 1 : 0)) { cluster_arrive(); cluster_wait(); }
                int guard = 0;
                while (ld_acquire(FLG(F_H + r * 64 + n)) < htgt) { if (++guard > 2000000) __trap(); __nanosleep(40); }
                fence_async_global();
                if (H1_LATE && r == 1) named_bar(12, 64);
                if (n) mwait(bb + B_HE, (n - 1) & 1);
                if (lane < 8)
                    asm volatile("cp.async.bulk.shared::cluster.global.mbarrier::complete_tx::bytes.multicast::cluster [%0], [%1], %2, [%3], %4;" ::"r"(sb + O_H + r * 40960 + lane * 5120),
                                 "l"(g_ht + (r * NSEG + n) * 2560 + lane * 320), "r"(HBYTES), "r"(bb + B_HF + r * 8), "h"(mask) : "memory");
                __syncwarp();
            }
        } else {
            cluster_arrive(); cluster_wait();
            if (head && role == 2) {
#pragma unroll 1
                for (int t = 0; t < NT; t++) {
                    auto put = [&](int l, int n) {
                        asm volatile("cp.async.bulk.global.shared::cta.bulk_group [%0], [%1], %2;" ::"l"(g_ot + ((l * NSEG + n) * 256 + h * 8) * 64), "r"(sb + O_VT + (t & 1) * 16384 + l * 8192), "r"(8192) : "memory");
                        asm volatile("cp.async.bulk.commit_group;" ::: "memory");
                    };
                    auto publish = [&](int l, int n) {
                        asm volatile("cp.async.bulk.wait_group 0;" ::: "memory");
                        fence_async_global();
                        red_release(FLG(F_O + l * 64 + n) + (h >> 3), 1);
                        GT(true, 200 + l * 64 + n);
                    };
                    if (O0_EARLY && t < NSEG) {
                        mwait(bb + B_OTF + 8, t & 1);
                        if (lane == 0) { put(0, t); publish(0, t); }
                        __syncwarp();
                    }
                    mwait(bb + B_OTF, t & 1);
                    if (OT_LATE && t < NT - 1) named_bar(6, 128);
                    const int l = lane & 1, n = t - l * LAG;
                    const bool mine = lane < 2 && n >= 0 && n < NSEG && (l || !O0_EARLY);
                    if (mine) {
                        put(l, n);
                        asm volatile("cp.async.bulk.wait_group.read 0;" ::: "memory");
                    }
                    __syncwarp();
                    if (lane == 0) mbar_arrive(bb + B_OTE);
                    if (mine) publish(l, n);
                    __syncwarp();
                }
            }
            if (!head && lane == 0) {
#pragma unroll 1
                for (int k = 0; k < 25; k++) {
                    const int rg = k / 5, r0 = rg == 1 ? 256 : 0;
                    mwait(bb + B_OTF + (k & 1) * 8, (k >> 1) & 1);
                    asm volatile("cp.async.bulk.global.shared::cta.bulk_group [%0], [%1], %2;" ::"l"(g_Y + (sp * 5 + k - 5 * rg) * S_LEN + (rg ? rg - 1 : 0) * 512 + r0),
                                 "r"(sb + CV_Y + (k & 1) * 8192 + r0 * 16), "r"(rg < 2 ? 4096 : 8192) : "memory");
                    asm volatile("cp.async.bulk.commit_group;" ::: "memory");
                    asm volatile("cp.async.bulk.wait_group 0;" ::: "memory");
                    mbar_arrive(bb + B_OTE + (k & 1) * 16);
                    fence_async_global();
                    red_release(FLG(F_CV + rg), 1);
                    GT(true, 50 + k);
                }
            }
            __syncwarp();
        }
    }
    cluster_arrive(); cluster_wait();
    if (blockIdx.x == 0 && tid == 0) atomicAdd(&g_epoch, 1);
}
}

namespace ws {
constexpr int OP_SS = 17;
constexpr int P_RING = 0, P_AS = 131072, P_STG = P_AS + 2 * OP_SS * 2048, P_BAR = P_STG + 16384, OP_SMEM = P_BAR + 256;
constexpr int PB_FULL = 0, PB_EMPTY = 128, PB_SF = 144, PB_SE = 176;
static_assert(OP_SMEM <= 232448, "smem");

__global__ void __launch_bounds__(384, 1) op_kernel(const bf16* __restrict__ Wo, const bf16* __restrict__ Bk, const bf16* __restrict__ Bv, const bf16* __restrict__ shiftk) {
    extern __shared__ __align__(1024) unsigned char smem_raw[];
    const int tid = threadIdx.x, warp = __shfl_sync(0xffffffffu, tid >> 5, 0), lane = tid & 31;
    const int nb = blockIdx.x % 5, ks = blockIdx.x / 5;
    const uint32_t sb = smem_u32(smem_raw), bb = sb + P_BAR;
    if (tid == 0) {
        if ((sb & 0xFFFFFFu) != 1024) __trap();
        for (int i = 0; i < 16; i++) mbar_init(bb + PB_FULL + i * 8, 1);
        for (int i = 0; i < 2; i++) mbar_init(bb + PB_EMPTY + i * 8, 2);
        for (int i = 0; i < 4; i++) { mbar_init(bb + PB_SF + i * 8, 4); mbar_init(bb + PB_SE + i * 8, 1); }
        asm volatile("fence.mbarrier_init.release.cluster;" ::: "memory");
    }
    GT(tid == 0, 8);
    __syncthreads();
    if (warp < 4) {
        asm volatile("setmaxnreg.dec.sync.aligned.u32 40;");
        if (warp == 0) {
            named_bar(3, 288);
            GT(lane == 0, 3);
            uint32_t it = 0;
            const int otgt = 8 * (ld_relaxed(&g_epoch) + 1);
#pragma unroll 1
            for (int q = 0; q < 2 * NT; q++) {
                const int l = q & 1, n = (q >> 1) - l * LAG;
                if (n < 0 || n >= NSEG) continue;
                int guard = 0;
                while (ld_acquire(FLG(F_O + l * 64 + n) + ks) < otgt) { if (++guard > 4000000) __trap(); __nanosleep(OP_NS); }
                fence_async_global();
                mwait(bb + PB_EMPTY + (it & 1) * 8, ((it >> 1) & 1) ^ 1);
                if (lane < 8) {
                    const uint32_t fb = bb + PB_FULL + ((it & 1) * 8 + lane) * 8;
                    mbar_expect_tx(fb, 8192);
                    asm volatile("cp.async.bulk.shared::cluster.global.mbarrier::complete_tx::bytes [%0], [%1], %2, [%3];" ::"r"(sb + P_RING + (it & 1) * 65536 + lane * 8192),
                                 "l"(g_ot + ((l * NSEG + n) * 256 + (ks * 8 + lane) * 8) * 64), "r"(8192), "r"(fb) : "memory");
                }
                __syncwarp();
                it++;
            }
        } else if (warp == 3) {
#pragma unroll 1
            for (int rg = 1; rg < 4; rg++) {
#pragma unroll 1
                for (int u = rg * 640 + blockIdx.x; u < rg * 640 + 640; u += 20) u_half(Bk, Bv, shiftk, u, lane);
                __syncwarp();
                if (lane == 0) red_release(FLG(F_U + rg + 1), 1);
                GT(lane == 0, 4 + rg);
            }
        } else if (lane == 0) {
            const int cw = warp - 1;
            uint32_t it = 0;
#pragma unroll 1
            for (int q = 0; q < 2 * NT; q++) {
                const int l = q & 1, n = (q >> 1) - l * LAG;
                if (n < 0 || n >= NSEG) continue;
                const uint32_t i = cw * 2 + (it & 1);
                mwait(bb + PB_SF + i * 8, (it >> 1) & 1);
                asm volatile("cp.async.bulk.global.shared::cta.bulk_group [%0], [%1], %2;" ::"l"(g_pt + (((l * NSEG + n) * 4 + ks) * 10 + nb * 2 + cw) * 256), "r"(sb + P_STG + i * 4096), "r"(4096) : "memory");
                asm volatile("cp.async.bulk.commit_group;" ::: "memory");
                asm volatile("cp.async.bulk.wait_group 0;" ::: "memory");
                mbar_arrive(bb + PB_SE + i * 8);
                fence_async_global();
                red_release(FLG(F_P + l * 64 + n), 1);
                GT(true, 330 + l * 64 + n);
                it++;
            }
        }
    } else {
        asm volatile("setmaxnreg.inc.sync.aligned.u32 232;");
        const int cw = (warp >> 2) - 1, w4 = warp & 3, t7 = tid & 127;
        uint32_t wa[64 - OP_SS][4];
        {
            const bf16* W = Wo + (size_t)ks * 1024 * DM + nb * 128 + cw * 64 + (t7 & 7) * 8;
            const uint32_t so = (t7 >> 3) * 128 + (((t7 & 7) ^ ((t7 >> 3) & 7)) << 4);
            const uint32_t stg = sb + P_RING + cw * 65536;
            const uint32_t la = stg + ((lane & 7) + (lane >> 4) * 8) * 128 + (((w4 * 2 + ((lane >> 3) & 1)) ^ (lane & 7)) << 4);
#pragma unroll 4
            for (int i = 0; i < 32; i++) cp_async16(stg + i * 2048 + so, W + (size_t)((OP_SS + i) * 16 + (t7 >> 3)) * DM);
            cp_commit();
#pragma unroll 1
            for (int i = 0; i < OP_SS; i++) cp_async16(sb + P_AS + cw * OP_SS * 2048 + i * 2048 + so, W + (size_t)(i * 16 + (t7 >> 3)) * DM);
            cp_commit();
            cp_wait<1>();
            named_bar(1 + cw, 128);
#pragma unroll
            for (int j = 0; j < 32; j++) { const uint4 v = ldsm4t(la + j * 2048); wa[j][0] = v.x; wa[j][1] = v.y; wa[j][2] = v.z; wa[j][3] = v.w; }
            named_bar(1 + cw, 128);
#pragma unroll 1
            for (int i = 0; i < 32 - OP_SS; i++) cp_async16(stg + i * 2048 + so, W + (size_t)((OP_SS + 32 + i) * 16 + (t7 >> 3)) * DM);
            cp_commit();
            cp_wait<0>();
            named_bar(1 + cw, 128);
#pragma unroll
            for (int j = 0; j < 32 - OP_SS; j++) { const uint4 v = ldsm4t(la + j * 2048); wa[32 + j][0] = v.x; wa[32 + j][1] = v.y; wa[32 + j][2] = v.z; wa[32 + j][3] = v.w; }
            fence_async_smem();
            named_bar(3, 288);
        }
        const uint32_t ab = (1024 + P_AS + cw * OP_SS * 2048) >> 4;
        const int tk = 8 * ((lane & 7) >> 1) + 2 * (lane >> 4) + (lane & 1);
        const uint32_t ea = sb + P_STG + cw * 8192 + tk * 128 + (((2 * w4 + ((lane >> 3) & 1)) ^ (lane & 7)) << 4);
#pragma unroll 1
        for (uint32_t it = 0; it < 2 * NSEG; it++) {
            float acc[16];
            const uint32_t fb = bb + PB_FULL + (it & 1) * 64, par = (it >> 1) & 1;
            const uint32_t ob = opq(((1024 + P_RING) >> 4) + (it & 1) * 4096);
            uint32_t ok = 0;
#pragma unroll
            for (int j = 0; j < 64; j++) {
                if ((j & 7) == 0) {
                    if (j) wg_commit();
                    if (!ok) mslow(fb + j, par);
                    ok = j < 56 ? mtest(fb + j + 8, par) : mtest(bb + PB_SE + (cw * 2 + (it & 1)) * 8, par ^ 1);
                    if (j == 0) wg_fence();
                }
                const uint64_t db = mkdesc(ob + j * 64, 0x80000020u);
                if (j == 0) wg_n32t_sfirst(acc, mkdesc(ab, 0x40000040u), db);
                else if (j < OP_SS) wg_n32t_s(acc, mkdesc(ab + j * 128, 0x40000040u), db);
                else wg_n32t(acc, wa[j - OP_SS][0], wa[j - OP_SS][1], wa[j - OP_SS][2], wa[j - OP_SS][3], db);
            }
            wg_commit();
            if (!ok) mslow(bb + PB_SE + (cw * 2 + (it & 1)) * 8, par ^ 1);
            wg_wait<0>();
            if (t7 == 0) mbar_arrive(bb + PB_EMPTY + (it & 1) * 8);
            const uint32_t e = ea + (it & 1) * 4096;
            stsm4t(e, pack2(acc[0], acc[1]), pack2(acc[2], acc[3]), pack2(acc[4], acc[5]), pack2(acc[6], acc[7]));
            stsm4t(e + 512, pack2(acc[8], acc[9]), pack2(acc[10], acc[11]), pack2(acc[12], acc[13]), pack2(acc[14], acc[15]));
            fence_async_smem();
            __syncwarp();
            if (lane == 0) mbar_arrive(bb + PB_SF + (cw * 2 + (it & 1)) * 8);
        }
    }
}
}

namespace ws {
static void launch_all(void* const* d_in, void* d_out) {
    static bool inited = false;
    if (!inited) {
        inited = true;
        cudaFuncSetAttribute(head_kernel, cudaFuncAttributeMaxDynamicSharedMemorySize, HEAD_SMEM);
        cudaFuncSetAttribute(head_kernel, cudaFuncAttributeNonPortableClusterSizeAllowed, 1);
        cudaFuncSetAttribute(op_kernel, cudaFuncAttributeMaxDynamicSharedMemorySize, OP_SMEM);
    }
    HeadArgs A;
    A.x = (const bf16*)d_in[0]; A.mem0 = (const bf16*)d_in[1]; A.Wq = (const bf16*)d_in[2]; A.Wk = (const bf16*)d_in[3]; A.Wv = (const bf16*)d_in[4]; A.Wo = (const bf16*)d_in[5];
    A.Bk = (const bf16*)d_in[8]; A.Bv = (const bf16*)d_in[9]; A.shiftk = (const bf16*)d_in[10]; A.ssmk = (const bf16*)d_in[11]; A.ssmD = (const bf16*)d_in[12];
    A.out = (bf16*)d_out; A.h_target = 32;
    cudaStream_t s = cudaStreamPerThread;
    {
        cudaLaunchConfig_t cfg = {};
        cfg.gridDim = dim3(NCL * 16); cfg.blockDim = dim3(512); cfg.dynamicSmemBytes = HEAD_SMEM; cfg.stream = s;
        cudaLaunchAttribute at[2];
        at[0].id = cudaLaunchAttributeClusterDimension;
        at[0].val.clusterDim.x = 16; at[0].val.clusterDim.y = 1; at[0].val.clusterDim.z = 1;
        at[1].id = cudaLaunchAttributeProgrammaticStreamSerialization;
        at[1].val.programmaticStreamSerializationAllowed = 1;
        cfg.attrs = at; cfg.numAttrs = 1;
        cudaLaunchKernelEx(&cfg, head_kernel, A);
    }
    {
        cudaLaunchConfig_t cfg = {};
        cfg.gridDim = dim3(20); cfg.blockDim = dim3(384); cfg.dynamicSmemBytes = OP_SMEM; cfg.stream = s;
        cudaLaunchAttribute at[1];
        at[0].id = cudaLaunchAttributeProgrammaticStreamSerialization;
        at[0].val.programmaticStreamSerializationAllowed = 1;
        cfg.attrs = at; cfg.numAttrs = 1;
        cudaLaunchKernelEx(&cfg, op_kernel, A.Wo, A.Bk, A.Bv, A.shiftk);
    }
}
}

extern "C" void kernel_launch(void* const* d_in, const int* in_sizes, int n_in, void* d_out, int out_size) {
    (void)in_sizes; (void)n_in; (void)out_size;
    ws::launch_all(d_in, d_out);
}
```

```cpp
#include <cuda_runtime.h>
#include <cuda_bf16.h>
#include <stdint.h>
#include <cuda.h>

typedef __nv_bfloat16 bf16;
namespace ws {
constexpr int S_LEN = 2048, DM = 640, NH = 32, DH = 128, HD = NH * DH, SEG = 32, NSEG = S_LEN / SEG;

__device__ __forceinline__ float bf2f(bf16 v) { return __bfloat162float(v); }
__device__ __forceinline__ float rbf(float v) { return __bfloat162float(__float2bfloat16_rn(v)); }
__device__ __forceinline__ uint32_t pack2(float a, float b) {
    __nv_bfloat162 t = __floats2bfloat162_rn(a, b);
    return *reinterpret_cast<uint32_t*>(&t);
}
__device__ __forceinline__ float blo(uint32_t v) { return __uint_as_float(v << 16); }
__device__ __forceinline__ float bhi(uint32_t v) { return __uint_as_float(v & 0xffff0000u); }
__device__ __forceinline__ uint32_t badd(uint32_t a, uint32_t b) { uint32_t r; asm("add.rn.bf16x2 %0, %1, %2;" : "=r"(r) : "r"(a), "r"(b)); return r; }
__device__ __forceinline__ uint32_t smem_u32(const void* p) { return (uint32_t)__cvta_generic_to_shared(p); }
__device__ __forceinline__ uint4 ldsm4(uint32_t a) {
    uint4 v;
    asm volatile("ldmatrix.sync.aligned.m8n8.x4.shared.b16 {%0,%1,%2,%3}, [%4];" : "=r"(v.x), "=r"(v.y), "=r"(v.z), "=r"(v.w) : "r"(a));
    return v;
}
__device__ __forceinline__ uint4 ldsm4t(uint32_t a) {
    uint4 v;
    asm volatile("ldmatrix.sync.aligned.m8n8.x4.trans.shared.b16 {%0,%1,%2,%3}, [%4];" : "=r"(v.x), "=r"(v.y), "=r"(v.z), "=r"(v.w) : "r"(a));
    return v;
}
__device__ __forceinline__ uint2 ldsm2t(uint32_t a) {
    uint2 v;
    asm volatile("ldmatrix.sync.aligned.m8n8.x2.trans.shared.b16 {%0,%1}, [%2];" : "=r"(v.x), "=r"(v.y) : "r"(a));
    return v;
}
__device__ __forceinline__ void stsm4(uint32_t a, uint32_t r0, uint32_t r1, uint32_t r2, uint32_t r3) {
    asm volatile("stmatrix.sync.aligned.m8n8.x4.shared.b16 [%0], {%1,%2,%3,%4};" ::"r"(a), "r"(r0), "r"(r1), "r"(r2), "r"(r3) : "memory");
}
__device__ __forceinline__ void stsm2(uint32_t a, uint32_t r0, uint32_t r1) {
    asm volatile("stmatrix.sync.aligned.m8n8.x2.shared.b16 [%0], {%1,%2};" ::"r"(a), "r"(r0), "r"(r1) : "memory");
}
__device__ __forceinline__ void stsm4t(uint32_t a, uint32_t r0, uint32_t r1, uint32_t r2, uint32_t r3) {
    asm volatile("stmatrix.sync.aligned.m8n8.x4.trans.shared.b16 [%0], {%1,%2,%3,%4};" ::"r"(a), "r"(r0), "r"(r1), "r"(r2), "r"(r3) : "memory");
}
__device__ __forceinline__ void mma16816(float* c, uint32_t a0, uint32_t a1, uint32_t a2, uint32_t a3, uint32_t b0, uint32_t b1) {
    asm("mma.sync.aligned.m16n8k16.row.col.f32.bf16.bf16.f32 {%0,%1,%2,%3}, {%4,%5,%6,%7}, {%8,%9}, {%0,%1,%2,%3};"
        : "+f"(c[0]), "+f"(c[1]), "+f"(c[2]), "+f"(c[3]) : "r"(a0), "r"(a1), "r"(a2), "r"(a3), "r"(b0), "r"(b1));
}
__device__ __forceinline__ void mmav(float* c, uint32_t a0, uint32_t a1, uint32_t a2, uint32_t a3, uint32_t b0, uint32_t b1) {
    asm volatile("mma.sync.aligned.m16n8k16.row.col.f32.bf16.bf16.f32 {%0,%1,%2,%3}, {%4,%5,%6,%7}, {%8,%9}, {%0,%1,%2,%3};"
        : "+f"(c[0]), "+f"(c[1]), "+f"(c[2]), "+f"(c[3]) : "r"(a0), "r"(a1), "r"(a2), "r"(a3), "r"(b0), "r"(b1));
}
__device__ __forceinline__ void mmau(float* c, const uint4& a, uint32_t b0, uint32_t b1) { mma16816(c, a.x, a.y, a.z, a.w, b0, b1); }
__device__ __forceinline__ void mma1688(float* c, uint32_t a0, uint32_t a1, uint32_t b0) {
    asm("mma.sync.aligned.m16n8k8.row.col.f32.bf16.bf16.f32 {%0,%1,%2,%3}, {%4,%5}, {%6}, {%0,%1,%2,%3};"
        : "+f"(c[0]), "+f"(c[1]), "+f"(c[2]), "+f"(c[3]) : "r"(a0), "r"(a1), "r"(b0));
}
__device__ __forceinline__ void mmav8(float* c, uint32_t a0, uint32_t a1, uint32_t b0) {
    asm volatile("mma.sync.aligned.m16n8k8.row.col.f32.bf16.bf16.f32 {%0,%1,%2,%3}, {%4,%5}, {%6}, {%0,%1,%2,%3};"
        : "+f"(c[0]), "+f"(c[1]), "+f"(c[2]), "+f"(c[3]) : "r"(a0), "r"(a1), "r"(b0));
}
__device__ __forceinline__ void cp_async16(uint32_t dst, const void* src) { asm volatile("cp.async.cg.shared.global [%0], [%1], 16;" ::"r"(dst), "l"(src)); }
__device__ __forceinline__ void cp_commit() { asm volatile("cp.async.commit_group;"); }
template <int N> __device__ __forceinline__ void cp_wait() { asm volatile("cp.async.wait_group %0;" ::"n"(N)); }
__device__ __forceinline__ uint4 lds128(uint32_t a) {
    uint4 v;
    asm volatile("ld.shared.v4.u32 {%0,%1,%2,%3}, [%4];" : "=r"(v.x), "=r"(v.y), "=r"(v.z), "=r"(v.w) : "r"(a));
    return v;
}
__device__ __forceinline__ uint2 lds64(uint32_t a) {
    uint2 v;
    asm volatile("ld.shared.v2.u32 {%0,%1}, [%2];" : "=r"(v.x), "=r"(v.y) : "r"(a));
    return v;
}
__device__ __forceinline__ uint32_t lds32(uint32_t a) { uint32_t v; asm volatile("ld.shared.u32 %0, [%1];" : "=r"(v) : "r"(a)); return v; }
__device__ __forceinline__ void sts32(uint32_t a, uint32_t x) { asm volatile("st.shared.u32 [%0], %1;" ::"r"(a), "r"(x) : "memory"); }
__device__ __forceinline__ void sts64(uint32_t a, uint32_t x, uint32_t y) { asm volatile("st.shared.v2.u32 [%0], {%1,%2};" ::"r"(a), "r"(x), "r"(y) : "memory"); }
__device__ __forceinline__ void sts128(uint32_t a, uint32_t x, uint32_t y, uint32_t z, uint32_t w) {
    asm volatile("st.shared.v4.u32 [%0], {%1,%2,%3,%4};" ::"r"(a), "r"(x), "r"(y), "r"(z), "r"(w) : "memory");
}
__device__ __forceinline__ uint4 ld_relaxed_v4(const void* p) {
    uint4 v;
    asm volatile("ld.relaxed.gpu.global.v4.u32 {%0,%1,%2,%3}, [%4];" : "=r"(v.x), "=r"(v.y), "=r"(v.z), "=r"(v.w) : "l"(p) : "memory");
    return v;
}
__device__ __forceinline__ uint2 ld_relaxed_v2(const void* p) {
    uint2 v;
    asm volatile("ld.relaxed.gpu.global.v2.u32 {%0,%1}, [%2];" : "=r"(v.x), "=r"(v.y) : "l"(p) : "memory");
    return v;
}
__device__ __forceinline__ void ld7_relaxed(uint4* x, const void* p) {
    asm volatile("ld.relaxed.gpu.global.v4.u32 {%0,%1,%2,%3}, [%28 + 0];\nld.relaxed.gpu.global.v4.u32 {%4,%5,%6,%7}, [%28 + 512];\nld.relaxed.gpu.global.v4.u32 {%8,%9,%10,%11}, [%28 + 1024];\nld.relaxed.gpu.global.v4.u32 {%12,%13,%14,%15}, [%28 + 1536];\nld.relaxed.gpu.global.v4.u32 {%16,%17,%18,%19}, [%28 + 2048];\nld.relaxed.gpu.global.v4.u32 {%20,%21,%22,%23}, [%28 + 2560];\nld.relaxed.gpu.global.v4.u32 {%24,%25,%26,%27}, [%28 + 3072];\n" : "=r"(x[0].x), "=r"(x[0].y), "=r"(x[0].z), "=r"(x[0].w), "=r"(x[1].x), "=r"(x[1].y), "=r"(x[1].z), "=r"(x[1].w), "=r"(x[2].x), "=r"(x[2].y), "=r"(x[2].z), "=r"(x[2].w), "=r"(x[3].x), "=r"(x[3].y), "=r"(x[3].z), "=r"(x[3].w), "=r"(x[4].x), "=r"(x[4].y), "=r"(x[4].z), "=r"(x[4].w), "=r"(x[5].x), "=r"(x[5].y), "=r"(x[5].z), "=r"(x[5].w), "=r"(x[6].x), "=r"(x[6].y), "=r"(x[6].z), "=r"(x[6].w) : "l"(p) : "memory");
}
__device__ __forceinline__ void ld7_relaxed(uint2* x, const void* p) {
    asm volatile("ld.relaxed.gpu.global.v2.u32 {%0,%1}, [%14 + 0];\nld.relaxed.gpu.global.v2.u32 {%2,%3}, [%14 + 512];\nld.relaxed.gpu.global.v2.u32 {%4,%5}, [%14 + 1024];\nld.relaxed.gpu.global.v2.u32 {%6,%7}, [%14 + 1536];\nld.relaxed.gpu.global.v2.u32 {%8,%9}, [%14 + 2048];\nld.relaxed.gpu.global.v2.u32 {%10,%11}, [%14 + 2560];\nld.relaxed.gpu.global.v2.u32 {%12,%13}, [%14 + 3072];\n" : "=r"(x[0].x), "=r"(x[0].y), "=r"(x[1].x), "=r"(x[1].y), "=r"(x[2].x), "=r"(x[2].y), "=r"(x[3].x), "=r"(x[3].y), "=r"(x[4].x), "=r"(x[4].y), "=r"(x[5].x), "=r"(x[5].y), "=r"(x[6].x), "=r"(x[6].y) : "l"(p) : "memory");
}
__device__ __forceinline__ void st_relaxed_v4(void* p, uint32_t a, uint32_t b, uint32_t c, uint32_t d) {
    asm volatile("st.relaxed.gpu.global.v4.u32 [%0], {%1,%2,%3,%4};" ::"l"(p), "r"(a), "r"(b), "r"(c), "r"(d) : "memory");
}
__device__ __forceinline__ void st_relaxed_v2(void* p, uint32_t a, uint32_t b) {
    asm volatile("st.relaxed.gpu.global.v2.u32 [%0], {%1,%2};" ::"l"(p), "r"(a), "r"(b) : "memory");
}
__device__ __forceinline__ uint32_t clear16(void* p) {
    uint32_t r;
    asm volatile("{\n.reg .b128 z, o;\n.reg .b64 a, b;\nmov.b64 a, 0;\nmov.b128 z, {a, a};\natom.relaxed.gpu.global.exch.b128 o, [%1], z;\nmov.b128 {a, b}, o;\ncvt.u32.u64 %0, a;\n}" : "=r"(r) : "l"(p) : "memory");
    return r;
}
__device__ __forceinline__ uint32_t nz(uint32_t v) { uint32_t r; asm("max.u32 %0, %1, 1;" : "=r"(r) : "r"(v)); return r; }
__device__ __forceinline__ void touch(const void* p) { asm volatile("prefetch.global.L2 [%0];" ::"l"(p) : "memory"); }
__device__ __forceinline__ int ld_relaxed(const int* p) {
    int v;
    asm volatile("ld.relaxed.gpu.global.u32 %0, [%1];" : "=r"(v) : "l"(p) : "memory");
    return v;
}
__device__ __forceinline__ int ld_acquire(const int* p) {
    int v;
    asm volatile("ld.acquire.gpu.global.u32 %0, [%1];" : "=r"(v) : "l"(p) : "memory");
    return v;
}
__device__ __forceinline__ void red_release(int* p, int v) { asm volatile("red.release.gpu.global.add.u32 [%0], %1;" ::"l"(p), "r"(v) : "memory"); }
__device__ __forceinline__ void mbar_init(uint32_t bar, int count) { asm volatile("mbarrier.init.shared::cta.b64 [%0], %1;" ::"r"(bar), "r"(count)); }
__device__ __forceinline__ void mbar_expect_tx(uint32_t bar, uint32_t bytes) {
    asm volatile("mbarrier.arrive.expect_tx.shared::cta.b64 _, [%0], %1;" ::"r"(bar), "r"(bytes) : "memory");
}
__device__ __forceinline__ void mbar_arrive(uint32_t bar) { asm volatile("mbarrier.arrive.shared::cta.b64 _, [%0];" ::"r"(bar) : "memory"); }
__device__ __forceinline__ void mbar_arrive_cluster(uint32_t bar) { asm volatile("mbarrier.arrive.shared::cluster.b64 _, [%0];" ::"r"(bar) : "memory"); }
__device__ __forceinline__ bool mtry(uint32_t bar, uint32_t parity) {
    uint32_t ok;
    asm volatile("{\n.reg .pred P1;\nmbarrier.try_wait.parity.shared::cta.b64 P1, [%1], %2;\nselp.u32 %0, 1, 0, P1;\n}\n" : "=r"(ok) : "r"(bar), "r"(parity) : "memory");
    return ok != 0;
}
__device__ __forceinline__ void mslow(uint32_t bar, uint32_t parity) {
    asm volatile(
        "{\n.reg .pred P1;\n.reg .u32 cnt;\n"
        "mov.u32 cnt, 0;\n"
        "LAB_WAIT:\n"
        "mbarrier.try_wait.parity.shared::cta.b64 P1, [%0], %1;\n"
        "@P1 bra DONE;\n"
        "add.u32 cnt, cnt, 1;\n"
        "setp.lt.u32 P1, cnt, 1000000;\n"
        "@P1 bra LAB_WAIT;\n"
        "trap;\n"
        "DONE:\n}\n" ::"r"(bar), "r"(parity) : "memory");
}
__device__ __forceinline__ void mwait(uint32_t bar, uint32_t parity) {
    asm volatile(
        "{\n.reg .pred P1, P2;\n.reg .u32 cnt;\n"
        "mov.u32 cnt, 0;\n"
        "LAB_WAIT:\n"
        "mbarrier.try_wait.parity.shared::cta.b64 P1, [%0], %1;\n"
        "add.u32 cnt, cnt, 1;\n"
        "setp.gt.u32 P2, cnt, 1000000;\n"
        "@P2 trap;\n"
        "@!P1 bra LAB_WAIT;\n"
        "}\n" ::"r"(bar), "r"(parity) : "memory");
}
__device__ __forceinline__ uint32_t mtest(uint32_t bar, uint32_t parity) {
    uint32_t ok;
    asm volatile("{\n.reg .pred P1;\nmbarrier.test_wait.parity.shared::cta.b64 P1, [%1], %2;\nselp.u32 %0, 1, 0, P1;\n}\n" : "=r"(ok) : "r"(bar), "r"(parity) : "memory");
    return ok;
}
__device__ __forceinline__ uint32_t mapa(uint32_t addr, uint32_t rank) {
    uint32_t r;
    asm("mapa.shared::cluster.u32 %0, %1, %2;" : "=r"(r) : "r"(addr), "r"(rank));
    return r;
}
__device__ __forceinline__ void st_async_b32(uint32_t addr, uint32_t a, uint32_t bar) {
    asm volatile("st.async.weak.shared::cluster.mbarrier::complete_tx::bytes.b32 [%0], %1, [%2];" ::"r"(addr), "r"(a), "r"(bar) : "memory");
}
__device__ __forceinline__ void st_async_v2(uint32_t addr, uint32_t a, uint32_t b, uint32_t bar) {
    asm volatile("st.async.weak.shared::cluster.mbarrier::complete_tx::bytes.v2.b32 [%0], {%1,%2}, [%3];" ::"r"(addr), "r"(a), "r"(b), "r"(bar) : "memory");
}
__device__ __forceinline__ void st_async_v2_lt(uint32_t addr, uint32_t a, uint32_t b, uint32_t bar, uint32_t x, uint32_t lim) {
    asm volatile("{\n.reg .pred p;\nsetp.lt.u32 p, %4, %5;\n@p st.async.weak.shared::cluster.mbarrier::complete_tx::bytes.v2.b32 [%0], {%1,%2}, [%3];\n}"
                 ::"r"(addr), "r"(a), "r"(b), "r"(bar), "r"(x), "r"(lim) : "memory");
}
__device__ __forceinline__ void st_async_v4(uint32_t addr, uint32_t a, uint32_t b, uint32_t c, uint32_t d, uint32_t bar) {
    asm volatile("st.async.weak.shared::cluster.mbarrier::complete_tx::bytes.v4.b32 [%0], {%1,%2,%3,%4}, [%5];" ::"r"(addr), "r"(a), "r"(b), "r"(c), "r"(d), "r"(bar) : "memory");
}
__device__ __forceinline__ void cluster_arrive() { asm volatile("barrier.cluster.arrive.release.aligned;" ::: "memory"); }
__device__ __forceinline__ void cluster_arrive_relaxed() { asm volatile("barrier.cluster.arrive.relaxed.aligned;" ::: "memory"); }
__device__ __forceinline__ void prefetch_l2(const void* p, uint32_t bytes) { asm volatile("cp.async.bulk.prefetch.L2.global [%0], %1;" ::"l"(p), "r"(bytes) : "memory"); }
__device__ __forceinline__ void cluster_wait() { asm volatile("barrier.cluster.wait.acquire.aligned;" ::: "memory"); }
__device__ __forceinline__ void named_bar(int id, int n) { asm volatile("bar.sync %0, %1;" ::"r"(id), "r"(n) : "memory"); }
__device__ __forceinline__ void named_arrive(int id, int n) { asm volatile("bar.arrive %0, %1;" ::"r"(id), "r"(n) : "memory"); }
__device__ __forceinline__ void fence_async_smem() { asm volatile("fence.proxy.async.shared::cta;" ::: "memory"); }
__device__ __forceinline__ void fence_async_global() { asm volatile("fence.proxy.async.global;" ::: "memory"); }
__device__ __forceinline__ void wg_fence() { asm volatile("wgmma.fence.sync.aligned;" ::: "memory"); }
__device__ __forceinline__ void wg_commit() { asm volatile("wgmma.commit_group.sync.aligned;" ::: "memory"); }
template <int N> __device__ __forceinline__ void wg_wait() { asm volatile("wgmma.wait_group.sync.aligned %0;" ::"n"(N) : "memory"); }
__device__ __forceinline__ uint64_t ndesc(uint32_t addr, uint32_t lbo, uint32_t sbo) {
    return (uint64_t)((addr & 0x3FFFF) >> 4) | ((uint64_t)(lbo >> 4) << 16) | ((uint64_t)(sbo >> 4) << 32);
}
__device__ __forceinline__ float ex2f(float x) { float y; asm("ex2.approx.ftz.f32 %0, %1;" : "=f"(y) : "f"(x)); return y; }
__device__ __forceinline__ float rcpf(float x) { float y; asm("rcp.approx.ftz.f32 %0, %1;" : "=f"(y) : "f"(x)); return y; }
__device__ __forceinline__ uint32_t clk32() { uint32_t c; asm volatile("mov.u32 %0, %clock;" : "=r"(c)); return c; }
__device__ __forceinline__ uint32_t opq(uint32_t x) { uint32_t y; asm volatile("mov.u32 %0, %1;" : "=r"(y) : "r"(x)); return y; }
__device__ __forceinline__ uint32_t rem(uint32_t addr, uint32_t rank) { return mapa(addr, rank); }
__device__ __forceinline__ uint64_t mkdesc(uint32_t lo, uint32_t hi) { uint64_t d; asm("mov.b64 %0, {%1,%2};" : "=l"(d) : "r"(lo), "r"(hi)); return d; }
__device__ __forceinline__ void delay(uint32_t n) {
    asm volatile("{\n.reg .pred P;\n.reg .u32 a, b;\nmov.u32 a, %clock;\nadd.u32 a, a, %0;\nDL:\nmov.u32 b, %clock;\nsub.u32 b, b, a;\nsetp.lt.s32 P, b, 0;\n@P bra.uni DL;\n}" ::"r"(n) : "memory");
}
#define UNI(x) __shfl_sync(0xffffffffu, (uint32_t)(x), 0)
__device__ __forceinline__ void wg_n16t(float* d, uint32_t a0, uint32_t a1, uint32_t a2, uint32_t a3, uint64_t db) {
    asm volatile("wgmma.mma_async.sync.aligned.m64n16k16.f32.bf16.bf16 {%0, %1, %2, %3, %4, %5, %6, %7}, {%8, %9, %10, %11}, %12, 1, 1, 1, 1;"
                 : "+f"(d[0]), "+f"(d[1]), "+f"(d[2]), "+f"(d[3]), "+f"(d[4]), "+f"(d[5]), "+f"(d[6]), "+f"(d[7]) : "r"(a0), "r"(a1), "r"(a2), "r"(a3), "l"(db));
}
__device__ __forceinline__ void wg_n16t_first(float* d, uint32_t a0, uint32_t a1, uint32_t a2, uint32_t a3, uint64_t db) {
    asm volatile("wgmma.mma_async.sync.aligned.m64n16k16.f32.bf16.bf16 {%0, %1, %2, %3, %4, %5, %6, %7}, {%8, %9, %10, %11}, %12, 0, 1, 1, 1;"
                 : "=f"(d[0]), "=f"(d[1]), "=f"(d[2]), "=f"(d[3]), "=f"(d[4]), "=f"(d[5]), "=f"(d[6]), "=f"(d[7]) : "r"(a0), "r"(a1), "r"(a2), "r"(a3), "l"(db));
}
__device__ __forceinline__ void wg_n32(float* d, uint32_t a0, uint32_t a1, uint32_t a2, uint32_t a3, uint64_t db) {
    asm volatile("wgmma.mma_async.sync.aligned.m64n32k16.f32.bf16.bf16 {%0, %1, %2, %3, %4, %5, %6, %7, %8, %9, %10, %11, %12, %13, %14, %15}, {%16, %17, %18, %19}, %20, 1, 1, 1, 0;"
                 : "+f"(d[0]), "+f"(d[1]), "+f"(d[2]), "+f"(d[3]), "+f"(d[4]), "+f"(d[5]), "+f"(d[6]), "+f"(d[7]), "+f"(d[8]), "+f"(d[9]), "+f"(d[10]), "+f"(d[11]), "+f"(d[12]), "+f"(d[13]), "+f"(d[14]), "+f"(d[15]) : "r"(a0), "r"(a1), "r"(a2), "r"(a3), "l"(db));
}
__device__ __forceinline__ void wg_n32_first(float* d, uint32_t a0, uint32_t a1, uint32_t a2, uint32_t a3, uint64_t db) {
    asm volatile("wgmma.mma_async.sync.aligned.m64n32k16.f32.bf16.bf16 {%0, %1, %2, %3, %4, %5, %6, %7, %8, %9, %10, %11, %12, %13, %14, %15}, {%16, %17, %18, %19}, %20, 0, 1, 1, 0;"
                 : "=f"(d[0]), "=f"(d[1]), "=f"(d[2]), "=f"(d[3]), "=f"(d[4]), "=f"(d[5]), "=f"(d[6]), "=f"(d[7]), "=f"(d[8]), "=f"(d[9]), "=f"(d[10]), "=f"(d[11]), "=f"(d[12]), "=f"(d[13]), "=f"(d[14]), "=f"(d[15]) : "r"(a0), "r"(a1), "r"(a2), "r"(a3), "l"(db));
}

__device__ __forceinline__ void wg_n16t_sfirst(float* d, uint64_t da, uint64_t db) {
    asm volatile("wgmma.mma_async.sync.aligned.m64n16k16.f32.bf16.bf16 {%0, %1, %2, %3, %4, %5, %6, %7}, %8, %9, 0, 1, 1, 1, 1;"
                 : "=f"(d[0]), "=f"(d[1]), "=f"(d[2]), "=f"(d[3]), "=f"(d[4]), "=f"(d[5]), "=f"(d[6]), "=f"(d[7]) : "l"(da), "l"(db));
}
__device__ __forceinline__ void wg_n32_sfirst(float* d, uint64_t da, uint64_t db) {
    asm volatile("wgmma.mma_async.sync.aligned.m64n32k16.f32.bf16.bf16 {%0, %1, %2, %3, %4, %5, %6, %7, %8, %9, %10, %11, %12, %13, %14, %15}, %16, %17, 0, 1, 1, 1, 0;"
                 : "=f"(d[0]), "=f"(d[1]), "=f"(d[2]), "=f"(d[3]), "=f"(d[4]), "=f"(d[5]), "=f"(d[6]), "=f"(d[7]), "=f"(d[8]), "=f"(d[9]), "=f"(d[10]), "=f"(d[11]), "=f"(d[12]), "=f"(d[13]), "=f"(d[14]), "=f"(d[15]) : "l"(da), "l"(db));
}

__device__ __forceinline__ void wg_n16t_s(float* d, uint64_t da, uint64_t db) {
    asm volatile("wgmma.mma_async.sync.aligned.m64n16k16.f32.bf16.bf16 {%0, %1, %2, %3, %4, %5, %6, %7}, %8, %9, 1, 1, 1, 1, 1;"
                 : "+f"(d[0]), "+f"(d[1]), "+f"(d[2]), "+f"(d[3]), "+f"(d[4]), "+f"(d[5]), "+f"(d[6]), "+f"(d[7]) : "l"(da), "l"(db));
}
__device__ __forceinline__ void wg_n64_sfirst(float* d, uint64_t da, uint64_t db) {
    asm volatile("wgmma.mma_async.sync.aligned.m64n64k16.f32.bf16.bf16 {%0, %1, %2, %3, %4, %5, %6, %7, %8, %9, %10, %11, %12, %13, %14, %15, %16, %17, %18, %19, %20, %21, %22, %23, %24, %25, %26, %27, %28, %29, %30, %31}, %32, %33, 0, 1, 1, 1, 0;"
                 : "=f"(d[0]), "=f"(d[1]), "=f"(d[2]), "=f"(d[3]), "=f"(d[4]), "=f"(d[5]), "=f"(d[6]), "=f"(d[7]), "=f"(d[8]), "=f"(d[9]), "=f"(d[10]), "=f"(d[11]), "=f"(d[12]), "=f"(d[13]), "=f"(d[14]), "=f"(d[15]), "=f"(d[16]), "=f"(d[17]), "=f"(d[18]), "=f"(d[19]), "=f"(d[20]), "=f"(d[21]), "=f"(d[22]), "=f"(d[23]), "=f"(d[24]), "=f"(d[25]), "=f"(d[26]), "=f"(d[27]), "=f"(d[28]), "=f"(d[29]), "=f"(d[30]), "=f"(d[31]) : "l"(da), "l"(db));
}
__device__ __forceinline__ void wg_n64_s(float* d, uint64_t da, uint64_t db) {
    asm volatile("wgmma.mma_async.sync.aligned.m64n64k16.f32.bf16.bf16 {%0, %1, %2, %3, %4, %5, %6, %7, %8, %9, %10, %11, %12, %13, %14, %15, %16, %17, %18, %19, %20, %21, %22, %23, %24, %25, %26, %27, %28, %29, %30, %31}, %32, %33, 1, 1, 1, 1, 0;"
                 : "+f"(d[0]), "+f"(d[1]), "+f"(d[2]), "+f"(d[3]), "+f"(d[4]), "+f"(d[5]), "+f"(d[6]), "+f"(d[7]), "+f"(d[8]), "+f"(d[9]), "+f"(d[10]), "+f"(d[11]), "+f"(d[12]), "+f"(d[13]), "+f"(d[14]), "+f"(d[15]), "+f"(d[16]), "+f"(d[17]), "+f"(d[18]), "+f"(d[19]), "+f"(d[20]), "+f"(d[21]), "+f"(d[22]), "+f"(d[23]), "+f"(d[24]), "+f"(d[25]), "+f"(d[26]), "+f"(d[27]), "+f"(d[28]), "+f"(d[29]), "+f"(d[30]), "+f"(d[31]) : "l"(da), "l"(db));
}
__device__ __forceinline__ void wg_n64(float* d, uint32_t a0, uint32_t a1, uint32_t a2, uint32_t a3, uint64_t db) {
    asm volatile("wgmma.mma_async.sync.aligned.m64n64k16.f32.bf16.bf16 {%0, %1, %2, %3, %4, %5, %6, %7, %8, %9, %10, %11, %12, %13, %14, %15, %16, %17, %18, %19, %20, %21, %22, %23, %24, %25, %26, %27, %28, %29, %30, %31}, {%32, %33, %34, %35}, %36, 1, 1, 1, 0;"
                 : "+f"(d[0]), "+f"(d[1]), "+f"(d[2]), "+f"(d[3]), "+f"(d[4]), "+f"(d[5]), "+f"(d[6]), "+f"(d[7]), "+f"(d[8]), "+f"(d[9]), "+f"(d[10]), "+f"(d[11]), "+f"(d[12]), "+f"(d[13]), "+f"(d[14]), "+f"(d[15]), "+f"(d[16]), "+f"(d[17]), "+f"(d[18]), "+f"(d[19]), "+f"(d[20]), "+f"(d[21]), "+f"(d[22]), "+f"(d[23]), "+f"(d[24]), "+f"(d[25]), "+f"(d[26]), "+f"(d[27]), "+f"(d[28]), "+f"(d[29]), "+f"(d[30]), "+f"(d[31]) : "r"(a0), "r"(a1), "r"(a2), "r"(a3), "l"(db));
}
__device__ __forceinline__ void wg_n64_first(float* d, uint32_t a0, uint32_t a1, uint32_t a2, uint32_t a3, uint64_t db) {
    asm volatile("wgmma.mma_async.sync.aligned.m64n64k16.f32.bf16.bf16 {%0, %1, %2, %3, %4, %5, %6, %7, %8, %9, %10, %11, %12, %13, %14, %15, %16, %17, %18, %19, %20, %21, %22, %23, %24, %25, %26, %27, %28, %29, %30, %31}, {%32, %33, %34, %35}, %36, 0, 1, 1, 0;"
                 : "=f"(d[0]), "=f"(d[1]), "=f"(d[2]), "=f"(d[3]), "=f"(d[4]), "=f"(d[5]), "=f"(d[6]), "=f"(d[7]), "=f"(d[8]), "=f"(d[9]), "=f"(d[10]), "=f"(d[11]), "=f"(d[12]), "=f"(d[13]), "=f"(d[14]), "=f"(d[15]), "=f"(d[16]), "=f"(d[17]), "=f"(d[18]), "=f"(d[19]), "=f"(d[20]), "=f"(d[21]), "=f"(d[22]), "=f"(d[23]), "=f"(d[24]), "=f"(d[25]), "=f"(d[26]), "=f"(d[27]), "=f"(d[28]), "=f"(d[29]), "=f"(d[30]), "=f"(d[31]) : "r"(a0), "r"(a1), "r"(a2), "r"(a3), "l"(db));
}

__device__ __forceinline__ void wg_n32t(float* d, uint32_t a0, uint32_t a1, uint32_t a2, uint32_t a3, uint64_t db) {
    asm volatile("wgmma.mma_async.sync.aligned.m64n32k16.f32.bf16.bf16 {%0, %1, %2, %3, %4, %5, %6, %7, %8, %9, %10, %11, %12, %13, %14, %15}, {%16, %17, %18, %19}, %20, 1, 1, 1, 1;"
                 : "+f"(d[0]), "+f"(d[1]), "+f"(d[2]), "+f"(d[3]), "+f"(d[4]), "+f"(d[5]), "+f"(d[6]), "+f"(d[7]), "+f"(d[8]), "+f"(d[9]), "+f"(d[10]), "+f"(d[11]), "+f"(d[12]), "+f"(d[13]), "+f"(d[14]), "+f"(d[15]) : "r"(a0), "r"(a1), "r"(a2), "r"(a3), "l"(db));
}
__device__ __forceinline__ void wg_n32t_first(float* d, uint32_t a0, uint32_t a1, uint32_t a2, uint32_t a3, uint64_t db) {
    asm volatile("wgmma.mma_async.sync.aligned.m64n32k16.f32.bf16.bf16 {%0, %1, %2, %3, %4, %5, %6, %7, %8, %9, %10, %11, %12, %13, %14, %15}, {%16, %17, %18, %19}, %20, 0, 1, 1, 1;"
                 : "=f"(d[0]), "=f"(d[1]), "=f"(d[2]), "=f"(d[3]), "=f"(d[4]), "=f"(d[5]), "=f"(d[6]), "=f"(d[7]), "=f"(d[8]), "=f"(d[9]), "=f"(d[10]), "=f"(d[11]), "=f"(d[12]), "=f"(d[13]), "=f"(d[14]), "=f"(d[15]) : "r"(a0), "r"(a1), "r"(a2), "r"(a3), "l"(db));
}
__device__ __forceinline__ void wg_n32t_sfirst(float* d, uint64_t da, uint64_t db) {
    asm volatile("wgmma.mma_async.sync.aligned.m64n32k16.f32.bf16.bf16 {%0, %1, %2, %3, %4, %5, %6, %7, %8, %9, %10, %11, %12, %13, %14, %15}, %16, %17, 0, 1, 1, 1, 1;"
                 : "=f"(d[0]), "=f"(d[1]), "=f"(d[2]), "=f"(d[3]), "=f"(d[4]), "=f"(d[5]), "=f"(d[6]), "=f"(d[7]), "=f"(d[8]), "=f"(d[9]), "=f"(d[10]), "=f"(d[11]), "=f"(d[12]), "=f"(d[13]), "=f"(d[14]), "=f"(d[15]) : "l"(da), "l"(db));
}
__device__ __forceinline__ void wg_n32t_s(float* d, uint64_t da, uint64_t db) {
    asm volatile("wgmma.mma_async.sync.aligned.m64n32k16.f32.bf16.bf16 {%0, %1, %2, %3, %4, %5, %6, %7, %8, %9, %10, %11, %12, %13, %14, %15}, %16, %17, 1, 1, 1, 1, 1;"
                 : "+f"(d[0]), "+f"(d[1]), "+f"(d[2]), "+f"(d[3]), "+f"(d[4]), "+f"(d[5]), "+f"(d[6]), "+f"(d[7]), "+f"(d[8]), "+f"(d[9]), "+f"(d[10]), "+f"(d[11]), "+f"(d[12]), "+f"(d[13]), "+f"(d[14]), "+f"(d[15]) : "l"(da), "l"(db));
}

__device__ __forceinline__ void wg_n32_kk(float* d, uint64_t da, uint64_t db) {
    asm volatile("wgmma.mma_async.sync.aligned.m64n32k16.f32.bf16.bf16 {%0, %1, %2, %3, %4, %5, %6, %7, %8, %9, %10, %11, %12, %13, %14, %15}, %16, %17, 1, 1, 1, 0, 0;"
                 : "+f"(d[0]), "+f"(d[1]), "+f"(d[2]), "+f"(d[3]), "+f"(d[4]), "+f"(d[5]), "+f"(d[6]), "+f"(d[7]), "+f"(d[8]), "+f"(d[9]), "+f"(d[10]), "+f"(d[11]), "+f"(d[12]), "+f"(d[13]), "+f"(d[14]), "+f"(d[15]) : "l"(da), "l"(db));
}

}

namespace ws {
#define LAGT 4
constexpr int LAG = LAGT, NT = NSEG + LAG, NCL = 7;
#define P1A 24
#define P1C 10
#define XD 350
#define TPV_PAUSE 1
#define OT_LATE 1
#define H1_LATE 2
#define O_BULK 0
#define O_DLY 0
#define BP 0
#define REG_G 200
#define REG_T 72
#define REG_X 40
#define PDA 8
#define PDC 8
template <int V> struct IC { static constexpr int value = V; };
#define HBYTES 5120
#define POST_NS 40
#define OP_NS 40
#define LN0_AHEAD 8
#define PRE_PDL 0
#define PRE_PF 0
#define OP_LATE 0
#define G_DLY 0
#define QUIET 0
constexpr int NB4 = QUIET ? 480 : 384;
#define TG_STEPS 40
#define NO_X 0
#define WTA 3
constexpr int WTC = 10 - 2 * WTA;
#define WR 4
#define OBK 2
#define TPVW 1
#define OBRES 1
#define O0_EARLY 1
#define BNS 0
#define SKEW 0
#define XS 250
#define WGRP 4
#define WFLY 2
#define XDUP 1
#define TPV_LATE 0
constexpr int XRS = 3;
constexpr int O_H = 0, O_MEM = 81920, O_RED = 102400, O_BAR = 110080, O_TAB = O_BAR + 192, O_BT = O_TAB + 128, O_TR = O_BAR + 512, O_X = O_TR + 1024;
constexpr int O_QRY = O_X, O_KEY = O_X + 10240, O_OBA = O_KEY + 10240, O_ST = O_OBA + 4096;
constexpr int O_VT = O_X, O_VM = O_VT + 32768, O_SM = O_VM + 4096, O_PB = O_SM + 3072;
constexpr int O_AS = 228352, O_WO = O_AS - 65536, HEAD_SMEM = O_AS + 4096, O_STG = 40960;
static_assert(O_ST + 8192 <= O_WO && O_PB + 10240 <= O_WO && O_AS % 1024 == 0 && O_STG + 163840 <= O_AS && HEAD_SMEM <= 232448, "smem");
constexpr int B_MEM = 0, B_RED = 64, B_SM = 88, B_ST = 96, B_OB = 104, B_HF = 112, B_HE = 128, B_OTF = 144, B_OTE = 160;

constexpr int F_H = 0, F_O = 128, F_P = 256, F_U = 384, F_CV = 392, F_Z = 399, NFLAG = 400;
__device__ int g_flags[NFLAG * 8];
#define FLG(i) (g_flags + (i) * 8)
__device__ uint4 g_ht[2 * NSEG * 2560];
__device__ uint4 g_ot[2 * NSEG * 256 * 64];
__device__ uint4 g_pt[2 * NSEG * 5120];
__device__ uint4 g_Y[80 * S_LEN];
__device__ uint4 g_U[DM * S_LEN / 8];
__device__ bf16 g_x[S_LEN * DM];
__device__ int g_epoch;
__device__ uint4 g_xc[XRS * 16 * 3 * 8 * 32];
#define GT(cond, i)
#define SC(cond, i)
#define SD(x)
#define TS(i)
#define TV(i, v)

}

namespace ws {
__device__ __forceinline__ uint32_t bmul2(uint32_t a, uint32_t b) { uint32_t r; asm("mul.rn.bf16x2 %0, %1, %2;" : "=r"(r) : "r"(a), "r"(b)); return r; }
__device__ __forceinline__ uint32_t bmax2(uint32_t a, uint32_t b) { uint32_t r; asm("max.bf16x2 %0, %1, %2;" : "=r"(r) : "r"(a), "r"(b)); return r; }
__device__ __forceinline__ void flag_wait(const int* f, int tgt, int ns) {
    int guard = 0;
    while (ld_relaxed(f) < tgt) { if (++guard > 4000000) __trap(); __nanosleep(ns); }
}
template <int STRIDE> __device__ __forceinline__ void ld5(uint32_t* w, const void* p) {
#pragma unroll
    for (int r = 0; r < 5; r++) { const uint2 v = __ldcg(reinterpret_cast<const uint2*>(reinterpret_cast<const char*>(p) + r * STRIDE)); w[2 * r] = v.x; w[2 * r + 1] = v.y; }
}
template <int STRIDE> __device__ __forceinline__ void st5(void* p, const uint32_t* w) {
#pragma unroll
    for (int r = 0; r < 5; r++) *reinterpret_cast<uint2*>(reinterpret_cast<char*>(p) + r * STRIDE) = make_uint2(w[2 * r], w[2 * r + 1]);
}
__device__ __forceinline__ void ln_row(const uint32_t* x, uint32_t* y) {
    const float c = blo(__shfl_sync(0xffffffffu, x[0], 0));
    float s0 = 0.f, s1 = 0.f, q0 = 0.f, q1 = 0.f;
#pragma unroll
    for (int i = 0; i < 10; i++) { const float d0 = blo(x[i]) - c, d1 = bhi(x[i]) - c; s0 += d0; s1 += d1; q0 = fmaf(d0, d0, q0); q1 = fmaf(d1, d1, q1); }
    float s = s0 + s1, q = q0 + q1;
#pragma unroll
    for (int o = 16; o > 0; o >>= 1) { s += __shfl_xor_sync(0xffffffffu, s, o); q += __shfl_xor_sync(0xffffffffu, q, o); }
    s *= 1.0f / DM;
    const float mean = c + s;
    q = fmaxf(fmaf(q, 1.0f / DM, -s * s), 0.f);
    const uint32_t nm = pack2(-mean, -mean);
    float sq;
    asm("sqrt.approx.ftz.f32 %0, %1;" : "=f"(sq) : "f"(rbf(rbf(q) + 1e-5f)));
    const float rd = rcpf(rbf(sq));
#pragma unroll
    for (int i = 0; i < 10; i++) { const uint32_t d = badd(x[i], nm); y[i] = pack2(blo(d) * rd, bhi(d) * rd); }
}
__device__ __forceinline__ void put_h(int l, int seg, int tok, int lane, const uint32_t* n) {
    uint4* pz = g_pt + (l * NSEG + seg) * 5120 + (lane >> 4) * 512 + tok * 16 + (lane & 15);
#pragma unroll
    for (int i = 0; i < 5; i++) pz[i * 1024] = make_uint4(0, 0, 0, 0);
    st5<8192>(reinterpret_cast<char*>(g_ht + (l * NSEG + seg) * 2560) + (lane >> 2) * 1024 + tok * 32 + (((lane & 3) * 8) ^ ((tok & 4) << 2)), n);
}
__device__ __forceinline__ void ln0_row(const bf16* x, int seg, int tok, int lane) {
    uint32_t v[10];
    ld5<256>(v, x + (size_t)(seg * SEG + tok) * DM + lane * 4);
    ln_row(v, v);
    put_h(0, seg, tok, lane, v);
    __syncwarp();
    if (lane == 0) red_release(FLG(F_H + seg), 1);
}
__device__ __forceinline__ void post_row(int l, int seg, int tok, int lane, const bf16* xin, bf16* xout, int ep) {
    const bool dry = ep == 0;
    uint32_t x[10], y[10], n[10];
    const int row = seg * SEG + tok;
    SC(tr, tb);
    const bool first = seg == 0;
    if (seg == 8 || ((seg & 15) == 0 && seg)) flag_wait(FLG(F_CV + (seg >> 4) + 1), 80 * ep, 50);
    const char* yp = reinterpret_cast<const char*>(g_Y) + ((size_t)(lane >> 1) * S_LEN + row) * 16 + (lane & 1) * 8;
    SC(tr, tb + 1);
    if (!first) ld5<16 * S_LEN * 16>(y, yp);
    if (l == 0) ld5<256>(x, xin + (size_t)row * DM + lane * 4);
    flag_wait(FLG(F_P + l * 64 + seg), 40 * ep, POST_NS);
    SC(tr, tb + 2);
    if (l) ld5<256>(x, xin + (size_t)row * DM + lane * 4);
    const uint4* pp = g_pt + (l * NSEG + seg) * 5120 + (lane >> 4) * 512 + tok * 16 + ((lane & 15) ^ ((tok >> 3) << 1));
    {
        uint4 a[5];
#pragma unroll
        for (int i = 0; i < 5; i++) a[i] = __ldcg(pp + i * 1024);
#pragma unroll
        for (int i = 0; i < 5; i++) {
            x[2 * i] = badd(x[2 * i], pack2(__uint_as_float(a[i].x), __uint_as_float(a[i].y)));
            x[2 * i + 1] = badd(x[2 * i + 1], pack2(__uint_as_float(a[i].z), __uint_as_float(a[i].w)));
        }
    }
    SC(tr && x[0] != 0x12345, tb + 3);
    if (first) { flag_wait(FLG(F_CV), 80 * ep, 50); ld5<16 * S_LEN * 16>(y, yp); }
    ln_row(x, n);
#pragma unroll
    for (int i = 0; i < 10; i++) x[i] = badd(x[i], bmul2(n[i], y[i]));
    SC(tr && x[0] != 0x12345, tb + 4);
    if (!dry) st5<256>(xout + (size_t)row * DM + lane * 4, x);
    if (l == 0) {
        ln_row(x, n);
        SC(tr && n[0] != 0x12345, tb + 5);
        if (!dry) put_h(1, seg, tok, lane, n);
        __syncwarp();
        if (lane == 0) red_release(FLG(F_H + 64 + seg), dry ? 0 : 1);
        SC(tr, tb + 6);
    }
}
__device__ __forceinline__ void u_half(const bf16* Bk, const bf16* Bv, const bf16* shiftk, int unit, int lane) {
    const int odd = lane & 1, t0 = (unit / 20) * 16 + odd * 8, cp = (unit % 20) * 16 + (lane >> 1);
    uint32_t kk[11], vv[8];
    const uint32_t* pk = reinterpret_cast<const uint32_t*>(Bk + (size_t)t0 * DM) + cp;
    const uint32_t* pv = reinterpret_cast<const uint32_t*>(Bv + (size_t)t0 * DM) + cp;
#pragma unroll
    for (int i = 0; i < 11; i++) kk[i] = (i >= 3 || t0 > 0) ? __ldg(pk + (i - 3) * (DM / 2)) : 0u;
#pragma unroll
    for (int i = 0; i < 8; i++) vv[i] = __ldg(pv + i * (DM / 2));
    const uint4 sh0 = __ldg(reinterpret_cast<const uint4*>(shiftk + cp * 8));
    const uint32_t s0 = __byte_perm(sh0.x, sh0.z, 0x5410), s1 = __byte_perm(sh0.x, sh0.z, 0x7632), s2 = __byte_perm(sh0.y, sh0.w, 0x5410), s3 = __byte_perm(sh0.y, sh0.w, 0x7632);
#pragma unroll
    for (int t = 0; t < 8; t++)
        vv[t] = bmul2(badd(badd(badd(bmul2(kk[t], s3), bmul2(kk[t + 1], s2)), bmul2(kk[t + 2], s1)), bmul2(kk[t + 3], s0)), vv[t]);
    uint4* d = g_U + (size_t)(cp * 2) * (S_LEN / 8) + (t0 >> 6) * 8 + ((((t0 ^ 56) & 63) >> 3) ^ ((t0 >> 6) & 7));
#pragma unroll
    for (int c = 0; c < 2; c++) {
        const uint32_t sel = c ? 0x7632 : 0x5410;
        d[c * (S_LEN / 8)] = make_uint4(__byte_perm(vv[7], vv[6], sel), __byte_perm(vv[5], vv[4], sel), __byte_perm(vv[3], vv[2], sel), __byte_perm(vv[1], vv[0], sel));
    }
}
constexpr int CV_E = 4224, CV_W = 2 * 4096 + 3 * CV_E + 128, CV_HI = O_X, CV_Y = CV_HI + 4 * CV_W, CV_T = CV_Y + 16384, CV_Z = CV_T + 16384;
static_assert(4 * CV_W <= O_RED && CV_W % 128 == 0 && CV_Z + 128 <= HEAD_SMEM, "conv buffers");
__device__ __forceinline__ void conv_unit(uint32_t ub, uint32_t e0, uint32_t e1, uint32_t zrow, uint32_t tt, uint32_t Dv, int rg, int nq, int lane, uint32_t zero, int tb) {
    const int g7 = 7 - (lane >> 2), tq = lane & 3;
    SC(tb >= 0, tb + 3);
    for (int i = lane; i < 32 * nq + 8; i += 32) {
        const uint4 v = lds128(e0 + i * 16);
        const uint32_t nx = lds32(e0 + i * 16 + 16);
        sts128(e1 + i * 16, __byte_perm(v.x, v.y, 0x5432), __byte_perm(v.y, v.z, 0x5432), __byte_perm(v.z, v.w, 0x5432), __byte_perm(v.w, nx, 0x5432));
    }
    __syncwarp();
    SC(tb >= 0, tb + 4);
    float acc[4][4];
#pragma unroll
    for (int i = 0; i < 16; i++) (&acc[0][0])[i] = 0.f;
    uint32_t wb = (g7 & 1) ? e0 + (1 + g7 + 2 * tq) * 2 : e1 + (g7 + 2 * tq) * 2;
    int row = 8 * rg + (lane & 7);
    auto ldb = [&](uint4* b) {
        const uint32_t x = row < 0 ? zrow : ub + row * 128 + (((lane >> 3) ^ (row & 7)) << 4);
        b[0] = ldsm4(x); b[1] = ldsm4(x ^ 64);
        row--;
    };
    uint4 Q[16], b[2][2];
    Q[15].w = lds32(wb);
    auto ldq = [&](int q, int o) { Q[q].y = lds32(wb + o * 32 + 16); Q[q].w = lds32(wb + o * 32 + 32); };
    auto cpq = [&](int q) { Q[q].x = Q[(q + 15) & 15].w + zero; Q[q].z = Q[q].y + zero; };
#pragma unroll
    for (int q = 0; q < 11; q++) ldq(q, q);
#pragma unroll
    for (int q = 0; q < 7; q++) cpq(q);
    ldb(b[0]);
#pragma unroll 1
    for (int D0 = nq; D0 > 0; D0--) {
#pragma unroll
        for (int d = 0; d < 4; d++) {
            ldb(b[(d + 1) & 1]);
#pragma unroll
            for (int q = 11; q < 15; q++) ldq((4 * d + q) & 15, 4 * d + q);
#pragma unroll
            for (int ks = 0; ks < 4; ks++) {
                const uint4& bb_ = b[d & 1][ks >> 1];
#pragma unroll
                for (int m = 0; m < 4; m++) {
                    const uint4& a = Q[(4 * d + m + ks) & 15];
                    mmav(acc[m], a.x, a.y, a.z, a.w, (ks & 1) ? bb_.z : bb_.x, (ks & 1) ? bb_.w : bb_.y);
                }
                cpq((4 * d + 7 + ks) & 15);
            }
        }
        wb += 512;
    }
    SC(tb >= 0 && acc[0][0] != 1.2345f, tb + 5);
    const uint32_t ua = ub + (8 * rg + (lane & 7)) * 128 + (((lane >> 3) ^ (lane & 7)) << 4);
    const uint4 u0 = ldsm4t(ua), u1 = ldsm4t(ua ^ 64);
    auto y = [&](int m, int hf, uint32_t u) { return badd(pack2(acc[m][2 * hf], acc[m][2 * hf + 1]), bmul2(u, Dv)); };
    stsm4t(tt, y(0, 0, u1.w), y(0, 1, u1.z), y(1, 0, u1.y), y(1, 1, u1.x));
    stsm4t(tt ^ 64, y(2, 0, u0.w), y(2, 1, u0.z), y(3, 0, u0.y), y(3, 1, u0.x));
}
}

namespace ws {
struct HeadArgs { const bf16 *x, *mem0, *Wq, *Wk, *Wv, *Wo, *Bk, *Bv, *shiftk, *ssmk, *ssmD; bf16* out; int h_target; };

__global__ void __launch_bounds__(512, 1) head_kernel(const __grid_constant__ HeadArgs A) {
    extern __shared__ __align__(1024) unsigned char smem_raw[];
    const int tid = threadIdx.x, warp = __shfl_sync(0xffffffffu, tid >> 5, 0), lane = tid & 31;
    const int cq = blockIdx.x >> 4, r = blockIdx.x & 15;
    const int nh = cq < 4 ? 5 : 4, hi = r / 3, role = r - hi * 3;
    const bool head = r < 3 * nh;
    const int h = (cq < 4 ? 5 * cq : 4 * cq + 4) + hi;
    const uint32_t sb = smem_u32(smem_raw), bb = sb + O_BAR;
    GT(tid == 0, 1);
    const int sp = cq < 4 ? cq : 4 * cq + r - 24;
    if (tid == 0) {
        if ((sb & 0xFFFFFFu) != 1024) __trap();
        for (int i = 0; i < 12; i++) mbar_init(bb + i * 8, 1);
        mbar_init(bb + B_ST, role == 2 ? 1 : 5);
        mbar_init(bb + B_OB, 1); mbar_init(bb + B_OB + 64, 1);
        mbar_init(bb + B_HF, 1); mbar_init(bb + B_HF + 8, 1);
        mbar_init(bb + B_HE, 6 * nh);
        mbar_init(bb + B_OTF, head ? 4 : 8); mbar_init(bb + B_OTE, 1); mbar_init(bb + B_OTF + 8, head ? 4 : 8); mbar_init(bb + B_OTE + 16, 1);
        asm volatile("fence.mbarrier_init.release.cluster;" ::: "memory");
        mbar_expect_tx(bb + B_RED, nh * 1280);
        mbar_expect_tx(bb + B_SM, 3072); mbar_expect_tx(bb + B_ST, role == 2 ? 5120 : 4096);
        if (role != 2) { mbar_expect_tx(bb + B_OB, 2048); mbar_expect_tx(bb + B_OB + 64, 2048); }
        mbar_expect_tx(bb + B_HF, 8 * HBYTES); mbar_expect_tx(bb + B_HF + 8, 8 * HBYTES);
    }
    asm volatile("griddepcontrol.launch_dependents;");
    __syncwarp();
    cluster_arrive_relaxed();
    if (warp < 8) {
        asm volatile("setmaxnreg.inc.sync.aligned.u32 %0;" ::"n"(REG_G));
        const int wg = warp >> 2, w4 = warp & 3;
        if (head) {
            const bf16* W = (role == 2 ? A.Wv + wg * 64 : (wg ? A.Wk : A.Wq) + role * 64) + h * DH;
            const uint32_t stg = sb + O_STG + wg * 81920;
            const int t7 = tid & 127;
            if (G_DLY) delay(G_DLY);
            GT(tid == 0, 80);
#pragma unroll 1
            for (int i0 = 0; i0 < 40; i0 += WGRP) {
#pragma unroll
                for (int i = i0; i < i0 + WGRP; i++) {
                    const int row = i * 16 + (t7 >> 3), ch = t7 & 7;
                    cp_async16(stg + row * 128 + ((ch ^ (row & 7)) << 4), W + (size_t)row * HD + ch * 8);
                }
                cp_commit();
                cp_wait<WFLY>();
            }
            GT(tid == 0, 81);
        }
        if (head) {
            cluster_wait();
            GT(tid == 0, 82);
            uint32_t wa[40][4];
            cp_wait<0>();
            GT(tid == 0, 83);
            named_bar(8 + wg, 128);
            {
                const uint32_t la = sb + O_STG + wg * 81920 + ((lane & 7) + (lane >> 4) * 8) * 128 + (((w4 * 2 + ((lane >> 3) & 1)) ^ (lane & 7)) << 4);
                { const uint4 v = lds128(sb + O_STG + wg * 81920 + (r >> 1) * 10240 + (tid & 127) * 16); sts128(sb + O_AS + wg * 2048 + (tid & 127) * 16, v.x, v.y, v.z, v.w); }
#pragma unroll
                for (int j = 1; j < 40; j++) {
                    const int kk = (((r >> 1) - j / 5) & 7) * 5 + j % 5;
                    const uint4 v = ldsm4t(la + kk * 2048);
                    wa[j][0] = v.x; wa[j][1] = v.y; wa[j][2] = v.z; wa[j][3] = v.w;
                }
            }
            named_bar(10, 384);
            GT(tid == 0, 2);
            fence_async_smem();
            named_bar(8 + wg, 128);
            cluster_arrive_relaxed();
            float acc[16];
            const uint32_t ep_q = role == 2 ? sb + O_VM + warp * 512 + (lane ^ ((lane >> 3) & 1)) * 16
                                            : sb + O_QRY + wg * 10240 + ((lane >> 1) & 1) * 5120 + (4 * (lane >> 4) + 2 * ((lane >> 2) & 1) + (lane & 1)) * 128 +
                                                  (((2 * w4 + ((lane >> 3) & 1)) ^ (4 * (lane >> 4) + 2 * ((lane >> 2) & 1) + (lane & 1)) ^ ((lane & 2) << 1)) << 4);
            const uint32_t ep_t = role == 2 ? sb + O_VT + warp * 1024 + ((lane >> 3) & 1) * 512 + (lane >> 4) * 128 + (lane & 7) * 16
                                            : sb + O_QRY + wg * 10240 + (8 + 8 * (lane >> 4) + (lane & 7)) * 128 + (((2 * w4 + ((lane >> 3) & 1)) ^ (lane & 7)) << 4);
                        const int pz = role == 2 ? P1C : P1A;
            const uint32_t ab = (1024 + O_AS + wg * 2048) >> 4;
            uint32_t ok = 1;
            const uint32_t tidk = __shfl_sync(0xffffffffu, tid, lane);
            auto token_gemm = [&](auto ll, const bool pause, const uint32_t vo, const uint32_t nbar, const uint32_t npar, const int t) {
                constexpr int l = decltype(ll)::value;
                constexpr uint32_t hb = ((1024 + O_H + l * 40960) >> 4) | (1u << 16);
                const uint32_t pr = opq(r >> 1);
                if (l) TS(15); else TS(14);
                wg_fence();
#pragma unroll
                for (int j = 0; j < 40; j++) {
                    const uint64_t db = mkdesc(hb + ((pr - j / 5) & 7) * 320 + (j % 5) * 64, 0xC0000010u);
                    if (j == 0) wg_n32_sfirst(acc, mkdesc(ab, 0x40000040u), db);
                    else if (j < TG_STEPS) wg_n32(acc, wa[j][0], wa[j][1], wa[j][2], wa[j][3], db);
                    if (l == 0 && (j + 1 == P1A || j + 1 == P1C)) {
                        if (pause && pz == j + 1) {
                            wg_commit();
                            if (role == 2) mwait(bb + B_OTE, vo >> 14);
                            wg_wait<0>();
                            named_arrive(3, 384);
                            named_bar(4, NB4);
                            if (SKEW && wg) delay(SKEW);
                            wg_fence();
                        }
                    }
                }
                wg_commit();
                ok = mtest(nbar, npar);
                wg_wait<0>();
                uint32_t pk[8];
#pragma unroll
                for (int i = 0; i < 8; i++) pk[i] = pack2(acc[2 * i], acc[2 * i + 1]);
                if (role == 2) {
                    stsm4(ep_t + l * 8192 + vo, pk[0], pk[1], pk[2], pk[3]);
                    stsm4(ep_t + l * 8192 + vo + 256, pk[4], pk[5], pk[6], pk[7]);
                } else {
                    stsm4t((ep_t ^ (l << 6)) + l * 5120, pk[0], pk[1], pk[2], pk[3]);
                    stsm4t((ep_t ^ (l << 6)) + l * 5120 + 2048, pk[4], pk[5], pk[6], pk[7]);
                }
                asm volatile("{\n.reg .pred p, q;\nsetp.eq.u32 p, %0, 0;\nsetp.eq.u32 q, %1, 0;\n"
                             "@p mbarrier.arrive.expect_tx.shared::cta.b64 _, [%2], %3;\n@q mbarrier.arrive.shared::cluster.b64 _, [%4];\n}"
                             ::"r"(tidk), "r"(tidk & 127), "r"(bb + B_HF + l * 8), "r"(8 * HBYTES), "r"(mapa(bb + B_HE, l)) : "memory");
            };
            GT(tid == 0, 86);
            mwait(bb + B_HF, 0);
            GT(tid == 0, 87);
            token_gemm(IC<0>{}, false, 0, bb + B_MEM, 1, -1);
            GT(tid == 0, 88);
            named_bar(11, 384);
            cluster_wait();
            named_arrive(13, 384);
#pragma unroll 1
            for (int t = 0; t < NT; t++) {
                GT(tid == 0 && blockIdx.x == 98, 100 + t);
                TS(0);
                const uint32_t mp = (t & 1) ^ 1;
                const bool tg0 = t + 1 < NSEG, tg1 = t + 1 >= LAG;
                constexpr uint32_t mb = ((1024 + O_MEM) >> 4) | (16u << 16);
#pragma unroll
                for (int G = 0; G < 8; G++) {
                    if (__builtin_expect(!ok, 0)) mwait(bb + B_MEM + G * 8, mp);
                    ok = mtest(G < 7 ? bb + B_MEM + (G + 1) * 8 : bb + B_HF, mp);
                    if (G == 0) { TS(1); wg_fence(); }
                    if (G == 7) TS(2);
                    if (G == 1) TS(8); if (G == 2) TS(9); if (G == 3) TS(10); if (G == 4) TS(11); if (G == 5) TS(12); if (G == 6) TS(13);
#pragma unroll
                    for (int u = 0; u < 5; u++) {
                        const int j = G * 5 + u;
                        const uint64_t db = mkdesc(mb + j * 32, 8);
                        if (j == 0) wg_n16t_sfirst(acc, mkdesc(ab, 0x40000040u), db);
                        else wg_n16t(acc, wa[j][0], wa[j][1], wa[j][2], wa[j][3], db);
                    }
                    wg_commit();
                }
                if (role == 2 && t) named_bar(5, 384);
                wg_wait<0>();
                TS(3);
                if (role == 2) sts128(ep_q, pack2(acc[0], acc[1]), pack2(acc[2], acc[3]), pack2(acc[4], acc[5]), pack2(acc[6], acc[7]));
                else stsm4t(ep_q, pack2(acc[0], acc[1]), pack2(acc[2], acc[3]), pack2(acc[4], acc[5]), pack2(acc[6], acc[7]));
                named_arrive(1, 384);
                if (tidk < 8) mbar_expect_tx(bb + B_MEM + tidk * 8, 2560);
                if (t == NT - 1) break;
                if (tg0) {
                    if (__builtin_expect(!ok, 0)) mwait(bb + B_HF, mp);
                    if (role != 2) named_bar(2, 384);
                    token_gemm(IC<0>{}, true, mp * 16384, tg1 ? bb + B_HF + 8 : bb + B_MEM, tg1 ? (t + 1 - LAG) & 1 : mp ^ 1, t);
                } else {
                    if (role == 2) mwait(bb + B_OTE, mp); else named_bar(2, 384);
                    named_arrive(3, 384); named_bar(4, NB4);
                    ok = 0;
                }
                TS(5);
                if (tg1) {
                    if (__builtin_expect(!ok, 0)) mwait(bb + B_HF + 8, (t + 1 - LAG) & 1);
                    token_gemm(IC<1>{}, false, mp * 16384, bb + B_MEM, mp ^ 1, t);
                }
                TS(6);
                named_arrive(13, 384);
            }
        } else {
            cluster_wait(); cluster_arrive_relaxed();
            const int ep = ld_relaxed(&g_epoch) + 1;
            const uint32_t cb = sb + (warp < 4 ? warp * CV_W : CV_HI + (warp - 4) * CV_W), lb = bb + B_MEM + warp * 8;
            auto fetch = [&](int k) {
                const int ps = k / 5, rg = ps ? ps - 1 : 0, ch = (sp * 5 + k - 5 * ps) * 8 + warp;
                if (k == 5 * ps) { flag_wait(FLG(F_U + ps), (ps > 1 ? 20 : (ps ? 32 : 320)) * ep, 50); fence_async_global(); }
                if (lane == 0) {
                    const uint32_t nb = ps ? ps * 1024 : 512;
                    mbar_expect_tx(lb, 2 * nb);
                    asm volatile("cp.async.bulk.shared::cluster.global.mbarrier::complete_tx::bytes [%0], [%1], %2, [%3];" ::"r"(cb + (k & 1) * 4096), "l"(g_U + ch * (S_LEN / 8)), "r"(nb), "r"(lb) : "memory");
                    asm volatile("cp.async.bulk.shared::cluster.global.mbarrier::complete_tx::bytes [%0], [%1], %2, [%3];" ::"r"(cb + 8192 + (k & 1) * CV_E + 128), "l"(A.ssmk + (size_t)ch * S_LEN), "r"(nb), "r"(lb) : "memory");
                }
                __syncwarp();
            };
            sts32(cb + 8192 + lane * 4, 0u); sts32(cb + 8192 + CV_E + lane * 4, 0u);
            if (warp == 0) sts32(sb + CV_Z + lane * 4, 0u);
            uint32_t dv = 0;
            if (lane < 5) {
                prefetch_l2(A.ssmk + (size_t)((sp * 5 + lane) * 8 + warp) * S_LEN, 1024);
                dv = *reinterpret_cast<const unsigned short*>(A.ssmD + (sp * 5 + lane) * 8 + warp) * 0x10001u;
            }
            named_bar(8, 256);
#pragma unroll 1
            for (int k = -1; k < 25; k++) {
                const int ps = k < 0 ? 0 : k / 5, rg = ps ? ps - 1 : 0;
                const uint32_t Dv = __shfl_sync(0xffffffffu, dv, k - 5 * ps);
                const int tb = sp == 0 && tid == 0 && k >= -1 && k < 7 ? 72 + k * 8 : -1;
                SC(tb >= 0, tb);
                if (k >= 0) {
                    mwait(lb, k & 1);
                    SC(tb >= 0, tb + 1);
                    if (k - 5 * ps < 4) { fence_async_smem(); fetch(k + 1); }
                    SC(tb >= 0, tb + 2);
                }
                const uint32_t tt = sb + CV_T + (k & 1) * 8192;
                conv_unit(cb + (k & 1) * 4096, cb + 8192 + (k & 1) * CV_E, cb + 8192 + 2 * CV_E + 64, sb + CV_Z,
                          tt + warp * 1024 + (lane & 7) * 128 + (((lane >> 3) ^ (lane & 7) ^ warp) & 7) * 16, Dv, rg, ps ? 2 * ps : 1, lane, (uint32_t)A.h_target >> 8, tb);
                if (k >= 0) mwait(bb + B_OTE + (k & 1) * 16, ((k >> 1) & 1) ^ 1);
                named_bar(8, 256);
                {
                    const uint32_t la = tt + (lane & 7) * 1024 + warp * 128 + (((lane >> 3) ^ (lane & 7) ^ warp) & 7) * 16;
                    const uint4 v0 = ldsm4t(la), v1 = ldsm4t(la ^ 64);
                    const uint32_t ya = sb + CV_Y + (k & 1) * 8192 + (warp * 64 + (lane >> 3) * 8 + 7 - (lane & 7)) * 16;
                    stsm4(ya, v0.x, v0.y, v0.z, v0.w);
                    stsm4(ya + 512, v1.x, v1.y, v1.z, v1.w);
                }
                SC(tb >= 0, tb + 6);
                fence_async_smem();
                __syncwarp();
                if (k >= 0 && lane == 0) mbar_arrive(bb + B_OTF + (k & 1) * 8);
                if (k < 0 || (k - 5 * ps == 4 && k < 24)) fetch(k + 1);
                if (k < 0 && lane < 5) prefetch_l2(A.ssmk + (size_t)((sp * 5 + lane) * 8 + warp) * S_LEN + 512, 3072);
            }
            cluster_wait();
        }
    } else if (warp < 12) {
        asm volatile("setmaxnreg.dec.sync.aligned.u32 %0;" ::"n"(REG_T));
        const int w = warp & 3, c = w >> 1, hh = w & 1;
        const uint32_t lane0 = __shfl_sync(0xffffffffu, tid & 31, tid & 31);
        if (head) {
            const int tile0 = role * 4 * WTA, ntile = role == 2 ? 4 * WTC : 4 * WTA;
            const uint32_t wo = sb + O_WO;
            uint32_t mi[5][4];
#pragma unroll
            for (int i = 0; i < 5; i++)
#pragma unroll
                for (int q = 0; q < 4; q++) {
                    const unsigned short* mp = reinterpret_cast<const unsigned short*>(A.mem0) + 2 * q * DM + i * 128 + (tid & 127);
                    mi[i][q] = mp[0] | (uint32_t)mp[DM] << 16;
                }
            cluster_wait();
            named_bar(10, 384);
#pragma unroll
            for (int i = 0; i < 5; i++) {
                const int col = i * 128 + (tid & 127), kk = col >> 4, pr = (kk * 13) >> 6;
                const uint32_t ma = sb + O_MEM + ((((r >> 1) - pr) & 7) * 5 + kk - 5 * pr) * 512 + (col & 8) * 32 + (col & 7) * 16;
                sts128(ma, mi[i][0], mi[i][0], mi[i][1], mi[i][1]);
                sts128(ma + 128, mi[i][2], mi[i][2], mi[i][3], mi[i][3]);
            }
            fence_async_smem();
            named_arrive(11, 384);
            for (int i = tid & 127; i < ntile * 256; i += 128) {
                const int ti = i >> 8, p = (i >> 1) & 127, ch = i & 1;
                const int ks = p >> 4, kh = (p >> 3) & 1, e8 = p & 7;
                const int dim = 64 * (ks >> 2) + 16 * (e8 >> 1) + 8 * (e8 & 1) + 2 * (ks & 3) + kh;
                cp_async16(wo + ti * 4096 + p * 32 + ((ch ^ ((p >> 2) & 1)) << 4), A.Wo + (size_t)(h * DH + dim) * DM + (tile0 + ti) * 16 + ch * 8);
            }
            cp_commit();
            if (lane < 8) {
                const int u = 2 * (tile0 + w + 4 * (lane >> 1)) + (lane & 1), ow = u / 5;
                const int sl = u - 5 * ow;
                sts32(sb + O_TAB + w * 32 + lane * 4, mapa(sb + O_RED + (sl >> 1) * 2560 + (sl & 1) * 256 + hi * (sl < 4 ? 512 : 256), ow & 15));
            }
            cluster_arrive_relaxed(); cluster_wait();
            cp_wait<0>();
            named_bar(7, 128);
            const uint32_t wo_a = wo + w * 4096 + ((lane >> 4) * 8 + (lane & 7)) * 32 + ((((lane >> 3) & 1) ^ ((lane >> 2) & 1)) << 4);
            const uint32_t ob_0 = sb + (role == 2 ? O_PB : O_OBA) + (lane >> 4) * 2048 + ((lane >> 3) & 1) * 128 + ((lane & 7) ^ ((lane >> 1) & 4)) * 16;
            const float cs = 0.08838834764831845f * 1.4426950408889634f;
            auto w_frag = [&](auto four, int i) {
                return ldsm4t(wo_a + (i < 16 || decltype(four)::value == 4 ? (i >> 4) * 32768 + (i & 1) * 16384 + ((i >> 1) & 7) * 512 : 32768 + (i & 1) * 2048 + ((i >> 1) & 7) * 512));
            };
            auto w_pre = [&](auto four, auto pd, uint4* wf) {
#pragma unroll
                for (int i = 0; i < decltype(pd)::value; i++) wf[i] = w_frag(four, i);
            };
            auto w_run = [&](auto four, auto pd, auto rem_, uint4* wf, int t, const uint32_t ob_a, auto&& before_last) {
                constexpr int NTL = decltype(four)::value, PD = decltype(pd)::value, NF = 8 * NTL, NP = NTL > 2 ? 2 : 1;
                constexpr bool REMOTE = decltype(rem_)::value;
                const uint32_t ln = opq(lane0), l8 = (ln & 2) * 64 + (ln >> 2) * 16 + (ln & 1) * 8, rb = (bb + B_RED) & 0xFFFFFFu;
                auto slot = [](int i) { return i < 8 ? i : 8 - WR + (i - 8) % WR; };
                uint4 obr[8];
#pragma unroll
                for (int k = 0; k < 4; k++) obr[k] = ldsm4(ob_a + k * 256);
#pragma unroll
                for (int p = 0; p < NP; p++) {
                    const bool split = p == 1 && NTL == 3;
                    const int nk = split ? 4 : 8;
                    float d[4][4];
                    uint4 ta;
#pragma unroll
                    for (int i = 0; i < 16; i++) (&d[0][0])[i] = 0.f;
#pragma unroll
                    for (int ks = 0; ks < 8; ks++) {
                        if (ks >= nk) continue;
                        if (p == 0 && ks == OBK) {
                            if (REMOTE) { mwait(bb + B_OB + 64, t & 1); TS(7); }
#pragma unroll
                            for (int k = 4; k < 8; k++) obr[k] = ldsm4(ob_a + k * 256);
                        }
                        if (ks == nk - 2) ta = lds128(sb + O_TAB + w * 32 + p * 16);
#pragma unroll
                        for (int u = 0; u < 2; u++) {
                            const int i = p * 16 + ks * 2 + u;
                            const uint4& o = obr[split && u ? ks + 4 : ks];
                            const uint4& f = wf[slot(i)];
                            mmav(d[2 * u], f.x, f.y, f.z, f.w, o.x, o.y);
                            mmav(d[2 * u + 1], f.x, f.y, f.z, f.w, o.z, o.w);
                            if (i + WR >= 8 && i + WR < NF) wf[slot(i + WR)] = w_frag(four, i + WR);
                        }
                    }
                    if (p) TS(10); else TS(8);
                    if (p == NP - 1) before_last();
                    if (split) {
#pragma unroll
                        for (int i = 0; i < 4; i++) { d[0][i] += d[2][i]; d[1][i] += d[3][i]; }
                    }
                    st_async_v2(ta.x + l8, pack2(d[0][0], d[0][1]), pack2(d[1][0], d[1][1]), (ta.x & 0xFF000000u) | rb);
                    st_async_v2(ta.y + l8, pack2(d[0][2], d[0][3]), pack2(d[1][2], d[1][3]), (ta.y & 0xFF000000u) | rb);
                    if (!split) {
                        st_async_v2(ta.z + l8, pack2(d[2][0], d[2][1]), pack2(d[3][0], d[3][1]), (ta.z & 0xFF000000u) | rb);
                        st_async_v2(ta.w + l8, pack2(d[2][2], d[2][3]), pack2(d[3][2], d[3][3]), (ta.w & 0xFF000000u) | rb);
                    }
                }
            };
            if (role != 2) {
#pragma unroll 1
                for (int t = 0; t < NT; t++) {
                    const uint32_t lane = opq(lane0);
                    const uint32_t dc = mapa(sb, hi * 3 + 2), dp = mapa(sb, hi * 3 + (role ^ 1));
                    const uint32_t qa = sb + O_QRY + c * 5120 + (lane & 7) * 128;
                    const uint32_t sw = (((lane >> 3) ^ (lane & 7)) << 4) ^ (c << 6);
                    {
                        const uint32_t ka = qa + 10240;
                        const uint32_t kt = sb + O_KEY + c * 5120 + (lane & 15) * 128, kx = (((lane >> 4) ^ (lane & 7)) << 4) ^ (c << 6);
                        const uint32_t sd = dc + O_SM + role * 1536 + c * 768 + lane * 4, sbar = dc + O_BAR + B_SM;
                        const uint32_t ta = sb + O_QRY + c * 5120 + (8 + 16 * hh + ((lane & 15) ^ (role * 8))) * 128;
                        uint4 a[4], f[4];
                        named_bar(13, 384);
#pragma unroll
                        for (int i = 0; i < 4; i++) f[i] = ldsm4(kt + 1024 + hh * 2048 + (kx ^ (i << 5) ^ (hh << 6)));
#pragma unroll
                        for (int i = 0; i < 4; i++) a[i] = ldsm4(ta + (kx ^ (i << 5)));
                        const uint32_t kd = ka + (1 + 2 * hh) * 1024 + sw;
                        uint4 k[5];
                        k[1] = ldsm4(kd); k[2] = ldsm4(kd + 1024);
                        {
                            const uint32_t qh = qa + (sw ^ (hh << 6)), kh = kt + (kx ^ (hh << 6));
                            named_bar(1, 384);
                            const uint4 q0 = ldsm4(qh), g0 = ldsm4(kh), g1 = ldsm4(kh ^ 32), q1 = ldsm4(qh ^ 64);
                            float s0[4] = {0.f, 0.f, 0.f, 0.f}, s1[4] = {0.f, 0.f, 0.f, 0.f}, s2[4] = {0.f, 0.f, 0.f, 0.f}, s3[4] = {0.f, 0.f, 0.f, 0.f};
                            mmav(s0, f[0].x, f[0].y, f[0].z, f[0].w, q0.x, q0.y); mmav(s1, f[1].x, f[1].y, f[1].z, f[1].w, q0.z, q0.w);
                            mmav(s2, g0.x, g0.y, g0.z, g0.w, q0.x, q0.y); mmav(s3, g1.x, g1.y, g1.z, g1.w, q0.z, q0.w);
                            mmav(s0, f[2].x, f[2].y, f[2].z, f[2].w, q1.x, q1.y); mmav(s1, f[3].x, f[3].y, f[3].z, f[3].w, q1.z, q1.w);
                            k[0] = ldsm4(ka + sw); k[3] = ldsm4(ka + 1024 + sw); k[4] = ldsm4(ka + 2048 + sw);
                            st_async_b32(sd + hh * 128, pack2(s2[0] + s3[0], s2[1] + s3[1]), sbar);
                            st_async_b32(sd + 256 + hh * 256, pack2(s0[0] + s1[0], s0[1] + s1[1]), sbar);
                            st_async_b32(sd + 384 + hh * 256, pack2(s0[2] + s1[2], s0[3] + s1[3]), sbar);
                        }
                        TS(1);
                        float u[5][4];
#pragma unroll
                        for (int i = 0; i < 20; i++) (&u[0][0])[i] = 0.f;
                        auto half = [&](auto nn, const uint4& a0, const uint4& a1, bool more) {
                            constexpr int NU = decltype(nn)::value;
                            constexpr int ord[5] = {1, 2, 0, 3, 4};
#pragma unroll
                            for (int i = 0; i < NU; i++) mmav(u[ord[i]], a0.x, a0.y, a0.z, a0.w, k[ord[i]].x, k[ord[i]].y);
#pragma unroll
                            for (int i = 0; i < NU; i++) {
                                const int n = ord[i];
                                mmav(u[n], a1.x, a1.y, a1.z, a1.w, k[n].z, k[n].w);
                                if (more) k[n] = ldsm4(((n == 0 ? ka + sw : (n < 3 ? kd + (n - 1) * 1024 : ka + (n - 2) * 1024 + sw))) ^ 64);
                            }
                        };
                        auto fu = [](float x) { return __float_as_uint(x); };
                        const uint32_t so = O_ST + c * 2048 + hh * 768, td = dp + so, tb = dp + O_BAR + B_ST, lo = sb + so + 4096;
                        if (hh) {
                            half(IC<5>{}, a[0], a[1], true); half(IC<5>{}, a[2], a[3], false);
                            st_async_v4(td + lane * 16, fu(u[0][2]), fu(u[0][3]), fu(u[1][2]), fu(u[1][3]), tb);
                            st_async_v4(td + 512 + lane * 16, fu(u[2][2]), fu(u[2][3]), fu(u[3][2]), fu(u[3][3]), tb);
                            st_async_v2(td + 1024 + lane * 8, fu(u[4][2]), fu(u[4][3]), tb);
                            sts128(lo + lane * 16, fu(u[0][0]), fu(u[0][1]), fu(u[1][0]), fu(u[1][1]));
                            sts128(lo + 512 + lane * 16, fu(u[2][0]), fu(u[2][1]), fu(u[3][0]), fu(u[3][1]));
                            sts64(lo + 1024 + lane * 8, fu(u[4][0]), fu(u[4][1]));
                        } else {
                            half(IC<3>{}, a[0], a[1], true); half(IC<3>{}, a[2], a[3], false);
                            st_async_v4(td + lane * 16, fu(u[0][2]), fu(u[0][3]), fu(u[1][2]), fu(u[1][3]), tb);
                            st_async_v2(td + 512 + lane * 8, fu(u[2][2]), fu(u[2][3]), tb);
                            sts128(lo + lane * 16, fu(u[0][0]), fu(u[0][1]), fu(u[1][0]), fu(u[1][1]));
                            sts64(lo + 512 + lane * 8, fu(u[2][0]), fu(u[2][1]));
                        }
                        if (t < NT - 1) named_arrive(2, 384);
                        __syncwarp();
                        if (lane == 0) mbar_arrive(bb + B_ST);
                        TS(2);
                    }
                    if (t == NT - 1) break;
                    uint4 wf[PDA];
                    w_pre(IC<WTA>{}, IC<PDA>{}, wf);
                    mwait(bb + B_OB, t & 1);
                    TS(3);
                    named_bar(3, 384);
                    w_run(IC<WTA>{}, IC<PDA>{}, IC<1>{}, wf, t, ob_0, []() {});
                    named_arrive(4, NB4);
                    if (w == 0 && lane == 0) { mbar_expect_tx(bb + B_OB, 2048); mbar_expect_tx(bb + B_OB + 64, 2048); }
                    TS(5);
                }
            } else {
#pragma unroll 1
                for (int t = 0; t < NT; t++) {
                    const uint32_t lane = opq(lane0);
                    const int g = lane >> 2, tq = lane & 3;
                    const uint32_t vm_a = sb + O_VM + (g * 4 + 2 * (tq & 1) + (c ^ ((g >> 1) & 1))) * 16 + (tq >> 1) * 8;
                    const uint32_t vt_a = sb + O_VT + (t & 1) * 16384 + ((lane >> 3) & 1) * 512 + (lane >> 4) * 128 + (lane & 7) * 16;
                    named_bar(13, 384);
                    uint4 va[4][2];
#pragma unroll
                    for (int i = 0; i < 4; i++) {
                        va[i][0] = ldsm4(vt_a + c * 8192 + (4 * hh + i) * 1024);
                        va[i][1] = ldsm4(vt_a + c * 8192 + (4 * hh + i) * 1024 + 256);
                    }
                    const uint32_t sa = opq(sb + O_SM + c * 768 + 256 + lane * 16), sa2 = opq(sb + O_SM + c * 768 + (lane & 15) * 16 + (lane >> 4) * 1536), vm_b = opq(vm_a + hh * 2048);
                    named_bar(1, 384);
                    if (__builtin_expect(t < NT - 1, 1)) {
                        uint2 vm[4];
#pragma unroll
                        for (int i = 0; i < 4; i++) vm[i] = lds64(vm_b + i * 512);
                        mwait(bb + B_SM, t & 1);
                        TS(1);
                        const uint4 x0 = ldsm4t(sa), y0 = ldsm4t(sa + 1536), x1 = ldsm4t(sa2);
                        float s[10];
                        s[2] = blo(x0.x) + blo(y0.x); s[3] = bhi(x0.x) + bhi(y0.x); s[4] = blo(x0.y) + blo(y0.y); s[5] = bhi(x0.y) + bhi(y0.y);
                        s[6] = blo(x0.z) + blo(y0.z); s[7] = bhi(x0.z) + bhi(y0.z); s[8] = blo(x0.w) + blo(y0.w); s[9] = bhi(x0.w) + bhi(y0.w);
                        s[0] = (blo(x1.x) + blo(x1.y)) + (blo(x1.z) + blo(x1.w)); s[1] = (bhi(x1.x) + bhi(x1.y)) + (bhi(x1.z) + bhi(x1.w));
                        float mx = fmaxf(fmaxf(fmaxf(s[0], s[1]), fmaxf(s[2], s[3])), fmaxf(fmaxf(fmaxf(s[4], s[5]), fmaxf(s[6], s[7])), fmaxf(s[8], s[9])));
                        const float m1 = __shfl_xor_sync(0xffffffffu, mx, 1), m2 = __shfl_xor_sync(0xffffffffu, mx, 2), m3 = __shfl_xor_sync(0xffffffffu, mx, 3);
                        mx = fmaxf(fmaxf(mx, m1), fmaxf(m2, m3)) * -cs;
                        uint32_t pb[5];
#pragma unroll
                        for (int i = 0; i < 5; i++) pb[i] = pack2(ex2f(fmaf(s[2 * i], cs, mx)), ex2f(fmaf(s[2 * i + 1], cs, mx)));
                        TS(9);
                        named_bar(3, 384);
                        float o[5][4];
#pragma unroll
                        for (int i = 0; i < 20; i++) (&o[0][0])[i] = 0.f;
                        const uint32_t one2 = 0x3F803F80u;
                        float z[2][4] = {{0.f, 0.f, 0.f, 0.f}, {0.f, 0.f, 0.f, 0.f}};
                        mmav8(o[4], one2, one2, pb[0]);
                        mmav(z[0], one2, one2, one2, one2, pb[1], pb[2]);
                        mmav(z[1], one2, one2, one2, one2, pb[3], pb[4]);
#pragma unroll
                        for (int i = 0; i < 4; i++) mmav8(o[i], vm[i].x, vm[i].y, pb[0]);
#pragma unroll
                        for (int i = 0; i < 4; i++) mmav(o[i], va[i][0].x, va[i][0].y, va[i][0].z, va[i][0].w, pb[1], pb[2]);
#pragma unroll
                        for (int i = 0; i < 4; i++) mmav(o[i], va[i][1].x, va[i][1].y, va[i][1].z, va[i][1].w, pb[3], pb[4]);
                        o[4][0] += z[0][0] + z[1][0]; o[4][1] += z[0][1] + z[1][1];
                        uint4 wf[PDC];
                        w_pre(IC<WTC>{}, IC<PDC>{}, wf);
                        const float r0 = rcpf(o[4][0]), r1 = rcpf(o[4][1]);
                        const uint32_t oo = c * 2048 + hh * 1024 + g * 128 + tq * 16 + (g & 1) * 64;
                        uint32_t e0[4], e1[4];
#pragma unroll
                        for (int i = 0; i < 4; i++) { e0[i] = pack2(o[i][0] * r0, o[i][2] * r0); e1[i] = pack2(o[i][1] * r1, o[i][3] * r1); }
                        sts128(sb + O_PB + (~t & 1) * 5120 + oo, e0[0], e0[1], e0[2], e0[3]);
                        sts128(sb + O_PB + (~t & 1) * 5120 + (oo ^ 64), e1[0], e1[1], e1[2], e1[3]);
                        {
                            const uint32_t da = mapa(sb + O_OBA, r - 2) + oo, ba = mapa(bb + B_OB + hh * 64, r - 2);
                            if (O_DLY) { named_bar(7, 128); if (hh) delay(O_DLY); }
                            st_async_v4(da, e0[0], e0[1], e0[2], e0[3], ba);
                            st_async_v4(da + 0x01000000u, e0[0], e0[1], e0[2], e0[3], ba + 0x01000000u);
                            st_async_v4(da ^ 64, e1[0], e1[1], e1[2], e1[3], ba);
                            st_async_v4((da ^ 64) + 0x01000000u, e1[0], e1[1], e1[2], e1[3], ba + 0x01000000u);
                        }
                        TS(3);
                        if (!O_DLY) named_bar(7, 128);
                        w_run(IC<WTC>{}, IC<PDC>{}, IC<0>{}, wf, t, ob_0 + (~t & 1) * 5120, []() {});
                        named_arrive(4, NB4);
                        mwait(bb + B_ST, t & 1);
                        TS(4);
                    } else { mwait(bb + B_SM, t & 1); mwait(bb + B_ST, t & 1); }
                    TS(5);
                    fence_async_smem();
                    if (TPV_LATE && t < NT - 1) named_bar(6, 224);
#pragma unroll 1
                    for (int l = t < NSEG ? 0 : 1; l < (t >= LAG ? 2 : 1); l++) {
                        const uint32_t pb_ = ((1024 + O_PB) >> 4) + (t & 1) * 320 + l * 160, va_ = (((1024 + O_VT) >> 4) + (t & 1) * 1024 + l * 512) | (8u << 16);
                        const uint32_t oa = sb + O_VT + (t & 1) * 16384 + l * 8192 + w * 1024 + g * 64 + ((tq ^ (g >> 1)) & 3) * 16;
                        const uint32_t vl = (vm_a ^ ((l ^ c) << 4)) + w * 512;
                        const uint2 a0 = lds64(vl), a1 = lds64(vl + 2048);
                        float d[2][16];
                        wg_fence();
                        wg_n32_first(d[0], a0.x, a0.y, 0u, 0u, mkdesc(pb_, 8));
                        wg_n32_first(d[1], a1.x, a1.y, 0u, 0u, mkdesc(pb_, 8));
#pragma unroll
                        for (int i = 0; i < 4; i++) wg_n32_kk(d[i & 1], mkdesc(va_ + (i & 1) * 256 + (i >> 1) * 16, 32), mkdesc(pb_ + 32 + (i >> 1) * 64 + (32u << 16), 8));
                        wg_commit();
                        if (l) TS(13); else TS(11);
                        wg_wait<0>();
                        if (l) TS(14); else TS(12);
#pragma unroll
                        for (int mt = 0; mt < 2; mt++) {
                            sts128(oa + mt * 4096, pack2(d[mt][0], d[mt][1]), pack2(d[mt][4], d[mt][5]), pack2(d[mt][8], d[mt][9]), pack2(d[mt][12], d[mt][13]));
                            sts128(oa + mt * 4096 + 512, pack2(d[mt][2], d[mt][3]), pack2(d[mt][6], d[mt][7]), pack2(d[mt][10], d[mt][11]), pack2(d[mt][14], d[mt][15]));
                        }
                        if (O0_EARLY && l == 0) {
                            fence_async_smem();
                            __syncwarp();
                            if (lane == 0) mbar_arrive(bb + B_OTF + 8);
                        }
                    }
                    TS(6);
                    if (w == 0 && lane == 0) { mbar_expect_tx(bb + B_ST, 5120); mbar_expect_tx(bb + B_SM, 3072); }
                    fence_async_smem();
                    __syncwarp();
                    if (lane == 0) mbar_arrive(bb + B_OTF);
                    if (t < NT - 1) named_arrive(5, 384);
                }
            }
        } else {
            cluster_wait(); cluster_arrive_relaxed();
            const int wi = sp * 4 + w, half = wi >> 5, tok = wi & 31, ep = ld_relaxed(&g_epoch) + 1;
            GT(lane == 0, 89);
            if (lane < LN0_AHEAD / 2) prefetch_l2(A.x + (size_t)((half + 2 * lane) * SEG + tok) * DM, 1280);
#pragma unroll 1
            for (int k = -LN0_AHEAD / 2; k < NT; k++) {
                const int s0 = k < 0 ? 2 * k + LN0_AHEAD + half : (half ? k + LN0_AHEAD : NSEG);
                if (s0 < NSEG) { ln0_row(A.x, s0, tok, lane); GT(lane == 0 && k < 0, 30 + s0); }
                if (k == -1 && half) {
#pragma unroll 1
                    for (int u = 320 + tok; u < 640; u += 32) u_half(A.Bk, A.Bv, A.shiftk, u, lane);
                    __syncwarp();
                    if (lane == 0) red_release(FLG(F_U + 1), 1);
                }
                const int n = k - half * LAG;
                if (k == -LN0_AHEAD / 2 + 1 || (n >= 0 && n < NSEG && k >= 0)) {
                    post_row(half, k < 0 ? 0 : n, tok, lane, half ? g_x : A.x, half ? A.out : g_x, k < 0 ? 0 : ep);
                    GT(lane == 0 && (n & 3) == 0 && k >= 0, 460 + half * 16 + (n >> 2)); GT(lane == 0 && n == 63 && half, 40);
                }
            }
            cluster_wait();
        }
    } else {
        asm volatile("setmaxnreg.dec.sync.aligned.u32 %0;" ::"n"(REG_X));
        cluster_wait();
        const int s = warp - 12;
        const uint32_t lane0 = __shfl_sync(0xffffffffu, tid & 31, tid & 31);
        if (s < 3) {
            cluster_arrive_relaxed();
            GT(lane == 0, 84);
            if (blockIdx.x * 3 + s < 320) {
                u_half(A.Bk, A.Bv, A.shiftk, blockIdx.x * 3 + s, lane);
                GT(lane == 0, 85);
                __syncwarp();
                if (lane == 0) red_release(FLG(F_U), 1);
                GT(lane == 0, 4);
            }
            const int ztgt = 3 * 16 * NCL * (ld_relaxed(&g_epoch) + 1);
#pragma unroll
            for (int i = 0; i < XRS; i++) st_relaxed_v4(g_xc + ((i * 16 + r) * 3 + s) * 256 + cq * 32 + lane, 0, 0, 0, 0);
            __syncwarp();
            if (lane == 0) red_release(FLG(F_Z), 1);
            cluster_wait();
            constexpr uint32_t XSLOT = 16 * 3 * 4096;
            uint32_t xo_ = (r * 3 + s) * 4096;
            if (s == 0) {
                const uint32_t G = lane >> 1, d = ((r + 2 * G) & 15) ^ (lane & 1);
                const bool ok = lane < 16 && d < 3 * nh;
                const uint32_t pos = __popc(__ballot_sync(0xffffffffu, ok) & ((1u << lane) - 1u));
                if (ok) { sts32(sb + O_BT + pos * 8, (d << 24) + G * 2560); sts32(sb + O_BT + pos * 8 + 4, mapa(bb + B_MEM + G * 8, d)); }
            }
            while (ld_acquire(FLG(F_Z)) < ztgt) __nanosleep(100);
            named_bar(14, 96);
#pragma unroll 1
            for (int t = 0; t < NT; t++) {
                const uint32_t lane = opq(lane0);
                if (head && role != 2) {
                    auto soft = [&](auto uu, auto vv, int c0, int hh) {
                        constexpr int U = decltype(uu)::value, NV = decltype(vv)::value;
                        const uint32_t dc = mapa(sb, hi * 3 + 2), sa = sb + O_ST + c0 * 2048 + hh * 768;
                        const uint32_t pd = dc + O_PB + (t & 1) * 5120 + c0 * 2560 + (2 * hh + role) * 128 + lane * 4, pbar = dc + O_BAR + B_ST;
                        const int lim = 8 * role + (int)(lane >> 2) - 2 * (int)(lane & 3);
                        auto uf = [](uint32_t x) { return __uint_as_float(x); };
                        mwait(bb + B_ST, t & 1);
                        if (H1_LATE == 2 && r == 1 && U == 2 && t >= LAG - 1 && t < NT - 1) named_arrive(12, 64);
                        uint32_t z[U][NV];
                        auto zz = [](float x, float y) { const uint32_t w = pack2(x, y); return pack2(blo(w) * 0.08838834764831845f, bhi(w) * 0.08838834764831845f); };
#pragma unroll
                        for (int i = 0; i < U; i++) {
                            const uint4 v = lds128(sa + i * 2048 + lane * 16), w = lds128(sa + i * 2048 + 4096 + lane * 16);
                            z[i][0] = zz(uf(v.x) + uf(w.x), uf(v.y) + uf(w.y));
                            z[i][1] = zz(lim < 0 ? -INFINITY : uf(v.z) + uf(w.z), lim < 1 ? -INFINITY : uf(v.w) + uf(w.w));
                            if (NV == 3) {
                                const uint2 x = lds64(sa + i * 2048 + 512 + lane * 8), y = lds64(sa + i * 2048 + 4608 + lane * 8);
                                z[i][2] = zz(lim < 8 ? -INFINITY : uf(x.x) + uf(y.x), lim < 9 ? -INFINITY : uf(x.y) + uf(y.y));
                            } else {
                                const uint4 x = lds128(sa + 512 + lane * 16), y = lds128(sa + 4608 + lane * 16);
                                const uint2 p = lds64(sa + 1024 + lane * 8), q = lds64(sa + 5120 + lane * 8);
                                z[i][2] = zz(lim < 8 ? -INFINITY : uf(x.x) + uf(y.x), lim < 9 ? -INFINITY : uf(x.y) + uf(y.y));
                                z[i][NV - 2] = zz(uf(x.z) + uf(y.z), uf(x.w) + uf(y.w));
                                z[i][NV - 1] = zz(uf(p.x) + uf(q.x), uf(p.y) + uf(q.y));
                            }
                        }
                        const float l2e = 1.4426950408889634f;
                        float e[U][2 * NV], sum[U];
#pragma unroll
                        for (int i = 0; i < U; i++) {
                            uint32_t zm = bmax2(bmax2(z[i][0], z[i][1]), z[i][2]);
                            if (NV == 5) zm = bmax2(zm, bmax2(z[i][NV - 2], z[i][NV - 1]));
                            zm = bmax2(zm, __shfl_xor_sync(0xffffffffu, zm, 1));
                            zm = bmax2(zm, __shfl_xor_sync(0xffffffffu, zm, 2));
                            const float mx = fmaxf(blo(zm), bhi(zm)) * -l2e;
                            sum[i] = 0.f;
#pragma unroll
                            for (int n = 0; n < NV; n++) { e[i][2 * n] = ex2f(fmaf(blo(z[i][n]), l2e, mx)); e[i][2 * n + 1] = ex2f(fmaf(bhi(z[i][n]), l2e, mx)); }
                            sum[i] = ((e[i][0] + e[i][1]) + (e[i][2] + e[i][3])) + (e[i][4] + e[i][5]);
                            if (NV == 5) sum[i] += (e[i][2 * NV - 4] + e[i][2 * NV - 3]) + (e[i][2 * NV - 2] + e[i][2 * NV - 1]);
                            sum[i] += __shfl_xor_sync(0xffffffffu, sum[i], 1);
                            sum[i] += __shfl_xor_sync(0xffffffffu, sum[i], 2);
                            sum[i] = rcpf(sum[i]);
                        }
#pragma unroll
                        for (int i = 0; i < U; i++)
#pragma unroll
                            for (int n = 0; n < 5; n++)
                                st_async_b32(pd + i * 2560 + (n == 0 ? 0 : (NV == 3 ? n : (n < 3 ? n + 2 : n - 2)) * 512), n < NV ? pack2(e[i][2 * n] * sum[i], e[i][2 * n + 1] * sum[i]) : 0u, pbar);
                    };
                    if (s < 2) soft(IC<1>{}, IC<5>{}, s, 1); else soft(IC<2>{}, IC<3>{}, 0, 0);
                    TS(12);
                    named_bar(14, 96);
                    if (s == 0 && lane == 0) mbar_expect_tx(bb + B_ST, 4096);
                    if (H1_LATE == 1 && r == 1 && s == 0 && t >= LAG - 1 && t < NT - 1) named_arrive(12, 64);
                }
                if (t == NT - 1) break;
                uint32_t m0 = 0x80008000u, m1 = 0x80008000u;
                if (t < LAG && cq == 0) {
                    const uint32_t ch = s < 2 ? lane : lane >> 1;
                    const unsigned short* mp = reinterpret_cast<const unsigned short*>(A.mem0) + (((ch >> 3) & 1) * 4 + (s < 2 ? 0 : (lane & 1) * 2)) * DM + (5 * r + 2 * s + (ch >> 4)) * 8 + (ch & 7);
                    m0 = max(mp[0] | (uint32_t)mp[DM] << 16, 1u);
                    if (s < 2) m1 = max(mp[2 * DM] | (uint32_t)mp[3 * DM] << 16, 1u);
                }
                const bool late = t >= LAG;
                auto sum5 = [](uint32_t a, uint32_t b, uint32_t c, uint32_t d, uint32_t e) { return nz(badd(badd(badd(a, b), e), badd(c, d))); };
                auto sum7 = [](uint32_t a, uint32_t b, uint32_t c, uint32_t d, uint32_t e, uint32_t f, uint32_t h_) {
                    return badd(badd(badd(a, b), badd(c, d)), badd(badd(e, f), h_));
                };
                auto min3 = [](uint32_t a, uint32_t b, uint32_t c) { return min(min(a, b), c); };
                auto bcast = [&](auto two, const uint32_t aa, uint32_t x0, uint32_t x1, uint32_t x2, uint32_t x3) {
                    auto send = [&](uint32_t o, uint32_t bar) { if (decltype(two)::value) st_async_v4(aa + o, x0, x1, x2, x3, bar); else st_async_v2(aa + o, x0, x1, bar); };
                    const uint32_t tb0 = clk32();
                    auto pace = [&](int k) { if (BP) while (__any_sync(0xffffffffu, clk32() - tb0 < (uint32_t)(k * BP))) {} };
                    uint4 e[6];
                    e[0] = lds128(sb + O_BT);
                    TS(8);
                    send(e[0].x, e[0].y); send(e[0].z, e[0].w);
                    TS(9);
                    if (BNS) __nanosleep(BNS);
#pragma unroll
                    for (int i = 1; i < 6; i++) e[i] = lds128(sb + O_BT + i * 16);
#pragma unroll
                    for (int i = 1; i < 6; i++) { pace(i); send(e[i].x, e[i].y); send(e[i].z, e[i].w); }
                    if (nh == 5) {
                        const uint4 f0 = lds128(sb + O_BT + 96);
                        const uint2 f1 = lds64(sb + O_BT + 112);
                        pace(6); send(f0.x, f0.y); send(f0.z, f0.w); pace(7); send(f1.x, f1.y);
                    }
                };
                const uint32_t ma = (sb + O_MEM + (5 * (r & 1) + 2 * s) * 256) & 0xFFFFFFu;
                int guard = 0;
                if (s < 2) {
                    const uint32_t ra = sb + O_RED + s * 2560 + lane * 16;
                    uint4* xb = reinterpret_cast<uint4*>(reinterpret_cast<char*>(g_xc) + xo_ + lane * 16);
                    uint4* xo = xb + cq * 32;
                    touch(xo); touch(xb);
                    mwait(bb + B_RED, t & 1);
                    TS(0);
                    uint4 p[5];
#pragma unroll
                    for (int i = 0; i < 5; i++) p[i] = i < 4 || nh == 5 ? lds128(ra + i * 512) : make_uint4(0, 0, 0, 0);
                    const uint32_t u1 = sum5(p[0].y, p[1].y, p[2].y, p[3].y, p[4].y), u3 = sum5(p[0].w, p[1].w, p[2].w, p[3].w, p[4].w);
                    st_relaxed_v4(xo, sum5(p[0].x, p[1].x, p[2].x, p[3].x, p[4].x), late ? u1 : m0, sum5(p[0].z, p[1].z, p[2].z, p[3].z, p[4].z), late ? u3 : m1);
                    TS(1);
                    if (QUIET && head) named_arrive(4, NB4);
                    delay(XD);
                    uint4 x[NCL];
                    while (true) {
                        ld7_relaxed(x, xb);
                        const uint32_t mn = min3(min3(min3(x[0].x, x[0].y, x[0].z), min3(x[0].w, x[1].x, x[1].y), min3(x[1].z, x[1].w, x[2].x)),
                                                 min3(min3(x[2].y, x[2].z, x[2].w), min3(x[3].x, x[3].y, x[3].z), min3(x[3].w, x[4].x, x[4].y)),
                                                 min3(min3(x[4].z, x[4].w, x[5].x), min3(x[5].y, x[5].z, x[5].w), min(min3(x[6].x, x[6].y, x[6].z), x[6].w)));
                        if (NO_X || __all_sync(0xffffffffu, mn != 0)) break;
                        if (++guard > 2000000) __trap();
                    }
                    TS(2);
                    TV(4, guard);
                    bcast(IC<1>{}, ma + lane * 16, sum7(x[0].x, x[1].x, x[2].x, x[3].x, x[4].x, x[5].x, x[6].x), sum7(x[0].y, x[1].y, x[2].y, x[3].y, x[4].y, x[5].y, x[6].y),
                          sum7(x[0].z, x[1].z, x[2].z, x[3].z, x[4].z, x[5].z, x[6].z), sum7(x[0].w, x[1].w, x[2].w, x[3].w, x[4].w, x[5].w, x[6].w));
                } else {
                    const uint32_t ra = sb + O_RED + 5120 + lane * 8;
                    uint2* xb = reinterpret_cast<uint2*>(reinterpret_cast<char*>(g_xc) + xo_ + lane * 8);
                    uint2* xo = xb + cq * 64;
                    touch(xo); touch(xb);
                    mwait(bb + B_RED, t & 1);
                    TS(0);
                    uint2 p[5];
#pragma unroll
                    for (int i = 0; i < 5; i++) p[i] = i < 4 || nh == 5 ? lds64(ra + i * 256) : make_uint2(0, 0);
                    const uint32_t u1 = sum5(p[0].y, p[1].y, p[2].y, p[3].y, p[4].y);
                    st_relaxed_v2(xo, sum5(p[0].x, p[1].x, p[2].x, p[3].x, p[4].x), late ? u1 : m0);
                    if (lane == 0) mbar_expect_tx(bb + B_RED, nh * 1280);
                    TS(1);
                    if (QUIET && head) named_arrive(4, NB4);
                    delay(XD);
                    uint32_t y0, y1;
                    while (true) {
                        uint2 x[NCL];
                        ld7_relaxed(x, xb);
                        const uint32_t mn = min3(min3(min3(x[0].x, x[0].y, x[1].x), min3(x[1].y, x[2].x, x[2].y), min3(x[3].x, x[3].y, x[4].x)), min3(x[4].y, x[5].x, x[5].y), min(x[6].x, x[6].y));
                        y0 = sum7(x[0].x, x[1].x, x[2].x, x[3].x, x[4].x, x[5].x, x[6].x); y1 = sum7(x[0].y, x[1].y, x[2].y, x[3].y, x[4].y, x[5].y, x[6].y);
                        if (NO_X || __all_sync(0xffffffffu, mn != 0)) break;
                        if (++guard > 2000000) __trap();
                    }
                    TS(2);
                    TV(4, guard);
                    bcast(IC<0>{}, ma + lane * 8, y0, y1, 0u, 0u);
                }
                TS(3);
                if ((OT_LATE || TPV_LATE) && head && role == 2) named_arrive(6, TPV_LATE ? 224 : 128);
                xo_ += XSLOT; if (xo_ >= XRS * XSLOT) xo_ -= XRS * XSLOT;
                {
                    const uint32_t zo = xo_ + XSLOT >= XRS * XSLOT ? xo_ + XSLOT - XRS * XSLOT : xo_ + XSLOT;
                    char* zp = reinterpret_cast<char*>(g_xc) + zo + cq * 512 + lane * 16;
                    st_relaxed_v4(zp, 0, 0, 0, 0);
                    if (ld_relaxed_v4(zp).x) __trap();
                }
            }
        } else if (r < 2) {
            const uint16_t mask = (uint16_t)((1u << (3 * nh)) - 1u);
            const int htgt = A.h_target * (ld_relaxed(&g_epoch) + 1);
#pragma unroll 1
            for (int n = 0; n < NSEG; n++) {
                if (n == (r == 0 ? 1 : 0)) { cluster_arrive(); cluster_wait(); }
                int guard = 0;
                while (ld_acquire(FLG(F_H + r * 64 + n)) < htgt) { if (++guard > 2000000) __trap(); __nanosleep(40); }
                fence_async_global();
                if (H1_LATE && r == 1) named_bar(12, 64);
                if (n) mwait(bb + B_HE, (n - 1) & 1);
                if (lane < 8)
                    asm volatile("cp.async.bulk.shared::cluster.global.mbarrier::complete_tx::bytes.multicast::cluster [%0], [%1], %2, [%3], %4;" ::"r"(sb + O_H + r * 40960 + lane * 5120),
                                 "l"(g_ht + (r * NSEG + n) * 2560 + lane * 320), "r"(HBYTES), "r"(bb + B_HF + r * 8), "h"(mask) : "memory");
                __syncwarp();
            }
        } else {
            cluster_arrive(); cluster_wait();
            if (head && role == 2) {
#pragma unroll 1
                for (int t = 0; t < NT; t++) {
                    auto put = [&](int l, int n) {
                        asm volatile("cp.async.bulk.global.shared::cta.bulk_group [%0], [%1], %2;" ::"l"(g_ot + ((l * NSEG + n) * 256 + h * 8) * 64), "r"(sb + O_VT + (t & 1) * 16384 + l * 8192), "r"(8192) : "memory");
                        asm volatile("cp.async.bulk.commit_group;" ::: "memory");
                    };
                    auto publish = [&](int l, int n) {
                        asm volatile("cp.async.bulk.wait_group 0;" ::: "memory");
                        fence_async_global();
                        red_release(FLG(F_O + l * 64 + n) + (h >> 3), 1);
                        GT(true, 200 + l * 64 + n);
                    };
                    if (O0_EARLY && t < NSEG) {
                        mwait(bb + B_OTF + 8, t & 1);
                        if (lane == 0) { put(0, t); publish(0, t); }
                        __syncwarp();
                    }
                    mwait(bb + B_OTF, t & 1);
                    if (OT_LATE && !TPV_LATE && t < NT - 1) named_bar(6, 128);
                    const int l = lane & 1, n = t - l * LAG;
                    const bool mine = lane < 2 && n >= 0 && n < NSEG && (l || !O0_EARLY);
                    if (mine) {
                        put(l, n);
                        asm volatile("cp.async.bulk.wait_group.read 0;" ::: "memory");
                    }
                    __syncwarp();
                    if (lane == 0) mbar_arrive(bb + B_OTE);
                    if (mine) publish(l, n);
                    __syncwarp();
                }
            }
            if (!head && lane == 0) {
#pragma unroll 1
                for (int k = 0; k < 25; k++) {
                    const int rg = k / 5, r0 = rg == 1 ? 256 : 0;
                    mwait(bb + B_OTF + (k & 1) * 8, (k >> 1) & 1);
                    asm volatile("cp.async.bulk.global.shared::cta.bulk_group [%0], [%1], %2;" ::"l"(g_Y + (sp * 5 + k - 5 * rg) * S_LEN + (rg ? rg - 1 : 0) * 512 + r0),
                                 "r"(sb + CV_Y + (k & 1) * 8192 + r0 * 16), "r"(rg < 2 ? 4096 : 8192) : "memory");
                    asm volatile("cp.async.bulk.commit_group;" ::: "memory");
                    asm volatile("cp.async.bulk.wait_group 0;" ::: "memory");
                    mbar_arrive(bb + B_OTE + (k & 1) * 16);
                    fence_async_global();
                    red_release(FLG(F_CV + rg), 1);
                    GT(true, 50 + k);
                }
            }
            __syncwarp();
        }
    }
    cluster_arrive(); cluster_wait();
    if (blockIdx.x == 0 && tid == 0) atomicAdd(&g_epoch, 1);
}
}

namespace ws {
constexpr int OP_SS = 17;
constexpr int P_RING = 0, P_AS = 131072, P_STG = P_AS + 2 * OP_SS * 2048, P_BAR = P_STG + 16384, OP_SMEM = P_BAR + 256;
constexpr int PB_FULL = 0, PB_EMPTY = 128, PB_SF = 144, PB_SE = 176;
static_assert(OP_SMEM <= 232448, "smem");

__global__ void __launch_bounds__(384, 1) op_kernel(const bf16* __restrict__ Wo, const bf16* __restrict__ Bk, const bf16* __restrict__ Bv, const bf16* __restrict__ shiftk) {
    extern __shared__ __align__(1024) unsigned char smem_raw[];
    const int tid = threadIdx.x, warp = __shfl_sync(0xffffffffu, tid >> 5, 0), lane = tid & 31;
    const int nb = blockIdx.x % 5, ks = blockIdx.x / 5;
    const uint32_t sb = smem_u32(smem_raw), bb = sb + P_BAR;
    if (tid == 0) {
        if ((sb & 0xFFFFFFu) != 1024) __trap();
        for (int i = 0; i < 16; i++) mbar_init(bb + PB_FULL + i * 8, 1);
        for (int i = 0; i < 2; i++) mbar_init(bb + PB_EMPTY + i * 8, 2);
        for (int i = 0; i < 4; i++) { mbar_init(bb + PB_SF + i * 8, 4); mbar_init(bb + PB_SE + i * 8, 1); }
        asm volatile("fence.mbarrier_init.release.cluster;" ::: "memory");
    }
    GT(tid == 0, 8);
    __syncthreads();
    if (warp < 4) {
        asm volatile("setmaxnreg.dec.sync.aligned.u32 40;");
        if (warp == 0) {
            named_bar(3, 288);
            GT(lane == 0, 3);
            uint32_t it = 0;
            const int otgt = 8 * (ld_relaxed(&g_epoch) + 1);
#pragma unroll 1
            for (int q = 0; q < 2 * NT; q++) {
                const int l = q & 1, n = (q >> 1) - l * LAG;
                if (n < 0 || n >= NSEG) continue;
                int guard = 0;
                while (ld_acquire(FLG(F_O + l * 64 + n) + ks) < otgt) { if (++guard > 4000000) __trap(); __nanosleep(OP_NS); }
                fence_async_global();
                mwait(bb + PB_EMPTY + (it & 1) * 8, ((it >> 1) & 1) ^ 1);
                if (lane < 8) {
                    const uint32_t fb = bb + PB_FULL + ((it & 1) * 8 + lane) * 8;
                    mbar_expect_tx(fb, 8192);
                    asm volatile("cp.async.bulk.shared::cluster.global.mbarrier::complete_tx::bytes [%0], [%1], %2, [%3];" ::"r"(sb + P_RING + (it & 1) * 65536 + lane * 8192),
                                 "l"(g_ot + ((l * NSEG + n) * 256 + (ks * 8 + lane) * 8) * 64), "r"(8192), "r"(fb) : "memory");
                }
                __syncwarp();
                it++;
            }
        } else if (warp == 3) {
#pragma unroll 1
            for (int rg = 1; rg < 4; rg++) {
#pragma unroll 1
                for (int u = rg * 640 + blockIdx.x; u < rg * 640 + 640; u += 20) u_half(Bk, Bv, shiftk, u, lane);
                __syncwarp();
                if (lane == 0) red_release(FLG(F_U + rg + 1), 1);
                GT(lane == 0 && rg, 4 + rg);
            }
        } else if (lane == 0) {
            const int cw = warp - 1;
            uint32_t it = 0;
#pragma unroll 1
            for (int q = 0; q < 2 * NT; q++) {
                const int l = q & 1, n = (q >> 1) - l * LAG;
                if (n < 0 || n >= NSEG) continue;
                mwait(bb + PB_SF + cw * 8, it & 1);
                asm volatile("cp.reduce.async.bulk.global.shared::cta.bulk_group.add.f32 [%0], [%1], %2;" ::"l"(g_pt + ((l * NSEG + n) * 10 + nb * 2 + cw) * 512), "r"(sb + P_STG + cw * 8192), "r"(8192) : "memory");
                asm volatile("cp.async.bulk.commit_group;" ::: "memory");
                asm volatile("cp.async.bulk.wait_group.read 0;" ::: "memory");
                mbar_arrive(bb + PB_SE + cw * 8);
                asm volatile("cp.async.bulk.wait_group 0;" ::: "memory");
                fence_async_global();
                red_release(FLG(F_P + l * 64 + n), 1);
                GT(true, 330 + l * 64 + n);
                it++;
            }
        }
    } else {
        asm volatile("setmaxnreg.inc.sync.aligned.u32 232;");
        const int cw = (warp >> 2) - 1, w4 = warp & 3, t7 = tid & 127;
        uint32_t wa[64 - OP_SS][4];
        if (OP_LATE) flag_wait(FLG(F_H), 32 * (ld_relaxed(&g_epoch) + 1), 200);
        {
            const bf16* W = Wo + (size_t)ks * 1024 * DM + nb * 128 + cw * 64 + (t7 & 7) * 8;
            const uint32_t so = (t7 >> 3) * 128 + (((t7 & 7) ^ ((t7 >> 3) & 7)) << 4);
            const uint32_t stg = sb + P_RING + cw * 65536;
            const uint32_t la = stg + ((lane & 7) + (lane >> 4) * 8) * 128 + (((w4 * 2 + ((lane >> 3) & 1)) ^ (lane & 7)) << 4);
#pragma unroll 4
            for (int i = 0; i < 32; i++) cp_async16(stg + i * 2048 + so, W + (size_t)((OP_SS + i) * 16 + (t7 >> 3)) * DM);
            cp_commit();
#pragma unroll 1
            for (int i = 0; i < OP_SS; i++) cp_async16(sb + P_AS + cw * OP_SS * 2048 + i * 2048 + so, W + (size_t)(i * 16 + (t7 >> 3)) * DM);
            cp_commit();
            cp_wait<1>();
            named_bar(1 + cw, 128);
#pragma unroll
            for (int j = 0; j < 32; j++) { const uint4 v = ldsm4t(la + j * 2048); wa[j][0] = v.x; wa[j][1] = v.y; wa[j][2] = v.z; wa[j][3] = v.w; }
            named_bar(1 + cw, 128);
#pragma unroll 1
            for (int i = 0; i < 32 - OP_SS; i++) cp_async16(stg + i * 2048 + so, W + (size_t)((OP_SS + 32 + i) * 16 + (t7 >> 3)) * DM);
            cp_commit();
            cp_wait<0>();
            named_bar(1 + cw, 128);
#pragma unroll
            for (int j = 0; j < 32 - OP_SS; j++) { const uint4 v = ldsm4t(la + j * 2048); wa[32 + j][0] = v.x; wa[32 + j][1] = v.y; wa[32 + j][2] = v.z; wa[32 + j][3] = v.w; }
            fence_async_smem();
            named_bar(3, 288);
        }
        const uint32_t ab = (1024 + P_AS + cw * OP_SS * 2048) >> 4;
        const uint32_t ea = sb + P_STG + cw * 8192 + (lane & 3) * 2048 + (((2 * w4) ^ (lane & 3)) << 5) + (lane >> 2) * 4;
#pragma unroll 1
        for (uint32_t it = 0; it < 2 * NSEG; it++) {
            float acc[16];
            const uint32_t fb = bb + PB_FULL + (it & 1) * 64, par = (it >> 1) & 1;
            const uint32_t ob = opq(((1024 + P_RING) >> 4) + (it & 1) * 4096);
            uint32_t ok = 0;
#pragma unroll
            for (int j = 0; j < 64; j++) {
                if ((j & 7) == 0) {
                    if (j) wg_commit();
                    if (!ok) mslow(fb + j, par);
                    ok = j < 56 ? mtest(fb + j + 8, par) : mtest(bb + PB_SE + cw * 8, (it & 1) ^ 1);
                    if (j == 0) wg_fence();
                }
                const uint64_t db = mkdesc(ob + j * 64, 0x80000020u);
                if (j == 0) wg_n32t_sfirst(acc, mkdesc(ab, 0x40000040u), db);
                else if (j < OP_SS) wg_n32t_s(acc, mkdesc(ab + j * 128, 0x40000040u), db);
                else wg_n32t(acc, wa[j - OP_SS][0], wa[j - OP_SS][1], wa[j - OP_SS][2], wa[j - OP_SS][3], db);
            }
            wg_commit();
            if (!ok) mslow(bb + PB_SE + cw * 8, (it & 1) ^ 1);
            wg_wait<0>();
            if (t7 == 0) mbar_arrive(bb + PB_EMPTY + (it & 1) * 8);
#pragma unroll
            for (int i = 0; i < 16; i++) sts32((ea ^ ((i & 2) << 4)) + ((i >> 2) * 2 + (i & 1)) * 256, __float_as_uint(acc[i]));
            fence_async_smem();
            __syncwarp();
            if (lane == 0) mbar_arrive(bb + PB_SF + cw * 8);
        }
    }
}
}

namespace ws {
static bool usable() {
    static int ok = -1;
    if (ok < 0) {
        cudaFuncSetAttribute(head_kernel, cudaFuncAttributeMaxDynamicSharedMemorySize, HEAD_SMEM);
        cudaFuncSetAttribute(head_kernel, cudaFuncAttributeNonPortableClusterSizeAllowed, 1);
        cudaFuncSetAttribute(op_kernel, cudaFuncAttributeMaxDynamicSharedMemorySize, OP_SMEM);
        cudaLaunchConfig_t cfg = {};
        cfg.gridDim = dim3(NCL * 16); cfg.blockDim = dim3(512); cfg.dynamicSmemBytes = HEAD_SMEM;
        cudaLaunchAttribute at[1];
        at[0].id = cudaLaunchAttributeClusterDimension;
        at[0].val.clusterDim.x = 16; at[0].val.clusterDim.y = 1; at[0].val.clusterDim.z = 1;
        cfg.attrs = at; cfg.numAttrs = 1;
        int n = 0, nsm = 0;
        cudaDeviceGetAttribute(&nsm, cudaDevAttrMultiProcessorCount, 0);
        ok = cudaOccupancyMaxActiveClusters(&n, head_kernel, &cfg) == cudaSuccess && n >= NCL && nsm >= NCL * 16 + 20;
        (void)cudaGetLastError();
    }
    return ok > 0;
}
static void launch_all(void* const* d_in, void* d_out) {
    HeadArgs A;
    A.x = (const bf16*)d_in[0]; A.mem0 = (const bf16*)d_in[1]; A.Wq = (const bf16*)d_in[2]; A.Wk = (const bf16*)d_in[3]; A.Wv = (const bf16*)d_in[4]; A.Wo = (const bf16*)d_in[5];
    A.Bk = (const bf16*)d_in[8]; A.Bv = (const bf16*)d_in[9]; A.shiftk = (const bf16*)d_in[10]; A.ssmk = (const bf16*)d_in[11]; A.ssmD = (const bf16*)d_in[12];
    A.out = (bf16*)d_out; A.h_target = 32;
    cudaStream_t s = cudaStreamPerThread;
    {
        cudaLaunchConfig_t cfg = {};
        cfg.gridDim = dim3(NCL * 16); cfg.blockDim = dim3(512); cfg.dynamicSmemBytes = HEAD_SMEM; cfg.stream = s;
        cudaLaunchAttribute at[2];
        at[0].id = cudaLaunchAttributeClusterDimension;
        at[0].val.clusterDim.x = 16; at[0].val.clusterDim.y = 1; at[0].val.clusterDim.z = 1;
        at[1].id = cudaLaunchAttributeProgrammaticStreamSerialization;
        at[1].val.programmaticStreamSerializationAllowed = 1;
        cfg.attrs = at; cfg.numAttrs = 1;
        cudaLaunchKernelEx(&cfg, head_kernel, A);
    }
    {
        cudaLaunchConfig_t cfg = {};
        cfg.gridDim = dim3(20); cfg.blockDim = dim3(384); cfg.dynamicSmemBytes = OP_SMEM; cfg.stream = s;
        cudaLaunchAttribute at[1];
        at[0].id = cudaLaunchAttributeProgrammaticStreamSerialization;
        at[0].val.programmaticStreamSerializationAllowed = 1;
        cfg.attrs = at; cfg.numAttrs = 1;
        cudaLaunchKernelEx(&cfg, op_kernel, A.Wo, A.Bk, A.Bv, A.shiftk);
    }
}
}

#undef BNS
#undef BP
#undef FLG
#undef GT
#undef G_DLY
#undef H1_LATE
#undef HBYTES
#undef LAGT
#undef LN0_AHEAD
#undef NO_X
#undef O0_EARLY
#undef OBK
#undef OBRES
#undef OP_LATE
#undef OP_NS
#undef OT_LATE
#undef O_BULK
#undef O_DLY
#undef P1A
#undef P1C
#undef PDA
#undef PDC
#undef POST_NS
#undef PRE_PDL
#undef PRE_PF
#undef QUIET
#undef REG_G
#undef REG_T
#undef REG_X
#undef SC
#undef SD
#undef SKEW
#undef TG_STEPS
#undef TPVW
#undef TPV_LATE
#undef TPV_PAUSE
#undef TS
#undef TV
#undef UNI
#undef WFLY
#undef WGRP
#undef WR
#undef WTA
#undef XD
#undef XDUP
#undef XS
namespace ni {

constexpr int S_LEN = 2048;
constexpr int DM = 640;
constexpr int NH = 32;
constexpr int DH = 128;
constexpr int HD = NH * DH;
constexpr int MEMR = 8;
constexpr int SEG = 32;
constexpr int NSEG = S_LEN / SEG;

__device__ __forceinline__ float bf2f(bf16 v) { return __bfloat162float(v); }
__device__ __forceinline__ bf16 f2bf(float v) { return __float2bfloat16_rn(v); }
__device__ __forceinline__ float rbf(float v) { return __bfloat162float(__float2bfloat16_rn(v)); }
__device__ __forceinline__ uint32_t pack2(float a, float b) {
    __nv_bfloat162 t = __floats2bfloat162_rn(a, b);
    return *reinterpret_cast<uint32_t*>(&t);
}
__device__ __forceinline__ uint32_t smem_u32(const void* p) { return (uint32_t)__cvta_generic_to_shared(p); }
__device__ __forceinline__ void ldsm_x4(uint32_t& r0, uint32_t& r1, uint32_t& r2, uint32_t& r3, uint32_t addr) {
    asm volatile("ldmatrix.sync.aligned.m8n8.x4.shared.b16 {%0,%1,%2,%3}, [%4];"
                 : "=r"(r0), "=r"(r1), "=r"(r2), "=r"(r3) : "r"(addr));
}
__device__ __forceinline__ void ldsm_x2(uint32_t& r0, uint32_t& r1, uint32_t addr) {
    asm volatile("ldmatrix.sync.aligned.m8n8.x2.shared.b16 {%0,%1}, [%2];" : "=r"(r0), "=r"(r1) : "r"(addr));
}
__device__ __forceinline__ void ldsm_x4_t(uint32_t& r0, uint32_t& r1, uint32_t& r2, uint32_t& r3, uint32_t addr) {
    asm volatile("ldmatrix.sync.aligned.m8n8.x4.trans.shared.b16 {%0,%1,%2,%3}, [%4];"
                 : "=r"(r0), "=r"(r1), "=r"(r2), "=r"(r3) : "r"(addr));
}
__device__ __forceinline__ void mma16816(float* c, uint32_t a0, uint32_t a1, uint32_t a2, uint32_t a3,
                                         uint32_t b0, uint32_t b1) {
    asm("mma.sync.aligned.m16n8k16.row.col.f32.bf16.bf16.f32 {%0,%1,%2,%3}, {%4,%5,%6,%7}, {%8,%9}, {%0,%1,%2,%3};"
        : "+f"(c[0]), "+f"(c[1]), "+f"(c[2]), "+f"(c[3])
        : "r"(a0), "r"(a1), "r"(a2), "r"(a3), "r"(b0), "r"(b1));
}
__device__ __forceinline__ void cp_async16(uint32_t dst, const void* src) {
    asm volatile("cp.async.cg.shared.global [%0], [%1], 16;" ::"r"(dst), "l"(src));
}
__device__ __forceinline__ void cp_commit() { asm volatile("cp.async.commit_group;"); }
template <int N> __device__ __forceinline__ void cp_wait() { asm volatile("cp.async.wait_group %0;" ::"n"(N)); }
__device__ __forceinline__ uint4 ld_relaxed_v4(const void* p) {
    uint4 v;
    asm volatile("ld.relaxed.gpu.global.v4.u32 {%0,%1,%2,%3}, [%4];"
                 : "=r"(v.x), "=r"(v.y), "=r"(v.z), "=r"(v.w) : "l"(p) : "memory");
    return v;
}
__device__ __forceinline__ void st_relaxed_v4(void* p, uint32_t a, uint32_t b, uint32_t c, uint32_t d) {
    asm volatile("st.relaxed.gpu.global.v4.u32 [%0], {%1,%2,%3,%4};" ::"l"(p), "r"(a), "r"(b), "r"(c), "r"(d) : "memory");
}
__device__ __forceinline__ int ld_acquire(const int* p) {
    int v;
    asm volatile("ld.acquire.gpu.global.u32 %0, [%1];" : "=r"(v) : "l"(p) : "memory");
    return v;
}
__device__ __forceinline__ void mbar_init(uint32_t bar, int count) {
    asm volatile("mbarrier.init.shared::cta.b64 [%0], %1;" ::"r"(bar), "r"(count));
}
__device__ __forceinline__ void mbar_expect_tx(uint32_t bar, uint32_t bytes) {
    asm volatile("mbarrier.arrive.expect_tx.shared::cta.b64 _, [%0], %1;" ::"r"(bar), "r"(bytes) : "memory");
}
__device__ __forceinline__ void mbar_arrive(uint32_t bar) {
    asm volatile("mbarrier.arrive.shared::cta.b64 _, [%0];" ::"r"(bar) : "memory");
}
constexpr int SPIN_LIMIT = 4000000;
__device__ __forceinline__ void mbar_wait_spin(uint32_t bar, uint32_t parity) {
    uint32_t ok = 0;
    int guard = 0;
    while (!ok && ++guard < SPIN_LIMIT) {
        asm volatile(
            "{\n.reg .pred P1;\n"
            "mbarrier.try_wait.parity.shared::cta.b64 P1, [%1], %2;\n"
            "selp.u32 %0, 1, 0, P1;\n}\n"
            : "=r"(ok) : "r"(bar), "r"(parity) : "memory");
    }
}
__device__ __forceinline__ uint32_t mapa(uint32_t addr, uint32_t rank) {
    uint32_t r;
    asm volatile("mapa.shared::cluster.u32 %0, %1, %2;" : "=r"(r) : "r"(addr), "r"(rank));
    return r;
}
__device__ __forceinline__ void st_async_u32(uint32_t addr, uint32_t v, uint32_t bar) {
    asm volatile("st.async.weak.shared::cluster.mbarrier::complete_tx::bytes.b32 [%0], %1, [%2];" ::"r"(addr), "r"(v), "r"(bar) : "memory");
}
__device__ __forceinline__ void st_async_v2(uint32_t addr, uint32_t a, uint32_t b, uint32_t bar) {
    asm volatile("st.async.weak.shared::cluster.mbarrier::complete_tx::bytes.v2.b32 [%0], {%1,%2}, [%3];" ::"r"(addr), "r"(a), "r"(b), "r"(bar) : "memory");
}
__device__ __forceinline__ void cluster_sync_all() {
    asm volatile("barrier.cluster.arrive.release.aligned;\nbarrier.cluster.wait.acquire.aligned;" ::: "memory");
}
__device__ __forceinline__ void named_bar(int id, int n) { asm volatile("bar.sync %0, %1;" ::"r"(id), "r"(n) : "memory"); }

}

namespace ni {
#define CHAIN_LAG 16
constexpr int CL = 16;
constexpr int OWN = DM / CL;
constexpr int NSRC = CL / 2;
constexpr int NCLU = 64 / CL;
constexpr int CSEG = 4;
constexpr int NCHK = NSEG / CSEG;
constexpr int LAG = CHAIN_LAG;
constexpr int NTICK = NSEG + LAG;

constexpr int F_KV = 0, F_MEM = 32, F_H = 64, F_OP = 96, F_CONV = 128, F_U = 130, F_PROG = 132, F_ZERO = 133, F_CNT = 136;
constexpr int NFLAG = 192;
__device__ int g_flags[NFLAG * 32];
#define FLG(i) (g_flags + (i) * 32)
constexpr int CHAIN_THREADS = 384;
__device__ bf16 g_Y[S_LEN * DM];
__device__ bf16 g_U[DM * S_LEN];
__device__ bf16 g_h[2][S_LEN * DM];
__device__ bf16 g_x[S_LEN * DM];
__device__ bf16 g_kv[2][S_LEN * HD];
#define PRING 4
constexpr int PROWS = PRING * 128, PG = 4;
__device__ bf16 g_part[2 * PROWS * PG * DM];
__device__ uint4 g_kvf[2 * NSEG * NH * 256];
__device__ uint32_t g_xc[2 * 2 * CL * NCLU * 8 * OWN];

#define TVAL(i, v)
#define TSTAMP(i)

#define NRQ 36
#define NRW 8
#define PDQ 4
#define PDW1 0
#define PROBE 2
#define PDW 6
constexpr int NSQ = 60 - NRQ, NSW = 20 - NRW;
__host__ __device__ constexpr bool q_smem(int i) { return ((i + 1) * NSQ) / 60 != (i * NSQ) / 60; }
__host__ __device__ constexpr int q_slot(int i) { return q_smem(i) ? (i * NSQ) / 60 : i - (i * NSQ) / 60; }
__host__ __device__ constexpr int w_tile(int i) { return i < 8 ? ((i & 1) ? 0 : 2) : (i < 16 ? (i & 1) : 1); }
__host__ __device__ constexpr int w_k(int i) { return i < 8 ? i / 2 : (i < 16 ? ((i & 1) ? (i - 8) / 2 : 4 + (i - 8) / 2) : i - 12); }
__host__ __device__ constexpr int w_acc(int i) { return (i >= 16 && (i & 1)) ? 3 : w_tile(i); }
__host__ __device__ constexpr bool w_smem(int i) { return i < PDW || NRW == 0 || ((i - PDW + 1) * NRW) / (20 - PDW) == ((i - PDW) * NRW) / (20 - PDW); }
__host__ __device__ constexpr int w_slot(int i) { return i < PDW ? i : (w_smem(i) ? i - ((i - PDW) * NRW) / (20 - PDW) : ((i - PDW) * NRW) / (20 - PDW)); }
constexpr int O_WQ = 0, O_WW = NSQ * 4096, O_REST = (NSQ + NSW) * 4096;
constexpr int C_TOK = 0, C_MEM = 12288, C_RED = C_MEM + 10240, C_Q = C_RED + 6144, C_K = C_Q + 2048, C_V = C_K + 2048, C_S = C_V + 4096,
              C_BAR = C_S + 3072, C_SIZE = 40960;
constexpr int S_BYTES = 3072 + 4096;
constexpr int B_S = 64, B_R = 72, B_T = 96, B_F = 104;
static_assert(C_BAR + 112 <= C_SIZE, "chain block");
constexpr int O_STB = O_REST - 61440;
static_assert((45 * NSQ) / 60 * 4096 <= O_STB && NSQ <= 32, "staging");
struct ChainSmem { unsigned char b[O_REST + 81920 + 1536]; };
static_assert(sizeof(ChainSmem) <= 232448, "smem");

struct ChainArgs {
    CUtensorMap tk[2], tv[2];
    const bf16 *x, *mem0, *Wq, *Wk, *Wv, *Wo;
    int kv_target;
};
__device__ __forceinline__ uint32_t movmat(uint32_t v) {
    uint32_t r;
    asm volatile("movmatrix.sync.aligned.m8n8.trans.b16 %0, %1;" : "=r"(r) : "r"(v));
    return r;
}
__device__ __forceinline__ void named_arrive(int id, int n) { asm volatile("bar.arrive %0, %1;" ::"r"(id), "r"(n) : "memory"); }
__device__ __forceinline__ void red_release(int* p, int v) { asm volatile("red.release.gpu.global.add.u32 [%0], %1;" ::"l"(p), "r"(v) : "memory"); }

#define CVT(i)
__device__ __forceinline__ uint4 lds128(uint32_t a) {
    uint4 v;
    asm volatile("ld.shared.v4.u32 {%0,%1,%2,%3}, [%4];" : "=r"(v.x), "=r"(v.y), "=r"(v.z), "=r"(v.w) : "r"(a));
    return v;
}
__device__ __forceinline__ uint2 lds64(uint32_t a) {
    uint2 v;
    asm volatile("ld.shared.v2.u32 {%0,%1}, [%2];" : "=r"(v.x), "=r"(v.y) : "r"(a));
    return v;
}
__device__ __forceinline__ uint32_t lds32(uint32_t a) {
    uint32_t v;
    asm volatile("ld.shared.u32 %0, [%1];" : "=r"(v) : "r"(a));
    return v;
}
__device__ __forceinline__ void sts64(uint32_t a, uint32_t x, uint32_t y) { asm volatile("st.shared.v2.u32 [%0], {%1,%2};" ::"r"(a), "r"(x), "r"(y) : "memory"); }
__device__ __forceinline__ void sts128(uint32_t a, uint32_t x, uint32_t y, uint32_t z, uint32_t w) {
    asm volatile("st.shared.v4.u32 [%0], {%1,%2,%3,%4};" ::"r"(a), "r"(x), "r"(y), "r"(z), "r"(w) : "memory");
}
__device__ __forceinline__ void st_async_v4(uint32_t addr, uint32_t a, uint32_t b, uint32_t c, uint32_t d, uint32_t bar) {
    asm volatile("st.async.weak.shared::cluster.mbarrier::complete_tx::bytes.v4.b32 [%0], {%1,%2,%3,%4}, [%5];" ::"r"(addr), "r"(a), "r"(b), "r"(c), "r"(d), "r"(bar) : "memory");
}
__device__ __forceinline__ uint2 ld_relaxed_v2(const void* p) {
    uint2 v;
    asm volatile("ld.relaxed.gpu.global.v2.u32 {%0,%1}, [%2];" : "=r"(v.x), "=r"(v.y) : "l"(p) : "memory");
    return v;
}
__device__ __forceinline__ void st_relaxed_v2(void* p, uint32_t a, uint32_t b) {
    asm volatile("st.relaxed.gpu.global.v2.u32 [%0], {%1,%2};" ::"l"(p), "r"(a), "r"(b) : "memory");
}
__device__ __forceinline__ float blo(uint32_t v) { return __uint_as_float(v << 16); }
__device__ __forceinline__ float bhi(uint32_t v) { return __uint_as_float(v & 0xffff0000u); }
__device__ __forceinline__ uint32_t badd2(uint32_t a, uint32_t b) {
    __nv_bfloat162 r = __hadd2(*reinterpret_cast<__nv_bfloat162*>(&a), *reinterpret_cast<__nv_bfloat162*>(&b));
    return *reinterpret_cast<uint32_t*>(&r);
}
__device__ __forceinline__ void mmau(float* c, const uint4& a, uint32_t b0, uint32_t b1) { mma16816(c, a.x, a.y, a.z, a.w, b0, b1); }

__device__ __forceinline__ void stsm_x4_t(uint32_t a, uint32_t r0, uint32_t r1, uint32_t r2, uint32_t r3) {
    asm volatile("stmatrix.sync.aligned.m8n8.x4.trans.shared.b16 [%0], {%1,%2,%3,%4};" ::"r"(a), "r"(r0), "r"(r1), "r"(r2), "r"(r3) : "memory");
}
__device__ __forceinline__ uint4 ldsm4(uint32_t a) { uint4 v; ldsm_x4(v.x, v.y, v.z, v.w, a); return v; }
__device__ __forceinline__ float ex2f(float x) { float y; asm("ex2.approx.ftz.f32 %0, %1;" : "=f"(y) : "f"(x)); return y; }
__device__ __forceinline__ float rcpf(float x) { float y; asm("rcp.approx.ftz.f32 %0, %1;" : "=f"(y) : "f"(x)); return y; }
#define XD 300
__device__ __forceinline__ void xdelay() {
    uint32_t t0, t1;
    asm volatile("mov.u32 %0, %clock;" : "=r"(t0));
    do { asm volatile("mov.u32 %0, %clock;" : "=r"(t1)); } while (t1 - t0 < XD);
}
template <int V> struct IC { static constexpr int value = V; };
__device__ __forceinline__ uint32_t opq(uint32_t x) { uint32_t y; asm volatile("mov.u32 %0, %1;" : "=r"(y) : "r"(x)); return y; }
#define UNI(x) __shfl_sync(0xffffffffu, (uint32_t)(x), 0)
__device__ __forceinline__ uint32_t mtest(uint32_t bar, uint32_t parity) {
    uint32_t ok;
    asm volatile("{\n.reg .pred P1;\nmbarrier.test_wait.parity.shared::cta.b64 P1, [%1], %2;\nselp.u32 %0, 1, 0, P1;\n}\n" : "=r"(ok) : "r"(bar), "r"(parity) : "memory");
    return ok;
}
__device__ __forceinline__ void mwait(uint32_t bar, uint32_t parity) {
    asm volatile(
        "{\n.reg .pred P1;\n.reg .u32 cnt;\n"
        "mbarrier.try_wait.parity.shared::cta.b64 P1, [%0], %1;\n"
        "@P1 bra DONE;\n"
        "mov.u32 cnt, 0;\n"
        "LAB_WAIT:\n"
        "mbarrier.try_wait.parity.shared::cta.b64 P1, [%0], %1;\n"
        "@P1 bra DONE;\n"
        "add.u32 cnt, cnt, 1;\n"
        "setp.lt.u32 P1, cnt, 4000000;\n"
        "@P1 bra LAB_WAIT;\n"
        "DONE:\n}\n" ::"r"(bar), "r"(parity) : "memory");
}

__global__ void __launch_bounds__(CHAIN_THREADS, 1) chain_kernel(const __grid_constant__ ChainArgs A) {
    extern __shared__ __align__(1024) unsigned char smem_raw[];
    const int tid = threadIdx.x, warp = __shfl_sync(0xffffffffu, tid >> 5, 0), lane = tid & 31;
    const int cq = blockIdx.x / CL, r = blockIdx.x % CL;
    const int h = cq * NSRC + (r >> 1), hf = r & 1;
    const uint32_t sb = smem_u32(smem_raw);
    asm volatile("griddepcontrol.launch_dependents;");
    CVT(0);
    if (warp == 8) {
        if (lane < 8) asm volatile("cp.async.bulk.prefetch.L2.global [%0], %1;" ::"l"(A.x + (size_t)(blockIdx.x * 8 + lane) * 2560), "r"(5120) : "memory");
        asm volatile("cp.async.bulk.prefetch.L2.global [%0], %1;" ::"l"((lane < 16 ? A.Wk : A.Wv) + (size_t)(blockIdx.x * 16 + (lane & 15)) * 2560), "r"(5120) : "memory");
        asm volatile("cp.async.bulk.prefetch.L2.global [%0], %1;" ::"l"((lane < 16 ? A.Wq : A.Wo) + (size_t)(blockIdx.x * 16 + (lane & 15)) * 2560), "r"(5120) : "memory");
    }
    CVT(1);
    if (warp < 8) {
        asm volatile("setmaxnreg.inc.sync.aligned.u32 232;");
        const int j = warp & 3, kh = warp >> 2;
        uint4 wr[NRQ + NRW];
        {
            auto load_round = [&](int gi) {
                const uint32_t buf = sb + ((gi & 1) ? O_STB : O_REST);
#pragma unroll
                for (int it = 0; it < 15; it++) {
                    const int i = tid + it * 256;
                    const int pc = i / 1920, rem = i % 1920, row = rem / 24, ch = rem % 24;
                    const int mat = ch >> 3, pi = ((r >> 1) - (2 * gi + pc)) & 7;
                    const bf16* W = mat == 0 ? A.Wq : (mat == 1 ? A.Wk : A.Wv);
                    cp_async16(buf + pc * 30720 + row * 384 + ((ch ^ (row & 7)) << 4), W + (size_t)(pi * 80 + row) * HD + h * DH + hf * 64 + (ch & 7) * 8);
                }
                cp_commit();
            };
            load_round(0);
            load_round(1);
#pragma unroll
            for (int gi = 0; gi < 4; gi++) {
                cp_wait<1>();
                named_bar(1, 256);
                const uint32_t pb = sb + ((gi & 1) ? O_STB : O_REST) + kh * 30720;
                uint4 tmp[8];
#pragma unroll
                for (int u = 0; u < 5; u++)
#pragma unroll
                    for (int tt = 0; tt < 3; tt++) {
                        const int row = u * 16 + (lane & 7) + (lane >> 4) * 8;
                        const int ch = tt * 8 + j * 2 + ((lane >> 3) & 1);
                        uint4 v;
                        ldsm_x4_t(v.x, v.y, v.z, v.w, pb + row * 384 + ((ch ^ (row & 7)) << 4));
                        const int i = (gi * 5 + u) * 3 + tt;
                        if (q_smem(i)) {
                            if (gi == 3) tmp[q_slot(i) & 7] = v;
                            else sts128(sb + O_WQ + q_slot(i) * 4096 + tid * 16, v.x, v.y, v.z, v.w);
                        } else wr[q_slot(i)] = v;
                    }
                named_bar(1, 256);
                if (gi == 3) {
#pragma unroll
                    for (int i = 45; i < 60; i++)
                        if (q_smem(i)) { const uint4 v = tmp[q_slot(i) & 7]; sts128(sb + O_WQ + q_slot(i) * 4096 + tid * 16, v.x, v.y, v.z, v.w); }
                }
                if (gi < 2) load_round(gi + 2);
                else if (gi == 2) {
                    for (int i = tid; i < 128 * 40; i += 256) {
                        const int row = i / 40, ch = i % 40;
                        cp_async16(sb + O_REST + row * 640 + ((ch ^ (row & 7)) << 4), A.Wo + ((size_t)h * DH + row) * DM + hf * 320 + ch * 8);
                    }
                    cp_commit();
                }
            }
            cp_wait<0>();
            named_bar(1, 256);
#pragma unroll
            for (int i = 0; i < 20; i++) {
                const int tl = w_tile(i), et = (w_k(i) + 4 * (warp & 1)) & 7;
                const int row = et * 16 + (lane & 7) + (lane >> 4) * 8;
                const int ch = (warp >> 1) * 10 + (tl == 2 ? 8 : (warp & 1) * 4 + tl * 2) + ((lane >> 3) & 1);
                uint4 v;
                ldsm_x4_t(v.x, v.y, v.z, v.w, sb + O_REST + row * 640 + ((ch ^ (row & 7)) << 4));
                if (w_smem(i)) sts128(sb + O_WW + w_slot(i) * 4096 + tid * 16, v.x, v.y, v.z, v.w);
                else wr[NRQ + w_slot(i)] = v;
            }
            named_bar(1, 256);
            for (int i = tid; i < 2560; i += 256) {
                const int ks = i >> 6, ln = (i >> 1) & 31, wd = i & 1;
                const int pi = ((r >> 1) - ks / 5) & 7;
                const uint32_t v = *reinterpret_cast<const uint32_t*>(A.mem0 + (ln >> 2) * DM + pi * 80 + (ks % 5) * 16 + wd * 8 + (ln & 3) * 2);
                const int o = ks % 5 == 4 ? ks * 256 + wd * 128 + ln * 4 : i * 4;
                asm volatile("st.shared.u32 [%0], %1;" ::"r"(sb + O_REST + C_MEM + o), "r"(v) : "memory");
                asm volatile("st.shared.u32 [%0], %1;" ::"r"(sb + O_REST + C_SIZE + C_MEM + o), "r"(v) : "memory");
            }
            if (tid < 2) {
                const uint32_t bb = sb + O_REST + tid * C_SIZE + C_BAR;
                for (int i = 0; i < 13; i++) mbar_init(bb + i * 8, 1);
                mbar_init(bb + B_F, 4);
                asm volatile("fence.mbarrier_init.release.cluster;" ::: "memory");
                mbar_expect_tx(bb + B_S, S_BYTES);
                for (int i = 0; i < 3; i++) mbar_expect_tx(bb + B_R + i * 8, 2048);
            }
            asm volatile("fence.proxy.async;" ::: "memory");
        }
        CVT(2);
        cluster_sync_all();
        const uint32_t wq_a = sb + O_WQ + tid * 16;
        const uint32_t cb0 = sb + O_REST;
        const uint32_t qk_a = cb0 + j * 512 + (lane & 7) * 16 + (lane < 16 ? C_Q + (lane >> 3) * 256 + kh * 128 : C_K + kh * 256 + ((lane >> 3) & 1) * 128);
        const uint32_t pd = UNI(mapa(sb, (uint32_t)(r ^ 1)) - sb), sd = UNI(mapa(sb, (uint32_t)r) - sb);
        const uint32_t od = UNI(mapa(sb, (uint32_t)(hf * 8 + warp)) - sb);
        const uint32_t oe = UNI(mapa(sb, (uint32_t)(hf * 8 + (warp & 6))) - sb), oo = UNI(mapa(sb, (uint32_t)(hf * 8 + (warp | 1))) - sb);
        const uint32_t u_mem = UNI(cb0 + C_MEM + kh * 1280), u_bm = UNI(cb0 + C_BAR + kh * 8);
        const uint32_t u_v = UNI(cb0 + C_V + hf * 2048 + j * 512 + kh * 256);
        const uint32_t u_ra = UNI(cb0 + C_RED + (r >> 1) * 256);
        const uint32_t u_ob0 = UNI(cb0 + C_Q + (warp & 1) * 1024), u_ob1 = UNI(cb0 + C_Q + ((warp & 1) ^ 1) * 1024);
        const uint32_t u_role = UNI(warp < 3 ? cb0 + C_S + hf * 1536 + warp * 512 : cb0 + C_V + j * 1024);
        const uint32_t t_tok = cb0 + C_TOK + ((lane & 7) + (lane >> 4) * 8) * 128 +
                               (warp < 3 ? warp * 2048 + ((((lane >> 3) & 1) ^ (lane & 7)) << 4) : 4096 + (j >> 1) * 4096 + ((((j & 1) * 4 + ((lane >> 3) & 1)) ^ (lane & 7)) << 4));
        uint4 qb[PDQ];
#pragma unroll
        for (int s = 0; s < PDQ; s++) qb[s] = lds128(wq_a + s * 4096);
        auto tick = [&](auto cc, const int n) {
            constexpr int c = decltype(cc)::value;
            constexpr uint32_t CO = c * C_SIZE;
            const uint32_t cb = cb0 + CO;
            const uint32_t par = (uint32_t)(n & 1);
            const uint32_t l4 = opq(lane * 4), l8 = l4 * 2, l16 = l4 * 4;
            float acc[3][4];
#pragma unroll
            for (int a = 0; a < 3; a++)
#pragma unroll
                for (int i = 0; i < 4; i++) acc[a][i] = 0.f;
            {
                const uint32_t mb = u_mem + CO + l8;
                uint2 bf[3];
                uint32_t ok = 1;
                auto ldb = [&](int ks) {
                    if (ks == 0) mwait(u_bm + CO, par ^ 1);
                    else if (ks % 5 == 0) { if (!ok) mwait(u_bm + CO + (ks / 5) * 16, par ^ 1); }
                    if (ks % 5 == PROBE && ks < 15) ok = mtest(u_bm + CO + (ks / 5 + 1) * 16, par ^ 1);
                    if (ks % 5 == 4) {
                        bf[ks % 3].x = lds32(u_mem + CO + l4 + (ks / 5) * 2560 + 1024);
                        bf[ks % 3].y = lds32(u_mem + CO + l4 + (ks / 5) * 2560 + 1152);
                    } else bf[ks % 3] = lds64(mb + (ks / 5) * 2560 + (ks % 5) * 256);
                };
                ldb(0);
                TSTAMP(c * 12 + 0);
                ldb(1);
#pragma unroll
                for (int ks = 0; ks < 20; ks++) {
                    if (ks + 2 < 20) ldb(ks + 2);
#pragma unroll
                    for (int tt = 0; tt < 3; tt++) {
                        const int i = ks * 3 + tt;
                        if (q_smem(i)) {
                            const int s = q_slot(i);
                            mmau(acc[tt], qb[s % PDQ], bf[ks % 3].x, bf[ks % 3].y);
                            if (s + PDQ < NSQ) qb[s % PDQ] = lds128(wq_a + (s + PDQ) * 4096);
                        } else mmau(acc[tt], wr[q_slot(i)], bf[ks % 3].x, bf[ks % 3].y);
                    }
                }
            }
            TSTAMP(c * 12 + 1);
            stsm_x4_t(opq(qk_a) + CO, pack2(acc[0][0], acc[0][1]), pack2(acc[0][2], acc[0][3]), pack2(acc[1][0], acc[1][1]), pack2(acc[1][2], acc[1][3]));
            const uint32_t v0 = pack2(acc[2][0], acc[2][1]), v1 = pack2(acc[2][2], acc[2][3]);
            if (n == NSEG - 1) {
                sts64(u_v + CO + l8, v0, v1);
                named_bar(1, 256);
                if (kh == 1 && lane == 0) mbar_arrive(cb + C_BAR + B_F);
#pragma unroll
                for (int s = 0; s < PDQ; s++) qb[s] = lds128(wq_a + s * 4096);
                return;
            }
            named_arrive(1, 384);
            st_async_v2(u_v + CO + l8 + pd, v0, v1, cb + C_BAR + B_S + pd);
            st_async_v2(u_v + CO + l8 + sd, v0, v1, cb + C_BAR + B_S + sd);
            uint4 wb[PDW];
            const uint32_t ww_a = wq_a + (O_WW - O_WQ);
            if (warp < 3) {
                uint4 kb[4];
                const uint32_t t_tk = opq(t_tok);
                mwait(cb + C_BAR + B_T, par);
#pragma unroll
                for (int i = 0; i < 4; i++) kb[i] = ldsm4((t_tk ^ (i << 5)) + CO);
                named_bar(1, 384);
                uint4 qa[4];
#pragma unroll
                for (int i = 0; i < 4; i++) qa[i] = ldsm4(cb + l16 + C_Q + i * 512);
                if (warp == 2) {
#pragma unroll
                    for (int i = 0; i < 4; i++) kb[i] = ldsm4(cb + l16 + C_K + i * 512);
                }
                float s0[4][4], s1[4][4];
#pragma unroll
                for (int i = 0; i < 4; i++) {
#pragma unroll
                    for (int q = 0; q < 4; q++) s0[i][q] = s1[i][q] = 0.f;
                    mmau(s0[i], qa[i], kb[i].x, kb[i].y);
                    mmau(s1[i], qa[i], kb[i].z, kb[i].w);
                }
                const float a0 = ((s0[0][0] + s0[0][2]) + (s0[1][0] + s0[1][2])) + ((s0[2][0] + s0[2][2]) + (s0[3][0] + s0[3][2]));
                const float a1 = ((s0[0][1] + s0[0][3]) + (s0[1][1] + s0[1][3])) + ((s0[2][1] + s0[2][3]) + (s0[3][1] + s0[3][3]));
                const float b0 = ((s1[0][0] + s1[0][2]) + (s1[1][0] + s1[1][2])) + ((s1[2][0] + s1[2][2]) + (s1[3][0] + s1[3][2]));
                const float b1 = ((s1[0][1] + s1[0][3]) + (s1[1][1] + s1[1][3])) + ((s1[2][1] + s1[2][3]) + (s1[3][1] + s1[3][3]));
                const uint32_t so = u_role + CO + l16, bs = cb + C_BAR + B_S;
                const float c0 = warp == 2 ? a0 + b0 : a0, c1 = warp == 2 ? a1 + b1 : a1;
                st_async_v4(so + pd, __float_as_uint(c0), __float_as_uint(c1), __float_as_uint(b0), __float_as_uint(b1), bs + pd);
                st_async_v4(so + sd, __float_as_uint(c0), __float_as_uint(c1), __float_as_uint(b0), __float_as_uint(b1), bs + sd);
                TSTAMP(c * 12 + 2);
#pragma unroll
                for (int s = 0; s < PDW; s++) wb[s] = lds128(ww_a + s * 4096);
            } else if (warp == 3) {
                named_bar(1, 384);
                if (lane < 8) mbar_expect_tx(cb + C_BAR + l8, 1280);
#pragma unroll
                for (int s = 0; s < PDW; s++) wb[s] = lds128(ww_a + s * 4096);
            } else {
                mwait(cb + C_BAR + B_T, par);
                uint4 va[2][2];
                const uint32_t t_tk = opq(t_tok);
#pragma unroll
                for (int e = 0; e < 2; e++)
#pragma unroll
                    for (int k = 0; k < 2; k++)
                        ldsm_x4_t(va[e][k].x, va[e][k].y, va[e][k].z, va[e][k].w, (t_tk ^ (e << 5)) + CO + k * 2048);
#pragma unroll
                for (int s2 = 0; s2 < PDW1; s2++) wb[s2] = lds128(ww_a + s2 * 4096);
                mwait(cb + C_BAR + B_S, par);
                TSTAMP(c * 12 + 3);
                const uint32_t xa = cb + l16 + C_S;
                const uint4 x0 = lds128(xa), y0 = lds128(xa + 1536), x1 = lds128(xa + 512), y1 = lds128(xa + 512 + 1536);
                const uint2 x2 = lds64(xa + 1024), y2 = lds64(xa + 1024 + 1536);
                const uint32_t fv = u_role + CO + l8;
                const float cs = 0.08838834764831845f * 1.4426950408889634f;
                float s[10];
                s[8] = __uint_as_float(x2.x) + __uint_as_float(y2.x); s[9] = __uint_as_float(x2.y) + __uint_as_float(y2.y);
                s[0] = __uint_as_float(x0.x) + __uint_as_float(y0.x); s[1] = __uint_as_float(x0.y) + __uint_as_float(y0.y);
                s[2] = __uint_as_float(x0.z) + __uint_as_float(y0.z); s[3] = __uint_as_float(x0.w) + __uint_as_float(y0.w);
                s[4] = __uint_as_float(x1.x) + __uint_as_float(y1.x); s[5] = __uint_as_float(x1.y) + __uint_as_float(y1.y);
                s[6] = __uint_as_float(x1.z) + __uint_as_float(y1.z); s[7] = __uint_as_float(x1.w) + __uint_as_float(y1.w);
                float mx = fmaxf(fmaxf(fmaxf(s[0], s[1]), fmaxf(s[2], s[3])), fmaxf(fmaxf(fmaxf(s[4], s[5]), fmaxf(s[6], s[7])), fmaxf(s[8], s[9])));
                const float m1 = __shfl_xor_sync(0xffffffffu, mx, 1), m2 = __shfl_xor_sync(0xffffffffu, mx, 2), m3 = __shfl_xor_sync(0xffffffffu, mx, 3);
                const uint2 vm00 = lds64(fv), vm01 = lds64(fv + 256), vm10 = lds64(fv + 512), vm11 = lds64(fv + 768);
                const uint4 vm0 = make_uint4(vm00.x, vm00.y, vm01.x, vm01.y), vm1 = make_uint4(vm10.x, vm10.y, vm11.x, vm11.y);
                mx = fmaxf(fmaxf(mx, m1), fmaxf(m2, m3)) * -cs;
                uint32_t pb[5];
                pb[4] = pack2(ex2f(fmaf(s[8], cs, mx)), ex2f(fmaf(s[9], cs, mx)));
#pragma unroll
                for (int i = 0; i < 4; i++) pb[i] = pack2(ex2f(fmaf(s[2 * i], cs, mx)), ex2f(fmaf(s[2 * i + 1], cs, mx)));
                float o[3][4];
#pragma unroll
                for (int i = 0; i < 4; i++) { o[0][i] = o[1][i] = o[2][i] = 0.f; }
                const uint32_t one2 = 0x3F803F80u;
                mma16816(o[2], one2, one2, one2, one2, pb[4], 0u);
                mmau(o[0], vm0, pb[4], pb[4]);
                mmau(o[1], vm1, pb[4], pb[4]);
                mma16816(o[2], one2, one2, one2, one2, pb[0], pb[1]);
                mmau(o[0], va[0][0], pb[0], pb[1]);
                mmau(o[1], va[1][0], pb[0], pb[1]);
                mma16816(o[2], one2, one2, one2, one2, pb[2], pb[3]);
                mmau(o[0], va[0][1], pb[2], pb[3]);
                mmau(o[1], va[1][1], pb[2], pb[3]);
                const float r0 = rcpf(o[2][0]), r1 = rcpf(o[2][1]);
                stsm_x4_t(cb + l16 + C_Q + j * 512, pack2(o[0][0] * r0, o[0][1] * r1), pack2(o[0][2] * r0, o[0][3] * r1), pack2(o[1][0] * r0, o[1][1] * r1), pack2(o[1][2] * r0, o[1][3] * r1));
                named_arrive(2, 384);
                TSTAMP(c * 12 + 4);
#pragma unroll
                for (int s2 = PDW1; s2 < PDW; s2++) wb[s2] = lds128(ww_a + s2 * 4096);
                if (lane == 0) mbar_arrive(cb + C_BAR + B_F);
                if (warp == 4 && lane == 0) mbar_expect_tx(cb + C_BAR + B_S, S_BYTES);
            }
            named_bar(2, 384);
            TSTAMP(c * 12 + 5);
            {
                uint4 ob[4];
                ob[0] = ldsm4(u_ob0 + CO + l16); ob[1] = ldsm4(u_ob0 + CO + l16 + 512);
                ob[2] = ldsm4(u_ob1 + CO + l16); ob[3] = ldsm4(u_ob1 + CO + l16 + 512);
                float d[4][4];
#pragma unroll
                for (int a = 0; a < 4; a++)
#pragma unroll
                    for (int i = 0; i < 4; i++) d[a][i] = 0.f;
                const uint32_t ra = u_ra + CO + l8, rb = cb + C_BAR + B_R;
#pragma unroll
                for (int i = 0; i < 20; i++) {
                    const int k = w_k(i), ac = w_acc(i);
                    const uint32_t b0 = (k & 1) ? ob[k >> 1].z : ob[k >> 1].x, b1 = (k & 1) ? ob[k >> 1].w : ob[k >> 1].y;
                    if (w_smem(i)) {
                        const int s = w_slot(i);
                        mmau(d[ac], wb[s % PDW], b0, b1);
                        if (s + PDW < NSW) wb[s % PDW] = lds128(ww_a + (s + PDW) * 4096);
                    } else mmau(d[ac], wr[NRQ + w_slot(i)], b0, b1);
                    if (i == 9) {
                        const uint32_t rs = u_ra + CO + l4 + 4096 + (warp & 1) * 128;
                        st_async_u32(rs + oe, pack2(d[2][0], d[2][1]), rb + 16 + oe);
                        st_async_u32(rs + oo, pack2(d[2][2], d[2][3]), rb + 16 + oo);
                    }
                    if (i == 17) st_async_v2(ra + od, pack2(d[0][0], d[0][1]), pack2(d[0][2], d[0][3]), rb + od);
                }
                st_async_v2(ra + 2048 + od, pack2(d[1][0] + d[3][0], d[1][1] + d[3][1]), pack2(d[1][2] + d[3][2], d[1][3] + d[3][3]), rb + 8 + od);
                TSTAMP(c * 12 + 6);
#pragma unroll
                for (int s = 0; s < PDQ; s++) qb[s] = lds128(wq_a + s * 4096);
            }
        };
#pragma unroll 1
        for (int t = 0; t < NTICK; t++) {
            if (t < NSEG) tick(IC<0>{}, t);
            if (t >= LAG) tick(IC<1>{}, t - LAG);
        }
    } else {
        asm volatile("setmaxnreg.dec.sync.aligned.u32 40;");
        const int s = warp - 8;
        cluster_sync_all();
        if (s < 3) {
#pragma unroll 1
            for (int hs = 0; hs < 2 * NTICK; hs++) {
                const int c = hs & 1, t = hs >> 1;
                const int n = t - c * LAG;
                if (n < 0 || n >= NSEG - 1) continue;
                const uint32_t cb = sb + O_REST + c * C_SIZE;
                const uint32_t par = (uint32_t)(n & 1);
                const uint32_t tag = (uint32_t)(n % 13) + 1u;
                uint32_t* xb = g_xc + (size_t)((c * 2 + par) * CL + r) * (NCLU * 320) + s * 128;
                const uint32_t ra = cb + C_RED + s * 2048 + lane * (s < 2 ? 8 : 4);
                mwait(cb + C_BAR + B_R + s * 8, par);
                TSTAMP(c * 12 + 7);
                uint4 p[4];
                if (s < 2) {
#pragma unroll
                    for (int i = 0; i < 4; i++) {
                        const uint2 a = lds64(ra + i * 512), b = lds64(ra + i * 512 + 256);
                        p[i] = make_uint4(a.x, a.y, b.x, b.y);
                    }
                } else {
#pragma unroll
                    for (int i = 0; i < 4; i++) p[i] = make_uint4(lds32(ra + i * 512), lds32(ra + i * 512 + 128), lds32(ra + i * 512 + 256), lds32(ra + i * 512 + 384));
                }
                if (lane == 0) mbar_expect_tx(cb + C_BAR + B_R + s * 8, 2048);
                uint32_t m0, m1;
                if (s < 2) {
                    float f0 = 0.f, f1 = 0.f, f2 = 0.f, f3 = 0.f;
#pragma unroll
                    for (int i = 0; i < 4; i++) {
                        f0 += blo(p[i].x) + blo(p[i].z); f1 += bhi(p[i].x) + bhi(p[i].z);
                        f2 += blo(p[i].y) + blo(p[i].w); f3 += bhi(p[i].y) + bhi(p[i].w);
                    }
                    xb += lane * 4;
                    const uint32_t u0 = (__float_as_uint(f0) & ~0xFu) | tag, u1 = (__float_as_uint(f1) & ~0xFu) | tag;
                    const uint32_t u2 = (__float_as_uint(f2) & ~0xFu) | tag, u3 = (__float_as_uint(f3) & ~0xFu) | tag;
                    st_relaxed_v4(xb + cq * 320, u0, u1, u2, u3);
                    TSTAMP(c * 12 + 8);
                    xdelay();
                    uint4 x[NCLU];
#pragma unroll
                    for (int k = 0; k < NCLU; k++) x[k] = make_uint4(u0, u1, u2, u3);
                    int guard = 0;
                    bool first = true;
                    while (true) {
                        bool ok = true;
#pragma unroll
                        for (int k = 0; k < NCLU; k++) {
                            const bool okk = k == cq || (!first && ((x[k].x ^ tag) | (x[k].y ^ tag) | (x[k].z ^ tag) | (x[k].w ^ tag)) << 28 == 0);
                            if (!okk) { x[k] = ld_relaxed_v4(xb + k * 320); ok = false; }
                        }
                        first = false;
                        if (__all_sync(0xffffffffu, ok) || ++guard > SPIN_LIMIT) break;
                    }
                    TVAL(c * 12 + 11, guard);
                    f0 = f1 = f2 = f3 = 0.f;
#pragma unroll
                    for (int k = 0; k < NCLU; k++) {
                        f0 += __uint_as_float(x[k].x & ~0xFu); f1 += __uint_as_float(x[k].y & ~0xFu);
                        f2 += __uint_as_float(x[k].z & ~0xFu); f3 += __uint_as_float(x[k].w & ~0xFu);
                    }
                    m0 = movmat(pack2(f0, f1)); m1 = movmat(pack2(f2, f3));
                } else {
                    float f0 = 0.f, f1 = 0.f;
#pragma unroll
                    for (int i = 0; i < 4; i++) {
                        f0 += (blo(p[i].x) + blo(p[i].y)) + (blo(p[i].z) + blo(p[i].w));
                        f1 += (bhi(p[i].x) + bhi(p[i].y)) + (bhi(p[i].z) + bhi(p[i].w));
                    }
                    xb += lane * 2;
                    const uint32_t u0 = (__float_as_uint(f0) & ~0xFu) | tag, u1 = (__float_as_uint(f1) & ~0xFu) | tag;
                    st_relaxed_v2(xb + cq * 320, u0, u1);
                    TSTAMP(c * 12 + 8);
                    xdelay();
                    uint2 x[NCLU];
#pragma unroll
                    for (int k = 0; k < NCLU; k++) x[k] = make_uint2(u0, u1);
                    int guard = 0;
                    bool first = true;
                    while (true) {
                        bool ok = true;
#pragma unroll
                        for (int k = 0; k < NCLU; k++) {
                            const bool okk = k == cq || (!first && ((x[k].x ^ tag) | (x[k].y ^ tag)) << 28 == 0);
                            if (!okk) { x[k] = ld_relaxed_v2(xb + k * 320); ok = false; }
                        }
                        first = false;
                        if (__all_sync(0xffffffffu, ok) || ++guard > SPIN_LIMIT) break;
                    }
                    TVAL(c * 12 + 11, guard);
                    f0 = f1 = 0.f;
#pragma unroll
                    for (int k = 0; k < NCLU; k++) { f0 += __uint_as_float(x[k].x & ~0xFu); f1 += __uint_as_float(x[k].y & ~0xFu); }
                    m0 = movmat(pack2(f0, f1)); m1 = 0;
                }
                TSTAMP(c * 12 + 9);
                const uint32_t ma = cb + C_MEM + (s < 2 ? lane * 8 + (hf * 2 + s) * 256 : 1024 + hf * 128 + lane * 4), bm = cb + C_BAR;
                if (s < 2) {
#pragma unroll
                    for (int G = 0; G < 8; G++)
#pragma unroll
                        for (int b = 0; b < 2; b++) {
                            const uint32_t dd = mapa(sb, (uint32_t)(((r + 2 * G) & 15) ^ b)) - sb;
                            st_async_v2(ma + G * 1280 + dd, m0, m1, bm + G * 8 + dd);
                        }
                } else {
#pragma unroll
                    for (int G = 0; G < 8; G++)
#pragma unroll
                        for (int b = 0; b < 2; b++) {
                            const uint32_t dd = mapa(sb, (uint32_t)(((r + 2 * G) & 15) ^ b)) - sb;
                            st_async_u32(ma + G * 1280 + dd, m0, bm + G * 8 + dd);
                        }
                }
                TSTAMP(c * 12 + 10);
            }
        } else {
            auto fetch = [&](int c, int seg) {
                if (lane == 0) {
                    if (seg % CSEG == 0) {
                        int guard = 0;
                        while (ld_acquire(FLG(F_KV + c * NCHK + seg / CSEG)) < A.kv_target && ++guard < SPIN_LIMIT) __nanosleep(64);
                    }
                    asm volatile("fence.proxy.async;" ::: "memory");
                    const uint32_t cb = sb + O_REST + c * C_SIZE;
                    const uint32_t bt = cb + C_BAR + B_T, d = cb + C_TOK;
                    mbar_expect_tx(bt, 12288);
                    const CUtensorMap* mk = &A.tk[c];
                    const CUtensorMap* mv = &A.tv[c];
                    asm volatile("cp.async.bulk.tensor.2d.shared::cluster.global.mbarrier::complete_tx::bytes [%0], [%1, {%3, %4}], [%2];" ::"r"(d),
                                 "l"(mk), "r"(bt), "r"(h * DH + hf * 64), "r"(seg * SEG) : "memory");
#pragma unroll
                    for (int i = 0; i < 2; i++)
                        asm volatile("cp.async.bulk.tensor.2d.shared::cluster.global.mbarrier::complete_tx::bytes [%0], [%1, {%3, %4}], [%2];" ::"r"(d + 4096 + i * 4096),
                                     "l"(mv), "r"(bt), "r"(h * DH + i * 64), "r"(seg * SEG) : "memory");
                }
                __syncwarp();
            };
            fetch(0, 0);
#pragma unroll 1
            for (int hs = 0; hs < 2 * NTICK; hs++) {
                const int c = hs & 1, t = hs >> 1;
                const int n = t - c * LAG;
                if (n < -1 || n >= NSEG) continue;
                if (n >= 0) {
                    const uint32_t cb = sb + O_REST + c * C_SIZE;
                    mwait(cb + C_BAR + B_F, (uint32_t)(n & 1));
                    uint4* fd = g_kvf + (size_t)((c * NSEG + n) * NH + h) * 256 + hf * 64 + lane;
#pragma unroll
                    for (int i = 0; i < 2; i++) {
                        const uint4 k0 = ldsm4(cb + C_K + i * 1024 + lane * 16), k1 = ldsm4(cb + C_K + i * 1024 + 512 + lane * 16);
                        fd[i * 32] = make_uint4(badd2(k0.x, k0.z), badd2(k0.y, k0.w), badd2(k1.x, k1.z), badd2(k1.y, k1.w));
                        const uint32_t va = cb + C_V + hf * 2048 + i * 1024 + lane * 8;
                        const uint2 v0 = lds64(va), v1 = lds64(va + 256), v2 = lds64(va + 512), v3 = lds64(va + 768);
                        fd[128 + i * 32] = make_uint4(badd2(v0.x, v1.x), badd2(v0.y, v1.y), badd2(v2.x, v3.x), badd2(v2.y, v3.y));
                    }
                    if (blockIdx.x == 0 && lane == 0 && (c == 0 || t >= NSEG)) asm volatile("st.relaxed.gpu.global.u32 [%0], %1;" ::"l"(FLG(F_PROG)), "r"(t + 1) : "memory");
                    if ((n % CSEG) == CSEG - 1) {
                        asm volatile("fence.proxy.async;" ::: "memory");
                        __syncwarp();
                        if (lane == 0) { red_release(FLG(F_MEM + c * NCHK + n / CSEG), 1); }
                    }
                }
                if (n + 1 < NSEG - 1) fetch(c, n + 1);
            }
        }
    }
    cluster_sync_all();
}
}

namespace ni {
constexpr int KV_TGT = 32, MEM_TGT = 64, OP_TGT = 16, CONV_TGT = 80, H_TGT = 128;
constexpr int PDIST = (LAG + 3) / 4;
#define QA_PRE 3
#define KV1_W 5
#define KV1_N 16
static_assert(QA_PRE < 4, "inputs of the chunk must be complete");
#define SPLAN 0x102030
#define URGENT 1
#define POST_NS 40

#define ELECT "{\n.reg .pred p;\nelect.sync _|p, 0xffffffff;\n@p "
__device__ __forceinline__ void tma_load_2d(uint32_t dst, const CUtensorMap* map, uint32_t bar, int c0, int c1) {
    asm volatile(ELECT "cp.async.bulk.tensor.2d.shared::cluster.global.mbarrier::complete_tx::bytes [%0], [%1, {%3, %4}], [%2];\n}" ::"r"(dst),
                 "l"(map), "r"(bar), "r"(c0), "r"(c1) : "memory");
}
__device__ __forceinline__ void tma_load_2d_mc(uint32_t dst, const CUtensorMap* map, uint32_t bar, int c0, int c1) {
    asm volatile(ELECT "cp.async.bulk.tensor.2d.shared::cluster.global.mbarrier::complete_tx::bytes.multicast::cluster [%0], [%1, {%3, %4}], [%2], %5;\n}" ::"r"(dst),
                 "l"(map), "r"(bar), "r"(c0), "r"(c1), "h"((unsigned short)3) : "memory");
}
__device__ __forceinline__ void tma_load_3d(uint32_t dst, const CUtensorMap* map, uint32_t bar, int c1, int c2) {
    asm volatile(ELECT "cp.async.bulk.tensor.3d.shared::cluster.global.mbarrier::complete_tx::bytes [%0], [%1, {%5, %3, %4}], [%2];\n}" ::"r"(dst),
                 "l"(map), "r"(bar), "r"(c1), "r"(c2), "r"(0) : "memory");
}
__device__ __forceinline__ void tma_load_3d_mc(uint32_t dst, const CUtensorMap* map, uint32_t bar, int c1, int c2) {
    asm volatile(ELECT "cp.async.bulk.tensor.3d.shared::cluster.global.mbarrier::complete_tx::bytes.multicast::cluster [%0], [%1, {%6, %3, %4}], [%2], %5;\n}" ::"r"(dst),
                 "l"(map), "r"(bar), "r"(c1), "r"(c2), "h"((unsigned short)3), "r"(0) : "memory");
}
__device__ __forceinline__ void bulk_load(uint32_t dst, const void* src, uint32_t bytes, uint32_t bar) {
    asm volatile(ELECT "cp.async.bulk.shared::cluster.global.mbarrier::complete_tx::bytes [%0], [%1], %2, [%3];\n}" ::"r"(dst), "l"(src), "r"(bytes), "r"(bar) : "memory");
}
__device__ __forceinline__ void expect_tx1(uint32_t bar, uint32_t bytes) {
    asm volatile(ELECT "mbarrier.arrive.expect_tx.shared::cta.b64 _, [%0], %1;\n}" ::"r"(bar), "r"(bytes) : "memory");
}
__device__ __forceinline__ void wg_fence() { asm volatile("wgmma.fence.sync.aligned;" ::: "memory"); }
__device__ __forceinline__ void wg_commit() { asm volatile("wgmma.commit_group.sync.aligned;" ::: "memory"); }
template <int N> __device__ __forceinline__ void wg_wait() { asm volatile("wgmma.wait_group.sync.aligned %0;" ::"n"(N) : "memory"); }
__device__ __forceinline__ uint64_t make_desc(uint32_t addr, uint32_t lbo, uint32_t sbo) {
    return (uint64_t)((addr & 0x3FFFF) >> 4) | ((uint64_t)((lbo & 0x3FFFF) >> 4) << 16) |
           ((uint64_t)((sbo & 0x3FFFF) >> 4) << 32) | (1ull << 62);
}
__device__ __forceinline__ void wgmma_m64n256k16(float* d, uint64_t da, uint64_t db) {
    asm volatile("{\n.reg .pred p;\nsetp.ne.b32 p, 1, 0;\n"
                 "wgmma.mma_async.sync.aligned.m64n256k16.f32.bf16.bf16 {%0, %1, %2, %3, %4, %5, %6, %7, %8, %9, %10, %11, %12, %13, %14, %15, %16, %17, %18, %19, %20, %21, %22, %23, %24, %25, %26, %27, %28, %29, %30, %31, %32, %33, %34, %35, %36, %37, %38, %39, %40, %41, %42, %43, %44, %45, %46, %47, %48, %49, %50, %51, %52, %53, %54, %55, %56, %57, %58, %59, %60, %61, %62, %63, %64, %65, %66, %67, %68, %69, %70, %71, %72, %73, %74, %75, %76, %77, %78, %79, %80, %81, %82, %83, %84, %85, %86, %87, %88, %89, %90, %91, %92, %93, %94, %95, %96, %97, %98, %99, %100, %101, %102, %103, %104, %105, %106, %107, %108, %109, %110, %111, %112, %113, %114, %115, %116, %117, %118, %119, %120, %121, %122, %123, %124, %125, %126, %127}, %128, %129, p, 1, 1, 0, 1;\n}\n"
                 : "+f"(d[0]), "+f"(d[1]), "+f"(d[2]), "+f"(d[3]), "+f"(d[4]), "+f"(d[5]), "+f"(d[6]), "+f"(d[7]), "+f"(d[8]), "+f"(d[9]), "+f"(d[10]), "+f"(d[11]), "+f"(d[12]), "+f"(d[13]), "+f"(d[14]), "+f"(d[15]), "+f"(d[16]), "+f"(d[17]), "+f"(d[18]), "+f"(d[19]), "+f"(d[20]), "+f"(d[21]), "+f"(d[22]), "+f"(d[23]), "+f"(d[24]), "+f"(d[25]), "+f"(d[26]), "+f"(d[27]), "+f"(d[28]), "+f"(d[29]), "+f"(d[30]), "+f"(d[31]), "+f"(d[32]), "+f"(d[33]), "+f"(d[34]), "+f"(d[35]), "+f"(d[36]), "+f"(d[37]), "+f"(d[38]), "+f"(d[39]), "+f"(d[40]), "+f"(d[41]), "+f"(d[42]), "+f"(d[43]), "+f"(d[44]), "+f"(d[45]), "+f"(d[46]), "+f"(d[47]), "+f"(d[48]), "+f"(d[49]), "+f"(d[50]), "+f"(d[51]), "+f"(d[52]), "+f"(d[53]), "+f"(d[54]), "+f"(d[55]), "+f"(d[56]), "+f"(d[57]), "+f"(d[58]), "+f"(d[59]), "+f"(d[60]), "+f"(d[61]), "+f"(d[62]), "+f"(d[63]), "+f"(d[64]), "+f"(d[65]), "+f"(d[66]), "+f"(d[67]), "+f"(d[68]), "+f"(d[69]), "+f"(d[70]), "+f"(d[71]), "+f"(d[72]), "+f"(d[73]), "+f"(d[74]), "+f"(d[75]), "+f"(d[76]), "+f"(d[77]), "+f"(d[78]), "+f"(d[79]), "+f"(d[80]), "+f"(d[81]), "+f"(d[82]), "+f"(d[83]), "+f"(d[84]), "+f"(d[85]), "+f"(d[86]), "+f"(d[87]), "+f"(d[88]), "+f"(d[89]), "+f"(d[90]), "+f"(d[91]), "+f"(d[92]), "+f"(d[93]), "+f"(d[94]), "+f"(d[95]), "+f"(d[96]), "+f"(d[97]), "+f"(d[98]), "+f"(d[99]), "+f"(d[100]), "+f"(d[101]), "+f"(d[102]), "+f"(d[103]), "+f"(d[104]), "+f"(d[105]), "+f"(d[106]), "+f"(d[107]), "+f"(d[108]), "+f"(d[109]), "+f"(d[110]), "+f"(d[111]), "+f"(d[112]), "+f"(d[113]), "+f"(d[114]), "+f"(d[115]), "+f"(d[116]), "+f"(d[117]), "+f"(d[118]), "+f"(d[119]), "+f"(d[120]), "+f"(d[121]), "+f"(d[122]), "+f"(d[123]), "+f"(d[124]), "+f"(d[125]), "+f"(d[126]), "+f"(d[127])
                 : "l"(da), "l"(db));
}
__device__ __forceinline__ void wgmma_m64n256k16_first(float* d, uint64_t da, uint64_t db) {
    asm volatile("{\n.reg .pred p;\nsetp.ne.b32 p, 0, 0;\n"
                 "wgmma.mma_async.sync.aligned.m64n256k16.f32.bf16.bf16 {%0, %1, %2, %3, %4, %5, %6, %7, %8, %9, %10, %11, %12, %13, %14, %15, %16, %17, %18, %19, %20, %21, %22, %23, %24, %25, %26, %27, %28, %29, %30, %31, %32, %33, %34, %35, %36, %37, %38, %39, %40, %41, %42, %43, %44, %45, %46, %47, %48, %49, %50, %51, %52, %53, %54, %55, %56, %57, %58, %59, %60, %61, %62, %63, %64, %65, %66, %67, %68, %69, %70, %71, %72, %73, %74, %75, %76, %77, %78, %79, %80, %81, %82, %83, %84, %85, %86, %87, %88, %89, %90, %91, %92, %93, %94, %95, %96, %97, %98, %99, %100, %101, %102, %103, %104, %105, %106, %107, %108, %109, %110, %111, %112, %113, %114, %115, %116, %117, %118, %119, %120, %121, %122, %123, %124, %125, %126, %127}, %128, %129, p, 1, 1, 0, 1;\n}\n"
                 : "=f"(d[0]), "=f"(d[1]), "=f"(d[2]), "=f"(d[3]), "=f"(d[4]), "=f"(d[5]), "=f"(d[6]), "=f"(d[7]), "=f"(d[8]), "=f"(d[9]), "=f"(d[10]), "=f"(d[11]), "=f"(d[12]), "=f"(d[13]), "=f"(d[14]), "=f"(d[15]), "=f"(d[16]), "=f"(d[17]), "=f"(d[18]), "=f"(d[19]), "=f"(d[20]), "=f"(d[21]), "=f"(d[22]), "=f"(d[23]), "=f"(d[24]), "=f"(d[25]), "=f"(d[26]), "=f"(d[27]), "=f"(d[28]), "=f"(d[29]), "=f"(d[30]), "=f"(d[31]), "=f"(d[32]), "=f"(d[33]), "=f"(d[34]), "=f"(d[35]), "=f"(d[36]), "=f"(d[37]), "=f"(d[38]), "=f"(d[39]), "=f"(d[40]), "=f"(d[41]), "=f"(d[42]), "=f"(d[43]), "=f"(d[44]), "=f"(d[45]), "=f"(d[46]), "=f"(d[47]), "=f"(d[48]), "=f"(d[49]), "=f"(d[50]), "=f"(d[51]), "=f"(d[52]), "=f"(d[53]), "=f"(d[54]), "=f"(d[55]), "=f"(d[56]), "=f"(d[57]), "=f"(d[58]), "=f"(d[59]), "=f"(d[60]), "=f"(d[61]), "=f"(d[62]), "=f"(d[63]), "=f"(d[64]), "=f"(d[65]), "=f"(d[66]), "=f"(d[67]), "=f"(d[68]), "=f"(d[69]), "=f"(d[70]), "=f"(d[71]), "=f"(d[72]), "=f"(d[73]), "=f"(d[74]), "=f"(d[75]), "=f"(d[76]), "=f"(d[77]), "=f"(d[78]), "=f"(d[79]), "=f"(d[80]), "=f"(d[81]), "=f"(d[82]), "=f"(d[83]), "=f"(d[84]), "=f"(d[85]), "=f"(d[86]), "=f"(d[87]), "=f"(d[88]), "=f"(d[89]), "=f"(d[90]), "=f"(d[91]), "=f"(d[92]), "=f"(d[93]), "=f"(d[94]), "=f"(d[95]), "=f"(d[96]), "=f"(d[97]), "=f"(d[98]), "=f"(d[99]), "=f"(d[100]), "=f"(d[101]), "=f"(d[102]), "=f"(d[103]), "=f"(d[104]), "=f"(d[105]), "=f"(d[106]), "=f"(d[107]), "=f"(d[108]), "=f"(d[109]), "=f"(d[110]), "=f"(d[111]), "=f"(d[112]), "=f"(d[113]), "=f"(d[114]), "=f"(d[115]), "=f"(d[116]), "=f"(d[117]), "=f"(d[118]), "=f"(d[119]), "=f"(d[120]), "=f"(d[121]), "=f"(d[122]), "=f"(d[123]), "=f"(d[124]), "=f"(d[125]), "=f"(d[126]), "=f"(d[127])
                 : "l"(da), "l"(db));
}
__device__ __forceinline__ void wgmma_rs_m64n128k16(float* d, const uint32_t* a, uint64_t db) {
    asm volatile("{\n.reg .pred p;\nsetp.ne.b32 p, 1, 0;\n"
                 "wgmma.mma_async.sync.aligned.m64n128k16.f32.bf16.bf16 {%0, %1, %2, %3, %4, %5, %6, %7, %8, %9, %10, %11, %12, %13, %14, %15, %16, %17, %18, %19, %20, %21, %22, %23, %24, %25, %26, %27, %28, %29, %30, %31, %32, %33, %34, %35, %36, %37, %38, %39, %40, %41, %42, %43, %44, %45, %46, %47, %48, %49, %50, %51, %52, %53, %54, %55, %56, %57, %58, %59, %60, %61, %62, %63}, {%64, %65, %66, %67}, %68, p, 1, 1, 1;\n}\n"
                 : "+f"(d[0]), "+f"(d[1]), "+f"(d[2]), "+f"(d[3]), "+f"(d[4]), "+f"(d[5]), "+f"(d[6]), "+f"(d[7]), "+f"(d[8]), "+f"(d[9]), "+f"(d[10]), "+f"(d[11]), "+f"(d[12]), "+f"(d[13]), "+f"(d[14]), "+f"(d[15]), "+f"(d[16]), "+f"(d[17]), "+f"(d[18]), "+f"(d[19]), "+f"(d[20]), "+f"(d[21]), "+f"(d[22]), "+f"(d[23]), "+f"(d[24]), "+f"(d[25]), "+f"(d[26]), "+f"(d[27]), "+f"(d[28]), "+f"(d[29]), "+f"(d[30]), "+f"(d[31]), "+f"(d[32]), "+f"(d[33]), "+f"(d[34]), "+f"(d[35]), "+f"(d[36]), "+f"(d[37]), "+f"(d[38]), "+f"(d[39]), "+f"(d[40]), "+f"(d[41]), "+f"(d[42]), "+f"(d[43]), "+f"(d[44]), "+f"(d[45]), "+f"(d[46]), "+f"(d[47]), "+f"(d[48]), "+f"(d[49]), "+f"(d[50]), "+f"(d[51]), "+f"(d[52]), "+f"(d[53]), "+f"(d[54]), "+f"(d[55]), "+f"(d[56]), "+f"(d[57]), "+f"(d[58]), "+f"(d[59]), "+f"(d[60]), "+f"(d[61]), "+f"(d[62]), "+f"(d[63])
                 : "r"(a[0]), "r"(a[1]), "r"(a[2]), "r"(a[3]), "l"(db));
}
__device__ __forceinline__ void wgmma_rs_m64n128k16_first(float* d, const uint32_t* a, uint64_t db) {
    asm volatile("{\n.reg .pred p;\nsetp.ne.b32 p, 0, 0;\n"
                 "wgmma.mma_async.sync.aligned.m64n128k16.f32.bf16.bf16 {%0, %1, %2, %3, %4, %5, %6, %7, %8, %9, %10, %11, %12, %13, %14, %15, %16, %17, %18, %19, %20, %21, %22, %23, %24, %25, %26, %27, %28, %29, %30, %31, %32, %33, %34, %35, %36, %37, %38, %39, %40, %41, %42, %43, %44, %45, %46, %47, %48, %49, %50, %51, %52, %53, %54, %55, %56, %57, %58, %59, %60, %61, %62, %63}, {%64, %65, %66, %67}, %68, p, 1, 1, 1;\n}\n"
                 : "=f"(d[0]), "=f"(d[1]), "=f"(d[2]), "=f"(d[3]), "=f"(d[4]), "=f"(d[5]), "=f"(d[6]), "=f"(d[7]), "=f"(d[8]), "=f"(d[9]), "=f"(d[10]), "=f"(d[11]), "=f"(d[12]), "=f"(d[13]), "=f"(d[14]), "=f"(d[15]), "=f"(d[16]), "=f"(d[17]), "=f"(d[18]), "=f"(d[19]), "=f"(d[20]), "=f"(d[21]), "=f"(d[22]), "=f"(d[23]), "=f"(d[24]), "=f"(d[25]), "=f"(d[26]), "=f"(d[27]), "=f"(d[28]), "=f"(d[29]), "=f"(d[30]), "=f"(d[31]), "=f"(d[32]), "=f"(d[33]), "=f"(d[34]), "=f"(d[35]), "=f"(d[36]), "=f"(d[37]), "=f"(d[38]), "=f"(d[39]), "=f"(d[40]), "=f"(d[41]), "=f"(d[42]), "=f"(d[43]), "=f"(d[44]), "=f"(d[45]), "=f"(d[46]), "=f"(d[47]), "=f"(d[48]), "=f"(d[49]), "=f"(d[50]), "=f"(d[51]), "=f"(d[52]), "=f"(d[53]), "=f"(d[54]), "=f"(d[55]), "=f"(d[56]), "=f"(d[57]), "=f"(d[58]), "=f"(d[59]), "=f"(d[60]), "=f"(d[61]), "=f"(d[62]), "=f"(d[63])
                 : "r"(a[0]), "r"(a[1]), "r"(a[2]), "r"(a[3]), "l"(db));
}

struct BulkMaps { CUtensorMap h, h2, wq, wk, wv, wo, kv, lu; };
struct BulkArgs {
    const bf16 *x, *ssmk, *ssmD, *Bk, *Bv, *shiftk;
    bf16* out;
};
enum { T_KV = 0, T_QA, T_CONV, T_ATT, T_POST, T_LN0 };
constexpr int MAXG = 52, SENT = MAXG - 1;
struct Sched { uint32_t chk[MAXG * 4]; uint32_t info[MAXG]; int sbeg[8]; };

constexpr int BK_STAGES = 4, BK_STAGE_BYTES = 49152, TSLOTS = 4;
struct BulkSmemTail {
    unsigned long long full[BK_STAGES], empty[BK_STAGES], tfull[TSLOTS], tempty[TSLOTS], sfull[4], sempty[4];
    int task[TSLOTS];
    uint32_t tab[MAXG * 5];
};
constexpr int BULK_STG = BK_STAGES * BK_STAGE_BYTES;
constexpr int BULK_TAIL = BULK_STG + 32768;
constexpr int BULK_SMEM = BULK_TAIL + (int)sizeof(BulkSmemTail);
static_assert(BULK_SMEM <= 232448, "bulk smem");
#define PACE 0
#define REG_C 224
#define REG_P 56

#define BT(lead, type, l, c, k)
#define TT(k)
#define FT(k)
#define TTV(k, v)
__device__ __forceinline__ void tma_store_2d(const CUtensorMap* map, uint32_t src, int c0, int c1) {
    asm volatile("cp.async.bulk.tensor.2d.global.shared::cta.bulk_group [%0, {%2, %3}], [%1];" ::"l"(map), "r"(src), "r"(c0), "r"(c1) : "memory");
}
__device__ __forceinline__ void bulk_commit() { asm volatile("cp.async.bulk.commit_group;" ::: "memory"); }
template <int N> __device__ __forceinline__ void bulk_wait_read() { asm volatile("cp.async.bulk.wait_group.read %0;" ::"n"(N) : "memory"); }
template <int N> __device__ __forceinline__ void bulk_wait() { asm volatile("cp.async.bulk.wait_group %0;" ::"n"(N) : "memory"); }
__device__ __forceinline__ void mbar_arrive_cluster(uint32_t bar) {
    asm volatile("mbarrier.arrive.shared::cluster.b64 _, [%0];" ::"r"(bar) : "memory");
}
__device__ __forceinline__ void stsm_x4(uint32_t addr, uint32_t r0, uint32_t r1, uint32_t r2, uint32_t r3) {
    asm volatile("stmatrix.sync.aligned.m8n8.x4.shared.b16 [%0], {%1,%2,%3,%4};" ::"r"(addr), "r"(r0), "r"(r1), "r"(r2), "r"(r3) : "memory");
}
__device__ __forceinline__ void mma1688(float* c, uint32_t a0, uint32_t a1, uint32_t b0) {
    asm("mma.sync.aligned.m16n8k8.row.col.f32.bf16.bf16.f32 {%0,%1,%2,%3}, {%4,%5}, {%6}, {%0,%1,%2,%3};"
        : "+f"(c[0]), "+f"(c[1]), "+f"(c[2]), "+f"(c[3]) : "r"(a0), "r"(a1), "r"(b0));
}
__device__ __forceinline__ int ld_relaxed(const int* p) {
    int v;
    asm volatile("ld.relaxed.gpu.global.u32 %0, [%1];" : "=r"(v) : "l"(p) : "memory");
    return v;
}
__device__ __forceinline__ void flag_wait(const int* f, int tgt, int ns) {
    int guard = 0;
    while (ld_relaxed(f) < tgt && ++guard < 4000000) __nanosleep(ns);
}
__device__ __forceinline__ void fence_async() { asm volatile("fence.proxy.async.global;" ::: "memory"); }
__device__ __forceinline__ uint32_t bmul2(uint32_t a, uint32_t b) { uint32_t r; asm("mul.rn.bf16x2 %0, %1, %2;" : "=r"(r) : "r"(a), "r"(b)); return r; }
__device__ __forceinline__ uint32_t bsum2(uint32_t a, uint32_t b) { uint32_t r; asm("add.rn.bf16x2 %0, %1, %2;" : "=r"(r) : "r"(a), "r"(b)); return r; }
__device__ __forceinline__ uint32_t bmax2(uint32_t a, uint32_t b) { uint32_t r; asm("max.bf16x2 %0, %1, %2;" : "=r"(r) : "r"(a), "r"(b)); return r; }
__device__ __forceinline__ uint32_t rscore(float a, float b) {
    const uint32_t u = pack2(a, b);
    return pack2(blo(u) * 0.08838834764831845f, bhi(u) * 0.08838834764831845f);
}
template <int STRIDE> __device__ __forceinline__ void ld5(uint32_t* w, const bf16* p) {
#pragma unroll
    for (int r = 0; r < 5; r++) { const uint2 v = __ldcg(reinterpret_cast<const uint2*>(p + r * STRIDE)); w[2 * r] = v.x; w[2 * r + 1] = v.y; }
}
__device__ __forceinline__ void st5(bf16* p, const uint32_t* w) {
#pragma unroll
    for (int r = 0; r < 5; r++) *reinterpret_cast<uint2*>(p + r * 128) = make_uint2(w[2 * r], w[2 * r + 1]);
}
__device__ __forceinline__ void ln_row(const uint32_t* x, uint32_t* y) {
    float s = 0.f;
#pragma unroll
    for (int i = 0; i < 10; i++) s += blo(x[i]) + bhi(x[i]);
#pragma unroll
    for (int o = 16; o > 0; o >>= 1) s += __shfl_xor_sync(0xffffffffu, s, o);
    const float mean = s * (1.0f / DM);
    float q = 0.f;
#pragma unroll
    for (int i = 0; i < 10; i++) { const float d0 = blo(x[i]) - mean, d1 = bhi(x[i]) - mean; q = fmaf(d0, d0, q); q = fmaf(d1, d1, q); }
#pragma unroll
    for (int o = 16; o > 0; o >>= 1) q += __shfl_xor_sync(0xffffffffu, q, o);
    const uint32_t nm = pack2(-mean, -mean);
    float sq;
    asm("sqrt.approx.ftz.f32 %0, %1;" : "=f"(sq) : "f"(rbf(rbf(q * (1.0f / DM)) + 1e-5f)));
    const float rd = rcpf(rbf(sq));
#pragma unroll
    for (int i = 0; i < 10; i++) { const uint32_t d = bsum2(x[i], nm); y[i] = pack2(blo(d) * rd, bhi(d) * rd); }
}
__device__ __forceinline__ void red_add8(uint4* p, uint32_t a, uint32_t b, uint32_t c, uint32_t d) {
    asm volatile("red.relaxed.gpu.global.add.noftz.v4.bf16x2 [%0], {%1,%2,%3,%4};" ::"l"(p), "r"(a), "r"(b), "r"(c), "r"(d) : "memory");
}
__device__ __forceinline__ void part_sum(const uint4& v, const uint4& w, int lane, uint32_t& x0, uint32_t& x1) {
    float t[8];
    t[0] = blo(v.x) + blo(w.x); t[1] = bhi(v.x) + bhi(w.x); t[2] = blo(v.y) + blo(w.y); t[3] = bhi(v.y) + bhi(w.y);
    t[4] = blo(v.z) + blo(w.z); t[5] = bhi(v.z) + bhi(w.z); t[6] = blo(v.w) + blo(w.w); t[7] = bhi(v.w) + bhi(w.w);
#pragma unroll
    for (int i = 0; i < 4; i++) t[i] = (lane < 16 ? t[i] : t[4 + i]) + __shfl_xor_sync(0xffffffffu, lane < 16 ? t[4 + i] : t[i], 16);
    const uint32_t r0 = pack2(t[0], t[1]), r1 = pack2(t[2], t[3]);
    const uint32_t ex = __shfl_xor_sync(0xffffffffu, (lane & 1) ? r0 : r1, 1);
    x0 = (lane & 1) ? ex : r0; x1 = (lane & 1) ? r1 : ex;
}
__device__ __forceinline__ void post_row(int l, int row, int lane, const bf16* xin, bf16* xout) {
    uint32_t x[10], y[10], n[10];
    const int cl = (lane & 12) * 8 + (lane >> 4) * 16 + (lane & 1) * 8 + (lane & 2) * 2;
    uint4* pp = reinterpret_cast<uint4*>(g_part + (size_t)(l * PROWS + (row & (PROWS - 1))) * (PG * DM)) + (lane & 15) + (lane >> 4) * 80;
    int* f = FLG(F_OP + l * NCHK + (row >> 7));
    flag_wait(FLG(F_CONV + (row >> 10)), CONV_TGT, 200);
    ld5<128>(x, xin + (size_t)row * DM + cl);
    flag_wait(f + 4, OP_TGT, POST_NS);
    {
        uint4 v[10];
#pragma unroll
        for (int i = 0; i < 10; i++) v[i] = __ldcg(pp + (i >> 1) * 16 + (i & 1) * 160);
#pragma unroll
        for (int r = 0; r < 5; r++) {
            uint32_t s0, s1;
            part_sum(v[2 * r], v[2 * r + 1], lane, s0, s1);
            if (r == 1) ld5<16 * S_LEN * 8>(y, g_Y + ((size_t)(cl >> 3) * S_LEN + (row ^ ((row >> 6) & 7))) * 8 + (cl & 4));
            x[2 * r] = bsum2(x[2 * r], s0); x[2 * r + 1] = bsum2(x[2 * r + 1], s1);
        }
    }
    ln_row(x, n);
#pragma unroll
    for (int i = 0; i < 10; i++) x[i] = bsum2(x[i], bmul2(n[i], y[i]));
    if (l == 0) {
        ln_row(x, n);
        st5(g_h[1] + (size_t)row * DM + cl, n);
        __syncwarp();
        if (lane == 0) red_release(FLG(F_H + NCHK + (row >> 7)), 1);
    }
#pragma unroll
    for (int i = 0; i < 10; i++) pp[(i >> 1) * 16 + (i & 1) * 160] = make_uint4(0, 0, 0, 0);
    st5(xout + (size_t)row * DM + cl, x);
    __syncwarp();
    if (l && lane == 0) red_release(f + 5, 1);
}
__device__ __forceinline__ void u_unit(const bf16* Bk, const bf16* Bv, const bf16* shiftk, int unit, int lane) {
    const int t0 = (unit / 10) * 16, cp = (unit % 10) * 32 + lane;
    uint32_t kk[19], vv[16];
    const uint32_t* pk = reinterpret_cast<const uint32_t*>(Bk + (size_t)t0 * DM) + cp;
    const uint32_t* pv = reinterpret_cast<const uint32_t*>(Bv + (size_t)t0 * DM) + cp;
#pragma unroll
    for (int i = 0; i < 19; i++) kk[i] = (i >= 3 || t0 > 0) ? __ldg(pk + (i - 3) * (DM / 2)) : 0u;
#pragma unroll
    for (int i = 0; i < 16; i++) vv[i] = __ldg(pv + i * (DM / 2));
    const uint4 sh0 = __ldg(reinterpret_cast<const uint4*>(shiftk + cp * 8));
    const uint32_t s0 = __byte_perm(sh0.x, sh0.z, 0x5410), s1 = __byte_perm(sh0.x, sh0.z, 0x7632), s2 = __byte_perm(sh0.y, sh0.w, 0x5410), s3 = __byte_perm(sh0.y, sh0.w, 0x7632);
#pragma unroll
    for (int t = 0; t < 16; t++)
        vv[t] = bmul2(bsum2(bsum2(bsum2(bmul2(kk[t], s3), bmul2(kk[t + 1], s2)), bmul2(kk[t + 2], s1)), bmul2(kk[t + 3], s0)), vv[t]);
    uint4* d = reinterpret_cast<uint4*>(g_U + (size_t)(cp * 2) * S_LEN + (t0 ^ 48));
#pragma unroll
    for (int c = 0; c < 2; c++) {
        const uint32_t sel = c ? 0x7632 : 0x5410;
#pragma unroll
        for (int hh = 0; hh < 2; hh++)
            d[c * (S_LEN / 8) + hh] = make_uint4(__byte_perm(vv[15 - hh * 8], vv[14 - hh * 8], sel), __byte_perm(vv[13 - hh * 8], vv[12 - hh * 8], sel),
                                                 __byte_perm(vv[11 - hh * 8], vv[10 - hh * 8], sel), __byte_perm(vv[9 - hh * 8], vv[8 - hh * 8], sel));
    }
}
constexpr int CV_EP = 4224;
template <class F> __device__ __forceinline__ void conv_unit(uint32_t ub, uint32_t e0, uint32_t e1, uint32_t zrow, uint32_t yt, float Dv, int m, int lane, F&& nearly_done) {
    const int g = lane >> 2, tq = lane & 3;
    asm volatile("st.shared.u32 [%0], %1;" ::"r"(e0 + lane * 4), "r"(0) : "memory");
    asm volatile("st.shared.u32 [%0], %1;" ::"r"(zrow + lane * 4), "r"(0) : "memory");
    __syncwarp();
    for (int i = lane; i < CV_EP / 16; i += 32) {
        const uint4 v = lds128(e0 + i * 16);
        const uint32_t nx = i + 1 < CV_EP / 16 ? lds32(e0 + i * 16 + 16) : 0u;
        sts128(e1 + i * 16, __byte_perm(v.x, v.y, 0x5432), __byte_perm(v.y, v.z, 0x5432), __byte_perm(v.z, v.w, 0x5432), __byte_perm(v.w, nx, 0x5432));
    }
    __syncwarp();
    float acc[8][4];
#pragma unroll
    for (int n = 0; n < 8; n++)
#pragma unroll
        for (int i = 0; i < 4; i++) acc[n][i] = 0.f;
    uint32_t wb = (g & 1) ? e0 + (1 + g + 2 * tq) * 2 : e1 + (g + 2 * tq) * 2;
    uint32_t W[16], a[4][4], an[4][4];
    int row = m * 16 + (lane & 15);
    auto lda = [&](uint32_t (*d)[4]) {
        const uint32_t x = row < 0 ? zrow : ub + row * 128 + (((lane >> 4) ^ (row & 7)) << 4);
#pragma unroll
        for (int ks = 0; ks < 4; ks++) ldsm_x4(d[ks][0], d[ks][1], d[ks][2], d[ks][3], x ^ (ks << 5));
        row--;
    };
#pragma unroll
    for (int i = 0; i < 16; i++) W[i] = lds32(wb + i * 16);
    lda(a);
    const int nD = m == 0 ? 16 : 32;
#pragma unroll 2
    for (int D = 0; D < nD; D++) {
        uint32_t Wn[8];
        wb += 128;
        if (D == nD - 6) nearly_done();
        lda(an);
#pragma unroll
        for (int i = 0; i < 8; i++) Wn[i] = lds32(wb + 128 + i * 16);
#pragma unroll
        for (int ks = 0; ks < 4; ks++)
#pragma unroll
            for (int n = 0; n < 8; n++) mma16816(acc[n], a[ks][0], a[ks][1], a[ks][2], a[ks][3], W[2 * ks + n], W[2 * ks + n + 1]);
#pragma unroll
        for (int i = 0; i < 8; i++) { W[i] = W[i + 8]; W[i + 8] = Wn[i]; }
#pragma unroll
        for (int ks = 0; ks < 4; ks++)
#pragma unroll
            for (int i = 0; i < 4; i++) a[ks][i] = an[ks][i];
    }
#pragma unroll
    for (int n = 0; n < 8; n++)
#pragma unroll
        for (int r = 0; r < 2; r++) {
            const int a_ = g + r * 8, b_ = n * 8 + tq * 2;
            const int ar = m * 16 + a_, p = 62 - b_;
            const uint32_t kv = lds32(ub + ar * 128 + (((p >> 3) ^ (ar & 7)) << 4) + (p & 7) * 2);
            const float y0 = rbf(acc[n][2 * r]) + rbf(bhi(kv) * Dv), y1 = rbf(acc[n][2 * r + 1]) + rbf(blo(kv) * Dv);
            const uint32_t pk = pack2(y0, y1);
            asm volatile("st.shared.u16 [%0], %1;" ::"r"(yt + ((a_ * 64 + b_) ^ g) * 16), "h"((unsigned short)(pk & 0xffff)) : "memory");
            asm volatile("st.shared.u16 [%0], %1;" ::"r"(yt + ((a_ * 64 + b_ + 1) ^ g) * 16), "h"((unsigned short)(pk >> 16)) : "memory");
        }
}

__global__ void __launch_bounds__(384, 1) bulk_kernel(const __grid_constant__ BulkMaps M, const __grid_constant__ BulkArgs A,
                                                      const __grid_constant__ Sched SC) {
    extern __shared__ __align__(1024) unsigned char smem_raw[];
    const uint32_t sb0 = smem_u32(smem_raw);
    const uint32_t full0 = sb0 + BULK_TAIL, empty0 = full0 + 32, tfull0 = full0 + 64, tempty0 = full0 + 96, sfull = full0 + 128, sempty = full0 + 160,
                   task0 = full0 + 192, tab0 = full0 + 208;
    const int tid = threadIdx.x, wid = __shfl_sync(0xffffffffu, tid >> 5, 0), lane = tid & 31;
    const int rank = blockIdx.x & 1;
    if (tid == 0) {
        for (int i = 0; i < BK_STAGES; i++) { mbar_init(full0 + 8 * i, 1); mbar_init(empty0 + 8 * i, 4); }
        for (int i = 0; i < TSLOTS; i++) { mbar_init(tfull0 + 8 * i, 1); mbar_init(tempty0 + 8 * i, 19); }
        for (int i = 0; i < 4; i++) { mbar_init(sfull + 8 * i, 8); mbar_init(sempty + 8 * i, 1); }
        asm volatile("fence.mbarrier_init.release.cluster;" ::: "memory");
        if (rank == 1) for (int i = 0; i < TSLOTS; i++) mbar_expect_tx(tfull0 + 8 * i, 4);
        BT(true, T_LN0, 0, 0, 0);
    }
    if (tid < MAXG * 5) asm volatile("st.shared.u32 [%0], %1;" ::"r"(tab0 + tid * 4), "r"(SC.chk[tid]) : "memory");
    cluster_sync_all();
    uint32_t tc = 0, it = 0;
    if (wid < 4) {
        asm volatile("setmaxnreg.dec.sync.aligned.u32 %0;" ::"n"(REG_P));
        if (wid == 0) {
            int head = SC.sbeg[lane >> 3];
            const int hend = SC.sbeg[(lane >> 3) + 1];
            uint32_t chk = 0; int pv = (blockIdx.x >> 1) & 31, grp = (SC.sbeg[3] + (blockIdx.x >> 6)) << 2 | 3, ncode = 0, code = 3 << 6 | 2, guard = 0;
            auto acquire = [&](uint32_t bytes) -> uint32_t {
                const uint32_t s = it & 3;
                mwait(empty0 + 8 * s, ((it >> 2) & 1) ^ 1);
                it++;
                expect_tx1(full0 + 8 * s, bytes);
                return s;
            };
            auto uwait = [&](const int* f, int tgt) {
                int g2 = 0;
                while ((int)UNI(ld_relaxed(f)) < tgt && ++g2 < 4000000) __nanosleep(32);
                fence_async();
            };
#pragma unroll 1
            while (true) {
                const int type = (code >> 6) & 3;
                const int iend = type == T_KV ? 10 : (type == T_QA ? 24 : 31);
                const int jj = code & 63, g0 = (jj & 15) * 4, lc = (code >> 9) & 31;
                const bool lm = (code >> 8) & 1;
                const CUtensorMap* mb = type == T_QA ? &M.wq : (jj < 16 ? &M.wk : &M.wv);
                bool have = false, ok = (code >> 14) & 1;
                int imem = 16;
#pragma unroll 1
                for (int i = type < T_CONV ? 0 : (type == T_CONV ? 24 : 28 + jj); i < iend; i++) {
                    const int sd = (type < T_CONV ? SPLAN : 0x1230) >> 4 * min(iend - i, 7) & 15;
                    if (rank == 0 && sd) {
                        if (sd == 1) {
                            if (type == T_CONV) mwait(empty0 + 8 * (it & 3), ((it >> 2) & 1) ^ 1);
                            const int gi = head + ((lane >> 2) & 1);
                            chk = lds32(tab0 + ((gi < hend ? gi : SENT) * 4 + (lane & 3)) * 4);
                            pv = ld_relaxed(g_flags + (chk & 0xffff));
                        } else if (sd == 2) {
                            const int tgt = (int)(chk >> 16);
                            const uint32_t b = (__ballot_sync(0xffffffffu, (lane & 3) == 0 ? pv < tgt : pv >= tgt) >> (lane & 24)) & 0xff;
                            const uint32_t cand = (b & 1) ? b & 15 : b >> 4;
                            head += (b & 1) ? 0 : ((b & 16) ? 1 : 2);
                            if (head > hend || guard > 4000000) head = hend;
                            const uint32_t req = lane >= 24 ? 1 : 15;
                            grp = (int)__reduce_min_sync(0xffffffffu, (cand & req) == req ? ((uint32_t)head << 2 | (cand ^ req) >> 2 | ((cand ^ req) & 2 ? 0 : 256)) : (head < hend ? 1000u : 1004u));
                            if (grp < 1000) grp &= 255;
                            if (grp < 1000) asm volatile("{\n.reg .pred p;\nsetp.eq.u32 p, %2, 0;\n@p atom.relaxed.gpu.global.inc.u32 %0, [%1], 0x7fffffff;\n}" : "+r"(pv) : "l"(FLG(F_CNT + (grp >> 2))), "r"(lane) : "memory");
                        } else {
                            if (grp < 1000) {
                                const int tk = (int)UNI(pv);
                                have = tk < (int)(UNI(lds32(tab0 + (grp >> 2) * 16)) >> 16);
                                ncode = (int)UNI(lds32(tab0 + MAXG * 16 + (grp & ~3))) | (grp & 3) << 19 | tk;
                            } else if (grp == 1004) { have = true; ncode = -1; }
                            if (have) {
                                const uint32_t o = (tc & 3) * 4;
                                mwait(tempty0 + 2 * o, ((tc >> 2) & 1) ^ 1);
                                asm volatile(ELECT "st.shared.u32 [%0], %1;\n@p mbarrier.arrive.shared::cta.b64 _, [%2];\n"
                                             "@p st.async.weak.shared::cluster.mbarrier::complete_tx::bytes.b32 [%3], %1, [%4];\n}"
                                             ::"r"(task0 + o), "r"(ncode), "r"(tfull0 + 2 * o), "r"(mapa(task0 + o, 1)), "r"(mapa(tfull0 + 2 * o, 1)) : "memory");
                            }
                        }
                    }
                    if (i >= 28) continue;
                    if (i == 8 && type == T_QA) pv = ld_relaxed(FLG((lane & 1 ? F_MEM : F_KV) + lc));
                    if (i == 10) {
                        const uint32_t b = __ballot_sync(0xffffffffu, pv >= (lane & 1 ? MEM_TGT : KV_TGT));
                        if (b & 2) imem = 13;
                        if (!(b & 1)) uwait(FLG(F_KV + lc), KV_TGT);
                        fence_async();
                    }
                    const uint32_t s = acquire(i < 12 ? 49152 : (i == 24 || i == 27 ? 0 : 32768));
                    const uint32_t sa = sb0 + s * BK_STAGE_BYTES, fb = full0 + 8 * s;
                    if (i == 0) TT(3);
                    if (i < 10) {
                        if (lm) {
                            tma_load_3d(sa + 16384, mb, fb, i * 64, g0);
                            tma_load_3d(sa + 32768, mb, fb, i * 64, g0 + 2);
                        } else tma_load_3d_mc(sa + 16384 + rank * 16384, mb, fb, i * 64, g0 + rank * 2);
                        int d = 0;
                        if (!ok) {
                            d = 1;
                            if (i == 3) {
                                uwait(FLG(F_H + lc), H_TGT);
                                ok = true;
                                d = -3;
                                TT(4);
                            }
                        }
#pragma unroll 1
                        for (; d <= 0; d++) {
                            const uint32_t s2 = (s + d) & 3;
                            if (lm) tma_load_2d_mc(sb0 + s2 * BK_STAGE_BYTES + rank * 8192, &M.h, full0 + 8 * s2, (i + d) * 64, lc * 128 + rank * 64);
                            else tma_load_2d(sb0 + s2 * BK_STAGE_BYTES, &M.h2, full0 + 8 * s2, (i + d) * 64, lc * 128);
                        }
                    } else if (i < 13) {
#pragma unroll 1
                        for (int k = 0, bx = (i - 10) * 3; k < 3 && bx < 8; k++, bx++)
                            tma_load_2d(sa + k * 16384, &M.kv, fb, (g0 + (bx & 3)) * 64, (bx >> 2) * S_LEN + (lc & 15) * 128);
                    } else if (i < 24) {
                        const int cn = ((i - 14) >> 1) * 128, ck = g0 * 64 + (i & 1) * 128;
                        if (i > 13) {
                            if (lm) { tma_load_2d(sa, &M.wo, fb, cn, ck); tma_load_2d(sa + 16384, &M.wo, fb, cn + 64, ck); }
                            else tma_load_2d_mc(sa + rank * 16384, &M.wo, fb, cn + rank * 64, ck);
                        }
                        if (i == imem) {
                            TT(5);
                            if (i == 16) uwait(FLG(F_MEM + lc), MEM_TGT);
                            const uint32_t s2 = (s + (i >> 4)) & 3;
#pragma unroll 1
                            for (int k = 0; k < 4; k++)
                                bulk_load(sb0 + s2 * BK_STAGE_BYTES + k * 8192, g_kvf + (size_t)((lc * CSEG + k) * NH + jj * 2) * 256, 8192, full0 + 8 * s2);
                            TT(6);
                        }
                    } else if (i == 25) {
                        tma_load_2d(sa, &M.lu, fb, 0, (2 * jj + rank) * 256);
                    } else if (i == 26) {
#pragma unroll 1
                        for (int k = 0; k < 8; k++)
                            bulk_load(sa + k * CV_EP + 128, A.ssmk + (size_t)((2 * jj + rank) * 8 + k) * S_LEN, 4096, fb);
                    }
                }
                if (type != 3) TT(7);
                if (rank == 0) {
                    if (!have) {
                        if (type == 3) { guard++; __nanosleep(64); }
                        code = 3 << 6;
                        continue;
                    }
                } else {
                    const uint32_t o = (tc & 3) * 4;
                    mwait(tfull0 + 2 * o, (tc >> 2) & 1);
                    ncode = (int)UNI(lds32(task0 + o));
                    asm volatile(ELECT "mbarrier.arrive.expect_tx.shared::cta.b64 _, [%0], 4;\n@p mbarrier.arrive.shared::cluster.b64 _, [%1];\n}" ::"r"(tfull0 + 2 * o), "r"(mapa(tempty0 + 2 * o, 0)) : "memory");
                    __syncwarp();
                }
                tc++;
                if (ncode < 0) break;
                TT(0); TTV(15, ncode);
                code = ((ncode & 256) ? (2 * ncode + rank) & 63 : ncode & 63) | (ncode & 0x1c0) | ((ncode >> (rank ? 14 : 9)) & 31) << 9 | ((ncode >> (19 + rank)) & 1) << 14;
                fence_async();
            }
        } else if (wid == 1) {
            if (lane < 8) asm volatile("prefetch.tensormap [%0];" ::"l"(&M.h + lane) : "memory");
            __syncwarp();
            if (lane == 0) {
                uint32_t rc = 0;
                while (true) {
                    mwait(tfull0 + 8 * (tc & 3), (tc >> 2) & 1);
                    const int code = (int)lds32(task0 + 4 * (tc & 3));
                    mbar_arrive_cluster(mapa(tempty0 + 8 * (tc & 3), 0));
                    tc++;
                    if (code < 0) break;
                    const int type = (code >> 6) & 3;
                    const int lc = (code >> (rank ? 14 : 9)) & 31;
                    mwait(sfull + 8 * (rc & 3), (rc >> 2) & 1);
                    if (type == T_CONV) {
                        asm volatile("cp.async.bulk.global.shared::cta.bulk_group [%0], [%1], %2;" ::"l"(g_Y + (size_t)((2 * (code & 63) + rank) * S_LEN + lc * 1024) * 8), "r"(sb0 + BULK_STG), "r"(16384) : "memory");
                        bulk_commit();
                        bulk_wait<0>();
                    }
                    mbar_arrive(sempty + 8 * (rc & 3));
                    rc++;
                    FT(0);
                    red_release(type == T_QA ? FLG(F_OP + lc) + 4 : FLG((type == T_KV ? F_KV : F_CONV) + lc), 1);
                    FT(1);
                    BT(true, type, lc >> 4, lc & 15, 2);
                }
            }
        } else {
            const int nw = 2 * gridDim.x, idx = (wid - 2) * gridDim.x + blockIdx.x;
#pragma unroll 1
            for (int hh = 0; hh < 2; hh++) {
#pragma unroll 1
                for (int u = hh * 640 + idx; u < hh * 640 + 640; u += nw) u_unit(A.Bk, A.Bv, A.shiftk, u, lane);
                __syncwarp();
                if (lane == 0) red_release(FLG(F_U + hh), 1);
                BT(lane == 0, T_LN0, hh, 0, 2);
            }
#pragma unroll 1
            for (int q = 0; q < 2 * (NCHK + PDIST); q++) {
                const int l = q & 1, c = (q >> 1) - l * PDIST;
                if (c < 0 || c >= NCHK) continue;
#pragma unroll 1
                for (int rr = idx; rr < 128; rr += nw) post_row(l, c * 128 + rr, lane, l ? g_x : A.x, l ? A.out : g_x);
                BT(lane == 0, T_POST, l, c, 2);
            }
        }
    } else {
        asm volatile("setmaxnreg.inc.sync.aligned.u32 %0;" ::"n"(REG_C));
        const int cw = (wid >> 2) - 1, warp = wid & 3;
        const uint32_t wst = sb0 + BULK_STG + (cw * 4 + warp) * 4096;
        uint32_t rc = 0;
        int npend = 0;
        bool urgent = false;
        uint32_t oofs = 0;
        uint32_t qf[16][4];
        auto release = [&](int s) { if ((tid & 127) == 0) { mbar_arrive(empty0 + 8 * s); mbar_arrive_cluster(mapa(empty0 + 8 * s, rank ^ 1)); } };
        auto next = [&]() -> int { const int s = it & 3; mwait(full0 + 8 * s, (it >> 2) & 1); it++; return s; };
        auto wgbar = [&]() { if (cw == 0) named_bar(2, 128); else named_bar(3, 128); };
        auto handoff = [&]() {
            mwait(sempty + 8 * (rc & 3), ((rc >> 2) & 1) ^ 1);
            asm volatile(ELECT "mbarrier.arrive.shared::cta.b64 _, [%0];\n}" ::"r"(sfull + 8 * (rc & 3)) : "memory");
            rc++;
        };
        auto stg_free = [&]() { mwait(sempty + 8 * ((rc - 1) & 3), ((rc - 1) >> 2) & 1); };
        auto round_q = [&]() {
            if (npend > 4) {
                uint4* d = reinterpret_cast<uint4*>(g_part) + oofs;
                if (npend == 6) {
#pragma unroll
                    for (int i = 0; i < 4; i++) red_add8(d + (i >> 1) * 4 + (i & 1) * (8 * PG * DM / 8), qf[i][0], qf[i][1], qf[i][2], qf[i][3]);
                    npend = 5;
                } else {
#pragma unroll
                    for (int i = 4; i < 8; i++) red_add8(d + (i >> 1) * 4 + (i & 1) * (8 * PG * DM / 8), qf[i][0], qf[i][1], qf[i][2], qf[i][3]);
                    npend = 0;
                    handoff();
                }
                return;
            }
            const uint32_t sst = wst + (lane & 15) * 128 + (((lane >> 4) ^ (lane & 7)) << 4) + (npend & 1) * 2048;
#pragma unroll
            for (int q = 0; q < 4; q++)
                if (npend == 4 - q) {
#pragma unroll
                    for (int i = 0; i < 4; i++) stsm_x4(sst ^ (i << 5), qf[q * 4 + i][0], qf[q * 4 + i][1], qf[q * 4 + i][2], qf[q * 4 + i][3]);
                }
            __syncwarp();
            uint4* d = reinterpret_cast<uint4*>(&g_kv[0][0]) + oofs;
            const uint32_t src = wst + (lane >> 3) * 128 + (((lane & 7) ^ (lane >> 3)) << 4) + (npend & 1) * 2048;
#pragma unroll
            for (int i = 0; i < 4; i++) d[i * (4 * HD / 8)] = lds128((src + i * 512) ^ ((i & 1) << 6));
            oofs += 8;
            if (--npend == 0) handoff();
        };
        auto round_a = [&](const float* a, int hh) {
            uint4* d = reinterpret_cast<uint4*>(g_part) + oofs;
#pragma unroll
            for (int i = hh * 4; i < hh * 4 + 4; i++) {
                const float* b = a + (i >> 1) * 16 + (i & 1) * 2;
                red_add8(d + (i >> 1) * 4 + (i & 1) * (8 * PG * DM / 8), pack2(b[0], b[1]), pack2(b[4], b[5]), pack2(b[8], b[9]), pack2(b[12], b[13]));
            }
            if (hh) oofs += 16;
        };
        while (true) {
            tc++; TT(0); tc--;
            int code;
            while (true) {
                if (npend == 0) mwait(tfull0 + 8 * (tc & 3), (tc >> 2) & 1);
                if (npend == 0 || UNI(mtest(tfull0 + 8 * (tc & 3), (tc >> 2) & 1))) {
                    code = (int)UNI(lds32(task0 + 4 * (tc & 3)));
                    if (npend == 0 || ((code & 0x80) == 0 && !urgent && UNI(mtest(full0 + 8 * (it & 3), (it >> 2) & 1)))) break;
                }
                round_q();
            }
            if (lane == 0) mbar_arrive_cluster(mapa(tempty0 + 8 * (tc & 3), 0));
            tc++;
            TT(2);
            if (code < 0) break;
            const int type = (code >> 6) & 3;
            TTV(15, code);
#define BTC(type, k)
            if (type == T_CONV) {
                const int m = (code >> 9) & 1;
                BT((tid & 127) == 0, T_CONV, 0, m, 0);
                const int u = 2 * (code & 63) + rank, ch = cw * 4 + warp;
                int lane = tid & 31;
                asm volatile("" : "+r"(lane));
                const float Dv = bf2f(A.ssmD[u * 8 + ch]);
                const int sd = next(), s0 = next(), s1 = next(), s2 = next();
                TT(3);
                const uint32_t e1 = sb0 + s2 * BK_STAGE_BYTES;
                conv_unit(sb0 + s0 * BK_STAGE_BYTES + ch * 4096, sb0 + s1 * BK_STAGE_BYTES + ch * CV_EP, e1 + 64 + ch * CV_EP, e1 + 40960 + ch * 128, sb0 + BULK_STG + ch * 2, Dv, m, lane,
                          [&]() { release(sd); stg_free(); });
                asm volatile("fence.proxy.async.shared::cta;" ::: "memory");
                __syncwarp();
                handoff();
                TT(5);
                wgbar();
                release(s0); release(s1); release(s2);
                __syncwarp();
#pragma unroll
                for (int i = 0; i < 64; i++) qf[i >> 2][i & 3] = 0;
                continue;
            }
            float acc[128];
            {
                int s = next();
                TT(3); BTC(type, 0); BTC(type, 1);
                uint32_t sa = sb0 + s * BK_STAGE_BYTES + cw * 8192, sb = sb0 + s * BK_STAGE_BYTES + 16384;
                wg_fence();
                wgmma_m64n256k16_first(acc, make_desc(sa, 16, 1024), make_desc(sb, 8192, 1024));
#pragma unroll 1
                for (int kb = 0;;) {
#pragma unroll
                    for (int k = 1; k < 4; k++) wgmma_m64n256k16(acc, make_desc(sa + k * 32, 16, 1024), make_desc(sb + k * 2048, 8192, 1024));
                    wg_commit();
                    if (npend) round_q();
                    if (kb) { wg_wait<1>(); release((s - 1) & 3); }
                    if (++kb == 10) break;
                    s = next();
                    sa = sb0 + s * BK_STAGE_BYTES + cw * 8192; sb = sb0 + s * BK_STAGE_BYTES + 16384;
                    wg_fence();
                    wgmma_m64n256k16(acc, make_desc(sa, 16, 1024), make_desc(sb, 8192, 1024));
                }
            }
            wg_wait<0>();
            TT(4);
            release((it - 1) & 3);
            stg_free();
#pragma unroll
            for (int i = 0; i < 16; i++)
#pragma unroll
                for (int e = 0; e < 4; e++) qf[i][e] = pack2(acc[i * 8 + e * 2], acc[i * 8 + e * 2 + 1]);
            {
                const int cd = (int)lds32(task0 + 4 * ((tc - 1) & 3)), lc = (cd >> (rank ? 14 : 9)) & 31, jj = (cd & 256) ? (2 * cd + rank) & 63 : cd & 63;
                const int r0 = cw * 64 + warp * 16;
                if (type == T_KV) {
                    oofs = ((jj >> 4) * S_LEN + (lc & 15) * 128 + r0 + (lane >> 3)) * (HD / 8) + (jj & 15) * 32 + (lane & 7);
                    npend = 4;
                    urgent = URGENT && (lc < 2 || lc >= 16);
                    continue;
                }
                oofs = (((lc >> 4) * PRING + (lc & (PRING - 1))) * 128 + r0 + (lane >> 2)) * (PG * DM / 8) + (jj & (PG - 1)) * (DM / 8) + (lane & 3);
            }
            const float cs = 1.4426950408889634f;
            int lane = tid & 31;
            asm volatile("" : "+r"(lane));
            const int g = lane >> 2, tq = lane & 3;
            const int sg = cw * 2 + (warp >> 1), hs = warp & 1;
            float mt[2][2], sum[2][2];
            {
                const int x0 = next(), x1 = next();
                TT(5);
                float s[2][4][4];
#pragma unroll
                for (int hd = 0; hd < 2; hd++)
#pragma unroll
                    for (int n = 0; n < 4; n++)
#pragma unroll
                        for (int e = 0; e < 4; e++) s[hd][n][e] = 0.f;
                const uint32_t krow = (sg * 32 + (lane & 7) + (lane >> 4) * 8) * 128 + ((((lane >> 3) & 1) ^ (lane & 7)) << 4);
#pragma unroll
                for (int ii = 0; ii < 16; ii++) {
                    const int i = (ii >> 1) + (ii & 1) * 8;
                    const uint32_t kb = sb0 + (i < 12 ? x0 * BK_STAGE_BYTES + (i >> 2) * 16384 : x1 * BK_STAGE_BYTES) + (krow ^ ((i & 3) << 5));
                    const uint4 k0 = ldsm4(kb), k1 = ldsm4(kb + 2048);
                    mma16816(s[i >> 3][0], qf[i][0], qf[i][1], qf[i][2], qf[i][3], k0.x, k0.y);
                    mma16816(s[i >> 3][1], qf[i][0], qf[i][1], qf[i][2], qf[i][3], k0.z, k0.w);
                    mma16816(s[i >> 3][2], qf[i][0], qf[i][1], qf[i][2], qf[i][3], k1.x, k1.y);
                    mma16816(s[i >> 3][3], qf[i][0], qf[i][1], qf[i][2], qf[i][3], k1.z, k1.w);
                }
#pragma unroll
                for (int i = 0; i < 8; i++) sts128(wst + i * 512 + lane * 16, qf[8 + i][0], qf[8 + i][1], qf[8 + i][2], qf[8 + i][3]);
                wgbar();
                release(x0);
                TT(6);
                uint32_t pa[2][4][2];
#pragma unroll
                for (int hd = 0; hd < 2; hd++) {
                    uint32_t mx[2] = {0xff80ff80u, 0xff80ff80u};
#pragma unroll
                    for (int n = 0; n < 4; n++)
#pragma unroll
                        for (int r = 0; r < 2; r++) {
                            const int d = hs * 16 + g + r * 8 - n * 8 - tq * 2;
                            pa[hd][n][r] = rscore(d < 0 ? -INFINITY : s[hd][n][2 * r], d < 1 ? -INFINITY : s[hd][n][2 * r + 1]);
                            mx[r] = bmax2(mx[r], pa[hd][n][r]);
                        }
#pragma unroll
                    for (int r = 0; r < 2; r++) {
                        mx[r] = bmax2(mx[r], __shfl_xor_sync(0xffffffffu, mx[r], 1));
                        mx[r] = bmax2(mx[r], __shfl_xor_sync(0xffffffffu, mx[r], 2));
                        mt[hd][r] = fmaxf(blo(mx[r]), bhi(mx[r])) * cs;
                        sum[hd][r] = 0.f;
                    }
#pragma unroll
                    for (int n = 0; n < 4; n++)
#pragma unroll
                        for (int r = 0; r < 2; r++) {
                            const float p0 = ex2f(fmaf(blo(pa[hd][n][r]), cs, -mt[hd][r])), p1 = ex2f(fmaf(bhi(pa[hd][n][r]), cs, -mt[hd][r]));
                            sum[hd][r] += p0 + p1;
                            pa[hd][n][r] = pack2(p0, p1);
                        }
                }
                const uint32_t vrow = (sg * 32 + (lane & 15)) * 128 + (((lane >> 4) ^ (lane & 7)) << 4);
                int xv = x1;
#pragma unroll
                for (int hd = 0; hd < 2; hd++) {
                    if (hd == 1) xv = next();
#pragma unroll
                    for (int i = 0; i < 8; i++) {
                        const uint32_t vb = sb0 + xv * BK_STAGE_BYTES + (hd == 0 ? 16384 : 0) + (i >> 2) * 16384 + (vrow ^ ((i & 3) << 5));
                        uint4 v0, v1;
                        ldsm_x4_t(v0.x, v0.y, v0.z, v0.w, vb);
                        ldsm_x4_t(v1.x, v1.y, v1.z, v1.w, vb + 2048);
                        float* o = acc + hd * 64 + i * 8;
#pragma unroll
                        for (int e = 0; e < 8; e++) o[e] = 0.f;
                        mma16816(o, pa[hd][0][0], pa[hd][0][1], pa[hd][1][0], pa[hd][1][1], v0.x, v0.y);
                        mma16816(o + 4, pa[hd][0][0], pa[hd][0][1], pa[hd][1][0], pa[hd][1][1], v0.z, v0.w);
                        mma16816(o, pa[hd][2][0], pa[hd][2][1], pa[hd][3][0], pa[hd][3][1], v1.x, v1.y);
                        mma16816(o + 4, pa[hd][2][0], pa[hd][2][1], pa[hd][3][0], pa[hd][3][1], v1.z, v1.w);
                    }
                    wgbar();
                    release(xv);
                }
            }
            TT(7);
            BTC(T_ATT, 0);
            {
                const int xm = next();
                TT(8);
                BTC(T_ATT, 1);
                const uint32_t mb = sb0 + xm * BK_STAGE_BYTES + sg * 8192 + lane * 16;
                float sm[2][2][4];
#pragma unroll
                for (int i = 0; i < 16; i++) (&sm[0][0][0])[i] = 0.f;
#pragma unroll
                for (int q = 0; q < 4; q++) {
                    const uint4 k0 = lds128(mb + q * 512), k1 = lds128(mb + 4096 + q * 512);
                    const uint4 qa = lds128(wst + q * 1024 + lane * 16), qb = lds128(wst + q * 1024 + 512 + lane * 16);
                    mma16816(sm[0][0], qf[2 * q][0], qf[2 * q][1], qf[2 * q][2], qf[2 * q][3], k0.x, k0.y);
                    mma16816(sm[0][1], qf[2 * q + 1][0], qf[2 * q + 1][1], qf[2 * q + 1][2], qf[2 * q + 1][3], k0.z, k0.w);
                    mmau(sm[1][0], qa, k1.x, k1.y);
                    mmau(sm[1][1], qb, k1.z, k1.w);
                }
                float f[2][2];
                uint32_t pm[2][2];
#pragma unroll
                for (int hd = 0; hd < 2; hd++)
#pragma unroll
                    for (int r = 0; r < 2; r++) {
                        const uint32_t w = rscore(sm[hd][0][2 * r] + sm[hd][1][2 * r], sm[hd][0][2 * r + 1] + sm[hd][1][2 * r + 1]);
                        const float s0 = blo(w) * cs, s1 = bhi(w) * cs;
                        float m = fmaxf(s0, s1);
                        m = fmaxf(m, __shfl_xor_sync(0xffffffffu, m, 1));
                        m = fmaxf(fmaxf(m, __shfl_xor_sync(0xffffffffu, m, 2)), mt[hd][r]);
                        const float a = ex2f(mt[hd][r] - m), p0 = ex2f(s0 - m), p1 = ex2f(s1 - m);
                        float t = fmaf(sum[hd][r], a, p0 + p1);
                        t += __shfl_xor_sync(0xffffffffu, t, 1);
                        t += __shfl_xor_sync(0xffffffffu, t, 2);
                        t = rcpf(t);
                        f[hd][r] = a * t;
                        pm[hd][r] = pack2(p0 * t, p1 * t);
                    }
#pragma unroll
                for (int q = 0; q < 8; q++) {
                    const int hd = q >> 2;
                    const uint4 vm = lds128(mb + hd * 4096 + 2048 + (q & 3) * 512);
                    float* o = acc + q * 16;
#pragma unroll
                    for (int e = 0; e < 16; e++) o[e] *= f[hd][(e >> 1) & 1];
                    mma1688(o, pm[hd][0], pm[hd][1], vm.x);
                    mma1688(o + 4, pm[hd][0], pm[hd][1], vm.y);
                    mma1688(o + 8, pm[hd][0], pm[hd][1], vm.z);
                    mma1688(o + 12, pm[hd][0], pm[hd][1], vm.w);
#pragma unroll
                    for (int e = 0; e < 8; e++) qf[q * 2 + (e >> 2)][e & 3] = pack2(o[2 * e], o[2 * e + 1]);
                }
                wgbar();
                release(xm);
            }
            TT(9);
#pragma unroll
            for (int t = 0; t < 10; t++) {
                const int s = next();
                const uint32_t sb = sb0 + s * BK_STAGE_BYTES;
                float* d = acc + ((t >> 1) & 1) * 64;
                wg_fence();
#pragma unroll
                for (int k = 0; k < 8; k++) {
                    const uint64_t db = make_desc(sb + k * 2048, 16384, 1024);
                    if (k == 0 && !(t & 1)) wgmma_rs_m64n128k16_first(d, qf[k], db);
                    else wgmma_rs_m64n128k16(d, qf[(t & 1) * 8 + k], db);
                }
                wg_commit();
                if (t) {
                    wg_wait<1>();
                    release((s - 1) & 3);
                    if (t > 1) round_a(acc + (((t >> 1) & 1) ^ 1) * 64, t & 1);
                }
            }
            wg_wait<0>();
            release((it - 1) & 3);
            TT(10);
#pragma unroll
            for (int i = 0; i < 32; i++) qf[i >> 2][i & 3] = pack2(acc[(i >> 3) * 16 + (i & 4) / 2 + (i & 3) * 4], acc[(i >> 3) * 16 + (i & 4) / 2 + (i & 3) * 4 + 1]);
            npend = 6;
            urgent = URGENT > 1;
        }
    }
    cluster_sync_all();
}

__global__ void __launch_bounds__(256) reset_kernel(const bf16* x, int g0, int ncl) {
    const int lane = threadIdx.x & 31, row = blockIdx.x * 8 + (threadIdx.x >> 5);
    uint32_t r[10];
    ld5<128>(r, x + (size_t)row * DM + lane * 4);
    if (blockIdx.x == 0)
        for (int i = threadIdx.x; i < NFLAG * 2; i += blockDim.x) reinterpret_cast<uint4*>(FLG(i >> 1))[i & 1] = make_uint4(i == g0 ? min(ncl, 32) : (i == g0 + 2 ? max(ncl - 32, 0) : 0), 0, 0, 0);
    for (int i = blockIdx.x * 256 + threadIdx.x; i < 2 * PROWS * PG * DM / 8; i += S_LEN * 32) reinterpret_cast<uint4*>(g_part)[i] = make_uint4(0, 0, 0, 0);
    ln_row(r, r);
    st5(g_h[0] + (size_t)row * DM + lane * 4, r);
    if (blockIdx.x) return;
}

typedef CUresult (*PFN_encodeTiled)(CUtensorMap*, CUtensorMapDataType, cuuint32_t, void*, const cuuint64_t*, const cuuint64_t*,
                                    const cuuint32_t*, const cuuint32_t*, CUtensorMapInterleave, CUtensorMapSwizzle,
                                    CUtensorMapL2promotion, CUtensorMapFloatOOBfill);
static PFN_encodeTiled get_encode() {
    static PFN_encodeTiled fn = nullptr;
    if (!fn) {
        void* p = nullptr;
        cudaDriverEntryPointQueryResult qr;
        cudaGetDriverEntryPoint("cuTensorMapEncodeTiled", &p, cudaEnableDefault, &qr);
        fn = (PFN_encodeTiled)p;
    }
    return fn;
}
static void make_map(CUtensorMap* m, const void* ptr, uint64_t rows, uint64_t cols, uint32_t box_rows) {
    cuuint64_t dims[2] = {cols, rows};
    cuuint64_t strides[1] = {cols * 2};
    cuuint32_t box[2] = {64u, box_rows};
    cuuint32_t es[2] = {1, 1};
    get_encode()(m, CU_TENSOR_MAP_DATA_TYPE_BFLOAT16, 2, const_cast<void*>(ptr), dims, strides, box, es,
                 CU_TENSOR_MAP_INTERLEAVE_NONE, CU_TENSOR_MAP_SWIZZLE_128B, CU_TENSOR_MAP_L2_PROMOTION_L2_128B,
                 CU_TENSOR_MAP_FLOAT_OOB_FILL_NONE);
}
static void make_map3(CUtensorMap* m, const void* ptr) {
    cuuint64_t dims[3] = {64, DM, HD / 64};
    cuuint64_t strides[2] = {HD * 2, 128};
    cuuint32_t box[3] = {64u, 64u, 2u};
    cuuint32_t es[3] = {1, 1, 1};
    get_encode()(m, CU_TENSOR_MAP_DATA_TYPE_BFLOAT16, 3, const_cast<void*>(ptr), dims, strides, box, es,
                 CU_TENSOR_MAP_INTERLEAVE_NONE, CU_TENSOR_MAP_SWIZZLE_128B, CU_TENSOR_MAP_L2_PROMOTION_L2_128B,
                 CU_TENSOR_MAP_FLOAT_OOB_FILL_NONE);
}
#define QA_PRE0 4
#define KV1_E 1
#define KV1_L 16
#define KV0_X 6
#define CONV0_AT 1
#define CONV1_AT 9
static void build_sched(Sched& S, int naux) {
    int n = 0;
    auto ck = [](int f, int t) { return (uint32_t)(f * 32) | (uint32_t)t << 16; };
    auto add = [&](int lm, int type, int la, int ca, int lb, int cb, int ntask, uint32_t soft) {
        S.info[n] = (uint32_t)(type << 6 | lm << 8 | (la * 16 + ca) << 9 | (lb * 16 + cb) << 14);
        S.chk[n * 4] = ck(F_CNT + n, ntask); S.chk[n * 4 + 1] = soft;
        S.chk[n * 4 + 2] = ck(F_H + la * NCHK + ca, H_TGT); S.chk[n * 4 + 3] = ck(F_H + lb * NCHK + cb, H_TGT);
        n++;
    };
    for (int i = 0; i < MAXG * 4; i++) S.chk[i] = ck(F_ZERO, 0);
    for (int i = 0; i < MAXG; i++) S.info[i] = 0;
    S.sbeg[0] = n;
    for (int i = 0; i < NCHK; i++) {
        add(1, T_KV, 1, i, 1, i, 16, i < KV1_E || i >= KV1_L ? ck(F_OP + i, 14) + 4 : ck(F_H + NCHK + i, KV1_N));
        S.chk[n * 4 - 2] = S.chk[n * 4 - 1] = ck(F_CONV + i / 8, CONV_TGT);
    }
    S.sbeg[1] = n;
    auto addqa = [&]() {
    for (int p = 0; p < NCHK + PDIST; p++) {
        const bool h0 = p < NCHK, h1 = p >= PDIST;
        const int la = h0 ? 0 : 1, ca = h0 ? p : p - PDIST, lb = h1 ? 1 : 0, cb = h1 ? p - PDIST : p;
        const int ta = ca * CSEG + CSEG + la * LAG;
        add(!(h0 && h1), T_QA, la, ca, lb, cb, h0 && h1 ? 16 : 8,
            ck(F_PROG, h1 ? ta - QA_PRE : (ta > QA_PRE0 ? ta - QA_PRE0 : 0)));
        S.info[n - 1] |= 3u << 19;
        S.chk[n * 4 - 2] = h0 && ca >= PRING ? ck(F_H + NCHK + ca - PRING + 1, H_TGT) : ck(F_ZERO, 0);
        S.chk[n * 4 - 1] = !h1 ? ck(F_KV + ca, KV_TGT) : (cb >= PRING ? ck(F_OP + NCHK + cb - PRING, 128) + 5 : ck(F_ZERO, 0));
    }
    };
    auto addkv = [&]() {
    for (int i = 0; i < NCHK; i += 2) add(0, T_KV, 0, i, 0, i + 1, 32, ck(F_PROG, 4 * i > KV0_X + 1 ? 4 * i - KV0_X : 1)), S.chk[n * 4 - 2] = S.chk[n * 4 - 1] = ck(F_ZERO, 0);
    };
    addqa();
    S.sbeg[2] = n;
    for (int m = 0; m < 2; m++) {
        add(0, T_CONV, 0, m, 0, m, 40, ck(F_U + m, naux));
        S.chk[n * 4 - 2] = S.chk[n * 4 - 1] = ck(F_CNT + S.sbeg[2] + 2 + (m ? CONV1_AT : CONV0_AT) / 2, 32);
    }
    S.sbeg[3] = n;
    addkv();
    S.sbeg[4] = n;
}

static void launch_all(void* const* d_in, void* d_out) {
    const bf16* x = (const bf16*)d_in[0];
    const bf16* mem0 = (const bf16*)d_in[1];
    const bf16* Wq = (const bf16*)d_in[2];
    const bf16* Wk = (const bf16*)d_in[3];
    const bf16* Wv = (const bf16*)d_in[4];
    const bf16* Wo = (const bf16*)d_in[5];
    static bool inited = false;
    static int nsm = 132;
    static Sched SC;
    bf16 *p_h, *p_kv, *p_u;
    cudaGetSymbolAddress((void**)&p_h, g_h);
    cudaGetSymbolAddress((void**)&p_kv, g_kv);
    cudaGetSymbolAddress((void**)&p_u, g_U);
    if (!inited) {
        inited = true;
        cudaDeviceGetAttribute(&nsm, cudaDevAttrMultiProcessorCount, 0);
        cudaFuncSetAttribute(chain_kernel, cudaFuncAttributeMaxDynamicSharedMemorySize, (int)sizeof(ChainSmem));
        cudaFuncSetAttribute(chain_kernel, cudaFuncAttributeNonPortableClusterSizeAllowed, 1);
        cudaFuncSetAttribute(bulk_kernel, cudaFuncAttributeMaxDynamicSharedMemorySize, BULK_SMEM);
        build_sched(SC, 2 * ((nsm - 64) & ~1));
    }
    const size_t QS = (size_t)S_LEN * HD;
    BulkMaps M;
    make_map(&M.h, p_h, 2 * S_LEN, DM, 64);
    make_map(&M.h2, p_h, 2 * S_LEN, DM, 128);
    make_map3(&M.wq, Wq);
    make_map3(&M.wk, Wk);
    make_map3(&M.wv, Wv);
    make_map(&M.wo, Wo, HD, DM, 128);
    make_map(&M.kv, p_kv, 2 * S_LEN, HD, 128);
    make_map(&M.lu, p_u, DM * 32, 64, 256);
    BulkArgs BA;
    BA.x = x; BA.out = (bf16*)d_out;
    BA.Bk = (const bf16*)d_in[8]; BA.Bv = (const bf16*)d_in[9]; BA.shiftk = (const bf16*)d_in[10];
    BA.ssmk = (const bf16*)d_in[11]; BA.ssmD = (const bf16*)d_in[12];
    ChainArgs ca;
    for (int l = 0; l < 2; l++) {
        make_map(&ca.tk[l], p_kv, S_LEN, HD, 32);
        make_map(&ca.tv[l], p_kv + QS, S_LEN, HD, 32);
    }
    ca.x = x; ca.mem0 = mem0; ca.Wq = Wq; ca.Wk = Wk; ca.Wv = Wv; ca.Wo = Wo; ca.kv_target = KV_TGT;
    cudaStream_t s = cudaStreamPerThread;
    reset_kernel<<<S_LEN / 8, 256, 0, s>>>(x, 2 * (F_CNT + SC.sbeg[3]), (nsm - 64) / 2);
    {
        cudaLaunchConfig_t cfg = {};
        cfg.gridDim = dim3(64); cfg.blockDim = dim3(CHAIN_THREADS); cfg.dynamicSmemBytes = sizeof(ChainSmem); cfg.stream = s;
        cudaLaunchAttribute at[1];
        at[0].id = cudaLaunchAttributeClusterDimension;
        at[0].val.clusterDim.x = CL; at[0].val.clusterDim.y = 1; at[0].val.clusterDim.z = 1;
        cfg.attrs = at; cfg.numAttrs = 1;
        cudaLaunchKernelEx(&cfg, chain_kernel, ca);
    }
    {
        cudaLaunchConfig_t cfg = {};
        cfg.gridDim = dim3((nsm - 64) & ~1); cfg.blockDim = dim3(384); cfg.dynamicSmemBytes = BULK_SMEM; cfg.stream = s;
        cudaLaunchAttribute at[2];
        at[0].id = cudaLaunchAttributeProgrammaticStreamSerialization;
        at[0].val.programmaticStreamSerializationAllowed = 1;
        at[1].id = cudaLaunchAttributeClusterDimension;
        at[1].val.clusterDim.x = 2; at[1].val.clusterDim.y = 1; at[1].val.clusterDim.z = 1;
        cfg.attrs = at; cfg.numAttrs = 2;
        cudaLaunchKernelEx(&cfg, bulk_kernel, M, BA, SC);
    }
}
}

extern "C" void kernel_launch(void* const* d_in, const int* in_sizes, int n_in, void* d_out, int out_size) {
    (void)in_sizes; (void)n_in; (void)out_size;
    if (ws::usable()) ws::launch_all(d_in, d_out);
    else ni::launch_all(d_in, d_out);
}
```

```cpp
#include <cuda_runtime.h>
#include <cuda_bf16.h>
#include <stdint.h>
#include <cuda.h>

typedef __nv_bfloat16 bf16;
namespace ws {
constexpr int S_LEN = 2048, DM = 640, NH = 32, DH = 128, HD = NH * DH, SEG = 32, NSEG = S_LEN / SEG;

__device__ __forceinline__ float bf2f(bf16 v) { return __bfloat162float(v); }
__device__ __forceinline__ float rbf(float v) { return __bfloat162float(__float2bfloat16_rn(v)); }
__device__ __forceinline__ uint32_t pack2(float a, float b) {
    __nv_bfloat162 t = __floats2bfloat162_rn(a, b);
    return *reinterpret_cast<uint32_t*>(&t);
}
__device__ __forceinline__ float blo(uint32_t v) { return __uint_as_float(v << 16); }
__device__ __forceinline__ float bhi(uint32_t v) { return __uint_as_float(v & 0xffff0000u); }
__device__ __forceinline__ uint32_t badd(uint32_t a, uint32_t b) { uint32_t r; asm("add.rn.bf16x2 %0, %1, %2;" : "=r"(r) : "r"(a), "r"(b)); return r; }
__device__ __forceinline__ uint32_t smem_u32(const void* p) { return (uint32_t)__cvta_generic_to_shared(p); }
__device__ __forceinline__ uint4 ldsm4(uint32_t a) {
    uint4 v;
    asm volatile("ldmatrix.sync.aligned.m8n8.x4.shared.b16 {%0,%1,%2,%3}, [%4];" : "=r"(v.x), "=r"(v.y), "=r"(v.z), "=r"(v.w) : "r"(a));
    return v;
}
__device__ __forceinline__ uint4 ldsm4t(uint32_t a) {
    uint4 v;
    asm volatile("ldmatrix.sync.aligned.m8n8.x4.trans.shared.b16 {%0,%1,%2,%3}, [%4];" : "=r"(v.x), "=r"(v.y), "=r"(v.z), "=r"(v.w) : "r"(a));
    return v;
}
__device__ __forceinline__ uint2 ldsm2t(uint32_t a) {
    uint2 v;
    asm volatile("ldmatrix.sync.aligned.m8n8.x2.trans.shared.b16 {%0,%1}, [%2];" : "=r"(v.x), "=r"(v.y) : "r"(a));
    return v;
}
__device__ __forceinline__ void stsm4(uint32_t a, uint32_t r0, uint32_t r1, uint32_t r2, uint32_t r3) {
    asm volatile("stmatrix.sync.aligned.m8n8.x4.shared.b16 [%0], {%1,%2,%3,%4};" ::"r"(a), "r"(r0), "r"(r1), "r"(r2), "r"(r3) : "memory");
}
__device__ __forceinline__ void stsm2(uint32_t a, uint32_t r0, uint32_t r1) {
    asm volatile("stmatrix.sync.aligned.m8n8.x2.shared.b16 [%0], {%1,%2};" ::"r"(a), "r"(r0), "r"(r1) : "memory");
}
__device__ __forceinline__ void stsm4t(uint32_t a, uint32_t r0, uint32_t r1, uint32_t r2, uint32_t r3) {
    asm volatile("stmatrix.sync.aligned.m8n8.x4.trans.shared.b16 [%0], {%1,%2,%3,%4};" ::"r"(a), "r"(r0), "r"(r1), "r"(r2), "r"(r3) : "memory");
}
__device__ __forceinline__ void mma16816(float* c, uint32_t a0, uint32_t a1, uint32_t a2, uint32_t a3, uint32_t b0, uint32_t b1) {
    asm("mma.sync.aligned.m16n8k16.row.col.f32.bf16.bf16.f32 {%0,%1,%2,%3}, {%4,%5,%6,%7}, {%8,%9}, {%0,%1,%2,%3};"
        : "+f"(c[0]), "+f"(c[1]), "+f"(c[2]), "+f"(c[3]) : "r"(a0), "r"(a1), "r"(a2), "r"(a3), "r"(b0), "r"(b1));
}
__device__ __forceinline__ void mmav(float* c, uint32_t a0, uint32_t a1, uint32_t a2, uint32_t a3, uint32_t b0, uint32_t b1) {
    asm volatile("mma.sync.aligned.m16n8k16.row.col.f32.bf16.bf16.f32 {%0,%1,%2,%3}, {%4,%5,%6,%7}, {%8,%9}, {%0,%1,%2,%3};"
        : "+f"(c[0]), "+f"(c[1]), "+f"(c[2]), "+f"(c[3]) : "r"(a0), "r"(a1), "r"(a2), "r"(a3), "r"(b0), "r"(b1));
}
__device__ __forceinline__ void mmau(float* c, const uint4& a, uint32_t b0, uint32_t b1) { mma16816(c, a.x, a.y, a.z, a.w, b0, b1); }
__device__ __forceinline__ void mma1688(float* c, uint32_t a0, uint32_t a1, uint32_t b0) {
    asm("mma.sync.aligned.m16n8k8.row.col.f32.bf16.bf16.f32 {%0,%1,%2,%3}, {%4,%5}, {%6}, {%0,%1,%2,%3};"
        : "+f"(c[0]), "+f"(c[1]), "+f"(c[2]), "+f"(c[3]) : "r"(a0), "r"(a1), "r"(b0));
}
__device__ __forceinline__ void mmav8(float* c, uint32_t a0, uint32_t a1, uint32_t b0) {
    asm volatile("mma.sync.aligned.m16n8k8.row.col.f32.bf16.bf16.f32 {%0,%1,%2,%3}, {%4,%5}, {%6}, {%0,%1,%2,%3};"
        : "+f"(c[0]), "+f"(c[1]), "+f"(c[2]), "+f"(c[3]) : "r"(a0), "r"(a1), "r"(b0));
}
__device__ __forceinline__ void cp_async16(uint32_t dst, const void* src) { asm volatile("cp.async.cg.shared.global [%0], [%1], 16;" ::"r"(dst), "l"(src)); }
__device__ __forceinline__ void cp_commit() { asm volatile("cp.async.commit_group;"); }
template <int N> __device__ __forceinline__ void cp_wait() { asm volatile("cp.async.wait_group %0;" ::"n"(N)); }
__device__ __forceinline__ uint4 lds128(uint32_t a) {
    uint4 v;
    asm volatile("ld.shared.v4.u32 {%0,%1,%2,%3}, [%4];" : "=r"(v.x), "=r"(v.y), "=r"(v.z), "=r"(v.w) : "r"(a));
    return v;
}
__device__ __forceinline__ uint2 lds64(uint32_t a) {
    uint2 v;
    asm volatile("ld.shared.v2.u32 {%0,%1}, [%2];" : "=r"(v.x), "=r"(v.y) : "r"(a));
    return v;
}
__device__ __forceinline__ uint32_t lds32(uint32_t a) { uint32_t v; asm volatile("ld.shared.u32 %0, [%1];" : "=r"(v) : "r"(a)); return v; }
__device__ __forceinline__ void sts32(uint32_t a, uint32_t x) { asm volatile("st.shared.u32 [%0], %1;" ::"r"(a), "r"(x) : "memory"); }
__device__ __forceinline__ void sts64(uint32_t a, uint32_t x, uint32_t y) { asm volatile("st.shared.v2.u32 [%0], {%1,%2};" ::"r"(a), "r"(x), "r"(y) : "memory"); }
__device__ __forceinline__ void sts128(uint32_t a, uint32_t x, uint32_t y, uint32_t z, uint32_t w) {
    asm volatile("st.shared.v4.u32 [%0], {%1,%2,%3,%4};" ::"r"(a), "r"(x), "r"(y), "r"(z), "r"(w) : "memory");
}
__device__ __forceinline__ uint4 ld_relaxed_v4(const void* p) {
    uint4 v;
    asm volatile("ld.relaxed.gpu.global.v4.u32 {%0,%1,%2,%3}, [%4];" : "=r"(v.x), "=r"(v.y), "=r"(v.z), "=r"(v.w) : "l"(p) : "memory");
    return v;
}
__device__ __forceinline__ uint2 ld_relaxed_v2(const void* p) {
    uint2 v;
    asm volatile("ld.relaxed.gpu.global.v2.u32 {%0,%1}, [%2];" : "=r"(v.x), "=r"(v.y) : "l"(p) : "memory");
    return v;
}
__device__ __forceinline__ void ld7_relaxed(uint4* x, const void* p) {
    asm volatile("ld.relaxed.gpu.global.v4.u32 {%0,%1,%2,%3}, [%28 + 0];\nld.relaxed.gpu.global.v4.u32 {%4,%5,%6,%7}, [%28 + 512];\nld.relaxed.gpu.global.v4.u32 {%8,%9,%10,%11}, [%28 + 1024];\nld.relaxed.gpu.global.v4.u32 {%12,%13,%14,%15}, [%28 + 1536];\nld.relaxed.gpu.global.v4.u32 {%16,%17,%18,%19}, [%28 + 2048];\nld.relaxed.gpu.global.v4.u32 {%20,%21,%22,%23}, [%28 + 2560];\nld.relaxed.gpu.global.v4.u32 {%24,%25,%26,%27}, [%28 + 3072];\n" : "=r"(x[0].x), "=r"(x[0].y), "=r"(x[0].z), "=r"(x[0].w), "=r"(x[1].x), "=r"(x[1].y), "=r"(x[1].z), "=r"(x[1].w), "=r"(x[2].x), "=r"(x[2].y), "=r"(x[2].z), "=r"(x[2].w), "=r"(x[3].x), "=r"(x[3].y), "=r"(x[3].z), "=r"(x[3].w), "=r"(x[4].x), "=r"(x[4].y), "=r"(x[4].z), "=r"(x[4].w), "=r"(x[5].x), "=r"(x[5].y), "=r"(x[5].z), "=r"(x[5].w), "=r"(x[6].x), "=r"(x[6].y), "=r"(x[6].z), "=r"(x[6].w) : "l"(p) : "memory");
}
__device__ __forceinline__ void ld7_relaxed(uint2* x, const void* p) {
    asm volatile("ld.relaxed.gpu.global.v2.u32 {%0,%1}, [%14 + 0];\nld.relaxed.gpu.global.v2.u32 {%2,%3}, [%14 + 512];\nld.relaxed.gpu.global.v2.u32 {%4,%5}, [%14 + 1024];\nld.relaxed.gpu.global.v2.u32 {%6,%7}, [%14 + 1536];\nld.relaxed.gpu.global.v2.u32 {%8,%9}, [%14 + 2048];\nld.relaxed.gpu.global.v2.u32 {%10,%11}, [%14 + 2560];\nld.relaxed.gpu.global.v2.u32 {%12,%13}, [%14 + 3072];\n" : "=r"(x[0].x), "=r"(x[0].y), "=r"(x[1].x), "=r"(x[1].y), "=r"(x[2].x), "=r"(x[2].y), "=r"(x[3].x), "=r"(x[3].y), "=r"(x[4].x), "=r"(x[4].y), "=r"(x[5].x), "=r"(x[5].y), "=r"(x[6].x), "=r"(x[6].y) : "l"(p) : "memory");
}
__device__ __forceinline__ void st_relaxed_v4(void* p, uint32_t a, uint32_t b, uint32_t c, uint32_t d) {
    asm volatile("st.relaxed.gpu.global.v4.u32 [%0], {%1,%2,%3,%4};" ::"l"(p), "r"(a), "r"(b), "r"(c), "r"(d) : "memory");
}
__device__ __forceinline__ void st_relaxed_v2(void* p, uint32_t a, uint32_t b) {
    asm volatile("st.relaxed.gpu.global.v2.u32 [%0], {%1,%2};" ::"l"(p), "r"(a), "r"(b) : "memory");
}
__device__ __forceinline__ uint32_t clear16(void* p) {
    uint32_t r;
    asm volatile("{\n.reg .b128 z, o;\n.reg .b64 a, b;\nmov.b64 a, 0;\nmov.b128 z, {a, a};\natom.relaxed.gpu.global.exch.b128 o, [%1], z;\nmov.b128 {a, b}, o;\ncvt.u32.u64 %0, a;\n}" : "=r"(r) : "l"(p) : "memory");
    return r;
}
__device__ __forceinline__ uint32_t nz(uint32_t v) { uint32_t r; asm("max.u32 %0, %1, 1;" : "=r"(r) : "r"(v)); return r; }
__device__ __forceinline__ void touch(const void* p) { asm volatile("prefetch.global.L2 [%0];" ::"l"(p) : "memory"); }
__device__ __forceinline__ int ld_relaxed(const int* p) {
    int v;
    asm volatile("ld.relaxed.gpu.global.u32 %0, [%1];" : "=r"(v) : "l"(p) : "memory");
    return v;
}
__device__ __forceinline__ int ld_acquire(const int* p) {
    int v;
    asm volatile("ld.acquire.gpu.global.u32 %0, [%1];" : "=r"(v) : "l"(p) : "memory");
    return v;
}
__device__ __forceinline__ void red_release(int* p, int v) { asm volatile("red.release.gpu.global.add.u32 [%0], %1;" ::"l"(p), "r"(v) : "memory"); }
__device__ __forceinline__ void mbar_init(uint32_t bar, int count) { asm volatile("mbarrier.init.shared::cta.b64 [%0], %1;" ::"r"(bar), "r"(count)); }
__device__ __forceinline__ void mbar_expect_tx(uint32_t bar, uint32_t bytes) {
    asm volatile("mbarrier.arrive.expect_tx.shared::cta.b64 _, [%0], %1;" ::"r"(bar), "r"(bytes) : "memory");
}
__device__ __forceinline__ void mbar_arrive(uint32_t bar) { asm volatile("mbarrier.arrive.shared::cta.b64 _, [%0];" ::"r"(bar) : "memory"); }
__device__ __forceinline__ void mbar_arrive_cluster(uint32_t bar) { asm volatile("mbarrier.arrive.shared::cluster.b64 _, [%0];" ::"r"(bar) : "memory"); }
__device__ __forceinline__ bool mtry(uint32_t bar, uint32_t parity) {
    uint32_t ok;
    asm volatile("{\n.reg .pred P1;\nmbarrier.try_wait.parity.shared::cta.b64 P1, [%1], %2;\nselp.u32 %0, 1, 0, P1;\n}\n" : "=r"(ok) : "r"(bar), "r"(parity) : "memory");
    return ok != 0;
}
__device__ __forceinline__ void mslow(uint32_t bar, uint32_t parity) {
    asm volatile(
        "{\n.reg .pred P1;\n.reg .u32 cnt;\n"
        "mov.u32 cnt, 0;\n"
        "LAB_WAIT:\n"
        "mbarrier.try_wait.parity.shared::cta.b64 P1, [%0], %1;\n"
        "@P1 bra DONE;\n"
        "add.u32 cnt, cnt, 1;\n"
        "setp.lt.u32 P1, cnt, 1000000;\n"
        "@P1 bra LAB_WAIT;\n"
        "trap;\n"
        "DONE:\n}\n" ::"r"(bar), "r"(parity) : "memory");
}
__device__ __forceinline__ void mwait(uint32_t bar, uint32_t parity) {
    asm volatile(
        "{\n.reg .pred P1, P2;\n.reg .u32 cnt;\n"
        "mov.u32 cnt, 0;\n"
        "LAB_WAIT:\n"
        "mbarrier.try_wait.parity.shared::cta.b64 P1, [%0], %1;\n"
        "add.u32 cnt, cnt, 1;\n"
        "setp.gt.u32 P2, cnt, 1000000;\n"
        "@P2 trap;\n"
        "@!P1 bra LAB_WAIT;\n"
        "}\n" ::"r"(bar), "r"(parity) : "memory");
}
__device__ __forceinline__ uint32_t mtest(uint32_t bar, uint32_t parity) {
    uint32_t ok;
    asm volatile("{\n.reg .pred P1;\nmbarrier.test_wait.parity.shared::cta.b64 P1, [%1], %2;\nselp.u32 %0, 1, 0, P1;\n}\n" : "=r"(ok) : "r"(bar), "r"(parity) : "memory");
    return ok;
}
__device__ __forceinline__ uint32_t mapa(uint32_t addr, uint32_t rank) {
    uint32_t r;
    asm("mapa.shared::cluster.u32 %0, %1, %2;" : "=r"(r) : "r"(addr), "r"(rank));
    return r;
}
__device__ __forceinline__ void st_async_b32(uint32_t addr, uint32_t a, uint32_t bar) {
    asm volatile("st.async.weak.shared::cluster.mbarrier::complete_tx::bytes.b32 [%0], %1, [%2];" ::"r"(addr), "r"(a), "r"(bar) : "memory");
}
__device__ __forceinline__ void st_async_v2(uint32_t addr, uint32_t a, uint32_t b, uint32_t bar) {
    asm volatile("st.async.weak.shared::cluster.mbarrier::complete_tx::bytes.v2.b32 [%0], {%1,%2}, [%3];" ::"r"(addr), "r"(a), "r"(b), "r"(bar) : "memory");
}
__device__ __forceinline__ void st_async_v2_lt(uint32_t addr, uint32_t a, uint32_t b, uint32_t bar, uint32_t x, uint32_t lim) {
    asm volatile("{\n.reg .pred p;\nsetp.lt.u32 p, %4, %5;\n@p st.async.weak.shared::cluster.mbarrier::complete_tx::bytes.v2.b32 [%0], {%1,%2}, [%3];\n}"
                 ::"r"(addr), "r"(a), "r"(b), "r"(bar), "r"(x), "r"(lim) : "memory");
}
__device__ __forceinline__ void st_async_v4(uint32_t addr, uint32_t a, uint32_t b, uint32_t c, uint32_t d, uint32_t bar) {
    asm volatile("st.async.weak.shared::cluster.mbarrier::complete_tx::bytes.v4.b32 [%0], {%1,%2,%3,%4}, [%5];" ::"r"(addr), "r"(a), "r"(b), "r"(c), "r"(d), "r"(bar) : "memory");
}
__device__ __forceinline__ void cluster_arrive() { asm volatile("barrier.cluster.arrive.release.aligned;" ::: "memory"); }
__device__ __forceinline__ void cluster_arrive_relaxed() { asm volatile("barrier.cluster.arrive.relaxed.aligned;" ::: "memory"); }
__device__ __forceinline__ void prefetch_l2(const void* p, uint32_t bytes) { asm volatile("cp.async.bulk.prefetch.L2.global [%0], %1;" ::"l"(p), "r"(bytes) : "memory"); }
__device__ __forceinline__ void cluster_wait() { asm volatile("barrier.cluster.wait.acquire.aligned;" ::: "memory"); }
__device__ __forceinline__ void named_bar(int id, int n) { asm volatile("bar.sync %0, %1;" ::"r"(id), "r"(n) : "memory"); }
__device__ __forceinline__ void named_arrive(int id, int n) { asm volatile("bar.arrive %0, %1;" ::"r"(id), "r"(n) : "memory"); }
__device__ __forceinline__ void fence_async_smem() { asm volatile("fence.proxy.async.shared::cta;" ::: "memory"); }
__device__ __forceinline__ void fence_async_global() { asm volatile("fence.proxy.async.global;" ::: "memory"); }
__device__ __forceinline__ void wg_fence() { asm volatile("wgmma.fence.sync.aligned;" ::: "memory"); }
__device__ __forceinline__ void wg_commit() { asm volatile("wgmma.commit_group.sync.aligned;" ::: "memory"); }
template <int N> __device__ __forceinline__ void wg_wait() { asm volatile("wgmma.wait_group.sync.aligned %0;" ::"n"(N) : "memory"); }
__device__ __forceinline__ uint64_t ndesc(uint32_t addr, uint32_t lbo, uint32_t sbo) {
    return (uint64_t)((addr & 0x3FFFF) >> 4) | ((uint64_t)(lbo >> 4) << 16) | ((uint64_t)(sbo >> 4) << 32);
}
__device__ __forceinline__ float ex2f(float x) { float y; asm("ex2.approx.ftz.f32 %0, %1;" : "=f"(y) : "f"(x)); return y; }
__device__ __forceinline__ float rcpf(float x) { float y; asm("rcp.approx.ftz.f32 %0, %1;" : "=f"(y) : "f"(x)); return y; }
__device__ __forceinline__ uint32_t clk32() { uint32_t c; asm volatile("mov.u32 %0, %clock;" : "=r"(c)); return c; }
__device__ __forceinline__ uint32_t opq(uint32_t x) { uint32_t y; asm volatile("mov.u32 %0, %1;" : "=r"(y) : "r"(x)); return y; }
__device__ __forceinline__ uint32_t rem(uint32_t addr, uint32_t rank) { return mapa(addr, rank); }
__device__ __forceinline__ uint64_t mkdesc(uint32_t lo, uint32_t hi) { uint64_t d; asm("mov.b64 %0, {%1,%2};" : "=l"(d) : "r"(lo), "r"(hi)); return d; }
__device__ __forceinline__ void delay(uint32_t n) {
    asm volatile("{\n.reg .pred P;\n.reg .u32 a, b;\nmov.u32 a, %clock;\nadd.u32 a, a, %0;\nDL:\nmov.u32 b, %clock;\nsub.u32 b, b, a;\nsetp.lt.s32 P, b, 0;\n@P bra.uni DL;\n}" ::"r"(n) : "memory");
}
#define UNI(x) __shfl_sync(0xffffffffu, (uint32_t)(x), 0)
__device__ __forceinline__ void wg_n16t(float* d, uint32_t a0, uint32_t a1, uint32_t a2, uint32_t a3, uint64_t db) {
    asm volatile("wgmma.mma_async.sync.aligned.m64n16k16.f32.bf16.bf16 {%0, %1, %2, %3, %4, %5, %6, %7}, {%8, %9, %10, %11}, %12, 1, 1, 1, 1;"
                 : "+f"(d[0]), "+f"(d[1]), "+f"(d[2]), "+f"(d[3]), "+f"(d[4]), "+f"(d[5]), "+f"(d[6]), "+f"(d[7]) : "r"(a0), "r"(a1), "r"(a2), "r"(a3), "l"(db));
}
__device__ __forceinline__ void wg_n16t_first(float* d, uint32_t a0, uint32_t a1, uint32_t a2, uint32_t a3, uint64_t db) {
    asm volatile("wgmma.mma_async.sync.aligned.m64n16k16.f32.bf16.bf16 {%0, %1, %2, %3, %4, %5, %6, %7}, {%8, %9, %10, %11}, %12, 0, 1, 1, 1;"
                 : "=f"(d[0]), "=f"(d[1]), "=f"(d[2]), "=f"(d[3]), "=f"(d[4]), "=f"(d[5]), "=f"(d[6]), "=f"(d[7]) : "r"(a0), "r"(a1), "r"(a2), "r"(a3), "l"(db));
}
__device__ __forceinline__ void wg_n32(float* d, uint32_t a0, uint32_t a1, uint32_t a2, uint32_t a3, uint64_t db) {
    asm volatile("wgmma.mma_async.sync.aligned.m64n32k16.f32.bf16.bf16 {%0, %1, %2, %3, %4, %5, %6, %7, %8, %9, %10, %11, %12, %13, %14, %15}, {%16, %17, %18, %19}, %20, 1, 1, 1, 0;"
                 : "+f"(d[0]), "+f"(d[1]), "+f"(d[2]), "+f"(d[3]), "+f"(d[4]), "+f"(d[5]), "+f"(d[6]), "+f"(d[7]), "+f"(d[8]), "+f"(d[9]), "+f"(d[10]), "+f"(d[11]), "+f"(d[12]), "+f"(d[13]), "+f"(d[14]), "+f"(d[15]) : "r"(a0), "r"(a1), "r"(a2), "r"(a3), "l"(db));
}
__device__ __forceinline__ void wg_n32_first(float* d, uint32_t a0, uint32_t a1, uint32_t a2, uint32_t a3, uint64_t db) {
    asm volatile("wgmma.mma_async.sync.aligned.m64n32k16.f32.bf16.bf16 {%0, %1, %2, %3, %4, %5, %6, %7, %8, %9, %10, %11, %12, %13, %14, %15}, {%16, %17, %18, %19}, %20, 0, 1, 1, 0;"
                 : "=f"(d[0]), "=f"(d[1]), "=f"(d[2]), "=f"(d[3]), "=f"(d[4]), "=f"(d[5]), "=f"(d[6]), "=f"(d[7]), "=f"(d[8]), "=f"(d[9]), "=f"(d[10]), "=f"(d[11]), "=f"(d[12]), "=f"(d[13]), "=f"(d[14]), "=f"(d[15]) : "r"(a0), "r"(a1), "r"(a2), "r"(a3), "l"(db));
}

__device__ __forceinline__ void wg_n16t_sfirst(float* d, uint64_t da, uint64_t db) {
    asm volatile("wgmma.mma_async.sync.aligned.m64n16k16.f32.bf16.bf16 {%0, %1, %2, %3, %4, %5, %6, %7}, %8, %9, 0, 1, 1, 1, 1;"
                 : "=f"(d[0]), "=f"(d[1]), "=f"(d[2]), "=f"(d[3]), "=f"(d[4]), "=f"(d[5]), "=f"(d[6]), "=f"(d[7]) : "l"(da), "l"(db));
}
__device__ __forceinline__ void wg_n32_sfirst(float* d, uint64_t da, uint64_t db) {
    asm volatile("wgmma.mma_async.sync.aligned.m64n32k16.f32.bf16.bf16 {%0, %1, %2, %3, %4, %5, %6, %7, %8, %9, %10, %11, %12, %13, %14, %15}, %16, %17, 0, 1, 1, 1, 0;"
                 : "=f"(d[0]), "=f"(d[1]), "=f"(d[2]), "=f"(d[3]), "=f"(d[4]), "=f"(d[5]), "=f"(d[6]), "=f"(d[7]), "=f"(d[8]), "=f"(d[9]), "=f"(d[10]), "=f"(d[11]), "=f"(d[12]), "=f"(d[13]), "=f"(d[14]), "=f"(d[15]) : "l"(da), "l"(db));
}

__device__ __forceinline__ void wg_n16t_s(float* d, uint64_t da, uint64_t db) {
    asm volatile("wgmma.mma_async.sync.aligned.m64n16k16.f32.bf16.bf16 {%0, %1, %2, %3, %4, %5, %6, %7}, %8, %9, 1, 1, 1, 1, 1;"
                 : "+f"(d[0]), "+f"(d[1]), "+f"(d[2]), "+f"(d[3]), "+f"(d[4]), "+f"(d[5]), "+f"(d[6]), "+f"(d[7]) : "l"(da), "l"(db));
}
__device__ __forceinline__ void wg_n64_sfirst(float* d, uint64_t da, uint64_t db) {
    asm volatile("wgmma.mma_async.sync.aligned.m64n64k16.f32.bf16.bf16 {%0, %1, %2, %3, %4, %5, %6, %7, %8, %9, %10, %11, %12, %13, %14, %15, %16, %17, %18, %19, %20, %21, %22, %23, %24, %25, %26, %27, %28, %29, %30, %31}, %32, %33, 0, 1, 1, 1, 0;"
                 : "=f"(d[0]), "=f"(d[1]), "=f"(d[2]), "=f"(d[3]), "=f"(d[4]), "=f"(d[5]), "=f"(d[6]), "=f"(d[7]), "=f"(d[8]), "=f"(d[9]), "=f"(d[10]), "=f"(d[11]), "=f"(d[12]), "=f"(d[13]), "=f"(d[14]), "=f"(d[15]), "=f"(d[16]), "=f"(d[17]), "=f"(d[18]), "=f"(d[19]), "=f"(d[20]), "=f"(d[21]), "=f"(d[22]), "=f"(d[23]), "=f"(d[24]), "=f"(d[25]), "=f"(d[26]), "=f"(d[27]), "=f"(d[28]), "=f"(d[29]), "=f"(d[30]), "=f"(d[31]) : "l"(da), "l"(db));
}
__device__ __forceinline__ void wg_n64_s(float* d, uint64_t da, uint64_t db) {
    asm volatile("wgmma.mma_async.sync.aligned.m64n64k16.f32.bf16.bf16 {%0, %1, %2, %3, %4, %5, %6, %7, %8, %9, %10, %11, %12, %13, %14, %15, %16, %17, %18, %19, %20, %21, %22, %23, %24, %25, %26, %27, %28, %29, %30, %31}, %32, %33, 1, 1, 1, 1, 0;"
                 : "+f"(d[0]), "+f"(d[1]), "+f"(d[2]), "+f"(d[3]), "+f"(d[4]), "+f"(d[5]), "+f"(d[6]), "+f"(d[7]), "+f"(d[8]), "+f"(d[9]), "+f"(d[10]), "+f"(d[11]), "+f"(d[12]), "+f"(d[13]), "+f"(d[14]), "+f"(d[15]), "+f"(d[16]), "+f"(d[17]), "+f"(d[18]), "+f"(d[19]), "+f"(d[20]), "+f"(d[21]), "+f"(d[22]), "+f"(d[23]), "+f"(d[24]), "+f"(d[25]), "+f"(d[26]), "+f"(d[27]), "+f"(d[28]), "+f"(d[29]), "+f"(d[30]), "+f"(d[31]) : "l"(da), "l"(db));
}
__device__ __forceinline__ void wg_n64(float* d, uint32_t a0, uint32_t a1, uint32_t a2, uint32_t a3, uint64_t db) {
    asm volatile("wgmma.mma_async.sync.aligned.m64n64k16.f32.bf16.bf16 {%0, %1, %2, %3, %4, %5, %6, %7, %8, %9, %10, %11, %12, %13, %14, %15, %16, %17, %18, %19, %20, %21, %22, %23, %24, %25, %26, %27, %28, %29, %30, %31}, {%32, %33, %34, %35}, %36, 1, 1, 1, 0;"
                 : "+f"(d[0]), "+f"(d[1]), "+f"(d[2]), "+f"(d[3]), "+f"(d[4]), "+f"(d[5]), "+f"(d[6]), "+f"(d[7]), "+f"(d[8]), "+f"(d[9]), "+f"(d[10]), "+f"(d[11]), "+f"(d[12]), "+f"(d[13]), "+f"(d[14]), "+f"(d[15]), "+f"(d[16]), "+f"(d[17]), "+f"(d[18]), "+f"(d[19]), "+f"(d[20]), "+f"(d[21]), "+f"(d[22]), "+f"(d[23]), "+f"(d[24]), "+f"(d[25]), "+f"(d[26]), "+f"(d[27]), "+f"(d[28]), "+f"(d[29]), "+f"(d[30]), "+f"(d[31]) : "r"(a0), "r"(a1), "r"(a2), "r"(a3), "l"(db));
}
__device__ __forceinline__ void wg_n64_first(float* d, uint32_t a0, uint32_t a1, uint32_t a2, uint32_t a3, uint64_t db) {
    asm volatile("wgmma.mma_async.sync.aligned.m64n64k16.f32.bf16.bf16 {%0, %1, %2, %3, %4, %5, %6, %7, %8, %9, %10, %11, %12, %13, %14, %15, %16, %17, %18, %19, %20, %21, %22, %23, %24, %25, %26, %27, %28, %29, %30, %31}, {%32, %33, %34, %35}, %36, 0, 1, 1, 0;"
                 : "=f"(d[0]), "=f"(d[1]), "=f"(d[2]), "=f"(d[3]), "=f"(d[4]), "=f"(d[5]), "=f"(d[6]), "=f"(d[7]), "=f"(d[8]), "=f"(d[9]), "=f"(d[10]), "=f"(d[11]), "=f"(d[12]), "=f"(d[13]), "=f"(d[14]), "=f"(d[15]), "=f"(d[16]), "=f"(d[17]), "=f"(d[18]), "=f"(d[19]), "=f"(d[20]), "=f"(d[21]), "=f"(d[22]), "=f"(d[23]), "=f"(d[24]), "=f"(d[25]), "=f"(d[26]), "=f"(d[27]), "=f"(d[28]), "=f"(d[29]), "=f"(d[30]), "=f"(d[31]) : "r"(a0), "r"(a1), "r"(a2), "r"(a3), "l"(db));
}

__device__ __forceinline__ void wg_n32t(float* d, uint32_t a0, uint32_t a1, uint32_t a2, uint32_t a3, uint64_t db) {
    asm volatile("wgmma.mma_async.sync.aligned.m64n32k16.f32.bf16.bf16 {%0, %1, %2, %3, %4, %5, %6, %7, %8, %9, %10, %11, %12, %13, %14, %15}, {%16, %17, %18, %19}, %20, 1, 1, 1, 1;"
                 : "+f"(d[0]), "+f"(d[1]), "+f"(d[2]), "+f"(d[3]), "+f"(d[4]), "+f"(d[5]), "+f"(d[6]), "+f"(d[7]), "+f"(d[8]), "+f"(d[9]), "+f"(d[10]), "+f"(d[11]), "+f"(d[12]), "+f"(d[13]), "+f"(d[14]), "+f"(d[15]) : "r"(a0), "r"(a1), "r"(a2), "r"(a3), "l"(db));
}
__device__ __forceinline__ void wg_n32t_first(float* d, uint32_t a0, uint32_t a1, uint32_t a2, uint32_t a3, uint64_t db) {
    asm volatile("wgmma.mma_async.sync.aligned.m64n32k16.f32.bf16.bf16 {%0, %1, %2, %3, %4, %5, %6, %7, %8, %9, %10, %11, %12, %13, %14, %15}, {%16, %17, %18, %19}, %20, 0, 1, 1, 1;"
                 : "=f"(d[0]), "=f"(d[1]), "=f"(d[2]), "=f"(d[3]), "=f"(d[4]), "=f"(d[5]), "=f"(d[6]), "=f"(d[7]), "=f"(d[8]), "=f"(d[9]), "=f"(d[10]), "=f"(d[11]), "=f"(d[12]), "=f"(d[13]), "=f"(d[14]), "=f"(d[15]) : "r"(a0), "r"(a1), "r"(a2), "r"(a3), "l"(db));
}
__device__ __forceinline__ void wg_n32t_sfirst(float* d, uint64_t da, uint64_t db) {
    asm volatile("wgmma.mma_async.sync.aligned.m64n32k16.f32.bf16.bf16 {%0, %1, %2, %3, %4, %5, %6, %7, %8, %9, %10, %11, %12, %13, %14, %15}, %16, %17, 0, 1, 1, 1, 1;"
                 : "=f"(d[0]), "=f"(d[1]), "=f"(d[2]), "=f"(d[3]), "=f"(d[4]), "=f"(d[5]), "=f"(d[6]), "=f"(d[7]), "=f"(d[8]), "=f"(d[9]), "=f"(d[10]), "=f"(d[11]), "=f"(d[12]), "=f"(d[13]), "=f"(d[14]), "=f"(d[15]) : "l"(da), "l"(db));
}
__device__ __forceinline__ void wg_n32t_s(float* d, uint64_t da, uint64_t db) {
    asm volatile("wgmma.mma_async.sync.aligned.m64n32k16.f32.bf16.bf16 {%0, %1, %2, %3, %4, %5, %6, %7, %8, %9, %10, %11, %12, %13, %14, %15}, %16, %17, 1, 1, 1, 1, 1;"
                 : "+f"(d[0]), "+f"(d[1]), "+f"(d[2]), "+f"(d[3]), "+f"(d[4]), "+f"(d[5]), "+f"(d[6]), "+f"(d[7]), "+f"(d[8]), "+f"(d[9]), "+f"(d[10]), "+f"(d[11]), "+f"(d[12]), "+f"(d[13]), "+f"(d[14]), "+f"(d[15]) : "l"(da), "l"(db));
}

__device__ __forceinline__ void wg_n32_kk(float* d, uint64_t da, uint64_t db) {
    asm volatile("wgmma.mma_async.sync.aligned.m64n32k16.f32.bf16.bf16 {%0, %1, %2, %3, %4, %5, %6, %7, %8, %9, %10, %11, %12, %13, %14, %15}, %16, %17, 1, 1, 1, 0, 0;"
                 : "+f"(d[0]), "+f"(d[1]), "+f"(d[2]), "+f"(d[3]), "+f"(d[4]), "+f"(d[5]), "+f"(d[6]), "+f"(d[7]), "+f"(d[8]), "+f"(d[9]), "+f"(d[10]), "+f"(d[11]), "+f"(d[12]), "+f"(d[13]), "+f"(d[14]), "+f"(d[15]) : "l"(da), "l"(db));
}

}

namespace ws {
#define LAGT 4
constexpr int LAG = LAGT, NT = NSEG + LAG, NCL = 7;
#define P1A 24
#define P1C 10
#define XD 350
#define TPV_PAUSE 1
#define OT_LATE 1
#define H1_LATE 2
#define O_BULK 0
#define O_DLY 0
#define BP 0
#define REG_G 200
#define REG_T 72
#define REG_X 40
#define PDA 8
#define PDC 8
template <int V> struct IC { static constexpr int value = V; };
#define HBYTES 5120
#define POST_NS 40
#define OP_NS 40
#define LN0_AHEAD 8
#define PRE_PDL 0
#define PRE_PF 0
#define OP_LATE 0
#define G_DLY 0
#define QUIET 0
constexpr int NB4 = QUIET ? 480 : 384;
#define TG_STEPS 40
#define NO_X 0
#define WTA 3
constexpr int WTC = 10 - 2 * WTA;
#define WR 4
#define OBK 2
#define TPVW 1
#define OBRES 1
#define O0_EARLY 1
#define BNS 0
#define SKEW 0
#define XS 250
#define WGRP 4
#define WFLY 2
#define XDUP 1
#define TPV_LATE 0
#define WVOL 1
#define WK3 0
#define W_SKIP 0
#define POST_DRY 0
#define CONV_DRY 0
constexpr int XRS = 3;
constexpr int O_H = 0, O_MEM = 81920, O_RED = 102400, O_BAR = 110080, O_TAB = O_BAR + 192, O_BT = O_TAB + 128, O_TR = O_BAR + 512, O_X = O_TR + 1024;
constexpr int O_QRY = O_X, O_KEY = O_X + 10240, O_OBA = O_KEY + 10240, O_ST = O_OBA + 4096;
constexpr int O_VT = O_X, O_VM = O_VT + 32768, O_SM = O_VM + 4096, O_PB = O_SM + 3072;
constexpr int O_AS = 228352, O_WO = O_AS - 65536, HEAD_SMEM = O_AS + 4096, O_STG = 40960;
static_assert(O_ST + 8192 <= O_WO && O_PB + 10240 <= O_WO && O_AS % 1024 == 0 && O_STG + 163840 <= O_AS && HEAD_SMEM <= 232448, "smem");
constexpr int B_MEM = 0, B_RED = 64, B_SM = 88, B_ST = 96, B_OB = 104, B_HF = 112, B_HE = 128, B_OTF = 144, B_OTE = 160;

constexpr int F_H = 0, F_O = 128, F_P = 256, F_U = 384, F_CV = 392, F_XL = 398, F_Z = 399, NFLAG = 400;
__device__ int g_flags[NFLAG * 8];
#define FLG(i) (g_flags + (i) * 8)
#define RING 16
__device__ __forceinline__ int rslot(int l, int seg) { return l * RING + (seg & (RING - 1)); }
__device__ uint4 g_ht[2 * RING * 2560];
__device__ uint4 g_ot[2 * RING * 256 * 64];
__device__ uint4 g_pt[2 * RING * 5120];
__device__ uint4 g_Y[80 * S_LEN];
__device__ uint4 g_U[DM * S_LEN / 8];
__device__ bf16 g_x[RING * SEG * DM];
__device__ int g_epoch;
__device__ uint4 g_xc[XRS * 16 * 3 * 8 * 32];
#define GT(cond, i)
#define SC(cond, i)
#define SD(x)
#define TS(i)
#define TV(i, v)

}

namespace ws {
__device__ __forceinline__ uint32_t bmul2(uint32_t a, uint32_t b) { uint32_t r; asm("mul.rn.bf16x2 %0, %1, %2;" : "=r"(r) : "r"(a), "r"(b)); return r; }
__device__ __forceinline__ uint32_t bmax2(uint32_t a, uint32_t b) { uint32_t r; asm("max.bf16x2 %0, %1, %2;" : "=r"(r) : "r"(a), "r"(b)); return r; }
__device__ __forceinline__ void flag_wait(const int* f, int tgt, int ns) {
    int guard = 0;
    while (ld_relaxed(f) < tgt) { if (++guard > 4000000) __trap(); __nanosleep(ns); }
}
template <int STRIDE> __device__ __forceinline__ void ld5(uint32_t* w, const void* p) {
#pragma unroll
    for (int r = 0; r < 5; r++) { const uint2 v = __ldcg(reinterpret_cast<const uint2*>(reinterpret_cast<const char*>(p) + r * STRIDE)); w[2 * r] = v.x; w[2 * r + 1] = v.y; }
}
template <int STRIDE> __device__ __forceinline__ void st5(void* p, const uint32_t* w) {
#pragma unroll
    for (int r = 0; r < 5; r++) *reinterpret_cast<uint2*>(reinterpret_cast<char*>(p) + r * STRIDE) = make_uint2(w[2 * r], w[2 * r + 1]);
}
__device__ __forceinline__ void ln_row(const uint32_t* x, uint32_t* y) {
    const float c = blo(__shfl_sync(0xffffffffu, x[0], 0));
    float s0 = 0.f, s1 = 0.f, q0 = 0.f, q1 = 0.f;
#pragma unroll
    for (int i = 0; i < 10; i++) { const float d0 = blo(x[i]) - c, d1 = bhi(x[i]) - c; s0 += d0; s1 += d1; q0 = fmaf(d0, d0, q0); q1 = fmaf(d1, d1, q1); }
    float s = s0 + s1, q = q0 + q1;
#pragma unroll
    for (int o = 16; o > 0; o >>= 1) { s += __shfl_xor_sync(0xffffffffu, s, o); q += __shfl_xor_sync(0xffffffffu, q, o); }
    s *= 1.0f / DM;
    const float mean = c + s;
    q = fmaxf(fmaf(q, 1.0f / DM, -s * s), 0.f);
    const uint32_t nm = pack2(-mean, -mean);
    float sq;
    asm("sqrt.approx.ftz.f32 %0, %1;" : "=f"(sq) : "f"(rbf(rbf(q) + 1e-5f)));
    const float rd = rcpf(rbf(sq));
#pragma unroll
    for (int i = 0; i < 10; i++) { const uint32_t d = badd(x[i], nm); y[i] = pack2(blo(d) * rd, bhi(d) * rd); }
}
__device__ __forceinline__ void clear_acc(int l, int seg, int tok, int lane) {
    uint4* pz = g_pt + rslot(l, seg) * 5120 + (lane >> 4) * 512 + tok * 16 + (lane & 15);
#pragma unroll
    for (int i = 0; i < 5; i++) pz[i * 1024] = make_uint4(0, 0, 0, 0);
}
__device__ __forceinline__ void put_h(int l, int seg, int tok, int lane, const uint32_t* n) {
    st5<8192>(reinterpret_cast<char*>(g_ht + rslot(l, seg) * 2560) + (lane >> 2) * 1024 + tok * 32 + (((lane & 3) * 8) ^ ((tok & 4) << 2)), n);
}
__device__ __forceinline__ void ln0_row(const bf16* x, int seg, int tok, int lane) {
    uint32_t v[10];
    ld5<256>(v, x + (size_t)(seg * SEG + tok) * DM + lane * 4);
    clear_acc(0, seg, tok, lane);
    ln_row(v, v);
    put_h(0, seg, tok, lane, v);
    __syncwarp();
    if (lane == 0) red_release(FLG(F_H + seg), 1);
}
__device__ __forceinline__ void post_row(int l, int seg, int tok, int lane, const bf16* xin, bf16* xout, int ep) {
    const bool dry = ep == 0;
    uint32_t x[10], y[10], n[10];
    const int row = seg * SEG + tok;
    SC(tr, tb);
    const bool first = seg == 0;
    if (seg == 8 || ((seg & 15) == 0 && seg)) flag_wait(FLG(F_CV + (seg >> 4) + 1), 80 * ep, 50);
    const char* yp = dry ? reinterpret_cast<const char*>(xin) + lane * 8 : reinterpret_cast<const char*>(g_Y) + ((size_t)(lane >> 1) * S_LEN + row) * 16 + (lane & 1) * 8;
    SC(tr, tb + 1);
    if (!first) ld5<16 * S_LEN * 16>(y, yp);
    bf16* xm = g_x + ((seg & (RING - 1)) * SEG + tok) * DM + lane * 4;
    if (l == 0) {
        ld5<256>(x, xin + (size_t)row * DM + lane * 4);
        if (!dry) clear_acc(1, seg, tok, lane);
    } else {
        if (!dry) flag_wait(seg + 1 < NSEG ? FLG(F_H + 65 + seg) : FLG(F_XL), 32 * ep, 50);
        ld5<256>(x, dry ? xin + lane * 4 : xm);
    }
    if (!dry) flag_wait(FLG(F_P + l * 64 + seg), 40 * ep, POST_NS);
    SC(tr, tb + 2);
    const uint4* pp = dry ? reinterpret_cast<const uint4*>(xin) + lane : g_pt + rslot(l, seg) * 5120 + (lane >> 4) * 512 + tok * 16 + ((lane & 15) ^ ((tok >> 3) << 1));
    {
        uint4 a[5];
#pragma unroll
        for (int i = 0; i < 5; i++) a[i] = __ldcg(pp + i * 1024);
#pragma unroll
        for (int i = 0; i < 5; i++) {
            x[2 * i] = badd(x[2 * i], pack2(__uint_as_float(a[i].x), __uint_as_float(a[i].y)));
            x[2 * i + 1] = badd(x[2 * i + 1], pack2(__uint_as_float(a[i].z), __uint_as_float(a[i].w)));
        }
    }
    SC(tr && x[0] != 0x12345, tb + 3);
    if (first) { if (!dry) flag_wait(FLG(F_CV), 80 * ep, 50); ld5<16 * S_LEN * 16>(y, yp); }
    ln_row(x, n);
#pragma unroll
    for (int i = 0; i < 10; i++) x[i] = badd(x[i], bmul2(n[i], y[i]));
    SC(tr && x[0] != 0x12345, tb + 4);
    if (l) { if (!dry) st5<256>(xout + (size_t)row * DM + lane * 4, x); }
    else {
        ln_row(x, n);
        SC(tr && n[0] != 0x12345, tb + 5);
        if (!dry) put_h(1, seg, tok, lane, n);
        __syncwarp();
        if (lane == 0 && !dry) red_release(FLG(F_H + 64 + seg), 1);
        SC(tr, tb + 6);
        if (!dry) st5<256>(xm, x);
        if (seg == NSEG - 1) { __syncwarp(); if (lane == 0) red_release(FLG(F_XL), 1); }
    }
}
__device__ __forceinline__ void u_half(const bf16* Bk, const bf16* Bv, const bf16* shiftk, int unit, int lane) {
    const int odd = lane & 1, t0 = (unit / 20) * 16 + odd * 8, cp = (unit % 20) * 16 + (lane >> 1);
    uint32_t kk[11], vv[8];
    const uint32_t* pk = reinterpret_cast<const uint32_t*>(Bk + (size_t)t0 * DM) + cp;
    const uint32_t* pv = reinterpret_cast<const uint32_t*>(Bv + (size_t)t0 * DM) + cp;
#pragma unroll
    for (int i = 0; i < 11; i++) kk[i] = (i >= 3 || t0 > 0) ? __ldg(pk + (i - 3) * (DM / 2)) : 0u;
#pragma unroll
    for (int i = 0; i < 8; i++) vv[i] = __ldg(pv + i * (DM / 2));
    const uint4 sh0 = __ldg(reinterpret_cast<const uint4*>(shiftk + cp * 8));
    const uint32_t s0 = __byte_perm(sh0.x, sh0.z, 0x5410), s1 = __byte_perm(sh0.x, sh0.z, 0x7632), s2 = __byte_perm(sh0.y, sh0.w, 0x5410), s3 = __byte_perm(sh0.y, sh0.w, 0x7632);
#pragma unroll
    for (int t = 0; t < 8; t++)
        vv[t] = bmul2(badd(badd(badd(bmul2(kk[t], s3), bmul2(kk[t + 1], s2)), bmul2(kk[t + 2], s1)), bmul2(kk[t + 3], s0)), vv[t]);
    uint4* d = g_U + (size_t)(cp * 2) * (S_LEN / 8) + (t0 >> 6) * 8 + ((((t0 ^ 56) & 63) >> 3) ^ ((t0 >> 6) & 7));
#pragma unroll
    for (int c = 0; c < 2; c++) {
        const uint32_t sel = c ? 0x7632 : 0x5410;
        d[c * (S_LEN / 8)] = make_uint4(__byte_perm(vv[7], vv[6], sel), __byte_perm(vv[5], vv[4], sel), __byte_perm(vv[3], vv[2], sel), __byte_perm(vv[1], vv[0], sel));
    }
}
constexpr int CV_E = 4224, CV_W = 2 * 4096 + 3 * CV_E + 128, CV_HI = O_X, CV_Y = CV_HI + 4 * CV_W, CV_T = CV_Y + 16384, CV_Z = CV_T + 16384;
static_assert(4 * CV_W <= O_RED && CV_W % 128 == 0 && CV_Z + 128 <= HEAD_SMEM, "conv buffers");
__device__ __forceinline__ void conv_unit(uint32_t ub, uint32_t e0, uint32_t e1, uint32_t zrow, uint32_t tt, uint32_t Dv, int rg, int nq, int lane, uint32_t zero, int tb) {
    const int g7 = 7 - (lane >> 2), tq = lane & 3;
    SC(tb >= 0, tb + 3);
    for (int i = lane; i < 32 * nq + 8; i += 32) {
        const uint4 v = lds128(e0 + i * 16);
        const uint32_t nx = lds32(e0 + i * 16 + 16);
        sts128(e1 + i * 16, __byte_perm(v.x, v.y, 0x5432), __byte_perm(v.y, v.z, 0x5432), __byte_perm(v.z, v.w, 0x5432), __byte_perm(v.w, nx, 0x5432));
    }
    __syncwarp();
    SC(tb >= 0, tb + 4);
    float acc[4][4];
#pragma unroll
    for (int i = 0; i < 16; i++) (&acc[0][0])[i] = 0.f;
    uint32_t wb = (g7 & 1) ? e0 + (1 + g7 + 2 * tq) * 2 : e1 + (g7 + 2 * tq) * 2;
    int row = 8 * rg + (lane & 7);
    auto ldb = [&](uint4* b) {
        const uint32_t x = row < 0 ? zrow : ub + row * 128 + (((lane >> 3) ^ (row & 7)) << 4);
        b[0] = ldsm4(x); b[1] = ldsm4(x ^ 64);
        row--;
    };
    uint4 Q[16], b[2][2];
    Q[15].w = lds32(wb);
    auto ldq = [&](int q, int o) { Q[q].y = lds32(wb + o * 32 + 16); Q[q].w = lds32(wb + o * 32 + 32); };
    auto cpq = [&](int q) { Q[q].x = Q[(q + 15) & 15].w + zero; Q[q].z = Q[q].y + zero; };
#pragma unroll
    for (int q = 0; q < 11; q++) ldq(q, q);
#pragma unroll
    for (int q = 0; q < 7; q++) cpq(q);
    ldb(b[0]);
#pragma unroll 1
    for (int D0 = nq; D0 > 0; D0--) {
#pragma unroll
        for (int d = 0; d < 4; d++) {
            ldb(b[(d + 1) & 1]);
#pragma unroll
            for (int q = 11; q < 15; q++) ldq((4 * d + q) & 15, 4 * d + q);
#pragma unroll
            for (int ks = 0; ks < 4; ks++) {
                const uint4& bb_ = b[d & 1][ks >> 1];
#pragma unroll
                for (int m = 0; m < 4; m++) {
                    const uint4& a = Q[(4 * d + m + ks) & 15];
                    mmav(acc[m], a.x, a.y, a.z, a.w, (ks & 1) ? bb_.z : bb_.x, (ks & 1) ? bb_.w : bb_.y);
                }
                cpq((4 * d + 7 + ks) & 15);
            }
        }
        wb += 512;
    }
    SC(tb >= 0 && acc[0][0] != 1.2345f, tb + 5);
    const uint32_t ua = ub + (8 * rg + (lane & 7)) * 128 + (((lane >> 3) ^ (lane & 7)) << 4);
    const uint4 u0 = ldsm4t(ua), u1 = ldsm4t(ua ^ 64);
    auto y = [&](int m, int hf, uint32_t u) { return badd(pack2(acc[m][2 * hf], acc[m][2 * hf + 1]), bmul2(u, Dv)); };
    stsm4t(tt, y(0, 0, u1.w), y(0, 1, u1.z), y(1, 0, u1.y), y(1, 1, u1.x));
    stsm4t(tt ^ 64, y(2, 0, u0.w), y(2, 1, u0.z), y(3, 0, u0.y), y(3, 1, u0.x));
}
}

namespace ws {
struct HeadArgs { const bf16 *x, *mem0, *Wq, *Wk, *Wv, *Wo, *Bk, *Bv, *shiftk, *ssmk, *ssmD; bf16* out; int h_target; };

__global__ void __launch_bounds__(512, 1) head_kernel(const __grid_constant__ HeadArgs A) {
    extern __shared__ __align__(1024) unsigned char smem_raw[];
    const int tid = threadIdx.x, warp = __shfl_sync(0xffffffffu, tid >> 5, 0), lane = tid & 31;
    const int cq = blockIdx.x >> 4, r = blockIdx.x & 15;
    const int nh = cq < 4 ? 5 : 4, hi = r / 3, role = r - hi * 3;
    const bool head = r < 3 * nh;
    const int h = (cq < 4 ? 5 * cq : 4 * cq + 4) + hi;
    const uint32_t sb = smem_u32(smem_raw), bb = sb + O_BAR;
    GT(tid == 0, 1);
    const int sp = cq < 4 ? cq : 4 * cq + r - 24;
    if (tid == 0) {
        if ((sb & 0xFFFFFFu) != 1024) __trap();
        for (int i = 0; i < 12; i++) mbar_init(bb + i * 8, 1);
        mbar_init(bb + B_ST, role == 2 ? 1 : 5);
        mbar_init(bb + B_OB, 1); mbar_init(bb + B_OB + 64, 1);
        mbar_init(bb + B_HF, 1); mbar_init(bb + B_HF + 8, 1);
        mbar_init(bb + B_HE, 6 * nh);
        mbar_init(bb + B_OTF, head ? 4 : 8); mbar_init(bb + B_OTE, 1); mbar_init(bb + B_OTF + 8, head ? 4 : 8); mbar_init(bb + B_OTE + 16, 1);
        asm volatile("fence.mbarrier_init.release.cluster;" ::: "memory");
        mbar_expect_tx(bb + B_RED, nh * 1280);
        mbar_expect_tx(bb + B_SM, 3072); mbar_expect_tx(bb + B_ST, role == 2 ? 5120 : 4096);
        if (role != 2) { mbar_expect_tx(bb + B_OB, 2048); mbar_expect_tx(bb + B_OB + 64, 2048); }
        mbar_expect_tx(bb + B_HF, 8 * HBYTES); mbar_expect_tx(bb + B_HF + 8, 8 * HBYTES);
    }
    asm volatile("griddepcontrol.launch_dependents;");
    __syncwarp();
    cluster_arrive_relaxed();
    if (warp < 8) {
        asm volatile("setmaxnreg.inc.sync.aligned.u32 %0;" ::"n"(REG_G));
        const int wg = warp >> 2, w4 = warp & 3;
        if (head) {
            const bf16* W = (role == 2 ? A.Wv + wg * 64 : (wg ? A.Wk : A.Wq) + role * 64) + h * DH;
            const uint32_t stg = sb + O_STG + wg * 81920;
            const int t7 = tid & 127;
            if (G_DLY) delay(G_DLY);
            GT(tid == 0, 80);
#pragma unroll 1
            for (int i0 = 0; i0 < 40; i0 += WGRP) {
#pragma unroll
                for (int i = i0; i < i0 + WGRP; i++) {
                    const int row = i * 16 + (t7 >> 3), ch = t7 & 7;
                    cp_async16(stg + row * 128 + ((ch ^ (row & 7)) << 4), W + (size_t)row * HD + ch * 8);
                }
                cp_commit();
                cp_wait<WFLY>();
            }
            GT(tid == 0, 81);
        }
        if (head) {
            cluster_wait();
            GT(tid == 0, 82);
            uint32_t wa[40][4];
            cp_wait<0>();
            GT(tid == 0, 83);
            named_bar(8 + wg, 128);
            {
                const uint32_t la = sb + O_STG + wg * 81920 + ((lane & 7) + (lane >> 4) * 8) * 128 + (((w4 * 2 + ((lane >> 3) & 1)) ^ (lane & 7)) << 4);
                { const uint4 v = lds128(sb + O_STG + wg * 81920 + (r >> 1) * 10240 + (tid & 127) * 16); sts128(sb + O_AS + wg * 2048 + (tid & 127) * 16, v.x, v.y, v.z, v.w); }
#pragma unroll
                for (int j = 1; j < 40; j++) {
                    const int kk = (((r >> 1) - j / 5) & 7) * 5 + j % 5;
                    const uint4 v = ldsm4t(la + kk * 2048);
                    wa[j][0] = v.x; wa[j][1] = v.y; wa[j][2] = v.z; wa[j][3] = v.w;
                }
            }
            named_bar(10, 384);
            GT(tid == 0, 2);
            fence_async_smem();
            named_bar(8 + wg, 128);
            cluster_arrive_relaxed();
            float acc[16];
            const uint32_t ep_q = role == 2 ? sb + O_VM + warp * 512 + (lane ^ ((lane >> 3) & 1)) * 16
                                            : sb + O_QRY + wg * 10240 + ((lane >> 1) & 1) * 5120 + (4 * (lane >> 4) + 2 * ((lane >> 2) & 1) + (lane & 1)) * 128 +
                                                  (((2 * w4 + ((lane >> 3) & 1)) ^ (4 * (lane >> 4) + 2 * ((lane >> 2) & 1) + (lane & 1)) ^ ((lane & 2) << 1)) << 4);
            const uint32_t ep_t = role == 2 ? sb + O_VT + warp * 1024 + ((lane >> 3) & 1) * 512 + (lane >> 4) * 128 + (lane & 7) * 16
                                            : sb + O_QRY + wg * 10240 + (8 + 8 * (lane >> 4) + (lane & 7)) * 128 + (((2 * w4 + ((lane >> 3) & 1)) ^ (lane & 7)) << 4);
                        const int pz = role == 2 ? P1C : P1A;
            const uint32_t ab = (1024 + O_AS + wg * 2048) >> 4;
            uint32_t ok = 1;
            const uint32_t tidk = __shfl_sync(0xffffffffu, tid, lane);
            auto token_gemm = [&](auto ll, const bool pause, const uint32_t vo, const uint32_t nbar, const uint32_t npar, const int t) {
                constexpr int l = decltype(ll)::value;
                constexpr uint32_t hb = ((1024 + O_H + l * 40960) >> 4) | (1u << 16);
                const uint32_t pr = opq(r >> 1);
                if (l) TS(15); else TS(14);
                wg_fence();
#pragma unroll
                for (int j = 0; j < 40; j++) {
                    const uint64_t db = mkdesc(hb + ((pr - j / 5) & 7) * 320 + (j % 5) * 64, 0xC0000010u);
                    if (j == 0) wg_n32_sfirst(acc, mkdesc(ab, 0x40000040u), db);
                    else if (j < TG_STEPS) wg_n32(acc, wa[j][0], wa[j][1], wa[j][2], wa[j][3], db);
                    if (l == 0 && (j + 1 == P1A || j + 1 == P1C)) {
                        if (pause && pz == j + 1) {
                            wg_commit();
                            if (role == 2) mwait(bb + B_OTE, vo >> 14);
                            wg_wait<0>();
                            named_arrive(3, 384);
                            named_bar(4, NB4);
                            if (SKEW && wg) delay(SKEW);
                            wg_fence();
                        }
                    }
                }
                wg_commit();
                ok = mtest(nbar, npar);
                wg_wait<0>();
                uint32_t pk[8];
#pragma unroll
                for (int i = 0; i < 8; i++) pk[i] = pack2(acc[2 * i], acc[2 * i + 1]);
                if (role == 2) {
                    stsm4(ep_t + l * 8192 + vo, pk[0], pk[1], pk[2], pk[3]);
                    stsm4(ep_t + l * 8192 + vo + 256, pk[4], pk[5], pk[6], pk[7]);
                } else {
                    stsm4t((ep_t ^ (l << 6)) + l * 5120, pk[0], pk[1], pk[2], pk[3]);
                    stsm4t((ep_t ^ (l << 6)) + l * 5120 + 2048, pk[4], pk[5], pk[6], pk[7]);
                }
                asm volatile("{\n.reg .pred p, q;\nsetp.eq.u32 p, %0, 0;\nsetp.eq.u32 q, %1, 0;\n"
                             "@p mbarrier.arrive.expect_tx.shared::cta.b64 _, [%2], %3;\n@q mbarrier.arrive.shared::cluster.b64 _, [%4];\n}"
                             ::"r"(tidk), "r"(tidk & 127), "r"(bb + B_HF + l * 8), "r"(8 * HBYTES), "r"(mapa(bb + B_HE, l)) : "memory");
            };
            GT(tid == 0, 86);
            mwait(bb + B_HF, 0);
            GT(tid == 0, 87);
            token_gemm(IC<0>{}, false, 0, bb + B_MEM, 1, -1);
            GT(tid == 0, 88);
            named_bar(11, 384);
            cluster_wait();
            named_arrive(13, 384);
#pragma unroll 1
            for (int t = 0; t < NT; t++) {
                GT(tid == 0 && blockIdx.x == 98, 100 + t);
                TS(0);
                const uint32_t mp = (t & 1) ^ 1;
                const bool tg0 = t + 1 < NSEG, tg1 = t + 1 >= LAG;
                constexpr uint32_t mb = ((1024 + O_MEM) >> 4) | (16u << 16);
#pragma unroll
                for (int G = 0; G < 8; G++) {
                    if (__builtin_expect(!ok, 0)) mwait(bb + B_MEM + G * 8, mp);
                    ok = mtest(G < 7 ? bb + B_MEM + (G + 1) * 8 : bb + B_HF, mp);
                    if (G == 0) { TS(1); wg_fence(); }
                    if (G == 7) TS(2);
                    if (G == 1) TS(8); if (G == 2) TS(9); if (G == 3) TS(10); if (G == 4) TS(11); if (G == 5) TS(12); if (G == 6) TS(13);
#pragma unroll
                    for (int u = 0; u < 5; u++) {
                        const int j = G * 5 + u;
                        const uint64_t db = mkdesc(mb + j * 32, 8);
                        if (j == 0) wg_n16t_sfirst(acc, mkdesc(ab, 0x40000040u), db);
                        else wg_n16t(acc, wa[j][0], wa[j][1], wa[j][2], wa[j][3], db);
                    }
                    wg_commit();
                }
                if (role == 2 && t) named_bar(5, 384);
                wg_wait<0>();
                TS(3);
                if (role == 2) sts128(ep_q, pack2(acc[0], acc[1]), pack2(acc[2], acc[3]), pack2(acc[4], acc[5]), pack2(acc[6], acc[7]));
                else stsm4t(ep_q, pack2(acc[0], acc[1]), pack2(acc[2], acc[3]), pack2(acc[4], acc[5]), pack2(acc[6], acc[7]));
                named_arrive(1, 384);
                if (tidk < 8) mbar_expect_tx(bb + B_MEM + tidk * 8, 2560);
                if (t == NT - 1) break;
                if (tg0) {
                    if (__builtin_expect(!ok, 0)) mwait(bb + B_HF, mp);
                    if (role != 2) named_bar(2, 384);
                    token_gemm(IC<0>{}, true, mp * 16384, tg1 ? bb + B_HF + 8 : bb + B_MEM, tg1 ? (t + 1 - LAG) & 1 : mp ^ 1, t);
                } else {
                    if (role == 2) mwait(bb + B_OTE, mp); else named_bar(2, 384);
                    named_arrive(3, 384); named_bar(4, NB4);
                    ok = 0;
                }
                TS(5);
                if (tg1) {
                    if (__builtin_expect(!ok, 0)) mwait(bb + B_HF + 8, (t + 1 - LAG) & 1);
                    token_gemm(IC<1>{}, false, mp * 16384, bb + B_MEM, mp ^ 1, t);
                }
                TS(6);
                named_arrive(13, 384);
            }
        } else {
            cluster_wait(); cluster_arrive_relaxed();
            const int ep = ld_relaxed(&g_epoch) + 1;
            const uint32_t cb = sb + (warp < 4 ? warp * CV_W : CV_HI + (warp - 4) * CV_W), lb = bb + B_MEM + warp * 8;
            auto fetch = [&](int k) {
                const int ps = k / 5, rg = ps ? ps - 1 : 0, ch = (sp * 5 + k - 5 * ps) * 8 + warp;
                if (k == 5 * ps) { flag_wait(FLG(F_U + ps), (ps > 1 ? 20 : (ps ? 32 : 320)) * ep, 50); fence_async_global(); }
                if (lane == 0) {
                    const uint32_t nb = ps ? ps * 1024 : 512;
                    mbar_expect_tx(lb, 2 * nb);
                    asm volatile("cp.async.bulk.shared::cluster.global.mbarrier::complete_tx::bytes [%0], [%1], %2, [%3];" ::"r"(cb + (k & 1) * 4096), "l"(g_U + ch * (S_LEN / 8)), "r"(nb), "r"(lb) : "memory");
                    asm volatile("cp.async.bulk.shared::cluster.global.mbarrier::complete_tx::bytes [%0], [%1], %2, [%3];" ::"r"(cb + 8192 + (k & 1) * CV_E + 128), "l"(A.ssmk + (size_t)ch * S_LEN), "r"(nb), "r"(lb) : "memory");
                }
                __syncwarp();
            };
            sts32(cb + 8192 + lane * 4, 0u); sts32(cb + 8192 + CV_E + lane * 4, 0u);
            if (warp == 0) sts32(sb + CV_Z + lane * 4, 0u);
            uint32_t dv = 0;
            if (lane < 5) {
                prefetch_l2(A.ssmk + (size_t)((sp * 5 + lane) * 8 + warp) * S_LEN, 1024);
                dv = *reinterpret_cast<const unsigned short*>(A.ssmD + (sp * 5 + lane) * 8 + warp) * 0x10001u;
            }
            named_bar(8, 256);
            if (!CONV_DRY) fetch(0);
#pragma unroll 1
            for (int k = CONV_DRY ? -1 : 0; k < 25; k++) {
                const int ps = k < 0 ? 0 : k / 5, rg = ps ? ps - 1 : 0;
                const uint32_t Dv = __shfl_sync(0xffffffffu, dv, k - 5 * ps);
                const int tb = sp == 0 && tid == 0 && k >= -1 && k < 7 ? 72 + k * 8 : -1;
                SC(tb >= 0, tb);
                if (k >= 0) {
                    mwait(lb, k & 1);
                    SC(tb >= 0, tb + 1);
                    if (k - 5 * ps < 4) { fence_async_smem(); fetch(k + 1); }
                    SC(tb >= 0, tb + 2);
                }
                const uint32_t tt = sb + CV_T + (k & 1) * 8192;
                conv_unit(cb + (k & 1) * 4096, cb + 8192 + (k & 1) * CV_E, cb + 8192 + 2 * CV_E + 64, sb + CV_Z,
                          tt + warp * 1024 + (lane & 7) * 128 + (((lane >> 3) ^ (lane & 7) ^ warp) & 7) * 16, Dv, rg, ps ? 2 * ps : 1, lane, (uint32_t)A.h_target >> 8, tb);
                if (k >= 0) mwait(bb + B_OTE + (k & 1) * 16, ((k >> 1) & 1) ^ 1);
                named_bar(8, 256);
                {
                    const uint32_t la = tt + (lane & 7) * 1024 + warp * 128 + (((lane >> 3) ^ (lane & 7) ^ warp) & 7) * 16;
                    const uint4 v0 = ldsm4t(la), v1 = ldsm4t(la ^ 64);
                    const uint32_t ya = sb + CV_Y + (k & 1) * 8192 + (warp * 64 + (lane >> 3) * 8 + 7 - (lane & 7)) * 16;
                    stsm4(ya, v0.x, v0.y, v0.z, v0.w);
                    stsm4(ya + 512, v1.x, v1.y, v1.z, v1.w);
                }
                SC(tb >= 0, tb + 6);
                fence_async_smem();
                __syncwarp();
                if (k >= 0 && lane == 0) mbar_arrive(bb + B_OTF + (k & 1) * 8);
                if (k < 0 || (k - 5 * ps == 4 && k < 24)) fetch(k + 1);
                if (k == 0 && lane < 5) prefetch_l2(A.ssmk + (size_t)((sp * 5 + lane) * 8 + warp) * S_LEN + 512, 3072);
            }
            cluster_wait();
        }
    } else if (warp < 12) {
        asm volatile("setmaxnreg.dec.sync.aligned.u32 %0;" ::"n"(REG_T));
        const int w = warp & 3, c = w >> 1, hh = w & 1;
        const uint32_t lane0 = __shfl_sync(0xffffffffu, tid & 31, tid & 31);
        if (head) {
            const int tile0 = role * 4 * WTA, ntile = role == 2 ? 4 * WTC : 4 * WTA;
            const uint32_t wo = sb + O_WO;
            uint32_t mi[5][4];
#pragma unroll
            for (int i = 0; i < 5; i++)
#pragma unroll
                for (int q = 0; q < 4; q++) {
                    const unsigned short* mp = reinterpret_cast<const unsigned short*>(A.mem0) + 2 * q * DM + i * 128 + (tid & 127);
                    mi[i][q] = mp[0] | (uint32_t)mp[DM] << 16;
                }
            cluster_wait();
            named_bar(10, 384);
#pragma unroll
            for (int i = 0; i < 5; i++) {
                const int col = i * 128 + (tid & 127), kk = col >> 4, pr = (kk * 13) >> 6;
                const uint32_t ma = sb + O_MEM + ((((r >> 1) - pr) & 7) * 5 + kk - 5 * pr) * 512 + (col & 8) * 32 + (col & 7) * 16;
                sts128(ma, mi[i][0], mi[i][0], mi[i][1], mi[i][1]);
                sts128(ma + 128, mi[i][2], mi[i][2], mi[i][3], mi[i][3]);
            }
            fence_async_smem();
            named_arrive(11, 384);
            for (int i = tid & 127; i < ntile * 256; i += 128) {
                const int ti = i >> 8, p = (i >> 1) & 127, ch = i & 1;
                const int ks = p >> 4, kh = (p >> 3) & 1, e8 = p & 7;
                const int dim = 64 * (ks >> 2) + 16 * (e8 >> 1) + 8 * (e8 & 1) + 2 * (ks & 3) + kh;
                cp_async16(wo + ti * 4096 + p * 32 + ((ch ^ ((p >> 2) & 1)) << 4), A.Wo + (size_t)(h * DH + dim) * DM + (tile0 + ti) * 16 + ch * 8);
            }
            cp_commit();
            if (lane < 8) {
                const int u = 2 * (tile0 + w + 4 * (lane >> 1)) + (lane & 1), ow = u / 5;
                const int sl = u - 5 * ow;
                sts32(sb + O_TAB + w * 32 + lane * 4, mapa(sb + O_RED + (sl >> 1) * 2560 + (sl & 1) * 256 + hi * (sl < 4 ? 512 : 256), ow & 15));
            }
            cluster_arrive_relaxed(); cluster_wait();
            cp_wait<0>();
            named_bar(7, 128);
            const uint32_t wo_a = wo + w * 4096 + ((lane >> 4) * 8 + (lane & 7)) * 32 + ((((lane >> 3) & 1) ^ ((lane >> 2) & 1)) << 4);
            const uint32_t ob_0 = sb + (role == 2 ? O_PB : O_OBA) + (lane >> 4) * 2048 + ((lane >> 3) & 1) * 128 + ((lane & 7) ^ ((lane >> 1) & 4)) * 16;
            const float cs = 0.08838834764831845f * 1.4426950408889634f;
            auto w_frag = [&](auto four, int i) {
                return ldsm4t(wo_a + (i < 16 || decltype(four)::value == 4 ? (i >> 4) * 32768 + (i & 1) * 16384 + ((i >> 1) & 7) * 512 : 32768 + (i & 1) * 2048 + ((i >> 1) & 7) * 512));
            };
            auto w_pre = [&](auto four, auto pd, uint4* wf) {
#pragma unroll
                for (int i = 0; i < decltype(pd)::value; i++) wf[i] = w_frag(four, i);
            };
            auto w_run = [&](auto four, auto pd, auto rem_, uint4* wf, int t, const uint32_t ob_a, auto&& before_last) {
                constexpr int NTL = decltype(four)::value, PD = decltype(pd)::value, NF = 8 * NTL, NP = NTL > 2 ? 2 : 1;
                constexpr bool REMOTE = decltype(rem_)::value;
                const uint32_t ln = opq(lane0), l8 = (ln & 2) * 64 + (ln >> 2) * 16 + (ln & 1) * 8, rb = (bb + B_RED) & 0xFFFFFFu;
                auto slot = [](int i) { return i < 8 ? i : 8 - WR + (i - 8) % WR; };
                uint4 obr[8];
#pragma unroll
                for (int k = 0; k < 4; k++) obr[k] = ldsm4(ob_a + k * 256);
#pragma unroll
                for (int p = 0; p < NP; p++) {
                    const bool split = p == 1 && NTL == 3;
                    const int nk = split ? 4 : 8;
                    float d[4][4];
                    uint4 ta;
#pragma unroll
                    for (int i = 0; i < 16; i++) (&d[0][0])[i] = 0.f;
#pragma unroll
                    for (int ks = 0; ks < 8; ks++) {
                        if (ks >= nk) continue;
                        if (W_SKIP == 3 || (W_SKIP == 1 && REMOTE) || (W_SKIP == 2 && !REMOTE)) { if (ks == nk - 2) ta = lds128(sb + O_TAB + w * 32 + p * 16); if (REMOTE && p == 0 && ks == OBK) mwait(bb + B_OB + 64, t & 1); continue; }
                        if (p == 0 && ks == OBK) {
                            if (REMOTE) { mwait(bb + B_OB + 64, t & 1); TS(7); }
#pragma unroll
                            for (int k = 4; k < 8; k++) obr[k] = ldsm4(ob_a + k * 256);
                        }
                        if (ks == nk - 2) ta = lds128(sb + O_TAB + w * 32 + p * 16);
#pragma unroll
                        for (int u = 0; u < 2; u++) {
                            const int i = p * 16 + ks * 2 + u;
                            const uint4& o = obr[split && u ? ks + 4 : ks];
                            const uint4& f = wf[slot(i)];
                            if (WVOL) { mmav(d[2 * u], f.x, f.y, f.z, f.w, o.x, o.y); mmav(d[2 * u + 1], f.x, f.y, f.z, f.w, o.z, o.w); }
                            else { mmau(d[2 * u], f, o.x, o.y); mmau(d[2 * u + 1], f, o.z, o.w); }
                            if (i + WR >= 8 && i + WR < NF) wf[slot(i + WR)] = w_frag(four, i + WR);
                        }
                    }
                    if (p) TS(10); else TS(8);
                    if (p == NP - 1) before_last();
                    if (split) {
#pragma unroll
                        for (int i = 0; i < 4; i++) { d[0][i] += d[2][i]; d[1][i] += d[3][i]; }
                    }
                    st_async_v2(ta.x + l8, pack2(d[0][0], d[0][1]), pack2(d[1][0], d[1][1]), (ta.x & 0xFF000000u) | rb);
                    st_async_v2(ta.y + l8, pack2(d[0][2], d[0][3]), pack2(d[1][2], d[1][3]), (ta.y & 0xFF000000u) | rb);
                    if (!split) {
                        st_async_v2(ta.z + l8, pack2(d[2][0], d[2][1]), pack2(d[3][0], d[3][1]), (ta.z & 0xFF000000u) | rb);
                        st_async_v2(ta.w + l8, pack2(d[2][2], d[2][3]), pack2(d[3][2], d[3][3]), (ta.w & 0xFF000000u) | rb);
                    }
                }
            };
            if (role != 2) {
#pragma unroll 1
                for (int t = 0; t < NT; t++) {
                    const uint32_t lane = opq(lane0);
                    const uint32_t dc = mapa(sb, hi * 3 + 2), dp = mapa(sb, hi * 3 + (role ^ 1));
                    const uint32_t qa = sb + O_QRY + c * 5120 + (lane & 7) * 128;
                    const uint32_t sw = (((lane >> 3) ^ (lane & 7)) << 4) ^ (c << 6);
                    {
                        const uint32_t ka = qa + 10240;
                        const uint32_t kt = sb + O_KEY + c * 5120 + (lane & 15) * 128, kx = (((lane >> 4) ^ (lane & 7)) << 4) ^ (c << 6);
                        const uint32_t sd = dc + O_SM + role * 1536 + c * 768 + lane * 4, sbar = dc + O_BAR + B_SM;
                        const uint32_t ta = sb + O_QRY + c * 5120 + (8 + 16 * hh + ((lane & 15) ^ (role * 8))) * 128;
                        uint4 a[4], f[4];
                        named_bar(13, 384);
#pragma unroll
                        for (int i = 0; i < 4; i++) f[i] = ldsm4(kt + 1024 + hh * 2048 + (kx ^ (i << 5) ^ (hh << 6)));
#pragma unroll
                        for (int i = 0; i < 4; i++) a[i] = ldsm4(ta + (kx ^ (i << 5)));
                        const uint32_t kd = ka + (1 + 2 * hh) * 1024 + sw;
                        uint4 k[5];
                        k[1] = ldsm4(kd); k[2] = ldsm4(kd + 1024);
                        {
                            const uint32_t qh = qa + (sw ^ (hh << 6)), kh = kt + (kx ^ (hh << 6));
                            named_bar(1, 384);
                            const uint4 q0 = ldsm4(qh), g0 = ldsm4(kh), g1 = ldsm4(kh ^ 32), q1 = ldsm4(qh ^ 64);
                            float s0[4] = {0.f, 0.f, 0.f, 0.f}, s1[4] = {0.f, 0.f, 0.f, 0.f}, s2[4] = {0.f, 0.f, 0.f, 0.f}, s3[4] = {0.f, 0.f, 0.f, 0.f};
                            mmav(s0, f[0].x, f[0].y, f[0].z, f[0].w, q0.x, q0.y); mmav(s1, f[1].x, f[1].y, f[1].z, f[1].w, q0.z, q0.w);
                            mmav(s2, g0.x, g0.y, g0.z, g0.w, q0.x, q0.y); mmav(s3, g1.x, g1.y, g1.z, g1.w, q0.z, q0.w);
                            mmav(s0, f[2].x, f[2].y, f[2].z, f[2].w, q1.x, q1.y); mmav(s1, f[3].x, f[3].y, f[3].z, f[3].w, q1.z, q1.w);
                            k[0] = ldsm4(ka + sw); k[3] = ldsm4(ka + 1024 + sw); k[4] = ldsm4(ka + 2048 + sw);
                            st_async_b32(sd + hh * 128, pack2(s2[0] + s3[0], s2[1] + s3[1]), sbar);
                            st_async_b32(sd + 256 + hh * 256, pack2(s0[0] + s1[0], s0[1] + s1[1]), sbar);
                            st_async_b32(sd + 384 + hh * 256, pack2(s0[2] + s1[2], s0[3] + s1[3]), sbar);
                        }
                        TS(1);
                        float u[5][4];
#pragma unroll
                        for (int i = 0; i < 20; i++) (&u[0][0])[i] = 0.f;
                        auto half = [&](auto nn, const uint4& a0, const uint4& a1, bool more) {
                            constexpr int NU = decltype(nn)::value;
                            constexpr int ord[5] = {1, 2, 0, 3, 4};
#pragma unroll
                            for (int i = 0; i < NU; i++) mmav(u[ord[i]], a0.x, a0.y, a0.z, a0.w, k[ord[i]].x, k[ord[i]].y);
#pragma unroll
                            for (int i = 0; i < NU; i++) {
                                const int n = ord[i];
                                mmav(u[n], a1.x, a1.y, a1.z, a1.w, k[n].z, k[n].w);
                                if (more) k[n] = ldsm4(((n == 0 ? ka + sw : (n < 3 ? kd + (n - 1) * 1024 : ka + (n - 2) * 1024 + sw))) ^ 64);
                            }
                        };
                        auto fu = [](float x) { return __float_as_uint(x); };
                        const uint32_t so = O_ST + c * 2048 + hh * 768, td = dp + so, tb = dp + O_BAR + B_ST, lo = sb + so + 4096;
                        if (hh) {
                            half(IC<5>{}, a[0], a[1], true); half(IC<5>{}, a[2], a[3], false);
                            st_async_v4(td + lane * 16, fu(u[0][2]), fu(u[0][3]), fu(u[1][2]), fu(u[1][3]), tb);
                            st_async_v4(td + 512 + lane * 16, fu(u[2][2]), fu(u[2][3]), fu(u[3][2]), fu(u[3][3]), tb);
                            st_async_v2(td + 1024 + lane * 8, fu(u[4][2]), fu(u[4][3]), tb);
                            sts128(lo + lane * 16, fu(u[0][0]), fu(u[0][1]), fu(u[1][0]), fu(u[1][1]));
                            sts128(lo + 512 + lane * 16, fu(u[2][0]), fu(u[2][1]), fu(u[3][0]), fu(u[3][1]));
                            sts64(lo + 1024 + lane * 8, fu(u[4][0]), fu(u[4][1]));
                        } else {
                            half(IC<3>{}, a[0], a[1], true); half(IC<3>{}, a[2], a[3], false);
                            st_async_v4(td + lane * 16, fu(u[0][2]), fu(u[0][3]), fu(u[1][2]), fu(u[1][3]), tb);
                            st_async_v2(td + 512 + lane * 8, fu(u[2][2]), fu(u[2][3]), tb);
                            sts128(lo + lane * 16, fu(u[0][0]), fu(u[0][1]), fu(u[1][0]), fu(u[1][1]));
                            sts64(lo + 512 + lane * 8, fu(u[2][0]), fu(u[2][1]));
                        }
                        if (t < NT - 1) named_arrive(2, 384);
                        __syncwarp();
                        if (lane == 0) mbar_arrive(bb + B_ST);
                        TS(2);
                    }
                    if (t == NT - 1) break;
                    uint4 wf[PDA];
                    w_pre(IC<WTA>{}, IC<PDA>{}, wf);
                    mwait(bb + B_OB, t & 1);
                    TS(3);
                    named_bar(3, 384);
                    w_run(IC<WTA>{}, IC<PDA>{}, IC<1>{}, wf, t, ob_0, []() {});
                    named_arrive(4, NB4);
                    if (w == 0 && lane == 0) { mbar_expect_tx(bb + B_OB, 2048); mbar_expect_tx(bb + B_OB + 64, 2048); }
                    TS(5);
                }
            } else {
#pragma unroll 1
                for (int t = 0; t < NT; t++) {
                    const uint32_t lane = opq(lane0);
                    const int g = lane >> 2, tq = lane & 3;
                    const uint32_t vm_a = sb + O_VM + (g * 4 + 2 * (tq & 1) + (c ^ ((g >> 1) & 1))) * 16 + (tq >> 1) * 8;
                    const uint32_t vt_a = sb + O_VT + (t & 1) * 16384 + ((lane >> 3) & 1) * 512 + (lane >> 4) * 128 + (lane & 7) * 16;
                    named_bar(13, 384);
                    uint4 va[4][2];
#pragma unroll
                    for (int i = 0; i < 4; i++) {
                        va[i][0] = ldsm4(vt_a + c * 8192 + (4 * hh + i) * 1024);
                        va[i][1] = ldsm4(vt_a + c * 8192 + (4 * hh + i) * 1024 + 256);
                    }
                    const uint32_t sa = opq(sb + O_SM + c * 768 + 256 + lane * 16), sa2 = opq(sb + O_SM + c * 768 + (lane & 15) * 16 + (lane >> 4) * 1536), vm_b = opq(vm_a + hh * 2048);
                    named_bar(1, 384);
                    if (__builtin_expect(t < NT - 1, 1)) {
                        uint2 vm[4];
#pragma unroll
                        for (int i = 0; i < 4; i++) vm[i] = lds64(vm_b + i * 512);
                        mwait(bb + B_SM, t & 1);
                        TS(1);
                        const uint4 x0 = ldsm4t(sa), y0 = ldsm4t(sa + 1536), x1 = ldsm4t(sa2);
                        float s[10];
                        s[2] = blo(x0.x) + blo(y0.x); s[3] = bhi(x0.x) + bhi(y0.x); s[4] = blo(x0.y) + blo(y0.y); s[5] = bhi(x0.y) + bhi(y0.y);
                        s[6] = blo(x0.z) + blo(y0.z); s[7] = bhi(x0.z) + bhi(y0.z); s[8] = blo(x0.w) + blo(y0.w); s[9] = bhi(x0.w) + bhi(y0.w);
                        s[0] = (blo(x1.x) + blo(x1.y)) + (blo(x1.z) + blo(x1.w)); s[1] = (bhi(x1.x) + bhi(x1.y)) + (bhi(x1.z) + bhi(x1.w));
                        float mx = fmaxf(fmaxf(fmaxf(s[0], s[1]), fmaxf(s[2], s[3])), fmaxf(fmaxf(fmaxf(s[4], s[5]), fmaxf(s[6], s[7])), fmaxf(s[8], s[9])));
                        const float m1 = __shfl_xor_sync(0xffffffffu, mx, 1), m2 = __shfl_xor_sync(0xffffffffu, mx, 2), m3 = __shfl_xor_sync(0xffffffffu, mx, 3);
                        mx = fmaxf(fmaxf(mx, m1), fmaxf(m2, m3)) * -cs;
                        uint32_t pb[5];
#pragma unroll
                        for (int i = 0; i < 5; i++) pb[i] = pack2(ex2f(fmaf(s[2 * i], cs, mx)), ex2f(fmaf(s[2 * i + 1], cs, mx)));
                        TS(9);
                        named_bar(3, 384);
                        float o[5][4];
#pragma unroll
                        for (int i = 0; i < 20; i++) (&o[0][0])[i] = 0.f;
                        const uint32_t one2 = 0x3F803F80u;
                        float z[2][4] = {{0.f, 0.f, 0.f, 0.f}, {0.f, 0.f, 0.f, 0.f}};
                        mmav8(o[4], one2, one2, pb[0]);
                        mmav(z[0], one2, one2, one2, one2, pb[1], pb[2]);
                        mmav(z[1], one2, one2, one2, one2, pb[3], pb[4]);
#pragma unroll
                        for (int i = 0; i < 4; i++) mmav8(o[i], vm[i].x, vm[i].y, pb[0]);
#pragma unroll
                        for (int i = 0; i < 4; i++) mmav(o[i], va[i][0].x, va[i][0].y, va[i][0].z, va[i][0].w, pb[1], pb[2]);
#pragma unroll
                        for (int i = 0; i < 4; i++) mmav(o[i], va[i][1].x, va[i][1].y, va[i][1].z, va[i][1].w, pb[3], pb[4]);
                        o[4][0] += z[0][0] + z[1][0]; o[4][1] += z[0][1] + z[1][1];
                        uint4 wf[PDC];
                        w_pre(IC<WTC>{}, IC<PDC>{}, wf);
                        const float r0 = rcpf(o[4][0]), r1 = rcpf(o[4][1]);
                        const uint32_t oo = c * 2048 + hh * 1024 + g * 128 + tq * 16 + (g & 1) * 64;
                        uint32_t e0[4], e1[4];
#pragma unroll
                        for (int i = 0; i < 4; i++) { e0[i] = pack2(o[i][0] * r0, o[i][2] * r0); e1[i] = pack2(o[i][1] * r1, o[i][3] * r1); }
                        sts128(sb + O_PB + (~t & 1) * 5120 + oo, e0[0], e0[1], e0[2], e0[3]);
                        sts128(sb + O_PB + (~t & 1) * 5120 + (oo ^ 64), e1[0], e1[1], e1[2], e1[3]);
                        {
                            const uint32_t da = mapa(sb + O_OBA, r - 2) + oo, ba = mapa(bb + B_OB + hh * 64, r - 2);
                            if (O_DLY) { named_bar(7, 128); if (hh) delay(O_DLY); }
                            st_async_v4(da, e0[0], e0[1], e0[2], e0[3], ba);
                            st_async_v4(da + 0x01000000u, e0[0], e0[1], e0[2], e0[3], ba + 0x01000000u);
                            st_async_v4(da ^ 64, e1[0], e1[1], e1[2], e1[3], ba);
                            st_async_v4((da ^ 64) + 0x01000000u, e1[0], e1[1], e1[2], e1[3], ba + 0x01000000u);
                        }
                        TS(3);
                        if (!O_DLY) named_bar(7, 128);
                        w_run(IC<WTC>{}, IC<PDC>{}, IC<0>{}, wf, t, ob_0 + (~t & 1) * 5120, []() {});
                        named_arrive(4, NB4);
                        mwait(bb + B_ST, t & 1);
                        TS(4);
                    } else { mwait(bb + B_SM, t & 1); mwait(bb + B_ST, t & 1); }
                    TS(5);
                    fence_async_smem();
                    if (TPV_LATE && t < NT - 1) named_bar(6, 224);
#pragma unroll 1
                    for (int l = t < NSEG ? 0 : 1; l < (t >= LAG ? 2 : 1); l++) {
                        const uint32_t pb_ = ((1024 + O_PB) >> 4) + (t & 1) * 320 + l * 160, va_ = (((1024 + O_VT) >> 4) + (t & 1) * 1024 + l * 512) | (8u << 16);
                        const uint32_t oa = sb + O_VT + (t & 1) * 16384 + l * 8192 + w * 1024 + g * 64 + ((tq ^ (g >> 1)) & 3) * 16;
                        const uint32_t vl = (vm_a ^ ((l ^ c) << 4)) + w * 512;
                        const uint2 a0 = lds64(vl), a1 = lds64(vl + 2048);
                        float d[2][16];
                        wg_fence();
                        wg_n32_first(d[0], a0.x, a0.y, 0u, 0u, mkdesc(pb_, 8));
                        wg_n32_first(d[1], a1.x, a1.y, 0u, 0u, mkdesc(pb_, 8));
#pragma unroll
                        for (int i = 0; i < 4; i++) wg_n32_kk(d[i & 1], mkdesc(va_ + (i & 1) * 256 + (i >> 1) * 16, 32), mkdesc(pb_ + 32 + (i >> 1) * 64 + (32u << 16), 8));
                        wg_commit();
                        if (l) TS(13); else TS(11);
                        wg_wait<0>();
                        if (l) TS(14); else TS(12);
                        if (O0_EARLY == 2 && l == (t < NSEG ? 0 : 1)) {
                            uint4* og = g_ot + (rslot(l, t - l * LAG) * 256 + h * 8 + w) * 64 + g * 4 + ((tq ^ (g >> 1)) & 3);
#pragma unroll
                            for (int mt = 0; mt < 2; mt++) {
                                og[mt * 256] = make_uint4(pack2(d[mt][0], d[mt][1]), pack2(d[mt][4], d[mt][5]), pack2(d[mt][8], d[mt][9]), pack2(d[mt][12], d[mt][13]));
                                og[mt * 256 + 32] = make_uint4(pack2(d[mt][2], d[mt][3]), pack2(d[mt][6], d[mt][7]), pack2(d[mt][10], d[mt][11]), pack2(d[mt][14], d[mt][15]));
                            }
                            __syncwarp();
                            if (lane == 0) mbar_arrive(bb + B_OTF + 8);
                            continue;
                        }
#pragma unroll
                        for (int mt = 0; mt < 2; mt++) {
                            sts128(oa + mt * 4096, pack2(d[mt][0], d[mt][1]), pack2(d[mt][4], d[mt][5]), pack2(d[mt][8], d[mt][9]), pack2(d[mt][12], d[mt][13]));
                            sts128(oa + mt * 4096 + 512, pack2(d[mt][2], d[mt][3]), pack2(d[mt][6], d[mt][7]), pack2(d[mt][10], d[mt][11]), pack2(d[mt][14], d[mt][15]));
                        }
                        if (O0_EARLY == 1 && l == 0) {
                            fence_async_smem();
                            __syncwarp();
                            if (lane == 0) mbar_arrive(bb + B_OTF + 8);
                        }
                    }
                    TS(6);
                    if (w == 0 && lane == 0) { mbar_expect_tx(bb + B_ST, 5120); mbar_expect_tx(bb + B_SM, 3072); }
                    fence_async_smem();
                    __syncwarp();
                    if (lane == 0) mbar_arrive(bb + B_OTF);
                    if (t < NT - 1) named_arrive(5, 384);
                }
            }
        } else {
            cluster_wait(); cluster_arrive_relaxed();
            const int wi = sp * 4 + w, half = wi >> 5, tok = wi & 31, ep = ld_relaxed(&g_epoch) + 1;
            GT(lane == 0, 89);
            if (lane < LN0_AHEAD / 2) prefetch_l2(A.x + (size_t)((half + 2 * lane) * SEG + tok) * DM, 1280);
#pragma unroll 1
            for (int k = -LN0_AHEAD / 2; k < NT; k++) {
                const int s0 = k < 0 ? 2 * k + LN0_AHEAD + half : (half ? k + LN0_AHEAD : NSEG);
                if (s0 < NSEG) { ln0_row(A.x, s0, tok, lane); GT(lane == 0 && k < 0, 30 + s0); }
                if (k == -1 && half) {
#pragma unroll 1
                    for (int u = 320 + tok; u < 640; u += 32) u_half(A.Bk, A.Bv, A.shiftk, u, lane);
                    __syncwarp();
                    if (lane == 0) red_release(FLG(F_U + 1), 1);
                }
                const int n = k - half * LAG;
                if ((POST_DRY && k == -LN0_AHEAD / 2 + 1) || (n >= 0 && n < NSEG && k >= 0)) {
                    post_row(half, k < 0 ? 0 : n, tok, lane, A.x, A.out, k < 0 ? 0 : ep);
                    GT(lane == 0 && (n & 3) == 0 && k >= 0, 460 + half * 16 + (n >> 2)); GT(lane == 0 && n == 63 && half, 40);
                }
            }
            cluster_wait();
        }
    } else {
        asm volatile("setmaxnreg.dec.sync.aligned.u32 %0;" ::"n"(REG_X));
        cluster_wait();
        const int s = warp - 12;
        const uint32_t lane0 = __shfl_sync(0xffffffffu, tid & 31, tid & 31);
        if (s < 3) {
            cluster_arrive_relaxed();
            GT(lane == 0, 84);
            if (blockIdx.x * 3 + s < 320) {
                u_half(A.Bk, A.Bv, A.shiftk, blockIdx.x * 3 + s, lane);
                GT(lane == 0, 85);
                __syncwarp();
                if (lane == 0) red_release(FLG(F_U), 1);
                GT(lane == 0, 4);
            }
            const int ztgt = 3 * 16 * NCL * (ld_relaxed(&g_epoch) + 1);
#pragma unroll
            for (int i = 0; i < XRS; i++) st_relaxed_v4(g_xc + ((i * 16 + r) * 3 + s) * 256 + cq * 32 + lane, 0, 0, 0, 0);
            __syncwarp();
            if (lane == 0) red_release(FLG(F_Z), 1);
            cluster_wait();
            constexpr uint32_t XSLOT = 16 * 3 * 4096;
            uint32_t xo_ = (r * 3 + s) * 4096;
            if (s == 0) {
                const uint32_t G = lane >> 1, d = ((r + 2 * G) & 15) ^ (lane & 1);
                const bool ok = lane < 16 && d < 3 * nh;
                const uint32_t pos = __popc(__ballot_sync(0xffffffffu, ok) & ((1u << lane) - 1u));
                if (ok) { sts32(sb + O_BT + pos * 8, (d << 24) + G * 2560); sts32(sb + O_BT + pos * 8 + 4, mapa(bb + B_MEM + G * 8, d)); }
            }
            while (ld_acquire(FLG(F_Z)) < ztgt) __nanosleep(100);
            named_bar(14, 96);
#pragma unroll 1
            for (int t = 0; t < NT; t++) {
                const uint32_t lane = opq(lane0);
                if (head && role != 2) {
                    auto soft = [&](auto uu, auto vv, int c0, int hh) {
                        constexpr int U = decltype(uu)::value, NV = decltype(vv)::value;
                        const uint32_t dc = mapa(sb, hi * 3 + 2), sa = sb + O_ST + c0 * 2048 + hh * 768;
                        const uint32_t pd = dc + O_PB + (t & 1) * 5120 + c0 * 2560 + (2 * hh + role) * 128 + lane * 4, pbar = dc + O_BAR + B_ST;
                        const int lim = 8 * role + (int)(lane >> 2) - 2 * (int)(lane & 3);
                        auto uf = [](uint32_t x) { return __uint_as_float(x); };
                        mwait(bb + B_ST, t & 1);
                        if (H1_LATE == 2 && r == 1 && U == 2 && t >= LAG - 1 && t < NT - 1) named_arrive(12, 64);
                        uint32_t z[U][NV];
                        auto zz = [](float x, float y) { const uint32_t w = pack2(x, y); return pack2(blo(w) * 0.08838834764831845f, bhi(w) * 0.08838834764831845f); };
#pragma unroll
                        for (int i = 0; i < U; i++) {
                            const uint4 v = lds128(sa + i * 2048 + lane * 16), w = lds128(sa + i * 2048 + 4096 + lane * 16);
                            z[i][0] = zz(uf(v.x) + uf(w.x), uf(v.y) + uf(w.y));
                            z[i][1] = zz(lim < 0 ? -INFINITY : uf(v.z) + uf(w.z), lim < 1 ? -INFINITY : uf(v.w) + uf(w.w));
                            if (NV == 3) {
                                const uint2 x = lds64(sa + i * 2048 + 512 + lane * 8), y = lds64(sa + i * 2048 + 4608 + lane * 8);
                                z[i][2] = zz(lim < 8 ? -INFINITY : uf(x.x) + uf(y.x), lim < 9 ? -INFINITY : uf(x.y) + uf(y.y));
                            } else {
                                const uint4 x = lds128(sa + 512 + lane * 16), y = lds128(sa + 4608 + lane * 16);
                                const uint2 p = lds64(sa + 1024 + lane * 8), q = lds64(sa + 5120 + lane * 8);
                                z[i][2] = zz(lim < 8 ? -INFINITY : uf(x.x) + uf(y.x), lim < 9 ? -INFINITY : uf(x.y) + uf(y.y));
                                z[i][NV - 2] = zz(uf(x.z) + uf(y.z), uf(x.w) + uf(y.w));
                                z[i][NV - 1] = zz(uf(p.x) + uf(q.x), uf(p.y) + uf(q.y));
                            }
                        }
                        const float l2e = 1.4426950408889634f;
                        float e[U][2 * NV], sum[U];
#pragma unroll
                        for (int i = 0; i < U; i++) {
                            uint32_t zm = bmax2(bmax2(z[i][0], z[i][1]), z[i][2]);
                            if (NV == 5) zm = bmax2(zm, bmax2(z[i][NV - 2], z[i][NV - 1]));
                            zm = bmax2(zm, __shfl_xor_sync(0xffffffffu, zm, 1));
                            zm = bmax2(zm, __shfl_xor_sync(0xffffffffu, zm, 2));
                            const float mx = fmaxf(blo(zm), bhi(zm)) * -l2e;
                            sum[i] = 0.f;
#pragma unroll
                            for (int n = 0; n < NV; n++) { e[i][2 * n] = ex2f(fmaf(blo(z[i][n]), l2e, mx)); e[i][2 * n + 1] = ex2f(fmaf(bhi(z[i][n]), l2e, mx)); }
                            sum[i] = ((e[i][0] + e[i][1]) + (e[i][2] + e[i][3])) + (e[i][4] + e[i][5]);
                            if (NV == 5) sum[i] += (e[i][2 * NV - 4] + e[i][2 * NV - 3]) + (e[i][2 * NV - 2] + e[i][2 * NV - 1]);
                            sum[i] += __shfl_xor_sync(0xffffffffu, sum[i], 1);
                            sum[i] += __shfl_xor_sync(0xffffffffu, sum[i], 2);
                            sum[i] = rcpf(sum[i]);
                        }
#pragma unroll
                        for (int i = 0; i < U; i++)
#pragma unroll
                            for (int n = 0; n < 5; n++)
                                st_async_b32(pd + i * 2560 + (n == 0 ? 0 : (NV == 3 ? n : (n < 3 ? n + 2 : n - 2)) * 512), n < NV ? pack2(e[i][2 * n] * sum[i], e[i][2 * n + 1] * sum[i]) : 0u, pbar);
                    };
                    if (s < 2) soft(IC<1>{}, IC<5>{}, s, 1); else soft(IC<2>{}, IC<3>{}, 0, 0);
                    TS(12);
                    named_bar(14, 96);
                    if (s == 0 && lane == 0) mbar_expect_tx(bb + B_ST, 4096);
                    if (H1_LATE == 1 && r == 1 && s == 0 && t >= LAG - 1 && t < NT - 1) named_arrive(12, 64);
                }
                if (t == NT - 1) break;
                uint32_t m0 = 0x80008000u, m1 = 0x80008000u;
                if (t < LAG && cq == 0) {
                    const uint32_t ch = s < 2 ? lane : lane >> 1;
                    const unsigned short* mp = reinterpret_cast<const unsigned short*>(A.mem0) + (((ch >> 3) & 1) * 4 + (s < 2 ? 0 : (lane & 1) * 2)) * DM + (5 * r + 2 * s + (ch >> 4)) * 8 + (ch & 7);
                    m0 = max(mp[0] | (uint32_t)mp[DM] << 16, 1u);
                    if (s < 2) m1 = max(mp[2 * DM] | (uint32_t)mp[3 * DM] << 16, 1u);
                }
                const bool late = t >= LAG;
                auto sum5 = [](uint32_t a, uint32_t b, uint32_t c, uint32_t d, uint32_t e) { return nz(badd(badd(badd(a, b), e), badd(c, d))); };
                auto sum7 = [](uint32_t a, uint32_t b, uint32_t c, uint32_t d, uint32_t e, uint32_t f, uint32_t h_) {
                    return badd(badd(badd(a, b), badd(c, d)), badd(badd(e, f), h_));
                };
                auto min3 = [](uint32_t a, uint32_t b, uint32_t c) { return min(min(a, b), c); };
                auto bcast = [&](auto two, const uint32_t aa, uint32_t x0, uint32_t x1, uint32_t x2, uint32_t x3) {
                    auto send = [&](uint32_t o, uint32_t bar) { if (decltype(two)::value) st_async_v4(aa + o, x0, x1, x2, x3, bar); else st_async_v2(aa + o, x0, x1, bar); };
                    const uint32_t tb0 = clk32();
                    auto pace = [&](int k) { if (BP) while (__any_sync(0xffffffffu, clk32() - tb0 < (uint32_t)(k * BP))) {} };
                    uint4 e[6];
                    e[0] = lds128(sb + O_BT);
                    TS(8);
                    send(e[0].x, e[0].y); send(e[0].z, e[0].w);
                    TS(9);
                    if (BNS) __nanosleep(BNS);
#pragma unroll
                    for (int i = 1; i < 6; i++) e[i] = lds128(sb + O_BT + i * 16);
#pragma unroll
                    for (int i = 1; i < 6; i++) { pace(i); send(e[i].x, e[i].y); send(e[i].z, e[i].w); }
                    if (nh == 5) {
                        const uint4 f0 = lds128(sb + O_BT + 96);
                        const uint2 f1 = lds64(sb + O_BT + 112);
                        pace(6); send(f0.x, f0.y); send(f0.z, f0.w); pace(7); send(f1.x, f1.y);
                    }
                };
                const uint32_t ma = (sb + O_MEM + (5 * (r & 1) + 2 * s) * 256) & 0xFFFFFFu;
                int guard = 0;
                if (s < 2) {
                    const uint32_t ra = sb + O_RED + s * 2560 + lane * 16;
                    uint4* xb = reinterpret_cast<uint4*>(reinterpret_cast<char*>(g_xc) + xo_ + lane * 16);
                    uint4* xo = xb + cq * 32;
                    touch(xo); touch(xb);
                    mwait(bb + B_RED, t & 1);
                    TS(0);
                    uint4 p[5];
#pragma unroll
                    for (int i = 0; i < 5; i++) p[i] = i < 4 || nh == 5 ? lds128(ra + i * 512) : make_uint4(0, 0, 0, 0);
                    const uint32_t u1 = sum5(p[0].y, p[1].y, p[2].y, p[3].y, p[4].y), u3 = sum5(p[0].w, p[1].w, p[2].w, p[3].w, p[4].w);
                    st_relaxed_v4(xo, sum5(p[0].x, p[1].x, p[2].x, p[3].x, p[4].x), late ? u1 : m0, sum5(p[0].z, p[1].z, p[2].z, p[3].z, p[4].z), late ? u3 : m1);
                    TS(1);
                    if (QUIET && head) named_arrive(4, NB4);
                    delay(XD);
                    uint4 x[NCL];
                    while (true) {
                        ld7_relaxed(x, xb);
                        const uint32_t mn = min3(min3(min3(x[0].x, x[0].y, x[0].z), min3(x[0].w, x[1].x, x[1].y), min3(x[1].z, x[1].w, x[2].x)),
                                                 min3(min3(x[2].y, x[2].z, x[2].w), min3(x[3].x, x[3].y, x[3].z), min3(x[3].w, x[4].x, x[4].y)),
                                                 min3(min3(x[4].z, x[4].w, x[5].x), min3(x[5].y, x[5].z, x[5].w), min(min3(x[6].x, x[6].y, x[6].z), x[6].w)));
                        if (NO_X || __all_sync(0xffffffffu, mn != 0)) break;
                        if (++guard > 2000000) __trap();
                    }
                    TS(2);
                    TV(4, guard);
                    bcast(IC<1>{}, ma + lane * 16, sum7(x[0].x, x[1].x, x[2].x, x[3].x, x[4].x, x[5].x, x[6].x), sum7(x[0].y, x[1].y, x[2].y, x[3].y, x[4].y, x[5].y, x[6].y),
                          sum7(x[0].z, x[1].z, x[2].z, x[3].z, x[4].z, x[5].z, x[6].z), sum7(x[0].w, x[1].w, x[2].w, x[3].w, x[4].w, x[5].w, x[6].w));
                } else {
                    const uint32_t ra = sb + O_RED + 5120 + lane * 8;
                    uint2* xb = reinterpret_cast<uint2*>(reinterpret_cast<char*>(g_xc) + xo_ + lane * 8);
                    uint2* xo = xb + cq * 64;
                    touch(xo); touch(xb);
                    mwait(bb + B_RED, t & 1);
                    TS(0);
                    uint2 p[5];
#pragma unroll
                    for (int i = 0; i < 5; i++) p[i] = i < 4 || nh == 5 ? lds64(ra + i * 256) : make_uint2(0, 0);
                    const uint32_t u1 = sum5(p[0].y, p[1].y, p[2].y, p[3].y, p[4].y);
                    st_relaxed_v2(xo, sum5(p[0].x, p[1].x, p[2].x, p[3].x, p[4].x), late ? u1 : m0);
                    if (lane == 0) mbar_expect_tx(bb + B_RED, nh * 1280);
                    TS(1);
                    if (QUIET && head) named_arrive(4, NB4);
                    delay(XD);
                    uint32_t y0, y1;
                    while (true) {
                        uint2 x[NCL];
                        ld7_relaxed(x, xb);
                        const uint32_t mn = min3(min3(min3(x[0].x, x[0].y, x[1].x), min3(x[1].y, x[2].x, x[2].y), min3(x[3].x, x[3].y, x[4].x)), min3(x[4].y, x[5].x, x[5].y), min(x[6].x, x[6].y));
                        y0 = sum7(x[0].x, x[1].x, x[2].x, x[3].x, x[4].x, x[5].x, x[6].x); y1 = sum7(x[0].y, x[1].y, x[2].y, x[3].y, x[4].y, x[5].y, x[6].y);
                        if (NO_X || __all_sync(0xffffffffu, mn != 0)) break;
                        if (++guard > 2000000) __trap();
                    }
                    TS(2);
                    TV(4, guard);
                    bcast(IC<0>{}, ma + lane * 8, y0, y1, 0u, 0u);
                }
                TS(3);
                if ((OT_LATE || TPV_LATE) && head && role == 2) named_arrive(6, TPV_LATE ? 224 : 128);
                xo_ += XSLOT; if (xo_ >= XRS * XSLOT) xo_ -= XRS * XSLOT;
                {
                    const uint32_t zo = xo_ + XSLOT >= XRS * XSLOT ? xo_ + XSLOT - XRS * XSLOT : xo_ + XSLOT;
                    char* zp = reinterpret_cast<char*>(g_xc) + zo + cq * 512 + lane * 16;
                    st_relaxed_v4(zp, 0, 0, 0, 0);
                    if (ld_relaxed_v4(zp).x) __trap();
                }
            }
        } else if (r < 2) {
            const uint16_t mask = (uint16_t)((1u << (3 * nh)) - 1u);
            const int htgt = A.h_target * (ld_relaxed(&g_epoch) + 1);
#pragma unroll 1
            for (int n = 0; n < NSEG; n++) {
                if (n == (r == 0 ? 1 : 0)) { cluster_arrive(); cluster_wait(); }
                int guard = 0;
                while (ld_acquire(FLG(F_H + r * 64 + n)) < htgt) { if (++guard > 2000000) __trap(); __nanosleep(40); }
                fence_async_global();
                if (H1_LATE && r == 1) named_bar(12, 64);
                if (n) mwait(bb + B_HE, (n - 1) & 1);
                if (lane < 8)
                    asm volatile("cp.async.bulk.shared::cluster.global.mbarrier::complete_tx::bytes.multicast::cluster [%0], [%1], %2, [%3], %4;" ::"r"(sb + O_H + r * 40960 + lane * 5120),
                                 "l"(g_ht + rslot(r, n) * 2560 + lane * 320), "r"(HBYTES), "r"(bb + B_HF + r * 8), "h"(mask) : "memory");
                __syncwarp();
            }
        } else {
            cluster_arrive(); cluster_wait();
            if (head && role == 2) {
#pragma unroll 1
                for (int t = 0; t < NT; t++) {
                    auto put = [&](int l, int n) {
                        asm volatile("cp.async.bulk.global.shared::cta.bulk_group [%0], [%1], %2;" ::"l"(g_ot + (rslot(l, n) * 256 + h * 8) * 64), "r"(sb + O_VT + (t & 1) * 16384 + l * 8192), "r"(8192) : "memory");
                        asm volatile("cp.async.bulk.commit_group;" ::: "memory");
                    };
                    auto publish = [&](int l, int n) {
                        asm volatile("cp.async.bulk.wait_group 0;" ::: "memory");
                        fence_async_global();
                        red_release(FLG(F_O + l * 64 + n) + (h >> 3), 1);
                        GT(true, 200 + l * 64 + n);
                    };
                    if (O0_EARLY == 2) {
                        const int l = t < NSEG ? 0 : 1;
                        mwait(bb + B_OTF + 8, t & 1);
                        if (lane == 0) { red_release(FLG(F_O + l * 64 + t - l * LAG) + (h >> 3), 1); GT(true, 200 + l * 64 + t - l * LAG); }
                        __syncwarp();
                    }
                    if (O0_EARLY == 1 && t < NSEG) {
                        mwait(bb + B_OTF + 8, t & 1);
                        if (lane == 0) { put(0, t); publish(0, t); }
                        __syncwarp();
                    }
                    mwait(bb + B_OTF, t & 1);
                    if (OT_LATE && !TPV_LATE && t < NT - 1) named_bar(6, 128);
                    const int l = lane & 1, n = t - l * LAG;
                    const bool mine = lane < 2 && n >= 0 && n < NSEG && (l || !O0_EARLY) && (O0_EARLY < 2 || t < NSEG);
                    if (mine) {
                        put(l, n);
                        asm volatile("cp.async.bulk.wait_group.read 0;" ::: "memory");
                    }
                    __syncwarp();
                    if (lane == 0) mbar_arrive(bb + B_OTE);
                    if (mine) publish(l, n);
                    __syncwarp();
                }
            }
            if (!head && lane == 0) {
#pragma unroll 1
                for (int k = 0; k < 25; k++) {
                    const int rg = k / 5, r0 = rg == 1 ? 256 : 0;
                    mwait(bb + B_OTF + (k & 1) * 8, (k >> 1) & 1);
                    asm volatile("cp.async.bulk.global.shared::cta.bulk_group [%0], [%1], %2;" ::"l"(g_Y + (sp * 5 + k - 5 * rg) * S_LEN + (rg ? rg - 1 : 0) * 512 + r0),
                                 "r"(sb + CV_Y + (k & 1) * 8192 + r0 * 16), "r"(rg < 2 ? 4096 : 8192) : "memory");
                    asm volatile("cp.async.bulk.commit_group;" ::: "memory");
                    asm volatile("cp.async.bulk.wait_group 0;" ::: "memory");
                    mbar_arrive(bb + B_OTE + (k & 1) * 16);
                    fence_async_global();
                    red_release(FLG(F_CV + rg), 1);
                    GT(true, 50 + k);
                }
            }
            __syncwarp();
        }
    }
    cluster_arrive(); cluster_wait();
    if (blockIdx.x == 0 && tid == 0) atomicAdd(&g_epoch, 1);
}
}

namespace ws {
constexpr int OP_SS = 17;
constexpr int P_RING = 0, P_AS = 131072, P_STG = P_AS + 2 * OP_SS * 2048, P_BAR = P_STG + 16384, OP_SMEM = P_BAR + 256;
constexpr int PB_FULL = 0, PB_EMPTY = 128, PB_SF = 144, PB_SE = 176;
static_assert(OP_SMEM <= 232448, "smem");

__global__ void __launch_bounds__(384, 1) op_kernel(const bf16* __restrict__ Wo, const bf16* __restrict__ Bk, const bf16* __restrict__ Bv, const bf16* __restrict__ shiftk) {
    extern __shared__ __align__(1024) unsigned char smem_raw[];
    const int tid = threadIdx.x, warp = __shfl_sync(0xffffffffu, tid >> 5, 0), lane = tid & 31;
    const int nb = blockIdx.x % 5, ks = blockIdx.x / 5;
    const uint32_t sb = smem_u32(smem_raw), bb = sb + P_BAR;
    if (tid == 0) {
        if ((sb & 0xFFFFFFu) != 1024) __trap();
        for (int i = 0; i < 16; i++) mbar_init(bb + PB_FULL + i * 8, 1);
        for (int i = 0; i < 2; i++) mbar_init(bb + PB_EMPTY + i * 8, 2);
        for (int i = 0; i < 4; i++) { mbar_init(bb + PB_SF + i * 8, 4); mbar_init(bb + PB_SE + i * 8, 1); }
        asm volatile("fence.mbarrier_init.release.cluster;" ::: "memory");
    }
    GT(tid == 0, 8);
    __syncthreads();
    if (warp < 4) {
        asm volatile("setmaxnreg.dec.sync.aligned.u32 40;");
        if (warp == 0) {
            named_bar(3, 288);
            GT(lane == 0, 3);
            uint32_t it = 0;
            const int otgt = 8 * (ld_relaxed(&g_epoch) + 1);
#pragma unroll 1
            for (int q = 0; q < 2 * NT; q++) {
                const int l = q & 1, n = (q >> 1) - l * LAG;
                if (n < 0 || n >= NSEG) continue;
                int guard = 0;
                while (ld_acquire(FLG(F_O + l * 64 + n) + ks) < otgt) { if (++guard > 4000000) __trap(); __nanosleep(OP_NS); }
                fence_async_global();
                mwait(bb + PB_EMPTY + (it & 1) * 8, ((it >> 1) & 1) ^ 1);
                if (lane < 8) {
                    const uint32_t fb = bb + PB_FULL + ((it & 1) * 8 + lane) * 8;
                    mbar_expect_tx(fb, 8192);
                    asm volatile("cp.async.bulk.shared::cluster.global.mbarrier::complete_tx::bytes [%0], [%1], %2, [%3];" ::"r"(sb + P_RING + (it & 1) * 65536 + lane * 8192),
                                 "l"(g_ot + (rslot(l, n) * 256 + (ks * 8 + lane) * 8) * 64), "r"(8192), "r"(fb) : "memory");
                }
                __syncwarp();
                it++;
            }
        } else if (warp == 3) {
#pragma unroll 1
            for (int rg = 1; rg < 4; rg++) {
#pragma unroll 1
                for (int u = rg * 640 + blockIdx.x; u < rg * 640 + 640; u += 20) u_half(Bk, Bv, shiftk, u, lane);
                __syncwarp();
                if (lane == 0) red_release(FLG(F_U + rg + 1), 1);
                GT(lane == 0 && rg, 4 + rg);
            }
        } else if (lane == 0) {
            const int cw = warp - 1;
            uint32_t it = 0;
#pragma unroll 1
            for (int q = 0; q < 2 * NT; q++) {
                const int l = q & 1, n = (q >> 1) - l * LAG;
                if (n < 0 || n >= NSEG) continue;
                mwait(bb + PB_SF + cw * 8, it & 1);
                asm volatile("cp.reduce.async.bulk.global.shared::cta.bulk_group.add.f32 [%0], [%1], %2;" ::"l"(g_pt + (rslot(l, n) * 10 + nb * 2 + cw) * 512), "r"(sb + P_STG + cw * 8192), "r"(8192) : "memory");
                asm volatile("cp.async.bulk.commit_group;" ::: "memory");
                asm volatile("cp.async.bulk.wait_group.read 0;" ::: "memory");
                mbar_arrive(bb + PB_SE + cw * 8);
                asm volatile("cp.async.bulk.wait_group 0;" ::: "memory");
                fence_async_global();
                red_release(FLG(F_P + l * 64 + n), 1);
                GT(true, 330 + l * 64 + n);
                it++;
            }
        }
    } else {
        asm volatile("setmaxnreg.inc.sync.aligned.u32 232;");
        const int cw = (warp >> 2) - 1, w4 = warp & 3, t7 = tid & 127;
        uint32_t wa[64 - OP_SS][4];
        if (OP_LATE) flag_wait(FLG(F_H), 32 * (ld_relaxed(&g_epoch) + 1), 200);
        {
            const bf16* W = Wo + (size_t)ks * 1024 * DM + nb * 128 + cw * 64 + (t7 & 7) * 8;
            const uint32_t so = (t7 >> 3) * 128 + (((t7 & 7) ^ ((t7 >> 3) & 7)) << 4);
            const uint32_t stg = sb + P_RING + cw * 65536;
            const uint32_t la = stg + ((lane & 7) + (lane >> 4) * 8) * 128 + (((w4 * 2 + ((lane >> 3) & 1)) ^ (lane & 7)) << 4);
#pragma unroll 4
            for (int i = 0; i < 32; i++) cp_async16(stg + i * 2048 + so, W + (size_t)((OP_SS + i) * 16 + (t7 >> 3)) * DM);
            cp_commit();
#pragma unroll 1
            for (int i = 0; i < OP_SS; i++) cp_async16(sb + P_AS + cw * OP_SS * 2048 + i * 2048 + so, W + (size_t)(i * 16 + (t7 >> 3)) * DM);
            cp_commit();
            cp_wait<1>();
            named_bar(1 + cw, 128);
#pragma unroll
            for (int j = 0; j < 32; j++) { const uint4 v = ldsm4t(la + j * 2048); wa[j][0] = v.x; wa[j][1] = v.y; wa[j][2] = v.z; wa[j][3] = v.w; }
            named_bar(1 + cw, 128);
#pragma unroll 1
            for (int i = 0; i < 32 - OP_SS; i++) cp_async16(stg + i * 2048 + so, W + (size_t)((OP_SS + 32 + i) * 16 + (t7 >> 3)) * DM);
            cp_commit();
            cp_wait<0>();
            named_bar(1 + cw, 128);
#pragma unroll
            for (int j = 0; j < 32 - OP_SS; j++) { const uint4 v = ldsm4t(la + j * 2048); wa[32 + j][0] = v.x; wa[32 + j][1] = v.y; wa[32 + j][2] = v.z; wa[32 + j][3] = v.w; }
            fence_async_smem();
            named_bar(3, 288);
        }
        const uint32_t ab = (1024 + P_AS + cw * OP_SS * 2048) >> 4;
        const uint32_t ea = sb + P_STG + cw * 8192 + (lane & 3) * 2048 + (((2 * w4) ^ (lane & 3)) << 5) + (lane >> 2) * 4;
#pragma unroll 1
        for (uint32_t it = 0; it < 2 * NSEG; it++) {
            float acc[16];
            const uint32_t fb = bb + PB_FULL + (it & 1) * 64, par = (it >> 1) & 1;
            const uint32_t ob = opq(((1024 + P_RING) >> 4) + (it & 1) * 4096);
            uint32_t ok = 0;
#pragma unroll
            for (int j = 0; j < 64; j++) {
                if ((j & 7) == 0) {
                    if (j) wg_commit();
                    if (!ok) mslow(fb + j, par);
                    ok = j < 56 ? mtest(fb + j + 8, par) : mtest(bb + PB_SE + cw * 8, (it & 1) ^ 1);
                    if (j == 0) wg_fence();
                }
                const uint64_t db = mkdesc(ob + j * 64, 0x80000020u);
                if (j == 0) wg_n32t_sfirst(acc, mkdesc(ab, 0x40000040u), db);
                else if (j < OP_SS) wg_n32t_s(acc, mkdesc(ab + j * 128, 0x40000040u), db);
                else wg_n32t(acc, wa[j - OP_SS][0], wa[j - OP_SS][1], wa[j - OP_SS][2], wa[j - OP_SS][3], db);
            }
            wg_commit();
            if (!ok) mslow(bb + PB_SE + cw * 8, (it & 1) ^ 1);
            wg_wait<0>();
            if (t7 == 0) mbar_arrive(bb + PB_EMPTY + (it & 1) * 8);
#pragma unroll
            for (int i = 0; i < 16; i++) sts32((ea ^ ((i & 2) << 4)) + ((i >> 2) * 2 + (i & 1)) * 256, __float_as_uint(acc[i]));
            fence_async_smem();
            __syncwarp();
            if (lane == 0) mbar_arrive(bb + PB_SF + cw * 8);
        }
    }
}
}

namespace ws {
static bool usable() {
    static int ok = -1;
    if (ok < 0) {
        cudaFuncSetAttribute(head_kernel, cudaFuncAttributeMaxDynamicSharedMemorySize, HEAD_SMEM);
        cudaFuncSetAttribute(head_kernel, cudaFuncAttributeNonPortableClusterSizeAllowed, 1);
        cudaFuncSetAttribute(op_kernel, cudaFuncAttributeMaxDynamicSharedMemorySize, OP_SMEM);
        cudaLaunchConfig_t cfg = {};
        cfg.gridDim = dim3(NCL * 16); cfg.blockDim = dim3(512); cfg.dynamicSmemBytes = HEAD_SMEM;
        cudaLaunchAttribute at[1];
        at[0].id = cudaLaunchAttributeClusterDimension;
        at[0].val.clusterDim.x = 16; at[0].val.clusterDim.y = 1; at[0].val.clusterDim.z = 1;
        cfg.attrs = at; cfg.numAttrs = 1;
        int n = 0, nsm = 0;
        cudaDeviceGetAttribute(&nsm, cudaDevAttrMultiProcessorCount, 0);
        ok = cudaOccupancyMaxActiveClusters(&n, head_kernel, &cfg) == cudaSuccess && n >= NCL && nsm >= NCL * 16 + 20;
        (void)cudaGetLastError();
    }
    return ok > 0;
}
static void launch_all(void* const* d_in, void* d_out) {
    HeadArgs A;
    A.x = (const bf16*)d_in[0]; A.mem0 = (const bf16*)d_in[1]; A.Wq = (const bf16*)d_in[2]; A.Wk = (const bf16*)d_in[3]; A.Wv = (const bf16*)d_in[4]; A.Wo = (const bf16*)d_in[5];
    A.Bk = (const bf16*)d_in[8]; A.Bv = (const bf16*)d_in[9]; A.shiftk = (const bf16*)d_in[10]; A.ssmk = (const bf16*)d_in[11]; A.ssmD = (const bf16*)d_in[12];
    A.out = (bf16*)d_out; A.h_target = 32;
    cudaStream_t s = cudaStreamPerThread;
    {
        cudaLaunchConfig_t cfg = {};
        cfg.gridDim = dim3(NCL * 16); cfg.blockDim = dim3(512); cfg.dynamicSmemBytes = HEAD_SMEM; cfg.stream = s;
        cudaLaunchAttribute at[2];
        at[0].id = cudaLaunchAttributeClusterDimension;
        at[0].val.clusterDim.x = 16; at[0].val.clusterDim.y = 1; at[0].val.clusterDim.z = 1;
        at[1].id = cudaLaunchAttributeProgrammaticStreamSerialization;
        at[1].val.programmaticStreamSerializationAllowed = 1;
        cfg.attrs = at; cfg.numAttrs = 1;
        cudaLaunchKernelEx(&cfg, head_kernel, A);
    }
    {
        cudaLaunchConfig_t cfg = {};
        cfg.gridDim = dim3(20); cfg.blockDim = dim3(384); cfg.dynamicSmemBytes = OP_SMEM; cfg.stream = s;
        cudaLaunchAttribute at[1];
        at[0].id = cudaLaunchAttributeProgrammaticStreamSerialization;
        at[0].val.programmaticStreamSerializationAllowed = 1;
        cfg.attrs = at; cfg.numAttrs = 1;
        cudaLaunchKernelEx(&cfg, op_kernel, A.Wo, A.Bk, A.Bv, A.shiftk);
    }
}
}

#undef BNS
#undef BP
#undef CONV_DRY
#undef FLG
#undef GT
#undef G_DLY
#undef H1_LATE
#undef HBYTES
#undef LAGT
#undef LN0_AHEAD
#undef NO_X
#undef O0_EARLY
#undef OBK
#undef OBRES
#undef OP_LATE
#undef OP_NS
#undef OT_LATE
#undef O_BULK
#undef O_DLY
#undef P1A
#undef P1C
#undef PDA
#undef PDC
#undef POST_DRY
#undef POST_NS
#undef PRE_PDL
#undef PRE_PF
#undef QUIET
#undef REG_G
#undef REG_T
#undef REG_X
#undef RING
#undef SC
#undef SD
#undef SKEW
#undef TG_STEPS
#undef TPVW
#undef TPV_LATE
#undef TPV_PAUSE
#undef TS
#undef TV
#undef UNI
#undef WFLY
#undef WGRP
#undef WK3
#undef WR
#undef WTA
#undef WVOL
#undef W_SKIP
#undef XD
#undef XDUP
#undef XS
namespace ni {

constexpr int S_LEN = 2048;
constexpr int DM = 640;
constexpr int NH = 32;
constexpr int DH = 128;
constexpr int HD = NH * DH;
constexpr int MEMR = 8;
constexpr int SEG = 32;
constexpr int NSEG = S_LEN / SEG;

__device__ __forceinline__ float bf2f(bf16 v) { return __bfloat162float(v); }
__device__ __forceinline__ bf16 f2bf(float v) { return __float2bfloat16_rn(v); }
__device__ __forceinline__ float rbf(float v) { return __bfloat162float(__float2bfloat16_rn(v)); }
__device__ __forceinline__ uint32_t pack2(float a, float b) {
    __nv_bfloat162 t = __floats2bfloat162_rn(a, b);
    return *reinterpret_cast<uint32_t*>(&t);
}
__device__ __forceinline__ uint32_t smem_u32(const void* p) { return (uint32_t)__cvta_generic_to_shared(p); }
__device__ __forceinline__ void ldsm_x4(uint32_t& r0, uint32_t& r1, uint32_t& r2, uint32_t& r3, uint32_t addr) {
    asm volatile("ldmatrix.sync.aligned.m8n8.x4.shared.b16 {%0,%1,%2,%3}, [%4];"
                 : "=r"(r0), "=r"(r1), "=r"(r2), "=r"(r3) : "r"(addr));
}
__device__ __forceinline__ void ldsm_x2(uint32_t& r0, uint32_t& r1, uint32_t addr) {
    asm volatile("ldmatrix.sync.aligned.m8n8.x2.shared.b16 {%0,%1}, [%2];" : "=r"(r0), "=r"(r1) : "r"(addr));
}
__device__ __forceinline__ void ldsm_x4_t(uint32_t& r0, uint32_t& r1, uint32_t& r2, uint32_t& r3, uint32_t addr) {
    asm volatile("ldmatrix.sync.aligned.m8n8.x4.trans.shared.b16 {%0,%1,%2,%3}, [%4];"
                 : "=r"(r0), "=r"(r1), "=r"(r2), "=r"(r3) : "r"(addr));
}
__device__ __forceinline__ void mma16816(float* c, uint32_t a0, uint32_t a1, uint32_t a2, uint32_t a3,
                                         uint32_t b0, uint32_t b1) {
    asm("mma.sync.aligned.m16n8k16.row.col.f32.bf16.bf16.f32 {%0,%1,%2,%3}, {%4,%5,%6,%7}, {%8,%9}, {%0,%1,%2,%3};"
        : "+f"(c[0]), "+f"(c[1]), "+f"(c[2]), "+f"(c[3])
        : "r"(a0), "r"(a1), "r"(a2), "r"(a3), "r"(b0), "r"(b1));
}
__device__ __forceinline__ void cp_async16(uint32_t dst, const void* src) {
    asm volatile("cp.async.cg.shared.global [%0], [%1], 16;" ::"r"(dst), "l"(src));
}
__device__ __forceinline__ void cp_commit() { asm volatile("cp.async.commit_group;"); }
template <int N> __device__ __forceinline__ void cp_wait() { asm volatile("cp.async.wait_group %0;" ::"n"(N)); }
__device__ __forceinline__ uint4 ld_relaxed_v4(const void* p) {
    uint4 v;
    asm volatile("ld.relaxed.gpu.global.v4.u32 {%0,%1,%2,%3}, [%4];"
                 : "=r"(v.x), "=r"(v.y), "=r"(v.z), "=r"(v.w) : "l"(p) : "memory");
    return v;
}
__device__ __forceinline__ void st_relaxed_v4(void* p, uint32_t a, uint32_t b, uint32_t c, uint32_t d) {
    asm volatile("st.relaxed.gpu.global.v4.u32 [%0], {%1,%2,%3,%4};" ::"l"(p), "r"(a), "r"(b), "r"(c), "r"(d) : "memory");
}
__device__ __forceinline__ int ld_acquire(const int* p) {
    int v;
    asm volatile("ld.acquire.gpu.global.u32 %0, [%1];" : "=r"(v) : "l"(p) : "memory");
    return v;
}
__device__ __forceinline__ void mbar_init(uint32_t bar, int count) {
    asm volatile("mbarrier.init.shared::cta.b64 [%0], %1;" ::"r"(bar), "r"(count));
}
__device__ __forceinline__ void mbar_expect_tx(uint32_t bar, uint32_t bytes) {
    asm volatile("mbarrier.arrive.expect_tx.shared::cta.b64 _, [%0], %1;" ::"r"(bar), "r"(bytes) : "memory");
}
__device__ __forceinline__ void mbar_arrive(uint32_t bar) {
    asm volatile("mbarrier.arrive.shared::cta.b64 _, [%0];" ::"r"(bar) : "memory");
}
constexpr int SPIN_LIMIT = 4000000;
__device__ __forceinline__ void mbar_wait_spin(uint32_t bar, uint32_t parity) {
    uint32_t ok = 0;
    int guard = 0;
    while (!ok && ++guard < SPIN_LIMIT) {
        asm volatile(
            "{\n.reg .pred P1;\n"
            "mbarrier.try_wait.parity.shared::cta.b64 P1, [%1], %2;\n"
            "selp.u32 %0, 1, 0, P1;\n}\n"
            : "=r"(ok) : "r"(bar), "r"(parity) : "memory");
    }
}
__device__ __forceinline__ uint32_t mapa(uint32_t addr, uint32_t rank) {
    uint32_t r;
    asm volatile("mapa.shared::cluster.u32 %0, %1, %2;" : "=r"(r) : "r"(addr), "r"(rank));
    return r;
}
__device__ __forceinline__ void st_async_u32(uint32_t addr, uint32_t v, uint32_t bar) {
    asm volatile("st.async.weak.shared::cluster.mbarrier::complete_tx::bytes.b32 [%0], %1, [%2];" ::"r"(addr), "r"(v), "r"(bar) : "memory");
}
__device__ __forceinline__ void st_async_v2(uint32_t addr, uint32_t a, uint32_t b, uint32_t bar) {
    asm volatile("st.async.weak.shared::cluster.mbarrier::complete_tx::bytes.v2.b32 [%0], {%1,%2}, [%3];" ::"r"(addr), "r"(a), "r"(b), "r"(bar) : "memory");
}
__device__ __forceinline__ void cluster_sync_all() {
    asm volatile("barrier.cluster.arrive.release.aligned;\nbarrier.cluster.wait.acquire.aligned;" ::: "memory");
}
__device__ __forceinline__ void named_bar(int id, int n) { asm volatile("bar.sync %0, %1;" ::"r"(id), "r"(n) : "memory"); }

}

namespace ni {
#define CHAIN_LAG 16
constexpr int CL = 16;
constexpr int OWN = DM / CL;
constexpr int NSRC = CL / 2;
constexpr int NCLU = 64 / CL;
constexpr int CSEG = 4;
constexpr int NCHK = NSEG / CSEG;
constexpr int LAG = CHAIN_LAG;
constexpr int NTICK = NSEG + LAG;

constexpr int F_KV = 0, F_MEM = 32, F_H = 64, F_OP = 96, F_CONV = 128, F_U = 130, F_PROG = 132, F_ZERO = 133, F_CNT = 136;
constexpr int NFLAG = 192;
__device__ int g_flags[NFLAG * 32];
#define FLG(i) (g_flags + (i) * 32)
constexpr int CHAIN_THREADS = 384;
__device__ bf16 g_Y[S_LEN * DM];
__device__ bf16 g_U[DM * S_LEN];
__device__ bf16 g_h[2][S_LEN * DM];
__device__ bf16 g_x[S_LEN * DM];
__device__ bf16 g_kv[2][S_LEN * HD];
#define PRING 4
constexpr int PROWS = PRING * 128, PG = 4;
__device__ bf16 g_part[2 * PROWS * PG * DM];
__device__ uint4 g_kvf[2 * NSEG * NH * 256];
__device__ uint32_t g_xc[2 * 2 * CL * NCLU * 8 * OWN];

#define TVAL(i, v)
#define TSTAMP(i)

#define NRQ 36
#define NRW 8
#define PDQ 4
#define PDW1 0
#define PROBE 2
#define PDW 6
constexpr int NSQ = 60 - NRQ, NSW = 20 - NRW;
__host__ __device__ constexpr bool q_smem(int i) { return ((i + 1) * NSQ) / 60 != (i * NSQ) / 60; }
__host__ __device__ constexpr int q_slot(int i) { return q_smem(i) ? (i * NSQ) / 60 : i - (i * NSQ) / 60; }
__host__ __device__ constexpr int w_tile(int i) { return i < 8 ? ((i & 1) ? 0 : 2) : (i < 16 ? (i & 1) : 1); }
__host__ __device__ constexpr int w_k(int i) { return i < 8 ? i / 2 : (i < 16 ? ((i & 1) ? (i - 8) / 2 : 4 + (i - 8) / 2) : i - 12); }
__host__ __device__ constexpr int w_acc(int i) { return (i >= 16 && (i & 1)) ? 3 : w_tile(i); }
__host__ __device__ constexpr bool w_smem(int i) { return i < PDW || NRW == 0 || ((i - PDW + 1) * NRW) / (20 - PDW) == ((i - PDW) * NRW) / (20 - PDW); }
__host__ __device__ constexpr int w_slot(int i) { return i < PDW ? i : (w_smem(i) ? i - ((i - PDW) * NRW) / (20 - PDW) : ((i - PDW) * NRW) / (20 - PDW)); }
constexpr int O_WQ = 0, O_WW = NSQ * 4096, O_REST = (NSQ + NSW) * 4096;
constexpr int C_TOK = 0, C_MEM = 12288, C_RED = C_MEM + 10240, C_Q = C_RED + 6144, C_K = C_Q + 2048, C_V = C_K + 2048, C_S = C_V + 4096,
              C_BAR = C_S + 3072, C_SIZE = 40960;
constexpr int S_BYTES = 3072 + 4096;
constexpr int B_S = 64, B_R = 72, B_T = 96, B_F = 104;
static_assert(C_BAR + 112 <= C_SIZE, "chain block");
constexpr int O_STB = O_REST - 61440;
static_assert((45 * NSQ) / 60 * 4096 <= O_STB && NSQ <= 32, "staging");
struct ChainSmem { unsigned char b[O_REST + 81920 + 1536]; };
static_assert(sizeof(ChainSmem) <= 232448, "smem");

struct ChainArgs {
    CUtensorMap tk[2], tv[2];
    const bf16 *x, *mem0, *Wq, *Wk, *Wv, *Wo;
    int kv_target;
};
__device__ __forceinline__ uint32_t movmat(uint32_t v) {
    uint32_t r;
    asm volatile("movmatrix.sync.aligned.m8n8.trans.b16 %0, %1;" : "=r"(r) : "r"(v));
    return r;
}
__device__ __forceinline__ void named_arrive(int id, int n) { asm volatile("bar.arrive %0, %1;" ::"r"(id), "r"(n) : "memory"); }
__device__ __forceinline__ void red_release(int* p, int v) { asm volatile("red.release.gpu.global.add.u32 [%0], %1;" ::"l"(p), "r"(v) : "memory"); }

#define CVT(i)
__device__ __forceinline__ uint4 lds128(uint32_t a) {
    uint4 v;
    asm volatile("ld.shared.v4.u32 {%0,%1,%2,%3}, [%4];" : "=r"(v.x), "=r"(v.y), "=r"(v.z), "=r"(v.w) : "r"(a));
    return v;
}
__device__ __forceinline__ uint2 lds64(uint32_t a) {
    uint2 v;
    asm volatile("ld.shared.v2.u32 {%0,%1}, [%2];" : "=r"(v.x), "=r"(v.y) : "r"(a));
    return v;
}
__device__ __forceinline__ uint32_t lds32(uint32_t a) {
    uint32_t v;
    asm volatile("ld.shared.u32 %0, [%1];" : "=r"(v) : "r"(a));
    return v;
}
__device__ __forceinline__ void sts64(uint32_t a, uint32_t x, uint32_t y) { asm volatile("st.shared.v2.u32 [%0], {%1,%2};" ::"r"(a), "r"(x), "r"(y) : "memory"); }
__device__ __forceinline__ void sts128(uint32_t a, uint32_t x, uint32_t y, uint32_t z, uint32_t w) {
    asm volatile("st.shared.v4.u32 [%0], {%1,%2,%3,%4};" ::"r"(a), "r"(x), "r"(y), "r"(z), "r"(w) : "memory");
}
__device__ __forceinline__ void st_async_v4(uint32_t addr, uint32_t a, uint32_t b, uint32_t c, uint32_t d, uint32_t bar) {
    asm volatile("st.async.weak.shared::cluster.mbarrier::complete_tx::bytes.v4.b32 [%0], {%1,%2,%3,%4}, [%5];" ::"r"(addr), "r"(a), "r"(b), "r"(c), "r"(d), "r"(bar) : "memory");
}
__device__ __forceinline__ uint2 ld_relaxed_v2(const void* p) {
    uint2 v;
    asm volatile("ld.relaxed.gpu.global.v2.u32 {%0,%1}, [%2];" : "=r"(v.x), "=r"(v.y) : "l"(p) : "memory");
    return v;
}
__device__ __forceinline__ void st_relaxed_v2(void* p, uint32_t a, uint32_t b) {
    asm volatile("st.relaxed.gpu.global.v2.u32 [%0], {%1,%2};" ::"l"(p), "r"(a), "r"(b) : "memory");
}
__device__ __forceinline__ float blo(uint32_t v) { return __uint_as_float(v << 16); }
__device__ __forceinline__ float bhi(uint32_t v) { return __uint_as_float(v & 0xffff0000u); }
__device__ __forceinline__ uint32_t badd2(uint32_t a, uint32_t b) {
    __nv_bfloat162 r = __hadd2(*reinterpret_cast<__nv_bfloat162*>(&a), *reinterpret_cast<__nv_bfloat162*>(&b));
    return *reinterpret_cast<uint32_t*>(&r);
}
__device__ __forceinline__ void mmau(float* c, const uint4& a, uint32_t b0, uint32_t b1) { mma16816(c, a.x, a.y, a.z, a.w, b0, b1); }

__device__ __forceinline__ void stsm_x4_t(uint32_t a, uint32_t r0, uint32_t r1, uint32_t r2, uint32_t r3) {
    asm volatile("stmatrix.sync.aligned.m8n8.x4.trans.shared.b16 [%0], {%1,%2,%3,%4};" ::"r"(a), "r"(r0), "r"(r1), "r"(r2), "r"(r3) : "memory");
}
__device__ __forceinline__ uint4 ldsm4(uint32_t a) { uint4 v; ldsm_x4(v.x, v.y, v.z, v.w, a); return v; }
__device__ __forceinline__ float ex2f(float x) { float y; asm("ex2.approx.ftz.f32 %0, %1;" : "=f"(y) : "f"(x)); return y; }
__device__ __forceinline__ float rcpf(float x) { float y; asm("rcp.approx.ftz.f32 %0, %1;" : "=f"(y) : "f"(x)); return y; }
#define XD 300
__device__ __forceinline__ void xdelay() {
    uint32_t t0, t1;
    asm volatile("mov.u32 %0, %clock;" : "=r"(t0));
    do { asm volatile("mov.u32 %0, %clock;" : "=r"(t1)); } while (t1 - t0 < XD);
}
template <int V> struct IC { static constexpr int value = V; };
__device__ __forceinline__ uint32_t opq(uint32_t x) { uint32_t y; asm volatile("mov.u32 %0, %1;" : "=r"(y) : "r"(x)); return y; }
#define UNI(x) __shfl_sync(0xffffffffu, (uint32_t)(x), 0)
__device__ __forceinline__ uint32_t mtest(uint32_t bar, uint32_t parity) {
    uint32_t ok;
    asm volatile("{\n.reg .pred P1;\nmbarrier.test_wait.parity.shared::cta.b64 P1, [%1], %2;\nselp.u32 %0, 1, 0, P1;\n}\n" : "=r"(ok) : "r"(bar), "r"(parity) : "memory");
    return ok;
}
__device__ __forceinline__ void mwait(uint32_t bar, uint32_t parity) {
    asm volatile(
        "{\n.reg .pred P1;\n.reg .u32 cnt;\n"
        "mbarrier.try_wait.parity.shared::cta.b64 P1, [%0], %1;\n"
        "@P1 bra DONE;\n"
        "mov.u32 cnt, 0;\n"
        "LAB_WAIT:\n"
        "mbarrier.try_wait.parity.shared::cta.b64 P1, [%0], %1;\n"
        "@P1 bra DONE;\n"
        "add.u32 cnt, cnt, 1;\n"
        "setp.lt.u32 P1, cnt, 4000000;\n"
        "@P1 bra LAB_WAIT;\n"
        "DONE:\n}\n" ::"r"(bar), "r"(parity) : "memory");
}

__global__ void __launch_bounds__(CHAIN_THREADS, 1) chain_kernel(const __grid_constant__ ChainArgs A) {
    extern __shared__ __align__(1024) unsigned char smem_raw[];
    const int tid = threadIdx.x, warp = __shfl_sync(0xffffffffu, tid >> 5, 0), lane = tid & 31;
    const int cq = blockIdx.x / CL, r = blockIdx.x % CL;
    const int h = cq * NSRC + (r >> 1), hf = r & 1;
    const uint32_t sb = smem_u32(smem_raw);
    asm volatile("griddepcontrol.launch_dependents;");
    CVT(0);
    if (warp == 8) {
        if (lane < 8) asm volatile("cp.async.bulk.prefetch.L2.global [%0], %1;" ::"l"(A.x + (size_t)(blockIdx.x * 8 + lane) * 2560), "r"(5120) : "memory");
        asm volatile("cp.async.bulk.prefetch.L2.global [%0], %1;" ::"l"((lane < 16 ? A.Wk : A.Wv) + (size_t)(blockIdx.x * 16 + (lane & 15)) * 2560), "r"(5120) : "memory");
        asm volatile("cp.async.bulk.prefetch.L2.global [%0], %1;" ::"l"((lane < 16 ? A.Wq : A.Wo) + (size_t)(blockIdx.x * 16 + (lane & 15)) * 2560), "r"(5120) : "memory");
    }
    CVT(1);
    if (warp < 8) {
        asm volatile("setmaxnreg.inc.sync.aligned.u32 232;");
        const int j = warp & 3, kh = warp >> 2;
        uint4 wr[NRQ + NRW];
        {
            auto load_round = [&](int gi) {
                const uint32_t buf = sb + ((gi & 1) ? O_STB : O_REST);
#pragma unroll
                for (int it = 0; it < 15; it++) {
                    const int i = tid + it * 256;
                    const int pc = i / 1920, rem = i % 1920, row = rem / 24, ch = rem % 24;
                    const int mat = ch >> 3, pi = ((r >> 1) - (2 * gi + pc)) & 7;
                    const bf16* W = mat == 0 ? A.Wq : (mat == 1 ? A.Wk : A.Wv);
                    cp_async16(buf + pc * 30720 + row * 384 + ((ch ^ (row & 7)) << 4), W + (size_t)(pi * 80 + row) * HD + h * DH + hf * 64 + (ch & 7) * 8);
                }
                cp_commit();
            };
            load_round(0);
            load_round(1);
#pragma unroll
            for (int gi = 0; gi < 4; gi++) {
                cp_wait<1>();
                named_bar(1, 256);
                const uint32_t pb = sb + ((gi & 1) ? O_STB : O_REST) + kh * 30720;
                uint4 tmp[8];
#pragma unroll
                for (int u = 0; u < 5; u++)
#pragma unroll
                    for (int tt = 0; tt < 3; tt++) {
                        const int row = u * 16 + (lane & 7) + (lane >> 4) * 8;
                        const int ch = tt * 8 + j * 2 + ((lane >> 3) & 1);
                        uint4 v;
                        ldsm_x4_t(v.x, v.y, v.z, v.w, pb + row * 384 + ((ch ^ (row & 7)) << 4));
                        const int i = (gi * 5 + u) * 3 + tt;
                        if (q_smem(i)) {
                            if (gi == 3) tmp[q_slot(i) & 7] = v;
                            else sts128(sb + O_WQ + q_slot(i) * 4096 + tid * 16, v.x, v.y, v.z, v.w);
                        } else wr[q_slot(i)] = v;
                    }
                named_bar(1, 256);
                if (gi == 3) {
#pragma unroll
                    for (int i = 45; i < 60; i++)
                        if (q_smem(i)) { const uint4 v = tmp[q_slot(i) & 7]; sts128(sb + O_WQ + q_slot(i) * 4096 + tid * 16, v.x, v.y, v.z, v.w); }
                }
                if (gi < 2) load_round(gi + 2);
                else if (gi == 2) {
                    for (int i = tid; i < 128 * 40; i += 256) {
                        const int row = i / 40, ch = i % 40;
                        cp_async16(sb + O_REST + row * 640 + ((ch ^ (row & 7)) << 4), A.Wo + ((size_t)h * DH + row) * DM + hf * 320 + ch * 8);
                    }
                    cp_commit();
                }
            }
            cp_wait<0>();
            named_bar(1, 256);
#pragma unroll
            for (int i = 0; i < 20; i++) {
                const int tl = w_tile(i), et = (w_k(i) + 4 * (warp & 1)) & 7;
                const int row = et * 16 + (lane & 7) + (lane >> 4) * 8;
                const int ch = (warp >> 1) * 10 + (tl == 2 ? 8 : (warp & 1) * 4 + tl * 2) + ((lane >> 3) & 1);
                uint4 v;
                ldsm_x4_t(v.x, v.y, v.z, v.w, sb + O_REST + row * 640 + ((ch ^ (row & 7)) << 4));
                if (w_smem(i)) sts128(sb + O_WW + w_slot(i) * 4096 + tid * 16, v.x, v.y, v.z, v.w);
                else wr[NRQ + w_slot(i)] = v;
            }
            named_bar(1, 256);
            for (int i = tid; i < 2560; i += 256) {
                const int ks = i >> 6, ln = (i >> 1) & 31, wd = i & 1;
                const int pi = ((r >> 1) - ks / 5) & 7;
                const uint32_t v = *reinterpret_cast<const uint32_t*>(A.mem0 + (ln >> 2) * DM + pi * 80 + (ks % 5) * 16 + wd * 8 + (ln & 3) * 2);
                const int o = ks % 5 == 4 ? ks * 256 + wd * 128 + ln * 4 : i * 4;
                asm volatile("st.shared.u32 [%0], %1;" ::"r"(sb + O_REST + C_MEM + o), "r"(v) : "memory");
                asm volatile("st.shared.u32 [%0], %1;" ::"r"(sb + O_REST + C_SIZE + C_MEM + o), "r"(v) : "memory");
            }
            if (tid < 2) {
                const uint32_t bb = sb + O_REST + tid * C_SIZE + C_BAR;
                for (int i = 0; i < 13; i++) mbar_init(bb + i * 8, 1);
                mbar_init(bb + B_F, 4);
                asm volatile("fence.mbarrier_init.release.cluster;" ::: "memory");
                mbar_expect_tx(bb + B_S, S_BYTES);
                for (int i = 0; i < 3; i++) mbar_expect_tx(bb + B_R + i * 8, 2048);
            }
            asm volatile("fence.proxy.async;" ::: "memory");
        }
        CVT(2);
        cluster_sync_all();
        const uint32_t wq_a = sb + O_WQ + tid * 16;
        const uint32_t cb0 = sb + O_REST;
        const uint32_t qk_a = cb0 + j * 512 + (lane & 7) * 16 + (lane < 16 ? C_Q + (lane >> 3) * 256 + kh * 128 : C_K + kh * 256 + ((lane >> 3) & 1) * 128);
        const uint32_t pd = UNI(mapa(sb, (uint32_t)(r ^ 1)) - sb), sd = UNI(mapa(sb, (uint32_t)r) - sb);
        const uint32_t od = UNI(mapa(sb, (uint32_t)(hf * 8 + warp)) - sb);
        const uint32_t oe = UNI(mapa(sb, (uint32_t)(hf * 8 + (warp & 6))) - sb), oo = UNI(mapa(sb, (uint32_t)(hf * 8 + (warp | 1))) - sb);
        const uint32_t u_mem = UNI(cb0 + C_MEM + kh * 1280), u_bm = UNI(cb0 + C_BAR + kh * 8);
        const uint32_t u_v = UNI(cb0 + C_V + hf * 2048 + j * 512 + kh * 256);
        const uint32_t u_ra = UNI(cb0 + C_RED + (r >> 1) * 256);
        const uint32_t u_ob0 = UNI(cb0 + C_Q + (warp & 1) * 1024), u_ob1 = UNI(cb0 + C_Q + ((warp & 1) ^ 1) * 1024);
        const uint32_t u_role = UNI(warp < 3 ? cb0 + C_S + hf * 1536 + warp * 512 : cb0 + C_V + j * 1024);
        const uint32_t t_tok = cb0 + C_TOK + ((lane & 7) + (lane >> 4) * 8) * 128 +
                               (warp < 3 ? warp * 2048 + ((((lane >> 3) & 1) ^ (lane & 7)) << 4) : 4096 + (j >> 1) * 4096 + ((((j & 1) * 4 + ((lane >> 3) & 1)) ^ (lane & 7)) << 4));
        uint4 qb[PDQ];
#pragma unroll
        for (int s = 0; s < PDQ; s++) qb[s] = lds128(wq_a + s * 4096);
        auto tick = [&](auto cc, const int n) {
            constexpr int c = decltype(cc)::value;
            constexpr uint32_t CO = c * C_SIZE;
            const uint32_t cb = cb0 + CO;
            const uint32_t par = (uint32_t)(n & 1);
            const uint32_t l4 = opq(lane * 4), l8 = l4 * 2, l16 = l4 * 4;
            float acc[3][4];
#pragma unroll
            for (int a = 0; a < 3; a++)
#pragma unroll
                for (int i = 0; i < 4; i++) acc[a][i] = 0.f;
            {
                const uint32_t mb = u_mem + CO + l8;
                uint2 bf[3];
                uint32_t ok = 1;
                auto ldb = [&](int ks) {
                    if (ks == 0) mwait(u_bm + CO, par ^ 1);
                    else if (ks % 5 == 0) { if (!ok) mwait(u_bm + CO + (ks / 5) * 16, par ^ 1); }
                    if (ks % 5 == PROBE && ks < 15) ok = mtest(u_bm + CO + (ks / 5 + 1) * 16, par ^ 1);
                    if (ks % 5 == 4) {
                        bf[ks % 3].x = lds32(u_mem + CO + l4 + (ks / 5) * 2560 + 1024);
                        bf[ks % 3].y = lds32(u_mem + CO + l4 + (ks / 5) * 2560 + 1152);
                    } else bf[ks % 3] = lds64(mb + (ks / 5) * 2560 + (ks % 5) * 256);
                };
                ldb(0);
                TSTAMP(c * 12 + 0);
                ldb(1);
#pragma unroll
                for (int ks = 0; ks < 20; ks++) {
                    if (ks + 2 < 20) ldb(ks + 2);
#pragma unroll
                    for (int tt = 0; tt < 3; tt++) {
                        const int i = ks * 3 + tt;
                        if (q_smem(i)) {
                            const int s = q_slot(i);
                            mmau(acc[tt], qb[s % PDQ], bf[ks % 3].x, bf[ks % 3].y);
                            if (s + PDQ < NSQ) qb[s % PDQ] = lds128(wq_a + (s + PDQ) * 4096);
                        } else mmau(acc[tt], wr[q_slot(i)], bf[ks % 3].x, bf[ks % 3].y);
                    }
                }
            }
            TSTAMP(c * 12 + 1);
            stsm_x4_t(opq(qk_a) + CO, pack2(acc[0][0], acc[0][1]), pack2(acc[0][2], acc[0][3]), pack2(acc[1][0], acc[1][1]), pack2(acc[1][2], acc[1][3]));
            const uint32_t v0 = pack2(acc[2][0], acc[2][1]), v1 = pack2(acc[2][2], acc[2][3]);
            if (n == NSEG - 1) {
                sts64(u_v + CO + l8, v0, v1);
                named_bar(1, 256);
                if (kh == 1 && lane == 0) mbar_arrive(cb + C_BAR + B_F);
#pragma unroll
                for (int s = 0; s < PDQ; s++) qb[s] = lds128(wq_a + s * 4096);
                return;
            }
            named_arrive(1, 384);
            st_async_v2(u_v + CO + l8 + pd, v0, v1, cb + C_BAR + B_S + pd);
            st_async_v2(u_v + CO + l8 + sd, v0, v1, cb + C_BAR + B_S + sd);
            uint4 wb[PDW];
            const uint32_t ww_a = wq_a + (O_WW - O_WQ);
            if (warp < 3) {
                uint4 kb[4];
                const uint32_t t_tk = opq(t_tok);
                mwait(cb + C_BAR + B_T, par);
#pragma unroll
                for (int i = 0; i < 4; i++) kb[i] = ldsm4((t_tk ^ (i << 5)) + CO);
                named_bar(1, 384);
                uint4 qa[4];
#pragma unroll
                for (int i = 0; i < 4; i++) qa[i] = ldsm4(cb + l16 + C_Q + i * 512);
                if (warp == 2) {
#pragma unroll
                    for (int i = 0; i < 4; i++) kb[i] = ldsm4(cb + l16 + C_K + i * 512);
                }
                float s0[4][4], s1[4][4];
#pragma unroll
                for (int i = 0; i < 4; i++) {
#pragma unroll
                    for (int q = 0; q < 4; q++) s0[i][q] = s1[i][q] = 0.f;
                    mmau(s0[i], qa[i], kb[i].x, kb[i].y);
                    mmau(s1[i], qa[i], kb[i].z, kb[i].w);
                }
                const float a0 = ((s0[0][0] + s0[0][2]) + (s0[1][0] + s0[1][2])) + ((s0[2][0] + s0[2][2]) + (s0[3][0] + s0[3][2]));
                const float a1 = ((s0[0][1] + s0[0][3]) + (s0[1][1] + s0[1][3])) + ((s0[2][1] + s0[2][3]) + (s0[3][1] + s0[3][3]));
                const float b0 = ((s1[0][0] + s1[0][2]) + (s1[1][0] + s1[1][2])) + ((s1[2][0] + s1[2][2]) + (s1[3][0] + s1[3][2]));
                const float b1 = ((s1[0][1] + s1[0][3]) + (s1[1][1] + s1[1][3])) + ((s1[2][1] + s1[2][3]) + (s1[3][1] + s1[3][3]));
                const uint32_t so = u_role + CO + l16, bs = cb + C_BAR + B_S;
                const float c0 = warp == 2 ? a0 + b0 : a0, c1 = warp == 2 ? a1 + b1 : a1;
                st_async_v4(so + pd, __float_as_uint(c0), __float_as_uint(c1), __float_as_uint(b0), __float_as_uint(b1), bs + pd);
                st_async_v4(so + sd, __float_as_uint(c0), __float_as_uint(c1), __float_as_uint(b0), __float_as_uint(b1), bs + sd);
                TSTAMP(c * 12 + 2);
#pragma unroll
                for (int s = 0; s < PDW; s++) wb[s] = lds128(ww_a + s * 4096);
            } else if (warp == 3) {
                named_bar(1, 384);
                if (lane < 8) mbar_expect_tx(cb + C_BAR + l8, 1280);
#pragma unroll
                for (int s = 0; s < PDW; s++) wb[s] = lds128(ww_a + s * 4096);
            } else {
                mwait(cb + C_BAR + B_T, par);
                uint4 va[2][2];
                const uint32_t t_tk = opq(t_tok);
#pragma unroll
                for (int e = 0; e < 2; e++)
#pragma unroll
                    for (int k = 0; k < 2; k++)
                        ldsm_x4_t(va[e][k].x, va[e][k].y, va[e][k].z, va[e][k].w, (t_tk ^ (e << 5)) + CO + k * 2048);
#pragma unroll
                for (int s2 = 0; s2 < PDW1; s2++) wb[s2] = lds128(ww_a + s2 * 4096);
                mwait(cb + C_BAR + B_S, par);
                TSTAMP(c * 12 + 3);
                const uint32_t xa = cb + l16 + C_S;
                const uint4 x0 = lds128(xa), y0 = lds128(xa + 1536), x1 = lds128(xa + 512), y1 = lds128(xa + 512 + 1536);
                const uint2 x2 = lds64(xa + 1024), y2 = lds64(xa + 1024 + 1536);
                const uint32_t fv = u_role + CO + l8;
                const float cs = 0.08838834764831845f * 1.4426950408889634f;
                float s[10];
                s[8] = __uint_as_float(x2.x) + __uint_as_float(y2.x); s[9] = __uint_as_float(x2.y) + __uint_as_float(y2.y);
                s[0] = __uint_as_float(x0.x) + __uint_as_float(y0.x); s[1] = __uint_as_float(x0.y) + __uint_as_float(y0.y);
                s[2] = __uint_as_float(x0.z) + __uint_as_float(y0.z); s[3] = __uint_as_float(x0.w) + __uint_as_float(y0.w);
                s[4] = __uint_as_float(x1.x) + __uint_as_float(y1.x); s[5] = __uint_as_float(x1.y) + __uint_as_float(y1.y);
                s[6] = __uint_as_float(x1.z) + __uint_as_float(y1.z); s[7] = __uint_as_float(x1.w) + __uint_as_float(y1.w);
                float mx = fmaxf(fmaxf(fmaxf(s[0], s[1]), fmaxf(s[2], s[3])), fmaxf(fmaxf(fmaxf(s[4], s[5]), fmaxf(s[6], s[7])), fmaxf(s[8], s[9])));
                const float m1 = __shfl_xor_sync(0xffffffffu, mx, 1), m2 = __shfl_xor_sync(0xffffffffu, mx, 2), m3 = __shfl_xor_sync(0xffffffffu, mx, 3);
                const uint2 vm00 = lds64(fv), vm01 = lds64(fv + 256), vm10 = lds64(fv + 512), vm11 = lds64(fv + 768);
                const uint4 vm0 = make_uint4(vm00.x, vm00.y, vm01.x, vm01.y), vm1 = make_uint4(vm10.x, vm10.y, vm11.x, vm11.y);
                mx = fmaxf(fmaxf(mx, m1), fmaxf(m2, m3)) * -cs;
                uint32_t pb[5];
                pb[4] = pack2(ex2f(fmaf(s[8], cs, mx)), ex2f(fmaf(s[9], cs, mx)));
#pragma unroll
                for (int i = 0; i < 4; i++) pb[i] = pack2(ex2f(fmaf(s[2 * i], cs, mx)), ex2f(fmaf(s[2 * i + 1], cs, mx)));
                float o[3][4];
#pragma unroll
                for (int i = 0; i < 4; i++) { o[0][i] = o[1][i] = o[2][i] = 0.f; }
                const uint32_t one2 = 0x3F803F80u;
                mma16816(o[2], one2, one2, one2, one2, pb[4], 0u);
                mmau(o[0], vm0, pb[4], pb[4]);
                mmau(o[1], vm1, pb[4], pb[4]);
                mma16816(o[2], one2, one2, one2, one2, pb[0], pb[1]);
                mmau(o[0], va[0][0], pb[0], pb[1]);
                mmau(o[1], va[1][0], pb[0], pb[1]);
                mma16816(o[2], one2, one2, one2, one2, pb[2], pb[3]);
                mmau(o[0], va[0][1], pb[2], pb[3]);
                mmau(o[1], va[1][1], pb[2], pb[3]);
                const float r0 = rcpf(o[2][0]), r1 = rcpf(o[2][1]);
                stsm_x4_t(cb + l16 + C_Q + j * 512, pack2(o[0][0] * r0, o[0][1] * r1), pack2(o[0][2] * r0, o[0][3] * r1), pack2(o[1][0] * r0, o[1][1] * r1), pack2(o[1][2] * r0, o[1][3] * r1));
                named_arrive(2, 384);
                TSTAMP(c * 12 + 4);
#pragma unroll
                for (int s2 = PDW1; s2 < PDW; s2++) wb[s2] = lds128(ww_a + s2 * 4096);
                if (lane == 0) mbar_arrive(cb + C_BAR + B_F);
                if (warp == 4 && lane == 0) mbar_expect_tx(cb + C_BAR + B_S, S_BYTES);
            }
            named_bar(2, 384);
            TSTAMP(c * 12 + 5);
            {
                uint4 ob[4];
                ob[0] = ldsm4(u_ob0 + CO + l16); ob[1] = ldsm4(u_ob0 + CO + l16 + 512);
                ob[2] = ldsm4(u_ob1 + CO + l16); ob[3] = ldsm4(u_ob1 + CO + l16 + 512);
                float d[4][4];
#pragma unroll
                for (int a = 0; a < 4; a++)
#pragma unroll
                    for (int i = 0; i < 4; i++) d[a][i] = 0.f;
                const uint32_t ra = u_ra + CO + l8, rb = cb + C_BAR + B_R;
#pragma unroll
                for (int i = 0; i < 20; i++) {
                    const int k = w_k(i), ac = w_acc(i);
                    const uint32_t b0 = (k & 1) ? ob[k >> 1].z : ob[k >> 1].x, b1 = (k & 1) ? ob[k >> 1].w : ob[k >> 1].y;
                    if (w_smem(i)) {
                        const int s = w_slot(i);
                        mmau(d[ac], wb[s % PDW], b0, b1);
                        if (s + PDW < NSW) wb[s % PDW] = lds128(ww_a + (s + PDW) * 4096);
                    } else mmau(d[ac], wr[NRQ + w_slot(i)], b0, b1);
                    if (i == 9) {
                        const uint32_t rs = u_ra + CO + l4 + 4096 + (warp & 1) * 128;
                        st_async_u32(rs + oe, pack2(d[2][0], d[2][1]), rb + 16 + oe);
                        st_async_u32(rs + oo, pack2(d[2][2], d[2][3]), rb + 16 + oo);
                    }
                    if (i == 17) st_async_v2(ra + od, pack2(d[0][0], d[0][1]), pack2(d[0][2], d[0][3]), rb + od);
                }
                st_async_v2(ra + 2048 + od, pack2(d[1][0] + d[3][0], d[1][1] + d[3][1]), pack2(d[1][2] + d[3][2], d[1][3] + d[3][3]), rb + 8 + od);
                TSTAMP(c * 12 + 6);
#pragma unroll
                for (int s = 0; s < PDQ; s++) qb[s] = lds128(wq_a + s * 4096);
            }
        };
#pragma unroll 1
        for (int t = 0; t < NTICK; t++) {
            if (t < NSEG) tick(IC<0>{}, t);
            if (t >= LAG) tick(IC<1>{}, t - LAG);
        }
    } else {
        asm volatile("setmaxnreg.dec.sync.aligned.u32 40;");
        const int s = warp - 8;
        cluster_sync_all();
        if (s < 3) {
#pragma unroll 1
            for (int hs = 0; hs < 2 * NTICK; hs++) {
                const int c = hs & 1, t = hs >> 1;
                const int n = t - c * LAG;
                if (n < 0 || n >= NSEG - 1) continue;
                const uint32_t cb = sb + O_REST + c * C_SIZE;
                const uint32_t par = (uint32_t)(n & 1);
                const uint32_t tag = (uint32_t)(n % 13) + 1u;
                uint32_t* xb = g_xc + (size_t)((c * 2 + par) * CL + r) * (NCLU * 320) + s * 128;
                const uint32_t ra = cb + C_RED + s * 2048 + lane * (s < 2 ? 8 : 4);
                mwait(cb + C_BAR + B_R + s * 8, par);
                TSTAMP(c * 12 + 7);
                uint4 p[4];
                if (s < 2) {
#pragma unroll
                    for (int i = 0; i < 4; i++) {
                        const uint2 a = lds64(ra + i * 512), b = lds64(ra + i * 512 + 256);
                        p[i] = make_uint4(a.x, a.y, b.x, b.y);
                    }
                } else {
#pragma unroll
                    for (int i = 0; i < 4; i++) p[i] = make_uint4(lds32(ra + i * 512), lds32(ra + i * 512 + 128), lds32(ra + i * 512 + 256), lds32(ra + i * 512 + 384));
                }
                if (lane == 0) mbar_expect_tx(cb + C_BAR + B_R + s * 8, 2048);
                uint32_t m0, m1;
                if (s < 2) {
                    float f0 = 0.f, f1 = 0.f, f2 = 0.f, f3 = 0.f;
#pragma unroll
                    for (int i = 0; i < 4; i++) {
                        f0 += blo(p[i].x) + blo(p[i].z); f1 += bhi(p[i].x) + bhi(p[i].z);
                        f2 += blo(p[i].y) + blo(p[i].w); f3 += bhi(p[i].y) + bhi(p[i].w);
                    }
                    xb += lane * 4;
                    const uint32_t u0 = (__float_as_uint(f0) & ~0xFu) | tag, u1 = (__float_as_uint(f1) & ~0xFu) | tag;
                    const uint32_t u2 = (__float_as_uint(f2) & ~0xFu) | tag, u3 = (__float_as_uint(f3) & ~0xFu) | tag;
                    st_relaxed_v4(xb + cq * 320, u0, u1, u2, u3);
                    TSTAMP(c * 12 + 8);
                    xdelay();
                    uint4 x[NCLU];
#pragma unroll
                    for (int k = 0; k < NCLU; k++) x[k] = make_uint4(u0, u1, u2, u3);
                    int guard = 0;
                    bool first = true;
                    while (true) {
                        bool ok = true;
#pragma unroll
                        for (int k = 0; k < NCLU; k++) {
                            const bool okk = k == cq || (!first && ((x[k].x ^ tag) | (x[k].y ^ tag) | (x[k].z ^ tag) | (x[k].w ^ tag)) << 28 == 0);
                            if (!okk) { x[k] = ld_relaxed_v4(xb + k * 320); ok = false; }
                        }
                        first = false;
                        if (__all_sync(0xffffffffu, ok) || ++guard > SPIN_LIMIT) break;
                    }
                    TVAL(c * 12 + 11, guard);
                    f0 = f1 = f2 = f3 = 0.f;
#pragma unroll
                    for (int k = 0; k < NCLU; k++) {
                        f0 += __uint_as_float(x[k].x & ~0xFu); f1 += __uint_as_float(x[k].y & ~0xFu);
                        f2 += __uint_as_float(x[k].z & ~0xFu); f3 += __uint_as_float(x[k].w & ~0xFu);
                    }
                    m0 = movmat(pack2(f0, f1)); m1 = movmat(pack2(f2, f3));
                } else {
                    float f0 = 0.f, f1 = 0.f;
#pragma unroll
                    for (int i = 0; i < 4; i++) {
                        f0 += (blo(p[i].x) + blo(p[i].y)) + (blo(p[i].z) + blo(p[i].w));
                        f1 += (bhi(p[i].x) + bhi(p[i].y)) + (bhi(p[i].z) + bhi(p[i].w));
                    }
                    xb += lane * 2;
                    const uint32_t u0 = (__float_as_uint(f0) & ~0xFu) | tag, u1 = (__float_as_uint(f1) & ~0xFu) | tag;
                    st_relaxed_v2(xb + cq * 320, u0, u1);
                    TSTAMP(c * 12 + 8);
                    xdelay();
                    uint2 x[NCLU];
#pragma unroll
                    for (int k = 0; k < NCLU; k++) x[k] = make_uint2(u0, u1);
                    int guard = 0;
                    bool first = true;
                    while (true) {
                        bool ok = true;
#pragma unroll
                        for (int k = 0; k < NCLU; k++) {
                            const bool okk = k == cq || (!first && ((x[k].x ^ tag) | (x[k].y ^ tag)) << 28 == 0);
                            if (!okk) { x[k] = ld_relaxed_v2(xb + k * 320); ok = false; }
                        }
                        first = false;
                        if (__all_sync(0xffffffffu, ok) || ++guard > SPIN_LIMIT) break;
                    }
                    TVAL(c * 12 + 11, guard);
                    f0 = f1 = 0.f;
#pragma unroll
                    for (int k = 0; k < NCLU; k++) { f0 += __uint_as_float(x[k].x & ~0xFu); f1 += __uint_as_float(x[k].y & ~0xFu); }
                    m0 = movmat(pack2(f0, f1)); m1 = 0;
                }
                TSTAMP(c * 12 + 9);
                const uint32_t ma = cb + C_MEM + (s < 2 ? lane * 8 + (hf * 2 + s) * 256 : 1024 + hf * 128 + lane * 4), bm = cb + C_BAR;
                if (s < 2) {
#pragma unroll
                    for (int G = 0; G < 8; G++)
#pragma unroll
                        for (int b = 0; b < 2; b++) {
                            const uint32_t dd = mapa(sb, (uint32_t)(((r + 2 * G) & 15) ^ b)) - sb;
                            st_async_v2(ma + G * 1280 + dd, m0, m1, bm + G * 8 + dd);
                        }
                } else {
#pragma unroll
                    for (int G = 0; G < 8; G++)
#pragma unroll
                        for (int b = 0; b < 2; b++) {
                            const uint32_t dd = mapa(sb, (uint32_t)(((r + 2 * G) & 15) ^ b)) - sb;
                            st_async_u32(ma + G * 1280 + dd, m0, bm + G * 8 + dd);
                        }
                }
                TSTAMP(c * 12 + 10);
            }
        } else {
            auto fetch = [&](int c, int seg) {
                if (lane == 0) {
                    if (seg % CSEG == 0) {
                        int guard = 0;
                        while (ld_acquire(FLG(F_KV + c * NCHK + seg / CSEG)) < A.kv_target && ++guard < SPIN_LIMIT) __nanosleep(64);
                    }
                    asm volatile("fence.proxy.async;" ::: "memory");
                    const uint32_t cb = sb + O_REST + c * C_SIZE;
                    const uint32_t bt = cb + C_BAR + B_T, d = cb + C_TOK;
                    mbar_expect_tx(bt, 12288);
                    const CUtensorMap* mk = &A.tk[c];
                    const CUtensorMap* mv = &A.tv[c];
                    asm volatile("cp.async.bulk.tensor.2d.shared::cluster.global.mbarrier::complete_tx::bytes [%0], [%1, {%3, %4}], [%2];" ::"r"(d),
                                 "l"(mk), "r"(bt), "r"(h * DH + hf * 64), "r"(seg * SEG) : "memory");
#pragma unroll
                    for (int i = 0; i < 2; i++)
                        asm volatile("cp.async.bulk.tensor.2d.shared::cluster.global.mbarrier::complete_tx::bytes [%0], [%1, {%3, %4}], [%2];" ::"r"(d + 4096 + i * 4096),
                                     "l"(mv), "r"(bt), "r"(h * DH + i * 64), "r"(seg * SEG) : "memory");
                }
                __syncwarp();
            };
            fetch(0, 0);
#pragma unroll 1
            for (int hs = 0; hs < 2 * NTICK; hs++) {
                const int c = hs & 1, t = hs >> 1;
                const int n = t - c * LAG;
                if (n < -1 || n >= NSEG) continue;
                if (n >= 0) {
                    const uint32_t cb = sb + O_REST + c * C_SIZE;
                    mwait(cb + C_BAR + B_F, (uint32_t)(n & 1));
                    uint4* fd = g_kvf + (size_t)((c * NSEG + n) * NH + h) * 256 + hf * 64 + lane;
#pragma unroll
                    for (int i = 0; i < 2; i++) {
                        const uint4 k0 = ldsm4(cb + C_K + i * 1024 + lane * 16), k1 = ldsm4(cb + C_K + i * 1024 + 512 + lane * 16);
                        fd[i * 32] = make_uint4(badd2(k0.x, k0.z), badd2(k0.y, k0.w), badd2(k1.x, k1.z), badd2(k1.y, k1.w));
                        const uint32_t va = cb + C_V + hf * 2048 + i * 1024 + lane * 8;
                        const uint2 v0 = lds64(va), v1 = lds64(va + 256), v2 = lds64(va + 512), v3 = lds64(va + 768);
                        fd[128 + i * 32] = make_uint4(badd2(v0.x, v1.x), badd2(v0.y, v1.y), badd2(v2.x, v3.x), badd2(v2.y, v3.y));
                    }
                    if (blockIdx.x == 0 && lane == 0 && (c == 0 || t >= NSEG)) asm volatile("st.relaxed.gpu.global.u32 [%0], %1;" ::"l"(FLG(F_PROG)), "r"(t + 1) : "memory");
                    if ((n % CSEG) == CSEG - 1) {
                        asm volatile("fence.proxy.async;" ::: "memory");
                        __syncwarp();
                        if (lane == 0) { red_release(FLG(F_MEM + c * NCHK + n / CSEG), 1); }
                    }
                }
                if (n + 1 < NSEG - 1) fetch(c, n + 1);
            }
        }
    }
    cluster_sync_all();
}
}

namespace ni {
constexpr int KV_TGT = 32, MEM_TGT = 64, OP_TGT = 16, CONV_TGT = 80, H_TGT = 128;
constexpr int PDIST = (LAG + 3) / 4;
#define QA_PRE 3
#define KV1_W 5
#define KV1_N 16
static_assert(QA_PRE < 4, "inputs of the chunk must be complete");
#define SPLAN 0x102030
#define URGENT 1
#define POST_NS 40

#define ELECT "{\n.reg .pred p;\nelect.sync _|p, 0xffffffff;\n@p "
__device__ __forceinline__ void tma_load_2d(uint32_t dst, const CUtensorMap* map, uint32_t bar, int c0, int c1) {
    asm volatile(ELECT "cp.async.bulk.tensor.2d.shared::cluster.global.mbarrier::complete_tx::bytes [%0], [%1, {%3, %4}], [%2];\n}" ::"r"(dst),
                 "l"(map), "r"(bar), "r"(c0), "r"(c1) : "memory");
}
__device__ __forceinline__ void tma_load_2d_mc(uint32_t dst, const CUtensorMap* map, uint32_t bar, int c0, int c1) {
    asm volatile(ELECT "cp.async.bulk.tensor.2d.shared::cluster.global.mbarrier::complete_tx::bytes.multicast::cluster [%0], [%1, {%3, %4}], [%2], %5;\n}" ::"r"(dst),
                 "l"(map), "r"(bar), "r"(c0), "r"(c1), "h"((unsigned short)3) : "memory");
}
__device__ __forceinline__ void tma_load_3d(uint32_t dst, const CUtensorMap* map, uint32_t bar, int c1, int c2) {
    asm volatile(ELECT "cp.async.bulk.tensor.3d.shared::cluster.global.mbarrier::complete_tx::bytes [%0], [%1, {%5, %3, %4}], [%2];\n}" ::"r"(dst),
                 "l"(map), "r"(bar), "r"(c1), "r"(c2), "r"(0) : "memory");
}
__device__ __forceinline__ void tma_load_3d_mc(uint32_t dst, const CUtensorMap* map, uint32_t bar, int c1, int c2) {
    asm volatile(ELECT "cp.async.bulk.tensor.3d.shared::cluster.global.mbarrier::complete_tx::bytes.multicast::cluster [%0], [%1, {%6, %3, %4}], [%2], %5;\n}" ::"r"(dst),
                 "l"(map), "r"(bar), "r"(c1), "r"(c2), "h"((unsigned short)3), "r"(0) : "memory");
}
__device__ __forceinline__ void bulk_load(uint32_t dst, const void* src, uint32_t bytes, uint32_t bar) {
    asm volatile(ELECT "cp.async.bulk.shared::cluster.global.mbarrier::complete_tx::bytes [%0], [%1], %2, [%3];\n}" ::"r"(dst), "l"(src), "r"(bytes), "r"(bar) : "memory");
}
__device__ __forceinline__ void expect_tx1(uint32_t bar, uint32_t bytes) {
    asm volatile(ELECT "mbarrier.arrive.expect_tx.shared::cta.b64 _, [%0], %1;\n}" ::"r"(bar), "r"(bytes) : "memory");
}
__device__ __forceinline__ void wg_fence() { asm volatile("wgmma.fence.sync.aligned;" ::: "memory"); }
__device__ __forceinline__ void wg_commit() { asm volatile("wgmma.commit_group.sync.aligned;" ::: "memory"); }
template <int N> __device__ __forceinline__ void wg_wait() { asm volatile("wgmma.wait_group.sync.aligned %0;" ::"n"(N) : "memory"); }
__device__ __forceinline__ uint64_t make_desc(uint32_t addr, uint32_t lbo, uint32_t sbo) {
    return (uint64_t)((addr & 0x3FFFF) >> 4) | ((uint64_t)((lbo & 0x3FFFF) >> 4) << 16) |
           ((uint64_t)((sbo & 0x3FFFF) >> 4) << 32) | (1ull << 62);
}
__device__ __forceinline__ void wgmma_m64n256k16(float* d, uint64_t da, uint64_t db) {
    asm volatile("{\n.reg .pred p;\nsetp.ne.b32 p, 1, 0;\n"
                 "wgmma.mma_async.sync.aligned.m64n256k16.f32.bf16.bf16 {%0, %1, %2, %3, %4, %5, %6, %7, %8, %9, %10, %11, %12, %13, %14, %15, %16, %17, %18, %19, %20, %21, %22, %23, %24, %25, %26, %27, %28, %29, %30, %31, %32, %33, %34, %35, %36, %37, %38, %39, %40, %41, %42, %43, %44, %45, %46, %47, %48, %49, %50, %51, %52, %53, %54, %55, %56, %57, %58, %59, %60, %61, %62, %63, %64, %65, %66, %67, %68, %69, %70, %71, %72, %73, %74, %75, %76, %77, %78, %79, %80, %81, %82, %83, %84, %85, %86, %87, %88, %89, %90, %91, %92, %93, %94, %95, %96, %97, %98, %99, %100, %101, %102, %103, %104, %105, %106, %107, %108, %109, %110, %111, %112, %113, %114, %115, %116, %117, %118, %119, %120, %121, %122, %123, %124, %125, %126, %127}, %128, %129, p, 1, 1, 0, 1;\n}\n"
                 : "+f"(d[0]), "+f"(d[1]), "+f"(d[2]), "+f"(d[3]), "+f"(d[4]), "+f"(d[5]), "+f"(d[6]), "+f"(d[7]), "+f"(d[8]), "+f"(d[9]), "+f"(d[10]), "+f"(d[11]), "+f"(d[12]), "+f"(d[13]), "+f"(d[14]), "+f"(d[15]), "+f"(d[16]), "+f"(d[17]), "+f"(d[18]), "+f"(d[19]), "+f"(d[20]), "+f"(d[21]), "+f"(d[22]), "+f"(d[23]), "+f"(d[24]), "+f"(d[25]), "+f"(d[26]), "+f"(d[27]), "+f"(d[28]), "+f"(d[29]), "+f"(d[30]), "+f"(d[31]), "+f"(d[32]), "+f"(d[33]), "+f"(d[34]), "+f"(d[35]), "+f"(d[36]), "+f"(d[37]), "+f"(d[38]), "+f"(d[39]), "+f"(d[40]), "+f"(d[41]), "+f"(d[42]), "+f"(d[43]), "+f"(d[44]), "+f"(d[45]), "+f"(d[46]), "+f"(d[47]), "+f"(d[48]), "+f"(d[49]), "+f"(d[50]), "+f"(d[51]), "+f"(d[52]), "+f"(d[53]), "+f"(d[54]), "+f"(d[55]), "+f"(d[56]), "+f"(d[57]), "+f"(d[58]), "+f"(d[59]), "+f"(d[60]), "+f"(d[61]), "+f"(d[62]), "+f"(d[63]), "+f"(d[64]), "+f"(d[65]), "+f"(d[66]), "+f"(d[67]), "+f"(d[68]), "+f"(d[69]), "+f"(d[70]), "+f"(d[71]), "+f"(d[72]), "+f"(d[73]), "+f"(d[74]), "+f"(d[75]), "+f"(d[76]), "+f"(d[77]), "+f"(d[78]), "+f"(d[79]), "+f"(d[80]), "+f"(d[81]), "+f"(d[82]), "+f"(d[83]), "+f"(d[84]), "+f"(d[85]), "+f"(d[86]), "+f"(d[87]), "+f"(d[88]), "+f"(d[89]), "+f"(d[90]), "+f"(d[91]), "+f"(d[92]), "+f"(d[93]), "+f"(d[94]), "+f"(d[95]), "+f"(d[96]), "+f"(d[97]), "+f"(d[98]), "+f"(d[99]), "+f"(d[100]), "+f"(d[101]), "+f"(d[102]), "+f"(d[103]), "+f"(d[104]), "+f"(d[105]), "+f"(d[106]), "+f"(d[107]), "+f"(d[108]), "+f"(d[109]), "+f"(d[110]), "+f"(d[111]), "+f"(d[112]), "+f"(d[113]), "+f"(d[114]), "+f"(d[115]), "+f"(d[116]), "+f"(d[117]), "+f"(d[118]), "+f"(d[119]), "+f"(d[120]), "+f"(d[121]), "+f"(d[122]), "+f"(d[123]), "+f"(d[124]), "+f"(d[125]), "+f"(d[126]), "+f"(d[127])
                 : "l"(da), "l"(db));
}
__device__ __forceinline__ void wgmma_m64n256k16_first(float* d, uint64_t da, uint64_t db) {
    asm volatile("{\n.reg .pred p;\nsetp.ne.b32 p, 0, 0;\n"
                 "wgmma.mma_async.sync.aligned.m64n256k16.f32.bf16.bf16 {%0, %1, %2, %3, %4, %5, %6, %7, %8, %9, %10, %11, %12, %13, %14, %15, %16, %17, %18, %19, %20, %21, %22, %23, %24, %25, %26, %27, %28, %29, %30, %31, %32, %33, %34, %35, %36, %37, %38, %39, %40, %41, %42, %43, %44, %45, %46, %47, %48, %49, %50, %51, %52, %53, %54, %55, %56, %57, %58, %59, %60, %61, %62, %63, %64, %65, %66, %67, %68, %69, %70, %71, %72, %73, %74, %75, %76, %77, %78, %79, %80, %81, %82, %83, %84, %85, %86, %87, %88, %89, %90, %91, %92, %93, %94, %95, %96, %97, %98, %99, %100, %101, %102, %103, %104, %105, %106, %107, %108, %109, %110, %111, %112, %113, %114, %115, %116, %117, %118, %119, %120, %121, %122, %123, %124, %125, %126, %127}, %128, %129, p, 1, 1, 0, 1;\n}\n"
                 : "=f"(d[0]), "=f"(d[1]), "=f"(d[2]), "=f"(d[3]), "=f"(d[4]), "=f"(d[5]), "=f"(d[6]), "=f"(d[7]), "=f"(d[8]), "=f"(d[9]), "=f"(d[10]), "=f"(d[11]), "=f"(d[12]), "=f"(d[13]), "=f"(d[14]), "=f"(d[15]), "=f"(d[16]), "=f"(d[17]), "=f"(d[18]), "=f"(d[19]), "=f"(d[20]), "=f"(d[21]), "=f"(d[22]), "=f"(d[23]), "=f"(d[24]), "=f"(d[25]), "=f"(d[26]), "=f"(d[27]), "=f"(d[28]), "=f"(d[29]), "=f"(d[30]), "=f"(d[31]), "=f"(d[32]), "=f"(d[33]), "=f"(d[34]), "=f"(d[35]), "=f"(d[36]), "=f"(d[37]), "=f"(d[38]), "=f"(d[39]), "=f"(d[40]), "=f"(d[41]), "=f"(d[42]), "=f"(d[43]), "=f"(d[44]), "=f"(d[45]), "=f"(d[46]), "=f"(d[47]), "=f"(d[48]), "=f"(d[49]), "=f"(d[50]), "=f"(d[51]), "=f"(d[52]), "=f"(d[53]), "=f"(d[54]), "=f"(d[55]), "=f"(d[56]), "=f"(d[57]), "=f"(d[58]), "=f"(d[59]), "=f"(d[60]), "=f"(d[61]), "=f"(d[62]), "=f"(d[63]), "=f"(d[64]), "=f"(d[65]), "=f"(d[66]), "=f"(d[67]), "=f"(d[68]), "=f"(d[69]), "=f"(d[70]), "=f"(d[71]), "=f"(d[72]), "=f"(d[73]), "=f"(d[74]), "=f"(d[75]), "=f"(d[76]), "=f"(d[77]), "=f"(d[78]), "=f"(d[79]), "=f"(d[80]), "=f"(d[81]), "=f"(d[82]), "=f"(d[83]), "=f"(d[84]), "=f"(d[85]), "=f"(d[86]), "=f"(d[87]), "=f"(d[88]), "=f"(d[89]), "=f"(d[90]), "=f"(d[91]), "=f"(d[92]), "=f"(d[93]), "=f"(d[94]), "=f"(d[95]), "=f"(d[96]), "=f"(d[97]), "=f"(d[98]), "=f"(d[99]), "=f"(d[100]), "=f"(d[101]), "=f"(d[102]), "=f"(d[103]), "=f"(d[104]), "=f"(d[105]), "=f"(d[106]), "=f"(d[107]), "=f"(d[108]), "=f"(d[109]), "=f"(d[110]), "=f"(d[111]), "=f"(d[112]), "=f"(d[113]), "=f"(d[114]), "=f"(d[115]), "=f"(d[116]), "=f"(d[117]), "=f"(d[118]), "=f"(d[119]), "=f"(d[120]), "=f"(d[121]), "=f"(d[122]), "=f"(d[123]), "=f"(d[124]), "=f"(d[125]), "=f"(d[126]), "=f"(d[127])
                 : "l"(da), "l"(db));
}
__device__ __forceinline__ void wgmma_rs_m64n128k16(float* d, const uint32_t* a, uint64_t db) {
    asm volatile("{\n.reg .pred p;\nsetp.ne.b32 p, 1, 0;\n"
                 "wgmma.mma_async.sync.aligned.m64n128k16.f32.bf16.bf16 {%0, %1, %2, %3, %4, %5, %6, %7, %8, %9, %10, %11, %12, %13, %14, %15, %16, %17, %18, %19, %20, %21, %22, %23, %24, %25, %26, %27, %28, %29, %30, %31, %32, %33, %34, %35, %36, %37, %38, %39, %40, %41, %42, %43, %44, %45, %46, %47, %48, %49, %50, %51, %52, %53, %54, %55, %56, %57, %58, %59, %60, %61, %62, %63}, {%64, %65, %66, %67}, %68, p, 1, 1, 1;\n}\n"
                 : "+f"(d[0]), "+f"(d[1]), "+f"(d[2]), "+f"(d[3]), "+f"(d[4]), "+f"(d[5]), "+f"(d[6]), "+f"(d[7]), "+f"(d[8]), "+f"(d[9]), "+f"(d[10]), "+f"(d[11]), "+f"(d[12]), "+f"(d[13]), "+f"(d[14]), "+f"(d[15]), "+f"(d[16]), "+f"(d[17]), "+f"(d[18]), "+f"(d[19]), "+f"(d[20]), "+f"(d[21]), "+f"(d[22]), "+f"(d[23]), "+f"(d[24]), "+f"(d[25]), "+f"(d[26]), "+f"(d[27]), "+f"(d[28]), "+f"(d[29]), "+f"(d[30]), "+f"(d[31]), "+f"(d[32]), "+f"(d[33]), "+f"(d[34]), "+f"(d[35]), "+f"(d[36]), "+f"(d[37]), "+f"(d[38]), "+f"(d[39]), "+f"(d[40]), "+f"(d[41]), "+f"(d[42]), "+f"(d[43]), "+f"(d[44]), "+f"(d[45]), "+f"(d[46]), "+f"(d[47]), "+f"(d[48]), "+f"(d[49]), "+f"(d[50]), "+f"(d[51]), "+f"(d[52]), "+f"(d[53]), "+f"(d[54]), "+f"(d[55]), "+f"(d[56]), "+f"(d[57]), "+f"(d[58]), "+f"(d[59]), "+f"(d[60]), "+f"(d[61]), "+f"(d[62]), "+f"(d[63])
                 : "r"(a[0]), "r"(a[1]), "r"(a[2]), "r"(a[3]), "l"(db));
}
__device__ __forceinline__ void wgmma_rs_m64n128k16_first(float* d, const uint32_t* a, uint64_t db) {
    asm volatile("{\n.reg .pred p;\nsetp.ne.b32 p, 0, 0;\n"
                 "wgmma.mma_async.sync.aligned.m64n128k16.f32.bf16.bf16 {%0, %1, %2, %3, %4, %5, %6, %7, %8, %9, %10, %11, %12, %13, %14, %15, %16, %17, %18, %19, %20, %21, %22, %23, %24, %25, %26, %27, %28, %29, %30, %31, %32, %33, %34, %35, %36, %37, %38, %39, %40, %41, %42, %43, %44, %45, %46, %47, %48, %49, %50, %51, %52, %53, %54, %55, %56, %57, %58, %59, %60, %61, %62, %63}, {%64, %65, %66, %67}, %68, p, 1, 1, 1;\n}\n"
                 : "=f"(d[0]), "=f"(d[1]), "=f"(d[2]), "=f"(d[3]), "=f"(d[4]), "=f"(d[5]), "=f"(d[6]), "=f"(d[7]), "=f"(d[8]), "=f"(d[9]), "=f"(d[10]), "=f"(d[11]), "=f"(d[12]), "=f"(d[13]), "=f"(d[14]), "=f"(d[15]), "=f"(d[16]), "=f"(d[17]), "=f"(d[18]), "=f"(d[19]), "=f"(d[20]), "=f"(d[21]), "=f"(d[22]), "=f"(d[23]), "=f"(d[24]), "=f"(d[25]), "=f"(d[26]), "=f"(d[27]), "=f"(d[28]), "=f"(d[29]), "=f"(d[30]), "=f"(d[31]), "=f"(d[32]), "=f"(d[33]), "=f"(d[34]), "=f"(d[35]), "=f"(d[36]), "=f"(d[37]), "=f"(d[38]), "=f"(d[39]), "=f"(d[40]), "=f"(d[41]), "=f"(d[42]), "=f"(d[43]), "=f"(d[44]), "=f"(d[45]), "=f"(d[46]), "=f"(d[47]), "=f"(d[48]), "=f"(d[49]), "=f"(d[50]), "=f"(d[51]), "=f"(d[52]), "=f"(d[53]), "=f"(d[54]), "=f"(d[55]), "=f"(d[56]), "=f"(d[57]), "=f"(d[58]), "=f"(d[59]), "=f"(d[60]), "=f"(d[61]), "=f"(d[62]), "=f"(d[63])
                 : "r"(a[0]), "r"(a[1]), "r"(a[2]), "r"(a[3]), "l"(db));
}

struct BulkMaps { CUtensorMap h, h2, wq, wk, wv, wo, kv, lu; };
struct BulkArgs {
    const bf16 *x, *ssmk, *ssmD, *Bk, *Bv, *shiftk;
    bf16* out;
};
enum { T_KV = 0, T_QA, T_CONV, T_ATT, T_POST, T_LN0 };
constexpr int MAXG = 52, SENT = MAXG - 1;
struct Sched { uint32_t chk[MAXG * 4]; uint32_t info[MAXG]; int sbeg[8]; };

constexpr int BK_STAGES = 4, BK_STAGE_BYTES = 49152, TSLOTS = 4;
struct BulkSmemTail {
    unsigned long long full[BK_STAGES], empty[BK_STAGES], tfull[TSLOTS], tempty[TSLOTS], sfull[4], sempty[4];
    int task[TSLOTS];
    uint32_t tab[MAXG * 5];
};
constexpr int BULK_STG = BK_STAGES * BK_STAGE_BYTES;
constexpr int BULK_TAIL = BULK_STG + 32768;
constexpr int BULK_SMEM = BULK_TAIL + (int)sizeof(BulkSmemTail);
static_assert(BULK_SMEM <= 232448, "bulk smem");
#define PACE 0
#define REG_C 224
#define REG_P 56

#define BT(lead, type, l, c, k)
#define TT(k)
#define FT(k)
#define TTV(k, v)
__device__ __forceinline__ void tma_store_2d(const CUtensorMap* map, uint32_t src, int c0, int c1) {
    asm volatile("cp.async.bulk.tensor.2d.global.shared::cta.bulk_group [%0, {%2, %3}], [%1];" ::"l"(map), "r"(src), "r"(c0), "r"(c1) : "memory");
}
__device__ __forceinline__ void bulk_commit() { asm volatile("cp.async.bulk.commit_group;" ::: "memory"); }
template <int N> __device__ __forceinline__ void bulk_wait_read() { asm volatile("cp.async.bulk.wait_group.read %0;" ::"n"(N) : "memory"); }
template <int N> __device__ __forceinline__ void bulk_wait() { asm volatile("cp.async.bulk.wait_group %0;" ::"n"(N) : "memory"); }
__device__ __forceinline__ void mbar_arrive_cluster(uint32_t bar) {
    asm volatile("mbarrier.arrive.shared::cluster.b64 _, [%0];" ::"r"(bar) : "memory");
}
__device__ __forceinline__ void stsm_x4(uint32_t addr, uint32_t r0, uint32_t r1, uint32_t r2, uint32_t r3) {
    asm volatile("stmatrix.sync.aligned.m8n8.x4.shared.b16 [%0], {%1,%2,%3,%4};" ::"r"(addr), "r"(r0), "r"(r1), "r"(r2), "r"(r3) : "memory");
}
__device__ __forceinline__ void mma1688(float* c, uint32_t a0, uint32_t a1, uint32_t b0) {
    asm("mma.sync.aligned.m16n8k8.row.col.f32.bf16.bf16.f32 {%0,%1,%2,%3}, {%4,%5}, {%6}, {%0,%1,%2,%3};"
        : "+f"(c[0]), "+f"(c[1]), "+f"(c[2]), "+f"(c[3]) : "r"(a0), "r"(a1), "r"(b0));
}
__device__ __forceinline__ int ld_relaxed(const int* p) {
    int v;
    asm volatile("ld.relaxed.gpu.global.u32 %0, [%1];" : "=r"(v) : "l"(p) : "memory");
    return v;
}
__device__ __forceinline__ void flag_wait(const int* f, int tgt, int ns) {
    int guard = 0;
    while (ld_relaxed(f) < tgt && ++guard < 4000000) __nanosleep(ns);
}
__device__ __forceinline__ void fence_async() { asm volatile("fence.proxy.async.global;" ::: "memory"); }
__device__ __forceinline__ uint32_t bmul2(uint32_t a, uint32_t b) { uint32_t r; asm("mul.rn.bf16x2 %0, %1, %2;" : "=r"(r) : "r"(a), "r"(b)); return r; }
__device__ __forceinline__ uint32_t bsum2(uint32_t a, uint32_t b) { uint32_t r; asm("add.rn.bf16x2 %0, %1, %2;" : "=r"(r) : "r"(a), "r"(b)); return r; }
__device__ __forceinline__ uint32_t bmax2(uint32_t a, uint32_t b) { uint32_t r; asm("max.bf16x2 %0, %1, %2;" : "=r"(r) : "r"(a), "r"(b)); return r; }
__device__ __forceinline__ uint32_t rscore(float a, float b) {
    const uint32_t u = pack2(a, b);
    return pack2(blo(u) * 0.08838834764831845f, bhi(u) * 0.08838834764831845f);
}
template <int STRIDE> __device__ __forceinline__ void ld5(uint32_t* w, const bf16* p) {
#pragma unroll
    for (int r = 0; r < 5; r++) { const uint2 v = __ldcg(reinterpret_cast<const uint2*>(p + r * STRIDE)); w[2 * r] = v.x; w[2 * r + 1] = v.y; }
}
__device__ __forceinline__ void st5(bf16* p, const uint32_t* w) {
#pragma unroll
    for (int r = 0; r < 5; r++) *reinterpret_cast<uint2*>(p + r * 128) = make_uint2(w[2 * r], w[2 * r + 1]);
}
__device__ __forceinline__ void ln_row(const uint32_t* x, uint32_t* y) {
    float s = 0.f;
#pragma unroll
    for (int i = 0; i < 10; i++) s += blo(x[i]) + bhi(x[i]);
#pragma unroll
    for (int o = 16; o > 0; o >>= 1) s += __shfl_xor_sync(0xffffffffu, s, o);
    const float mean = s * (1.0f / DM);
    float q = 0.f;
#pragma unroll
    for (int i = 0; i < 10; i++) { const float d0 = blo(x[i]) - mean, d1 = bhi(x[i]) - mean; q = fmaf(d0, d0, q); q = fmaf(d1, d1, q); }
#pragma unroll
    for (int o = 16; o > 0; o >>= 1) q += __shfl_xor_sync(0xffffffffu, q, o);
    const uint32_t nm = pack2(-mean, -mean);
    float sq;
    asm("sqrt.approx.ftz.f32 %0, %1;" : "=f"(sq) : "f"(rbf(rbf(q * (1.0f / DM)) + 1e-5f)));
    const float rd = rcpf(rbf(sq));
#pragma unroll
    for (int i = 0; i < 10; i++) { const uint32_t d = bsum2(x[i], nm); y[i] = pack2(blo(d) * rd, bhi(d) * rd); }
}
__device__ __forceinline__ void red_add8(uint4* p, uint32_t a, uint32_t b, uint32_t c, uint32_t d) {
    asm volatile("red.relaxed.gpu.global.add.noftz.v4.bf16x2 [%0], {%1,%2,%3,%4};" ::"l"(p), "r"(a), "r"(b), "r"(c), "r"(d) : "memory");
}
__device__ __forceinline__ void part_sum(const uint4& v, const uint4& w, int lane, uint32_t& x0, uint32_t& x1) {
    float t[8];
    t[0] = blo(v.x) + blo(w.x); t[1] = bhi(v.x) + bhi(w.x); t[2] = blo(v.y) + blo(w.y); t[3] = bhi(v.y) + bhi(w.y);
    t[4] = blo(v.z) + blo(w.z); t[5] = bhi(v.z) + bhi(w.z); t[6] = blo(v.w) + blo(w.w); t[7] = bhi(v.w) + bhi(w.w);
#pragma unroll
    for (int i = 0; i < 4; i++) t[i] = (lane < 16 ? t[i] : t[4 + i]) + __shfl_xor_sync(0xffffffffu, lane < 16 ? t[4 + i] : t[i], 16);
    const uint32_t r0 = pack2(t[0], t[1]), r1 = pack2(t[2], t[3]);
    const uint32_t ex = __shfl_xor_sync(0xffffffffu, (lane & 1) ? r0 : r1, 1);
    x0 = (lane & 1) ? ex : r0; x1 = (lane & 1) ? r1 : ex;
}
__device__ __forceinline__ void post_row(int l, int row, int lane, const bf16* xin, bf16* xout) {
    uint32_t x[10], y[10], n[10];
    const int cl = (lane & 12) * 8 + (lane >> 4) * 16 + (lane & 1) * 8 + (lane & 2) * 2;
    uint4* pp = reinterpret_cast<uint4*>(g_part + (size_t)(l * PROWS + (row & (PROWS - 1))) * (PG * DM)) + (lane & 15) + (lane >> 4) * 80;
    int* f = FLG(F_OP + l * NCHK + (row >> 7));
    flag_wait(FLG(F_CONV + (row >> 10)), CONV_TGT, 200);
    ld5<128>(x, xin + (size_t)row * DM + cl);
    flag_wait(f + 4, OP_TGT, POST_NS);
    {
        uint4 v[10];
#pragma unroll
        for (int i = 0; i < 10; i++) v[i] = __ldcg(pp + (i >> 1) * 16 + (i & 1) * 160);
#pragma unroll
        for (int r = 0; r < 5; r++) {
            uint32_t s0, s1;
            part_sum(v[2 * r], v[2 * r + 1], lane, s0, s1);
            if (r == 1) ld5<16 * S_LEN * 8>(y, g_Y + ((size_t)(cl >> 3) * S_LEN + (row ^ ((row >> 6) & 7))) * 8 + (cl & 4));
            x[2 * r] = bsum2(x[2 * r], s0); x[2 * r + 1] = bsum2(x[2 * r + 1], s1);
        }
    }
    ln_row(x, n);
#pragma unroll
    for (int i = 0; i < 10; i++) x[i] = bsum2(x[i], bmul2(n[i], y[i]));
    if (l == 0) {
        ln_row(x, n);
        st5(g_h[1] + (size_t)row * DM + cl, n);
        __syncwarp();
        if (lane == 0) red_release(FLG(F_H + NCHK + (row >> 7)), 1);
    }
#pragma unroll
    for (int i = 0; i < 10; i++) pp[(i >> 1) * 16 + (i & 1) * 160] = make_uint4(0, 0, 0, 0);
    st5(xout + (size_t)row * DM + cl, x);
    __syncwarp();
    if (l && lane == 0) red_release(f + 5, 1);
}
__device__ __forceinline__ void u_unit(const bf16* Bk, const bf16* Bv, const bf16* shiftk, int unit, int lane) {
    const int t0 = (unit / 10) * 16, cp = (unit % 10) * 32 + lane;
    uint32_t kk[19], vv[16];
    const uint32_t* pk = reinterpret_cast<const uint32_t*>(Bk + (size_t)t0 * DM) + cp;
    const uint32_t* pv = reinterpret_cast<const uint32_t*>(Bv + (size_t)t0 * DM) + cp;
#pragma unroll
    for (int i = 0; i < 19; i++) kk[i] = (i >= 3 || t0 > 0) ? __ldg(pk + (i - 3) * (DM / 2)) : 0u;
#pragma unroll
    for (int i = 0; i < 16; i++) vv[i] = __ldg(pv + i * (DM / 2));
    const uint4 sh0 = __ldg(reinterpret_cast<const uint4*>(shiftk + cp * 8));
    const uint32_t s0 = __byte_perm(sh0.x, sh0.z, 0x5410), s1 = __byte_perm(sh0.x, sh0.z, 0x7632), s2 = __byte_perm(sh0.y, sh0.w, 0x5410), s3 = __byte_perm(sh0.y, sh0.w, 0x7632);
#pragma unroll
    for (int t = 0; t < 16; t++)
        vv[t] = bmul2(bsum2(bsum2(bsum2(bmul2(kk[t], s3), bmul2(kk[t + 1], s2)), bmul2(kk[t + 2], s1)), bmul2(kk[t + 3], s0)), vv[t]);
    uint4* d = reinterpret_cast<uint4*>(g_U + (size_t)(cp * 2) * S_LEN + (t0 ^ 48));
#pragma unroll
    for (int c = 0; c < 2; c++) {
        const uint32_t sel = c ? 0x7632 : 0x5410;
#pragma unroll
        for (int hh = 0; hh < 2; hh++)
            d[c * (S_LEN / 8) + hh] = make_uint4(__byte_perm(vv[15 - hh * 8], vv[14 - hh * 8], sel), __byte_perm(vv[13 - hh * 8], vv[12 - hh * 8], sel),
                                                 __byte_perm(vv[11 - hh * 8], vv[10 - hh * 8], sel), __byte_perm(vv[9 - hh * 8], vv[8 - hh * 8], sel));
    }
}
constexpr int CV_EP = 4224;
template <class F> __device__ __forceinline__ void conv_unit(uint32_t ub, uint32_t e0, uint32_t e1, uint32_t zrow, uint32_t yt, float Dv, int m, int lane, F&& nearly_done) {
    const int g = lane >> 2, tq = lane & 3;
    asm volatile("st.shared.u32 [%0], %1;" ::"r"(e0 + lane * 4), "r"(0) : "memory");
    asm volatile("st.shared.u32 [%0], %1;" ::"r"(zrow + lane * 4), "r"(0) : "memory");
    __syncwarp();
    for (int i = lane; i < CV_EP / 16; i += 32) {
        const uint4 v = lds128(e0 + i * 16);
        const uint32_t nx = i + 1 < CV_EP / 16 ? lds32(e0 + i * 16 + 16) : 0u;
        sts128(e1 + i * 16, __byte_perm(v.x, v.y, 0x5432), __byte_perm(v.y, v.z, 0x5432), __byte_perm(v.z, v.w, 0x5432), __byte_perm(v.w, nx, 0x5432));
    }
    __syncwarp();
    float acc[8][4];
#pragma unroll
    for (int n = 0; n < 8; n++)
#pragma unroll
        for (int i = 0; i < 4; i++) acc[n][i] = 0.f;
    uint32_t wb = (g & 1) ? e0 + (1 + g + 2 * tq) * 2 : e1 + (g + 2 * tq) * 2;
    uint32_t W[16], a[4][4], an[4][4];
    int row = m * 16 + (lane & 15);
    auto lda = [&](uint32_t (*d)[4]) {
        const uint32_t x = row < 0 ? zrow : ub + row * 128 + (((lane >> 4) ^ (row & 7)) << 4);
#pragma unroll
        for (int ks = 0; ks < 4; ks++) ldsm_x4(d[ks][0], d[ks][1], d[ks][2], d[ks][3], x ^ (ks << 5));
        row--;
    };
#pragma unroll
    for (int i = 0; i < 16; i++) W[i] = lds32(wb + i * 16);
    lda(a);
    const int nD = m == 0 ? 16 : 32;
#pragma unroll 2
    for (int D = 0; D < nD; D++) {
        uint32_t Wn[8];
        wb += 128;
        if (D == nD - 6) nearly_done();
        lda(an);
#pragma unroll
        for (int i = 0; i < 8; i++) Wn[i] = lds32(wb + 128 + i * 16);
#pragma unroll
        for (int ks = 0; ks < 4; ks++)
#pragma unroll
            for (int n = 0; n < 8; n++) mma16816(acc[n], a[ks][0], a[ks][1], a[ks][2], a[ks][3], W[2 * ks + n], W[2 * ks + n + 1]);
#pragma unroll
        for (int i = 0; i < 8; i++) { W[i] = W[i + 8]; W[i + 8] = Wn[i]; }
#pragma unroll
        for (int ks = 0; ks < 4; ks++)
#pragma unroll
            for (int i = 0; i < 4; i++) a[ks][i] = an[ks][i];
    }
#pragma unroll
    for (int n = 0; n < 8; n++)
#pragma unroll
        for (int r = 0; r < 2; r++) {
            const int a_ = g + r * 8, b_ = n * 8 + tq * 2;
            const int ar = m * 16 + a_, p = 62 - b_;
            const uint32_t kv = lds32(ub + ar * 128 + (((p >> 3) ^ (ar & 7)) << 4) + (p & 7) * 2);
            const float y0 = rbf(acc[n][2 * r]) + rbf(bhi(kv) * Dv), y1 = rbf(acc[n][2 * r + 1]) + rbf(blo(kv) * Dv);
            const uint32_t pk = pack2(y0, y1);
            asm volatile("st.shared.u16 [%0], %1;" ::"r"(yt + ((a_ * 64 + b_) ^ g) * 16), "h"((unsigned short)(pk & 0xffff)) : "memory");
            asm volatile("st.shared.u16 [%0], %1;" ::"r"(yt + ((a_ * 64 + b_ + 1) ^ g) * 16), "h"((unsigned short)(pk >> 16)) : "memory");
        }
}

__global__ void __launch_bounds__(384, 1) bulk_kernel(const __grid_constant__ BulkMaps M, const __grid_constant__ BulkArgs A,
                                                      const __grid_constant__ Sched SC) {
    extern __shared__ __align__(1024) unsigned char smem_raw[];
    const uint32_t sb0 = smem_u32(smem_raw);
    const uint32_t full0 = sb0 + BULK_TAIL, empty0 = full0 + 32, tfull0 = full0 + 64, tempty0 = full0 + 96, sfull = full0 + 128, sempty = full0 + 160,
                   task0 = full0 + 192, tab0 = full0 + 208;
    const int tid = threadIdx.x, wid = __shfl_sync(0xffffffffu, tid >> 5, 0), lane = tid & 31;
    const int rank = blockIdx.x & 1;
    if (tid == 0) {
        for (int i = 0; i < BK_STAGES; i++) { mbar_init(full0 + 8 * i, 1); mbar_init(empty0 + 8 * i, 4); }
        for (int i = 0; i < TSLOTS; i++) { mbar_init(tfull0 + 8 * i, 1); mbar_init(tempty0 + 8 * i, 19); }
        for (int i = 0; i < 4; i++) { mbar_init(sfull + 8 * i, 8); mbar_init(sempty + 8 * i, 1); }
        asm volatile("fence.mbarrier_init.release.cluster;" ::: "memory");
        if (rank == 1) for (int i = 0; i < TSLOTS; i++) mbar_expect_tx(tfull0 + 8 * i, 4);
        BT(true, T_LN0, 0, 0, 0);
    }
    if (tid < MAXG * 5) asm volatile("st.shared.u32 [%0], %1;" ::"r"(tab0 + tid * 4), "r"(SC.chk[tid]) : "memory");
    cluster_sync_all();
    uint32_t tc = 0, it = 0;
    if (wid < 4) {
        asm volatile("setmaxnreg.dec.sync.aligned.u32 %0;" ::"n"(REG_P));
        if (wid == 0) {
            int head = SC.sbeg[lane >> 3];
            const int hend = SC.sbeg[(lane >> 3) + 1];
            uint32_t chk = 0; int pv = (blockIdx.x >> 1) & 31, grp = (SC.sbeg[3] + (blockIdx.x >> 6)) << 2 | 3, ncode = 0, code = 3 << 6 | 2, guard = 0;
            auto acquire = [&](uint32_t bytes) -> uint32_t {
                const uint32_t s = it & 3;
                mwait(empty0 + 8 * s, ((it >> 2) & 1) ^ 1);
                it++;
                expect_tx1(full0 + 8 * s, bytes);
                return s;
            };
            auto uwait = [&](const int* f, int tgt) {
                int g2 = 0;
                while ((int)UNI(ld_relaxed(f)) < tgt && ++g2 < 4000000) __nanosleep(32);
                fence_async();
            };
#pragma unroll 1
            while (true) {
                const int type = (code >> 6) & 3;
                const int iend = type == T_KV ? 10 : (type == T_QA ? 24 : 31);
                const int jj = code & 63, g0 = (jj & 15) * 4, lc = (code >> 9) & 31;
                const bool lm = (code >> 8) & 1;
                const CUtensorMap* mb = type == T_QA ? &M.wq : (jj < 16 ? &M.wk : &M.wv);
                bool have = false, ok = (code >> 14) & 1;
                int imem = 16;
#pragma unroll 1
                for (int i = type < T_CONV ? 0 : (type == T_CONV ? 24 : 28 + jj); i < iend; i++) {
                    const int sd = (type < T_CONV ? SPLAN : 0x1230) >> 4 * min(iend - i, 7) & 15;
                    if (rank == 0 && sd) {
                        if (sd == 1) {
                            if (type == T_CONV) mwait(empty0 + 8 * (it & 3), ((it >> 2) & 1) ^ 1);
                            const int gi = head + ((lane >> 2) & 1);
                            chk = lds32(tab0 + ((gi < hend ? gi : SENT) * 4 + (lane & 3)) * 4);
                            pv = ld_relaxed(g_flags + (chk & 0xffff));
                        } else if (sd == 2) {
                            const int tgt = (int)(chk >> 16);
                            const uint32_t b = (__ballot_sync(0xffffffffu, (lane & 3) == 0 ? pv < tgt : pv >= tgt) >> (lane & 24)) & 0xff;
                            const uint32_t cand = (b & 1) ? b & 15 : b >> 4;
                            head += (b & 1) ? 0 : ((b & 16) ? 1 : 2);
                            if (head > hend || guard > 4000000) head = hend;
                            const uint32_t req = lane >= 24 ? 1 : 15;
                            grp = (int)__reduce_min_sync(0xffffffffu, (cand & req) == req ? ((uint32_t)head << 2 | (cand ^ req) >> 2 | ((cand ^ req) & 2 ? 0 : 256)) : (head < hend ? 1000u : 1004u));
                            if (grp < 1000) grp &= 255;
                            if (grp < 1000) asm volatile("{\n.reg .pred p;\nsetp.eq.u32 p, %2, 0;\n@p atom.relaxed.gpu.global.inc.u32 %0, [%1], 0x7fffffff;\n}" : "+r"(pv) : "l"(FLG(F_CNT + (grp >> 2))), "r"(lane) : "memory");
                        } else {
                            if (grp < 1000) {
                                const int tk = (int)UNI(pv);
                                have = tk < (int)(UNI(lds32(tab0 + (grp >> 2) * 16)) >> 16);
                                ncode = (int)UNI(lds32(tab0 + MAXG * 16 + (grp & ~3))) | (grp & 3) << 19 | tk;
                            } else if (grp == 1004) { have = true; ncode = -1; }
                            if (have) {
                                const uint32_t o = (tc & 3) * 4;
                                mwait(tempty0 + 2 * o, ((tc >> 2) & 1) ^ 1);
                                asm volatile(ELECT "st.shared.u32 [%0], %1;\n@p mbarrier.arrive.shared::cta.b64 _, [%2];\n"
                                             "@p st.async.weak.shared::cluster.mbarrier::complete_tx::bytes.b32 [%3], %1, [%4];\n}"
                                             ::"r"(task0 + o), "r"(ncode), "r"(tfull0 + 2 * o), "r"(mapa(task0 + o, 1)), "r"(mapa(tfull0 + 2 * o, 1)) : "memory");
                            }
                        }
                    }
                    if (i >= 28) continue;
                    if (i == 8 && type == T_QA) pv = ld_relaxed(FLG((lane & 1 ? F_MEM : F_KV) + lc));
                    if (i == 10) {
                        const uint32_t b = __ballot_sync(0xffffffffu, pv >= (lane & 1 ? MEM_TGT : KV_TGT));
                        if (b & 2) imem = 13;
                        if (!(b & 1)) uwait(FLG(F_KV + lc), KV_TGT);
                        fence_async();
                    }
                    const uint32_t s = acquire(i < 12 ? 49152 : (i == 24 || i == 27 ? 0 : 32768));
                    const uint32_t sa = sb0 + s * BK_STAGE_BYTES, fb = full0 + 8 * s;
                    if (i == 0) TT(3);
                    if (i < 10) {
                        if (lm) {
                            tma_load_3d(sa + 16384, mb, fb, i * 64, g0);
                            tma_load_3d(sa + 32768, mb, fb, i * 64, g0 + 2);
                        } else tma_load_3d_mc(sa + 16384 + rank * 16384, mb, fb, i * 64, g0 + rank * 2);
                        int d = 0;
                        if (!ok) {
                            d = 1;
                            if (i == 3) {
                                uwait(FLG(F_H + lc), H_TGT);
                                ok = true;
                                d = -3;
                                TT(4);
                            }
                        }
#pragma unroll 1
                        for (; d <= 0; d++) {
                            const uint32_t s2 = (s + d) & 3;
                            if (lm) tma_load_2d_mc(sb0 + s2 * BK_STAGE_BYTES + rank * 8192, &M.h, full0 + 8 * s2, (i + d) * 64, lc * 128 + rank * 64);
                            else tma_load_2d(sb0 + s2 * BK_STAGE_BYTES, &M.h2, full0 + 8 * s2, (i + d) * 64, lc * 128);
                        }
                    } else if (i < 13) {
#pragma unroll 1
                        for (int k = 0, bx = (i - 10) * 3; k < 3 && bx < 8; k++, bx++)
                            tma_load_2d(sa + k * 16384, &M.kv, fb, (g0 + (bx & 3)) * 64, (bx >> 2) * S_LEN + (lc & 15) * 128);
                    } else if (i < 24) {
                        const int cn = ((i - 14) >> 1) * 128, ck = g0 * 64 + (i & 1) * 128;
                        if (i > 13) {
                            if (lm) { tma_load_2d(sa, &M.wo, fb, cn, ck); tma_load_2d(sa + 16384, &M.wo, fb, cn + 64, ck); }
                            else tma_load_2d_mc(sa + rank * 16384, &M.wo, fb, cn + rank * 64, ck);
                        }
                        if (i == imem) {
                            TT(5);
                            if (i == 16) uwait(FLG(F_MEM + lc), MEM_TGT);
                            const uint32_t s2 = (s + (i >> 4)) & 3;
#pragma unroll 1
                            for (int k = 0; k < 4; k++)
                                bulk_load(sb0 + s2 * BK_STAGE_BYTES + k * 8192, g_kvf + (size_t)((lc * CSEG + k) * NH + jj * 2) * 256, 8192, full0 + 8 * s2);
                            TT(6);
                        }
                    } else if (i == 25) {
                        tma_load_2d(sa, &M.lu, fb, 0, (2 * jj + rank) * 256);
                    } else if (i == 26) {
#pragma unroll 1
                        for (int k = 0; k < 8; k++)
                            bulk_load(sa + k * CV_EP + 128, A.ssmk + (size_t)((2 * jj + rank) * 8 + k) * S_LEN, 4096, fb);
                    }
                }
                if (type != 3) TT(7);
                if (rank == 0) {
                    if (!have) {
                        if (type == 3) { guard++; __nanosleep(64); }
                        code = 3 << 6;
                        continue;
                    }
                } else {
                    const uint32_t o = (tc & 3) * 4;
                    mwait(tfull0 + 2 * o, (tc >> 2) & 1);
                    ncode = (int)UNI(lds32(task0 + o));
                    asm volatile(ELECT "mbarrier.arrive.expect_tx.shared::cta.b64 _, [%0], 4;\n@p mbarrier.arrive.shared::cluster.b64 _, [%1];\n}" ::"r"(tfull0 + 2 * o), "r"(mapa(tempty0 + 2 * o, 0)) : "memory");
                    __syncwarp();
                }
                tc++;
                if (ncode < 0) break;
                TT(0); TTV(15, ncode);
                code = ((ncode & 256) ? (2 * ncode + rank) & 63 : ncode & 63) | (ncode & 0x1c0) | ((ncode >> (rank ? 14 : 9)) & 31) << 9 | ((ncode >> (19 + rank)) & 1) << 14;
                fence_async();
            }
        } else if (wid == 1) {
            if (lane < 8) asm volatile("prefetch.tensormap [%0];" ::"l"(&M.h + lane) : "memory");
            __syncwarp();
            if (lane == 0) {
                uint32_t rc = 0;
                while (true) {
                    mwait(tfull0 + 8 * (tc & 3), (tc >> 2) & 1);
                    const int code = (int)lds32(task0 + 4 * (tc & 3));
                    mbar_arrive_cluster(mapa(tempty0 + 8 * (tc & 3), 0));
                    tc++;
                    if (code < 0) break;
                    const int type = (code >> 6) & 3;
                    const int lc = (code >> (rank ? 14 : 9)) & 31;
                    mwait(sfull + 8 * (rc & 3), (rc >> 2) & 1);
                    if (type == T_CONV) {
                        asm volatile("cp.async.bulk.global.shared::cta.bulk_group [%0], [%1], %2;" ::"l"(g_Y + (size_t)((2 * (code & 63) + rank) * S_LEN + lc * 1024) * 8), "r"(sb0 + BULK_STG), "r"(16384) : "memory");
                        bulk_commit();
                        bulk_wait<0>();
                    }
                    mbar_arrive(sempty + 8 * (rc & 3));
                    rc++;
                    FT(0);
                    red_release(type == T_QA ? FLG(F_OP + lc) + 4 : FLG((type == T_KV ? F_KV : F_CONV) + lc), 1);
                    FT(1);
                    BT(true, type, lc >> 4, lc & 15, 2);
                }
            }
        } else {
            const int nw = 2 * gridDim.x, idx = (wid - 2) * gridDim.x + blockIdx.x;
#pragma unroll 1
            for (int hh = 0; hh < 2; hh++) {
#pragma unroll 1
                for (int u = hh * 640 + idx; u < hh * 640 + 640; u += nw) u_unit(A.Bk, A.Bv, A.shiftk, u, lane);
                __syncwarp();
                if (lane == 0) red_release(FLG(F_U + hh), 1);
                BT(lane == 0, T_LN0, hh, 0, 2);
            }
#pragma unroll 1
            for (int q = 0; q < 2 * (NCHK + PDIST); q++) {
                const int l = q & 1, c = (q >> 1) - l * PDIST;
                if (c < 0 || c >= NCHK) continue;
#pragma unroll 1
                for (int rr = idx; rr < 128; rr += nw) post_row(l, c * 128 + rr, lane, l ? g_x : A.x, l ? A.out : g_x);
                BT(lane == 0, T_POST, l, c, 2);
            }
        }
    } else {
        asm volatile("setmaxnreg.inc.sync.aligned.u32 %0;" ::"n"(REG_C));
        const int cw = (wid >> 2) - 1, warp = wid & 3;
        const uint32_t wst = sb0 + BULK_STG + (cw * 4 + warp) * 4096;
        uint32_t rc = 0;
        int npend = 0;
        bool urgent = false;
        uint32_t oofs = 0;
        uint32_t qf[16][4];
        auto release = [&](int s) { if ((tid & 127) == 0) { mbar_arrive(empty0 + 8 * s); mbar_arrive_cluster(mapa(empty0 + 8 * s, rank ^ 1)); } };
        auto next = [&]() -> int { const int s = it & 3; mwait(full0 + 8 * s, (it >> 2) & 1); it++; return s; };
        auto wgbar = [&]() { if (cw == 0) named_bar(2, 128); else named_bar(3, 128); };
        auto handoff = [&]() {
            mwait(sempty + 8 * (rc & 3), ((rc >> 2) & 1) ^ 1);
            asm volatile(ELECT "mbarrier.arrive.shared::cta.b64 _, [%0];\n}" ::"r"(sfull + 8 * (rc & 3)) : "memory");
            rc++;
        };
        auto stg_free = [&]() { mwait(sempty + 8 * ((rc - 1) & 3), ((rc - 1) >> 2) & 1); };
        auto round_q = [&]() {
            if (npend > 4) {
                uint4* d = reinterpret_cast<uint4*>(g_part) + oofs;
                if (npend == 6) {
#pragma unroll
                    for (int i = 0; i < 4; i++) red_add8(d + (i >> 1) * 4 + (i & 1) * (8 * PG * DM / 8), qf[i][0], qf[i][1], qf[i][2], qf[i][3]);
                    npend = 5;
                } else {
#pragma unroll
                    for (int i = 4; i < 8; i++) red_add8(d + (i >> 1) * 4 + (i & 1) * (8 * PG * DM / 8), qf[i][0], qf[i][1], qf[i][2], qf[i][3]);
                    npend = 0;
                    handoff();
                }
                return;
            }
            const uint32_t sst = wst + (lane & 15) * 128 + (((lane >> 4) ^ (lane & 7)) << 4) + (npend & 1) * 2048;
#pragma unroll
            for (int q = 0; q < 4; q++)
                if (npend == 4 - q) {
#pragma unroll
                    for (int i = 0; i < 4; i++) stsm_x4(sst ^ (i << 5), qf[q * 4 + i][0], qf[q * 4 + i][1], qf[q * 4 + i][2], qf[q * 4 + i][3]);
                }
            __syncwarp();
            uint4* d = reinterpret_cast<uint4*>(&g_kv[0][0]) + oofs;
            const uint32_t src = wst + (lane >> 3) * 128 + (((lane & 7) ^ (lane >> 3)) << 4) + (npend & 1) * 2048;
#pragma unroll
            for (int i = 0; i < 4; i++) d[i * (4 * HD / 8)] = lds128((src + i * 512) ^ ((i & 1) << 6));
            oofs += 8;
            if (--npend == 0) handoff();
        };
        auto round_a = [&](const float* a, int hh) {
            uint4* d = reinterpret_cast<uint4*>(g_part) + oofs;
#pragma unroll
            for (int i = hh * 4; i < hh * 4 + 4; i++) {
                const float* b = a + (i >> 1) * 16 + (i & 1) * 2;
                red_add8(d + (i >> 1) * 4 + (i & 1) * (8 * PG * DM / 8), pack2(b[0], b[1]), pack2(b[4], b[5]), pack2(b[8], b[9]), pack2(b[12], b[13]));
            }
            if (hh) oofs += 16;
        };
        while (true) {
            tc++; TT(0); tc--;
            int code;
            while (true) {
                if (npend == 0) mwait(tfull0 + 8 * (tc & 3), (tc >> 2) & 1);
                if (npend == 0 || UNI(mtest(tfull0 + 8 * (tc & 3), (tc >> 2) & 1))) {
                    code = (int)UNI(lds32(task0 + 4 * (tc & 3)));
                    if (npend == 0 || ((code & 0x80) == 0 && !urgent && UNI(mtest(full0 + 8 * (it & 3), (it >> 2) & 1)))) break;
                }
                round_q();
            }
            if (lane == 0) mbar_arrive_cluster(mapa(tempty0 + 8 * (tc & 3), 0));
            tc++;
            TT(2);
            if (code < 0) break;
            const int type = (code >> 6) & 3;
            TTV(15, code);
#define BTC(type, k)
            if (type == T_CONV) {
                const int m = (code >> 9) & 1;
                BT((tid & 127) == 0, T_CONV, 0, m, 0);
                const int u = 2 * (code & 63) + rank, ch = cw * 4 + warp;
                int lane = tid & 31;
                asm volatile("" : "+r"(lane));
                const float Dv = bf2f(A.ssmD[u * 8 + ch]);
                const int sd = next(), s0 = next(), s1 = next(), s2 = next();
                TT(3);
                const uint32_t e1 = sb0 + s2 * BK_STAGE_BYTES;
                conv_unit(sb0 + s0 * BK_STAGE_BYTES + ch * 4096, sb0 + s1 * BK_STAGE_BYTES + ch * CV_EP, e1 + 64 + ch * CV_EP, e1 + 40960 + ch * 128, sb0 + BULK_STG + ch * 2, Dv, m, lane,
                          [&]() { release(sd); stg_free(); });
                asm volatile("fence.proxy.async.shared::cta;" ::: "memory");
                __syncwarp();
                handoff();
                TT(5);
                wgbar();
                release(s0); release(s1); release(s2);
                __syncwarp();
#pragma unroll
                for (int i = 0; i < 64; i++) qf[i >> 2][i & 3] = 0;
                continue;
            }
            float acc[128];
            {
                int s = next();
                TT(3); BTC(type, 0); BTC(type, 1);
                uint32_t sa = sb0 + s * BK_STAGE_BYTES + cw * 8192, sb = sb0 + s * BK_STAGE_BYTES + 16384;
                wg_fence();
                wgmma_m64n256k16_first(acc, make_desc(sa, 16, 1024), make_desc(sb, 8192, 1024));
#pragma unroll 1
                for (int kb = 0;;) {
#pragma unroll
                    for (int k = 1; k < 4; k++) wgmma_m64n256k16(acc, make_desc(sa + k * 32, 16, 1024), make_desc(sb + k * 2048, 8192, 1024));
                    wg_commit();
                    if (npend) round_q();
                    if (kb) { wg_wait<1>(); release((s - 1) & 3); }
                    if (++kb == 10) break;
                    s = next();
                    sa = sb0 + s * BK_STAGE_BYTES + cw * 8192; sb = sb0 + s * BK_STAGE_BYTES + 16384;
                    wg_fence();
                    wgmma_m64n256k16(acc, make_desc(sa, 16, 1024), make_desc(sb, 8192, 1024));
                }
            }
            wg_wait<0>();
            TT(4);
            release((it - 1) & 3);
            stg_free();
#pragma unroll
            for (int i = 0; i < 16; i++)
#pragma unroll
                for (int e = 0; e < 4; e++) qf[i][e] = pack2(acc[i * 8 + e * 2], acc[i * 8 + e * 2 + 1]);
            {
                const int cd = (int)lds32(task0 + 4 * ((tc - 1) & 3)), lc = (cd >> (rank ? 14 : 9)) & 31, jj = (cd & 256) ? (2 * cd + rank) & 63 : cd & 63;
                const int r0 = cw * 64 + warp * 16;
                if (type == T_KV) {
                    oofs = ((jj >> 4) * S_LEN + (lc & 15) * 128 + r0 + (lane >> 3)) * (HD / 8) + (jj & 15) * 32 + (lane & 7);
                    npend = 4;
                    urgent = URGENT && (lc < 2 || lc >= 16);
                    continue;
                }
                oofs = (((lc >> 4) * PRING + (lc & (PRING - 1))) * 128 + r0 + (lane >> 2)) * (PG * DM / 8) + (jj & (PG - 1)) * (DM / 8) + (lane & 3);
            }
            const float cs = 1.4426950408889634f;
            int lane = tid & 31;
            asm volatile("" : "+r"(lane));
            const int g = lane >> 2, tq = lane & 3;
            const int sg = cw * 2 + (warp >> 1), hs = warp & 1;
            float mt[2][2], sum[2][2];
            {
                const int x0 = next(), x1 = next();
                TT(5);
                float s[2][4][4];
#pragma unroll
                for (int hd = 0; hd < 2; hd++)
#pragma unroll
                    for (int n = 0; n < 4; n++)
#pragma unroll
                        for (int e = 0; e < 4; e++) s[hd][n][e] = 0.f;
                const uint32_t krow = (sg * 32 + (lane & 7) + (lane >> 4) * 8) * 128 + ((((lane >> 3) & 1) ^ (lane & 7)) << 4);
#pragma unroll
                for (int ii = 0; ii < 16; ii++) {
                    const int i = (ii >> 1) + (ii & 1) * 8;
                    const uint32_t kb = sb0 + (i < 12 ? x0 * BK_STAGE_BYTES + (i >> 2) * 16384 : x1 * BK_STAGE_BYTES) + (krow ^ ((i & 3) << 5));
                    const uint4 k0 = ldsm4(kb), k1 = ldsm4(kb + 2048);
                    mma16816(s[i >> 3][0], qf[i][0], qf[i][1], qf[i][2], qf[i][3], k0.x, k0.y);
                    mma16816(s[i >> 3][1], qf[i][0], qf[i][1], qf[i][2], qf[i][3], k0.z, k0.w);
                    mma16816(s[i >> 3][2], qf[i][0], qf[i][1], qf[i][2], qf[i][3], k1.x, k1.y);
                    mma16816(s[i >> 3][3], qf[i][0], qf[i][1], qf[i][2], qf[i][3], k1.z, k1.w);
                }
#pragma unroll
                for (int i = 0; i < 8; i++) sts128(wst + i * 512 + lane * 16, qf[8 + i][0], qf[8 + i][1], qf[8 + i][2], qf[8 + i][3]);
                wgbar();
                release(x0);
                TT(6);
                uint32_t pa[2][4][2];
#pragma unroll
                for (int hd = 0; hd < 2; hd++) {
                    uint32_t mx[2] = {0xff80ff80u, 0xff80ff80u};
#pragma unroll
                    for (int n = 0; n < 4; n++)
#pragma unroll
                        for (int r = 0; r < 2; r++) {
                            const int d = hs * 16 + g + r * 8 - n * 8 - tq * 2;
                            pa[hd][n][r] = rscore(d < 0 ? -INFINITY : s[hd][n][2 * r], d < 1 ? -INFINITY : s[hd][n][2 * r + 1]);
                            mx[r] = bmax2(mx[r], pa[hd][n][r]);
                        }
#pragma unroll
                    for (int r = 0; r < 2; r++) {
                        mx[r] = bmax2(mx[r], __shfl_xor_sync(0xffffffffu, mx[r], 1));
                        mx[r] = bmax2(mx[r], __shfl_xor_sync(0xffffffffu, mx[r], 2));
                        mt[hd][r] = fmaxf(blo(mx[r]), bhi(mx[r])) * cs;
                        sum[hd][r] = 0.f;
                    }
#pragma unroll
                    for (int n = 0; n < 4; n++)
#pragma unroll
                        for (int r = 0; r < 2; r++) {
                            const float p0 = ex2f(fmaf(blo(pa[hd][n][r]), cs, -mt[hd][r])), p1 = ex2f(fmaf(bhi(pa[hd][n][r]), cs, -mt[hd][r]));
                            sum[hd][r] += p0 + p1;
                            pa[hd][n][r] = pack2(p0, p1);
                        }
                }
                const uint32_t vrow = (sg * 32 + (lane & 15)) * 128 + (((lane >> 4) ^ (lane & 7)) << 4);
                int xv = x1;
#pragma unroll
                for (int hd = 0; hd < 2; hd++) {
                    if (hd == 1) xv = next();
#pragma unroll
                    for (int i = 0; i < 8; i++) {
                        const uint32_t vb = sb0 + xv * BK_STAGE_BYTES + (hd == 0 ? 16384 : 0) + (i >> 2) * 16384 + (vrow ^ ((i & 3) << 5));
                        uint4 v0, v1;
                        ldsm_x4_t(v0.x, v0.y, v0.z, v0.w, vb);
                        ldsm_x4_t(v1.x, v1.y, v1.z, v1.w, vb + 2048);
                        float* o = acc + hd * 64 + i * 8;
#pragma unroll
                        for (int e = 0; e < 8; e++) o[e] = 0.f;
                        mma16816(o, pa[hd][0][0], pa[hd][0][1], pa[hd][1][0], pa[hd][1][1], v0.x, v0.y);
                        mma16816(o + 4, pa[hd][0][0], pa[hd][0][1], pa[hd][1][0], pa[hd][1][1], v0.z, v0.w);
                        mma16816(o, pa[hd][2][0], pa[hd][2][1], pa[hd][3][0], pa[hd][3][1], v1.x, v1.y);
                        mma16816(o + 4, pa[hd][2][0], pa[hd][2][1], pa[hd][3][0], pa[hd][3][1], v1.z, v1.w);
                    }
                    wgbar();
                    release(xv);
                }
            }
            TT(7);
            BTC(T_ATT, 0);
            {
                const int xm = next();
                TT(8);
                BTC(T_ATT, 1);
                const uint32_t mb = sb0 + xm * BK_STAGE_BYTES + sg * 8192 + lane * 16;
                float sm[2][2][4];
#pragma unroll
                for (int i = 0; i < 16; i++) (&sm[0][0][0])[i] = 0.f;
#pragma unroll
                for (int q = 0; q < 4; q++) {
                    const uint4 k0 = lds128(mb + q * 512), k1 = lds128(mb + 4096 + q * 512);
                    const uint4 qa = lds128(wst + q * 1024 + lane * 16), qb = lds128(wst + q * 1024 + 512 + lane * 16);
                    mma16816(sm[0][0], qf[2 * q][0], qf[2 * q][1], qf[2 * q][2], qf[2 * q][3], k0.x, k0.y);
                    mma16816(sm[0][1], qf[2 * q + 1][0], qf[2 * q + 1][1], qf[2 * q + 1][2], qf[2 * q + 1][3], k0.z, k0.w);
                    mmau(sm[1][0], qa, k1.x, k1.y);
                    mmau(sm[1][1], qb, k1.z, k1.w);
                }
                float f[2][2];
                uint32_t pm[2][2];
#pragma unroll
                for (int hd = 0; hd < 2; hd++)
#pragma unroll
                    for (int r = 0; r < 2; r++) {
                        const uint32_t w = rscore(sm[hd][0][2 * r] + sm[hd][1][2 * r], sm[hd][0][2 * r + 1] + sm[hd][1][2 * r + 1]);
                        const float s0 = blo(w) * cs, s1 = bhi(w) * cs;
                        float m = fmaxf(s0, s1);
                        m = fmaxf(m, __shfl_xor_sync(0xffffffffu, m, 1));
                        m = fmaxf(fmaxf(m, __shfl_xor_sync(0xffffffffu, m, 2)), mt[hd][r]);
                        const float a = ex2f(mt[hd][r] - m), p0 = ex2f(s0 - m), p1 = ex2f(s1 - m);
                        float t = fmaf(sum[hd][r], a, p0 + p1);
                        t += __shfl_xor_sync(0xffffffffu, t, 1);
                        t += __shfl_xor_sync(0xffffffffu, t, 2);
                        t = rcpf(t);
                        f[hd][r] = a * t;
                        pm[hd][r] = pack2(p0 * t, p1 * t);
                    }
#pragma unroll
                for (int q = 0; q < 8; q++) {
                    const int hd = q >> 2;
                    const uint4 vm = lds128(mb + hd * 4096 + 2048 + (q & 3) * 512);
                    float* o = acc + q * 16;
#pragma unroll
                    for (int e = 0; e < 16; e++) o[e] *= f[hd][(e >> 1) & 1];
                    mma1688(o, pm[hd][0], pm[hd][1], vm.x);
                    mma1688(o + 4, pm[hd][0], pm[hd][1], vm.y);
                    mma1688(o + 8, pm[hd][0], pm[hd][1], vm.z);
                    mma1688(o + 12, pm[hd][0], pm[hd][1], vm.w);
#pragma unroll
                    for (int e = 0; e < 8; e++) qf[q * 2 + (e >> 2)][e & 3] = pack2(o[2 * e], o[2 * e + 1]);
                }
                wgbar();
                release(xm);
            }
            TT(9);
#pragma unroll
            for (int t = 0; t < 10; t++) {
                const int s = next();
                const uint32_t sb = sb0 + s * BK_STAGE_BYTES;
                float* d = acc + ((t >> 1) & 1) * 64;
                wg_fence();
#pragma unroll
                for (int k = 0; k < 8; k++) {
                    const uint64_t db = make_desc(sb + k * 2048, 16384, 1024);
                    if (k == 0 && !(t & 1)) wgmma_rs_m64n128k16_first(d, qf[k], db);
                    else wgmma_rs_m64n128k16(d, qf[(t & 1) * 8 + k], db);
                }
                wg_commit();
                if (t) {
                    wg_wait<1>();
                    release((s - 1) & 3);
                    if (t > 1) round_a(acc + (((t >> 1) & 1) ^ 1) * 64, t & 1);
                }
            }
            wg_wait<0>();
            release((it - 1) & 3);
            TT(10);
#pragma unroll
            for (int i = 0; i < 32; i++) qf[i >> 2][i & 3] = pack2(acc[(i >> 3) * 16 + (i & 4) / 2 + (i & 3) * 4], acc[(i >> 3) * 16 + (i & 4) / 2 + (i & 3) * 4 + 1]);
            npend = 6;
            urgent = URGENT > 1;
        }
    }
    cluster_sync_all();
}

__global__ void __launch_bounds__(256) reset_kernel(const bf16* x, int g0, int ncl) {
    const int lane = threadIdx.x & 31, row = blockIdx.x * 8 + (threadIdx.x >> 5);
    uint32_t r[10];
    ld5<128>(r, x + (size_t)row * DM + lane * 4);
    if (blockIdx.x == 0)
        for (int i = threadIdx.x; i < NFLAG * 2; i += blockDim.x) reinterpret_cast<uint4*>(FLG(i >> 1))[i & 1] = make_uint4(i == g0 ? min(ncl, 32) : (i == g0 + 2 ? max(ncl - 32, 0) : 0), 0, 0, 0);
    for (int i = blockIdx.x * 256 + threadIdx.x; i < 2 * PROWS * PG * DM / 8; i += S_LEN * 32) reinterpret_cast<uint4*>(g_part)[i] = make_uint4(0, 0, 0, 0);
    ln_row(r, r);
    st5(g_h[0] + (size_t)row * DM + lane * 4, r);
    if (blockIdx.x) return;
}

typedef CUresult (*PFN_encodeTiled)(CUtensorMap*, CUtensorMapDataType, cuuint32_t, void*, const cuuint64_t*, const cuuint64_t*,
                                    const cuuint32_t*, const cuuint32_t*, CUtensorMapInterleave, CUtensorMapSwizzle,
                                    CUtensorMapL2promotion, CUtensorMapFloatOOBfill);
static PFN_encodeTiled get_encode() {
    static PFN_encodeTiled fn = nullptr;
    if (!fn) {
        void* p = nullptr;
        cudaDriverEntryPointQueryResult qr;
        cudaGetDriverEntryPoint("cuTensorMapEncodeTiled", &p, cudaEnableDefault, &qr);
        fn = (PFN_encodeTiled)p;
    }
    return fn;
}
static void make_map(CUtensorMap* m, const void* ptr, uint64_t rows, uint64_t cols, uint32_t box_rows) {
    cuuint64_t dims[2] = {cols, rows};
    cuuint64_t strides[1] = {cols * 2};
    cuuint32_t box[2] = {64u, box_rows};
    cuuint32_t es[2] = {1, 1};
    get_encode()(m, CU_TENSOR_MAP_DATA_TYPE_BFLOAT16, 2, const_cast<void*>(ptr), dims, strides, box, es,
                 CU_TENSOR_MAP_INTERLEAVE_NONE, CU_TENSOR_MAP_SWIZZLE_128B, CU_TENSOR_MAP_L2_PROMOTION_L2_128B,
                 CU_TENSOR_MAP_FLOAT_OOB_FILL_NONE);
}
static void make_map3(CUtensorMap* m, const void* ptr) {
    cuuint64_t dims[3] = {64, DM, HD / 64};
    cuuint64_t strides[2] = {HD * 2, 128};
    cuuint32_t box[3] = {64u, 64u, 2u};
    cuuint32_t es[3] = {1, 1, 1};
    get_encode()(m, CU_TENSOR_MAP_DATA_TYPE_BFLOAT16, 3, const_cast<void*>(ptr), dims, strides, box, es,
                 CU_TENSOR_MAP_INTERLEAVE_NONE, CU_TENSOR_MAP_SWIZZLE_128B, CU_TENSOR_MAP_L2_PROMOTION_L2_128B,
                 CU_TENSOR_MAP_FLOAT_OOB_FILL_NONE);
}
#define QA_PRE0 4
#define KV1_E 1
#define KV1_L 16
#define KV0_X 6
#define CONV0_AT 1
#define CONV1_AT 9
static void build_sched(Sched& S, int naux) {
    int n = 0;
    auto ck = [](int f, int t) { return (uint32_t)(f * 32) | (uint32_t)t << 16; };
    auto add = [&](int lm, int type, int la, int ca, int lb, int cb, int ntask, uint32_t soft) {
        S.info[n] = (uint32_t)(type << 6 | lm << 8 | (la * 16 + ca) << 9 | (lb * 16 + cb) << 14);
        S.chk[n * 4] = ck(F_CNT + n, ntask); S.chk[n * 4 + 1] = soft;
        S.chk[n * 4 + 2] = ck(F_H + la * NCHK + ca, H_TGT); S.chk[n * 4 + 3] = ck(F_H + lb * NCHK + cb, H_TGT);
        n++;
    };
    for (int i = 0; i < MAXG * 4; i++) S.chk[i] = ck(F_ZERO, 0);
    for (int i = 0; i < MAXG; i++) S.info[i] = 0;
    S.sbeg[0] = n;
    for (int i = 0; i < NCHK; i++) {
        add(1, T_KV, 1, i, 1, i, 16, i < KV1_E || i >= KV1_L ? ck(F_OP + i, 14) + 4 : ck(F_H + NCHK + i, KV1_N));
        S.chk[n * 4 - 2] = S.chk[n * 4 - 1] = ck(F_CONV + i / 8, CONV_TGT);
    }
    S.sbeg[1] = n;
    auto addqa = [&]() {
    for (int p = 0; p < NCHK + PDIST; p++) {
        const bool h0 = p < NCHK, h1 = p >= PDIST;
        const int la = h0 ? 0 : 1, ca = h0 ? p : p - PDIST, lb = h1 ? 1 : 0, cb = h1 ? p - PDIST : p;
        const int ta = ca * CSEG + CSEG + la * LAG;
        add(!(h0 && h1), T_QA, la, ca, lb, cb, h0 && h1 ? 16 : 8,
            ck(F_PROG, h1 ? ta - QA_PRE : (ta > QA_PRE0 ? ta - QA_PRE0 : 0)));
        S.info[n - 1] |= 3u << 19;
        S.chk[n * 4 - 2] = h0 && ca >= PRING ? ck(F_H + NCHK + ca - PRING + 1, H_TGT) : ck(F_ZERO, 0);
        S.chk[n * 4 - 1] = !h1 ? ck(F_KV + ca, KV_TGT) : (cb >= PRING ? ck(F_OP + NCHK + cb - PRING, 128) + 5 : ck(F_ZERO, 0));
    }
    };
    auto addkv = [&]() {
    for (int i = 0; i < NCHK; i += 2) add(0, T_KV, 0, i, 0, i + 1, 32, ck(F_PROG, 4 * i > KV0_X + 1 ? 4 * i - KV0_X : 1)), S.chk[n * 4 - 2] = S.chk[n * 4 - 1] = ck(F_ZERO, 0);
    };
    addqa();
    S.sbeg[2] = n;
    for (int m = 0; m < 2; m++) {
        add(0, T_CONV, 0, m, 0, m, 40, ck(F_U + m, naux));
        S.chk[n * 4 - 2] = S.chk[n * 4 - 1] = ck(F_CNT + S.sbeg[2] + 2 + (m ? CONV1_AT : CONV0_AT) / 2, 32);
    }
    S.sbeg[3] = n;
    addkv();
    S.sbeg[4] = n;
}

static void launch_all(void* const* d_in, void* d_out) {
    const bf16* x = (const bf16*)d_in[0];
    const bf16* mem0 = (const bf16*)d_in[1];
    const bf16* Wq = (const bf16*)d_in[2];
    const bf16* Wk = (const bf16*)d_in[3];
    const bf16* Wv = (const bf16*)d_in[4];
    const bf16* Wo = (const bf16*)d_in[5];
    static bool inited = false;
    static int nsm = 132;
    static Sched SC;
    bf16 *p_h, *p_kv, *p_u;
    cudaGetSymbolAddress((void**)&p_h, g_h);
    cudaGetSymbolAddress((void**)&p_kv, g_kv);
    cudaGetSymbolAddress((void**)&p_u, g_U);
    if (!inited) {
        inited = true;
        cudaDeviceGetAttribute(&nsm, cudaDevAttrMultiProcessorCount, 0);
        cudaFuncSetAttribute(chain_kernel, cudaFuncAttributeMaxDynamicSharedMemorySize, (int)sizeof(ChainSmem));
        cudaFuncSetAttribute(chain_kernel, cudaFuncAttributeNonPortableClusterSizeAllowed, 1);
        cudaFuncSetAttribute(bulk_kernel, cudaFuncAttributeMaxDynamicSharedMemorySize, BULK_SMEM);
        build_sched(SC, 2 * ((nsm - 64) & ~1));
    }
    const size_t QS = (size_t)S_LEN * HD;
    BulkMaps M;
    make_map(&M.h, p_h, 2 * S_LEN, DM, 64);
    make_map(&M.h2, p_h, 2 * S_LEN, DM, 128);
    make_map3(&M.wq, Wq);
    make_map3(&M.wk, Wk);
    make_map3(&M.wv, Wv);
    make_map(&M.wo, Wo, HD, DM, 128);
    make_map(&M.kv, p_kv, 2 * S_LEN, HD, 128);
    make_map(&M.lu, p_u, DM * 32, 64, 256);
    BulkArgs BA;
    BA.x = x; BA.out = (bf16*)d_out;
    BA.Bk = (const bf16*)d_in[8]; BA.Bv = (const bf16*)d_in[9]; BA.shiftk = (const bf16*)d_in[10];
    BA.ssmk = (const bf16*)d_in[11]; BA.ssmD = (const bf16*)d_in[12];
    ChainArgs ca;
    for (int l = 0; l < 2; l++) {
        make_map(&ca.tk[l], p_kv, S_LEN, HD, 32);
        make_map(&ca.tv[l], p_kv + QS, S_LEN, HD, 32);
    }
    ca.x = x; ca.mem0 = mem0; ca.Wq = Wq; ca.Wk = Wk; ca.Wv = Wv; ca.Wo = Wo; ca.kv_target = KV_TGT;
    cudaStream_t s = cudaStreamPerThread;
    reset_kernel<<<S_LEN / 8, 256, 0, s>>>(x, 2 * (F_CNT + SC.sbeg[3]), (nsm - 64) / 2);
    {
        cudaLaunchConfig_t cfg = {};
        cfg.gridDim = dim3(64); cfg.blockDim = dim3(CHAIN_THREADS); cfg.dynamicSmemBytes = sizeof(ChainSmem); cfg.stream = s;
        cudaLaunchAttribute at[1];
        at[0].id = cudaLaunchAttributeClusterDimension;
        at[0].val.clusterDim.x = CL; at[0].val.clusterDim.y = 1; at[0].val.clusterDim.z = 1;
        cfg.attrs = at; cfg.numAttrs = 1;
        cudaLaunchKernelEx(&cfg, chain_kernel, ca);
    }
    {
        cudaLaunchConfig_t cfg = {};
        cfg.gridDim = dim3((nsm - 64) & ~1); cfg.blockDim = dim3(384); cfg.dynamicSmemBytes = BULK_SMEM; cfg.stream = s;
        cudaLaunchAttribute at[2];
        at[0].id = cudaLaunchAttributeProgrammaticStreamSerialization;
        at[0].val.programmaticStreamSerializationAllowed = 1;
        at[1].id = cudaLaunchAttributeClusterDimension;
        at[1].val.clusterDim.x = 2; at[1].val.clusterDim.y = 1; at[1].val.clusterDim.z = 1;
        cfg.attrs = at; cfg.numAttrs = 2;
        cudaLaunchKernelEx(&cfg, bulk_kernel, M, BA, SC);
    }
}
}

extern "C" void kernel_launch(void* const* d_in, const int* in_sizes, int n_in, void* d_out, int out_size) {
    (void)in_sizes; (void)n_in; (void)out_size;
    if (ws::usable()) ws::launch_all(d_in, d_out);
    else ni::launch_all(d_in, d_out);
}
```

```cpp
#include <cuda_runtime.h>
#include <cuda_bf16.h>
#include <stdint.h>
#include <cuda.h>

typedef __nv_bfloat16 bf16;
namespace ws {
constexpr int S_LEN = 2048, DM = 640, NH = 32, DH = 128, HD = NH * DH, SEG = 32, NSEG = S_LEN / SEG;

__device__ __forceinline__ float bf2f(bf16 v) { return __bfloat162float(v); }
__device__ __forceinline__ float rbf(float v) { return __bfloat162float(__float2bfloat16_rn(v)); }
__device__ __forceinline__ uint32_t pack2(float a, float b) {
    __nv_bfloat162 t = __floats2bfloat162_rn(a, b);
    return *reinterpret_cast<uint32_t*>(&t);
}
__device__ __forceinline__ float blo(uint32_t v) { return __uint_as_float(v << 16); }
__device__ __forceinline__ float bhi(uint32_t v) { return __uint_as_float(v & 0xffff0000u); }
__device__ __forceinline__ uint32_t badd(uint32_t a, uint32_t b) { uint32_t r; asm("add.rn.bf16x2 %0, %1, %2;" : "=r"(r) : "r"(a), "r"(b)); return r; }
__device__ __forceinline__ uint32_t smem_u32(const void* p) { return (uint32_t)__cvta_generic_to_shared(p); }
__device__ __forceinline__ uint4 ldsm4(uint32_t a) {
    uint4 v;
    asm volatile("ldmatrix.sync.aligned.m8n8.x4.shared.b16 {%0,%1,%2,%3}, [%4];" : "=r"(v.x), "=r"(v.y), "=r"(v.z), "=r"(v.w) : "r"(a));
    return v;
}
__device__ __forceinline__ uint4 ldsm4t(uint32_t a) {
    uint4 v;
    asm volatile("ldmatrix.sync.aligned.m8n8.x4.trans.shared.b16 {%0,%1,%2,%3}, [%4];" : "=r"(v.x), "=r"(v.y), "=r"(v.z), "=r"(v.w) : "r"(a));
    return v;
}
__device__ __forceinline__ uint2 ldsm2t(uint32_t a) {
    uint2 v;
    asm volatile("ldmatrix.sync.aligned.m8n8.x2.trans.shared.b16 {%0,%1}, [%2];" : "=r"(v.x), "=r"(v.y) : "r"(a));
    return v;
}
__device__ __forceinline__ void stsm4(uint32_t a, uint32_t r0, uint32_t r1, uint32_t r2, uint32_t r3) {
    asm volatile("stmatrix.sync.aligned.m8n8.x4.shared.b16 [%0], {%1,%2,%3,%4};" ::"r"(a), "r"(r0), "r"(r1), "r"(r2), "r"(r3) : "memory");
}
__device__ __forceinline__ void stsm2(uint32_t a, uint32_t r0, uint32_t r1) {
    asm volatile("stmatrix.sync.aligned.m8n8.x2.shared.b16 [%0], {%1,%2};" ::"r"(a), "r"(r0), "r"(r1) : "memory");
}
__device__ __forceinline__ void stsm4t(uint32_t a, uint32_t r0, uint32_t r1, uint32_t r2, uint32_t r3) {
    asm volatile("stmatrix.sync.aligned.m8n8.x4.trans.shared.b16 [%0], {%1,%2,%3,%4};" ::"r"(a), "r"(r0), "r"(r1), "r"(r2), "r"(r3) : "memory");
}
__device__ __forceinline__ void mma16816(float* c, uint32_t a0, uint32_t a1, uint32_t a2, uint32_t a3, uint32_t b0, uint32_t b1) {
    asm("mma.sync.aligned.m16n8k16.row.col.f32.bf16.bf16.f32 {%0,%1,%2,%3}, {%4,%5,%6,%7}, {%8,%9}, {%0,%1,%2,%3};"
        : "+f"(c[0]), "+f"(c[1]), "+f"(c[2]), "+f"(c[3]) : "r"(a0), "r"(a1), "r"(a2), "r"(a3), "r"(b0), "r"(b1));
}
__device__ __forceinline__ void mmav(float* c, uint32_t a0, uint32_t a1, uint32_t a2, uint32_t a3, uint32_t b0, uint32_t b1) {
    asm volatile("mma.sync.aligned.m16n8k16.row.col.f32.bf16.bf16.f32 {%0,%1,%2,%3}, {%4,%5,%6,%7}, {%8,%9}, {%0,%1,%2,%3};"
        : "+f"(c[0]), "+f"(c[1]), "+f"(c[2]), "+f"(c[3]) : "r"(a0), "r"(a1), "r"(a2), "r"(a3), "r"(b0), "r"(b1));
}
__device__ __forceinline__ void mmau(float* c, const uint4& a, uint32_t b0, uint32_t b1) { mma16816(c, a.x, a.y, a.z, a.w, b0, b1); }
__device__ __forceinline__ void mma1688(float* c, uint32_t a0, uint32_t a1, uint32_t b0) {
    asm("mma.sync.aligned.m16n8k8.row.col.f32.bf16.bf16.f32 {%0,%1,%2,%3}, {%4,%5}, {%6}, {%0,%1,%2,%3};"
        : "+f"(c[0]), "+f"(c[1]), "+f"(c[2]), "+f"(c[3]) : "r"(a0), "r"(a1), "r"(b0));
}
__device__ __forceinline__ void mmav8(float* c, uint32_t a0, uint32_t a1, uint32_t b0) {
    asm volatile("mma.sync.aligned.m16n8k8.row.col.f32.bf16.bf16.f32 {%0,%1,%2,%3}, {%4,%5}, {%6}, {%0,%1,%2,%3};"
        : "+f"(c[0]), "+f"(c[1]), "+f"(c[2]), "+f"(c[3]) : "r"(a0), "r"(a1), "r"(b0));
}
__device__ __forceinline__ void cp_async16(uint32_t dst, const void* src) { asm volatile("cp.async.cg.shared.global [%0], [%1], 16;" ::"r"(dst), "l"(src)); }
__device__ __forceinline__ void cp_commit() { asm volatile("cp.async.commit_group;"); }
template <int N> __device__ __forceinline__ void cp_wait() { asm volatile("cp.async.wait_group %0;" ::"n"(N)); }
__device__ __forceinline__ uint4 lds128(uint32_t a) {
    uint4 v;
    asm volatile("ld.shared.v4.u32 {%0,%1,%2,%3}, [%4];" : "=r"(v.x), "=r"(v.y), "=r"(v.z), "=r"(v.w) : "r"(a));
    return v;
}
__device__ __forceinline__ uint2 lds64(uint32_t a) {
    uint2 v;
    asm volatile("ld.shared.v2.u32 {%0,%1}, [%2];" : "=r"(v.x), "=r"(v.y) : "r"(a));
    return v;
}
__device__ __forceinline__ uint32_t lds32(uint32_t a) { uint32_t v; asm volatile("ld.shared.u32 %0, [%1];" : "=r"(v) : "r"(a)); return v; }
__device__ __forceinline__ void sts32(uint32_t a, uint32_t x) { asm volatile("st.shared.u32 [%0], %1;" ::"r"(a), "r"(x) : "memory"); }
__device__ __forceinline__ void sts64(uint32_t a, uint32_t x, uint32_t y) { asm volatile("st.shared.v2.u32 [%0], {%1,%2};" ::"r"(a), "r"(x), "r"(y) : "memory"); }
__device__ __forceinline__ void sts128(uint32_t a, uint32_t x, uint32_t y, uint32_t z, uint32_t w) {
    asm volatile("st.shared.v4.u32 [%0], {%1,%2,%3,%4};" ::"r"(a), "r"(x), "r"(y), "r"(z), "r"(w) : "memory");
}
__device__ __forceinline__ uint4 ld_relaxed_v4(const void* p) {
    uint4 v;
    asm volatile("ld.relaxed.gpu.global.v4.u32 {%0,%1,%2,%3}, [%4];" : "=r"(v.x), "=r"(v.y), "=r"(v.z), "=r"(v.w) : "l"(p) : "memory");
    return v;
}
__device__ __forceinline__ uint2 ld_relaxed_v2(const void* p) {
    uint2 v;
    asm volatile("ld.relaxed.gpu.global.v2.u32 {%0,%1}, [%2];" : "=r"(v.x), "=r"(v.y) : "l"(p) : "memory");
    return v;
}
__device__ __forceinline__ void ld7_relaxed(uint4* x, const void* p) {
    asm volatile("ld.relaxed.gpu.global.v4.u32 {%0,%1,%2,%3}, [%28 + 0];\nld.relaxed.gpu.global.v4.u32 {%4,%5,%6,%7}, [%28 + 512];\nld.relaxed.gpu.global.v4.u32 {%8,%9,%10,%11}, [%28 + 1024];\nld.relaxed.gpu.global.v4.u32 {%12,%13,%14,%15}, [%28 + 1536];\nld.relaxed.gpu.global.v4.u32 {%16,%17,%18,%19}, [%28 + 2048];\nld.relaxed.gpu.global.v4.u32 {%20,%21,%22,%23}, [%28 + 2560];\nld.relaxed.gpu.global.v4.u32 {%24,%25,%26,%27}, [%28 + 3072];\n" : "=r"(x[0].x), "=r"(x[0].y), "=r"(x[0].z), "=r"(x[0].w), "=r"(x[1].x), "=r"(x[1].y), "=r"(x[1].z), "=r"(x[1].w), "=r"(x[2].x), "=r"(x[2].y), "=r"(x[2].z), "=r"(x[2].w), "=r"(x[3].x), "=r"(x[3].y), "=r"(x[3].z), "=r"(x[3].w), "=r"(x[4].x), "=r"(x[4].y), "=r"(x[4].z), "=r"(x[4].w), "=r"(x[5].x), "=r"(x[5].y), "=r"(x[5].z), "=r"(x[5].w), "=r"(x[6].x), "=r"(x[6].y), "=r"(x[6].z), "=r"(x[6].w) : "l"(p) : "memory");
}
__device__ __forceinline__ void ld7_relaxed(uint2* x, const void* p) {
    asm volatile("ld.relaxed.gpu.global.v2.u32 {%0,%1}, [%14 + 0];\nld.relaxed.gpu.global.v2.u32 {%2,%3}, [%14 + 512];\nld.relaxed.gpu.global.v2.u32 {%4,%5}, [%14 + 1024];\nld.relaxed.gpu.global.v2.u32 {%6,%7}, [%14 + 1536];\nld.relaxed.gpu.global.v2.u32 {%8,%9}, [%14 + 2048];\nld.relaxed.gpu.global.v2.u32 {%10,%11}, [%14 + 2560];\nld.relaxed.gpu.global.v2.u32 {%12,%13}, [%14 + 3072];\n" : "=r"(x[0].x), "=r"(x[0].y), "=r"(x[1].x), "=r"(x[1].y), "=r"(x[2].x), "=r"(x[2].y), "=r"(x[3].x), "=r"(x[3].y), "=r"(x[4].x), "=r"(x[4].y), "=r"(x[5].x), "=r"(x[5].y), "=r"(x[6].x), "=r"(x[6].y) : "l"(p) : "memory");
}
__device__ __forceinline__ void st_relaxed_v4(void* p, uint32_t a, uint32_t b, uint32_t c, uint32_t d) {
    asm volatile("st.relaxed.gpu.global.v4.u32 [%0], {%1,%2,%3,%4};" ::"l"(p), "r"(a), "r"(b), "r"(c), "r"(d) : "memory");
}
__device__ __forceinline__ void st_relaxed_v2(void* p, uint32_t a, uint32_t b) {
    asm volatile("st.relaxed.gpu.global.v2.u32 [%0], {%1,%2};" ::"l"(p), "r"(a), "r"(b) : "memory");
}
__device__ __forceinline__ uint32_t clear16(void* p) {
    uint32_t r;
    asm volatile("{\n.reg .b128 z, o;\n.reg .b64 a, b;\nmov.b64 a, 0;\nmov.b128 z, {a, a};\natom.relaxed.gpu.global.exch.b128 o, [%1], z;\nmov.b128 {a, b}, o;\ncvt.u32.u64 %0, a;\n}" : "=r"(r) : "l"(p) : "memory");
    return r;
}
__device__ __forceinline__ uint32_t nz(uint32_t v) { uint32_t r; asm("max.u32 %0, %1, 1;" : "=r"(r) : "r"(v)); return r; }
__device__ __forceinline__ void touch(const void* p) { asm volatile("prefetch.global.L2 [%0];" ::"l"(p) : "memory"); }
__device__ __forceinline__ int ld_relaxed(const int* p) {
    int v;
    asm volatile("ld.relaxed.gpu.global.u32 %0, [%1];" : "=r"(v) : "l"(p) : "memory");
    return v;
}
__device__ __forceinline__ int ld_acquire(const int* p) {
    int v;
    asm volatile("ld.acquire.gpu.global.u32 %0, [%1];" : "=r"(v) : "l"(p) : "memory");
    return v;
}
__device__ __forceinline__ void red_release(int* p, int v) { asm volatile("red.release.gpu.global.add.u32 [%0], %1;" ::"l"(p), "r"(v) : "memory"); }
__device__ __forceinline__ void mbar_init(uint32_t bar, int count) { asm volatile("mbarrier.init.shared::cta.b64 [%0], %1;" ::"r"(bar), "r"(count)); }
__device__ __forceinline__ void mbar_expect_tx(uint32_t bar, uint32_t bytes) {
    asm volatile("mbarrier.arrive.expect_tx.shared::cta.b64 _, [%0], %1;" ::"r"(bar), "r"(bytes) : "memory");
}
__device__ __forceinline__ void mbar_arrive(uint32_t bar) { asm volatile("mbarrier.arrive.shared::cta.b64 _, [%0];" ::"r"(bar) : "memory"); }
__device__ __forceinline__ void mbar_arrive_cluster(uint32_t bar) { asm volatile("mbarrier.arrive.shared::cluster.b64 _, [%0];" ::"r"(bar) : "memory"); }
__device__ __forceinline__ bool mtry(uint32_t bar, uint32_t parity) {
    uint32_t ok;
    asm volatile("{\n.reg .pred P1;\nmbarrier.try_wait.parity.shared::cta.b64 P1, [%1], %2;\nselp.u32 %0, 1, 0, P1;\n}\n" : "=r"(ok) : "r"(bar), "r"(parity) : "memory");
    return ok != 0;
}
__device__ __forceinline__ void mslow(uint32_t bar, uint32_t parity) {
    asm volatile(
        "{\n.reg .pred P1;\n.reg .u32 cnt;\n"
        "mov.u32 cnt, 0;\n"
        "LAB_WAIT:\n"
        "mbarrier.try_wait.parity.shared::cta.b64 P1, [%0], %1;\n"
        "@P1 bra DONE;\n"
        "add.u32 cnt, cnt, 1;\n"
        "setp.lt.u32 P1, cnt, 1000000;\n"
        "@P1 bra LAB_WAIT;\n"
        "trap;\n"
        "DONE:\n}\n" ::"r"(bar), "r"(parity) : "memory");
}
__device__ __forceinline__ void mwait(uint32_t bar, uint32_t parity) {
    asm volatile(
        "{\n.reg .pred P1, P2;\n.reg .u32 cnt;\n"
        "mov.u32 cnt, 0;\n"
        "LAB_WAIT:\n"
        "mbarrier.try_wait.parity.shared::cta.b64 P1, [%0], %1;\n"
        "add.u32 cnt, cnt, 1;\n"
        "setp.gt.u32 P2, cnt, 1000000;\n"
        "@P2 trap;\n"
        "@!P1 bra LAB_WAIT;\n"
        "}\n" ::"r"(bar), "r"(parity) : "memory");
}
__device__ __forceinline__ void mspin(uint32_t bar, uint32_t parity) {
    asm volatile(
        "{\n.reg .pred P1, P2;\n.reg .u32 cnt;\n"
        "mov.u32 cnt, 0;\n"
        "LAB_WAIT:\n"
        "mbarrier.test_wait.parity.shared::cta.b64 P1, [%0], %1;\n"
        "add.u32 cnt, cnt, 1;\n"
        "setp.gt.u32 P2, cnt, 40000000;\n"
        "@P2 trap;\n"
        "@!P1 bra LAB_WAIT;\n"
        "}\n" ::"r"(bar), "r"(parity) : "memory");
}
__device__ __forceinline__ uint32_t mtest(uint32_t bar, uint32_t parity) {
    uint32_t ok;
    asm volatile("{\n.reg .pred P1;\nmbarrier.test_wait.parity.shared::cta.b64 P1, [%1], %2;\nselp.u32 %0, 1, 0, P1;\n}\n" : "=r"(ok) : "r"(bar), "r"(parity) : "memory");
    return ok;
}
__device__ __forceinline__ uint32_t mapa(uint32_t addr, uint32_t rank) {
    uint32_t r;
    asm("mapa.shared::cluster.u32 %0, %1, %2;" : "=r"(r) : "r"(addr), "r"(rank));
    return r;
}
__device__ __forceinline__ void st_async_b32(uint32_t addr, uint32_t a, uint32_t bar) {
    asm volatile("st.async.weak.shared::cluster.mbarrier::complete_tx::bytes.b32 [%0], %1, [%2];" ::"r"(addr), "r"(a), "r"(bar) : "memory");
}
__device__ __forceinline__ void st_async_v2(uint32_t addr, uint32_t a, uint32_t b, uint32_t bar) {
    asm volatile("st.async.weak.shared::cluster.mbarrier::complete_tx::bytes.v2.b32 [%0], {%1,%2}, [%3];" ::"r"(addr), "r"(a), "r"(b), "r"(bar) : "memory");
}
__device__ __forceinline__ void st_async_v2_lt(uint32_t addr, uint32_t a, uint32_t b, uint32_t bar, uint32_t x, uint32_t lim) {
    asm volatile("{\n.reg .pred p;\nsetp.lt.u32 p, %4, %5;\n@p st.async.weak.shared::cluster.mbarrier::complete_tx::bytes.v2.b32 [%0], {%1,%2}, [%3];\n}"
                 ::"r"(addr), "r"(a), "r"(b), "r"(bar), "r"(x), "r"(lim) : "memory");
}
__device__ __forceinline__ void st_async_v4(uint32_t addr, uint32_t a, uint32_t b, uint32_t c, uint32_t d, uint32_t bar) {
    asm volatile("st.async.weak.shared::cluster.mbarrier::complete_tx::bytes.v4.b32 [%0], {%1,%2,%3,%4}, [%5];" ::"r"(addr), "r"(a), "r"(b), "r"(c), "r"(d), "r"(bar) : "memory");
}
__device__ __forceinline__ void st_async_v4p(uint32_t addr, uint32_t a, uint32_t b, uint32_t c, uint32_t d, uint32_t bar) {
    asm volatile("{\n.reg .pred p;\nsetp.ne.u32 p, %5, 0;\n@p st.async.weak.shared::cluster.mbarrier::complete_tx::bytes.v4.b32 [%0], {%1,%2,%3,%4}, [%5];\n}"
                 ::"r"(addr), "r"(a), "r"(b), "r"(c), "r"(d), "r"(bar) : "memory");
}
__device__ __forceinline__ void st_async_v2p(uint32_t addr, uint32_t a, uint32_t b, uint32_t bar) {
    asm volatile("{\n.reg .pred p;\nsetp.ne.u32 p, %3, 0;\n@p st.async.weak.shared::cluster.mbarrier::complete_tx::bytes.v2.b32 [%0], {%1,%2}, [%3];\n}"
                 ::"r"(addr), "r"(a), "r"(b), "r"(bar) : "memory");
}
__device__ __forceinline__ void cluster_arrive() { asm volatile("barrier.cluster.arrive.release.aligned;" ::: "memory"); }
__device__ __forceinline__ void cluster_arrive_relaxed() { asm volatile("barrier.cluster.arrive.relaxed.aligned;" ::: "memory"); }
__device__ __forceinline__ void prefetch_l2(const void* p, uint32_t bytes) { asm volatile("cp.async.bulk.prefetch.L2.global [%0], %1;" ::"l"(p), "r"(bytes) : "memory"); }
__device__ __forceinline__ void cluster_wait() { asm volatile("barrier.cluster.wait.acquire.aligned;" ::: "memory"); }
__device__ __forceinline__ void named_bar(int id, int n) { asm volatile("bar.sync %0, %1;" ::"r"(id), "r"(n) : "memory"); }
__device__ __forceinline__ void named_arrive(int id, int n) { asm volatile("bar.arrive %0, %1;" ::"r"(id), "r"(n) : "memory"); }
__device__ __forceinline__ void fence_async_smem() { asm volatile("fence.proxy.async.shared::cta;" ::: "memory"); }
__device__ __forceinline__ void fence_async_global() { asm volatile("fence.proxy.async.global;" ::: "memory"); }
__device__ __forceinline__ void wg_fence() { asm volatile("wgmma.fence.sync.aligned;" ::: "memory"); }
__device__ __forceinline__ void wg_commit() { asm volatile("wgmma.commit_group.sync.aligned;" ::: "memory"); }
template <int N> __device__ __forceinline__ void wg_wait() { asm volatile("wgmma.wait_group.sync.aligned %0;" ::"n"(N) : "memory"); }
__device__ __forceinline__ uint64_t ndesc(uint32_t addr, uint32_t lbo, uint32_t sbo) {
    return (uint64_t)((addr & 0x3FFFF) >> 4) | ((uint64_t)(lbo >> 4) << 16) | ((uint64_t)(sbo >> 4) << 32);
}
__device__ __forceinline__ float ex2f(float x) { float y; asm("ex2.approx.ftz.f32 %0, %1;" : "=f"(y) : "f"(x)); return y; }
__device__ __forceinline__ float rcpf(float x) { float y; asm("rcp.approx.ftz.f32 %0, %1;" : "=f"(y) : "f"(x)); return y; }
__device__ __forceinline__ uint32_t clk32() { uint32_t c; asm volatile("mov.u32 %0, %clock;" : "=r"(c)); return c; }
__device__ __forceinline__ uint32_t opq(uint32_t x) { uint32_t y; asm volatile("mov.u32 %0, %1;" : "=r"(y) : "r"(x)); return y; }
__device__ __forceinline__ uint32_t rem(uint32_t addr, uint32_t rank) { return mapa(addr, rank); }
__device__ __forceinline__ uint64_t mkdesc(uint32_t lo, uint32_t hi) { uint64_t d; asm("mov.b64 %0, {%1,%2};" : "=l"(d) : "r"(lo), "r"(hi)); return d; }
__device__ __forceinline__ void delay(uint32_t n) {
    asm volatile("{\n.reg .pred P;\n.reg .u32 a, b;\nmov.u32 a, %clock;\nadd.u32 a, a, %0;\nDL:\nmov.u32 b, %clock;\nsub.u32 b, b, a;\nsetp.lt.s32 P, b, 0;\n@P bra.uni DL;\n}" ::"r"(n) : "memory");
}
#define UNI(x) __shfl_sync(0xffffffffu, (uint32_t)(x), 0)
__device__ __forceinline__ void wg_n16t(float* d, uint32_t a0, uint32_t a1, uint32_t a2, uint32_t a3, uint64_t db) {
    asm volatile("wgmma.mma_async.sync.aligned.m64n16k16.f32.bf16.bf16 {%0, %1, %2, %3, %4, %5, %6, %7}, {%8, %9, %10, %11}, %12, 1, 1, 1, 1;"
                 : "+f"(d[0]), "+f"(d[1]), "+f"(d[2]), "+f"(d[3]), "+f"(d[4]), "+f"(d[5]), "+f"(d[6]), "+f"(d[7]) : "r"(a0), "r"(a1), "r"(a2), "r"(a3), "l"(db));
}
__device__ __forceinline__ void wg_n16t_first(float* d, uint32_t a0, uint32_t a1, uint32_t a2, uint32_t a3, uint64_t db) {
    asm volatile("wgmma.mma_async.sync.aligned.m64n16k16.f32.bf16.bf16 {%0, %1, %2, %3, %4, %5, %6, %7}, {%8, %9, %10, %11}, %12, 0, 1, 1, 1;"
                 : "=f"(d[0]), "=f"(d[1]), "=f"(d[2]), "=f"(d[3]), "=f"(d[4]), "=f"(d[5]), "=f"(d[6]), "=f"(d[7]) : "r"(a0), "r"(a1), "r"(a2), "r"(a3), "l"(db));
}
__device__ __forceinline__ void wg_n32(float* d, uint32_t a0, uint32_t a1, uint32_t a2, uint32_t a3, uint64_t db) {
    asm volatile("wgmma.mma_async.sync.aligned.m64n32k16.f32.bf16.bf16 {%0, %1, %2, %3, %4, %5, %6, %7, %8, %9, %10, %11, %12, %13, %14, %15}, {%16, %17, %18, %19}, %20, 1, 1, 1, 0;"
                 : "+f"(d[0]), "+f"(d[1]), "+f"(d[2]), "+f"(d[3]), "+f"(d[4]), "+f"(d[5]), "+f"(d[6]), "+f"(d[7]), "+f"(d[8]), "+f"(d[9]), "+f"(d[10]), "+f"(d[11]), "+f"(d[12]), "+f"(d[13]), "+f"(d[14]), "+f"(d[15]) : "r"(a0), "r"(a1), "r"(a2), "r"(a3), "l"(db));
}
__device__ __forceinline__ void wg_n32_first(float* d, uint32_t a0, uint32_t a1, uint32_t a2, uint32_t a3, uint64_t db) {
    asm volatile("wgmma.mma_async.sync.aligned.m64n32k16.f32.bf16.bf16 {%0, %1, %2, %3, %4, %5, %6, %7, %8, %9, %10, %11, %12, %13, %14, %15}, {%16, %17, %18, %19}, %20, 0, 1, 1, 0;"
                 : "=f"(d[0]), "=f"(d[1]), "=f"(d[2]), "=f"(d[3]), "=f"(d[4]), "=f"(d[5]), "=f"(d[6]), "=f"(d[7]), "=f"(d[8]), "=f"(d[9]), "=f"(d[10]), "=f"(d[11]), "=f"(d[12]), "=f"(d[13]), "=f"(d[14]), "=f"(d[15]) : "r"(a0), "r"(a1), "r"(a2), "r"(a3), "l"(db));
}

__device__ __forceinline__ void wg_n16t_sfirst(float* d, uint64_t da, uint64_t db) {
    asm volatile("wgmma.mma_async.sync.aligned.m64n16k16.f32.bf16.bf16 {%0, %1, %2, %3, %4, %5, %6, %7}, %8, %9, 0, 1, 1, 1, 1;"
                 : "=f"(d[0]), "=f"(d[1]), "=f"(d[2]), "=f"(d[3]), "=f"(d[4]), "=f"(d[5]), "=f"(d[6]), "=f"(d[7]) : "l"(da), "l"(db));
}
__device__ __forceinline__ void wg_n32_sfirst(float* d, uint64_t da, uint64_t db) {
    asm volatile("wgmma.mma_async.sync.aligned.m64n32k16.f32.bf16.bf16 {%0, %1, %2, %3, %4, %5, %6, %7, %8, %9, %10, %11, %12, %13, %14, %15}, %16, %17, 0, 1, 1, 1, 0;"
                 : "=f"(d[0]), "=f"(d[1]), "=f"(d[2]), "=f"(d[3]), "=f"(d[4]), "=f"(d[5]), "=f"(d[6]), "=f"(d[7]), "=f"(d[8]), "=f"(d[9]), "=f"(d[10]), "=f"(d[11]), "=f"(d[12]), "=f"(d[13]), "=f"(d[14]), "=f"(d[15]) : "l"(da), "l"(db));
}

__device__ __forceinline__ void wg_n16t_s(float* d, uint64_t da, uint64_t db) {
    asm volatile("wgmma.mma_async.sync.aligned.m64n16k16.f32.bf16.bf16 {%0, %1, %2, %3, %4, %5, %6, %7}, %8, %9, 1, 1, 1, 1, 1;"
                 : "+f"(d[0]), "+f"(d[1]), "+f"(d[2]), "+f"(d[3]), "+f"(d[4]), "+f"(d[5]), "+f"(d[6]), "+f"(d[7]) : "l"(da), "l"(db));
}
__device__ __forceinline__ void wg_n64_sfirst(float* d, uint64_t da, uint64_t db) {
    asm volatile("wgmma.mma_async.sync.aligned.m64n64k16.f32.bf16.bf16 {%0, %1, %2, %3, %4, %5, %6, %7, %8, %9, %10, %11, %12, %13, %14, %15, %16, %17, %18, %19, %20, %21, %22, %23, %24, %25, %26, %27, %28, %29, %30, %31}, %32, %33, 0, 1, 1, 1, 0;"
                 : "=f"(d[0]), "=f"(d[1]), "=f"(d[2]), "=f"(d[3]), "=f"(d[4]), "=f"(d[5]), "=f"(d[6]), "=f"(d[7]), "=f"(d[8]), "=f"(d[9]), "=f"(d[10]), "=f"(d[11]), "=f"(d[12]), "=f"(d[13]), "=f"(d[14]), "=f"(d[15]), "=f"(d[16]), "=f"(d[17]), "=f"(d[18]), "=f"(d[19]), "=f"(d[20]), "=f"(d[21]), "=f"(d[22]), "=f"(d[23]), "=f"(d[24]), "=f"(d[25]), "=f"(d[26]), "=f"(d[27]), "=f"(d[28]), "=f"(d[29]), "=f"(d[30]), "=f"(d[31]) : "l"(da), "l"(db));
}
__device__ __forceinline__ void wg_n64_s(float* d, uint64_t da, uint64_t db) {
    asm volatile("wgmma.mma_async.sync.aligned.m64n64k16.f32.bf16.bf16 {%0, %1, %2, %3, %4, %5, %6, %7, %8, %9, %10, %11, %12, %13, %14, %15, %16, %17, %18, %19, %20, %21, %22, %23, %24, %25, %26, %27, %28, %29, %30, %31}, %32, %33, 1, 1, 1, 1, 0;"
                 : "+f"(d[0]), "+f"(d[1]), "+f"(d[2]), "+f"(d[3]), "+f"(d[4]), "+f"(d[5]), "+f"(d[6]), "+f"(d[7]), "+f"(d[8]), "+f"(d[9]), "+f"(d[10]), "+f"(d[11]), "+f"(d[12]), "+f"(d[13]), "+f"(d[14]), "+f"(d[15]), "+f"(d[16]), "+f"(d[17]), "+f"(d[18]), "+f"(d[19]), "+f"(d[20]), "+f"(d[21]), "+f"(d[22]), "+f"(d[23]), "+f"(d[24]), "+f"(d[25]), "+f"(d[26]), "+f"(d[27]), "+f"(d[28]), "+f"(d[29]), "+f"(d[30]), "+f"(d[31]) : "l"(da), "l"(db));
}
__device__ __forceinline__ void wg_n64(float* d, uint32_t a0, uint32_t a1, uint32_t a2, uint32_t a3, uint64_t db) {
    asm volatile("wgmma.mma_async.sync.aligned.m64n64k16.f32.bf16.bf16 {%0, %1, %2, %3, %4, %5, %6, %7, %8, %9, %10, %11, %12, %13, %14, %15, %16, %17, %18, %19, %20, %21, %22, %23, %24, %25, %26, %27, %28, %29, %30, %31}, {%32, %33, %34, %35}, %36, 1, 1, 1, 0;"
                 : "+f"(d[0]), "+f"(d[1]), "+f"(d[2]), "+f"(d[3]), "+f"(d[4]), "+f"(d[5]), "+f"(d[6]), "+f"(d[7]), "+f"(d[8]), "+f"(d[9]), "+f"(d[10]), "+f"(d[11]), "+f"(d[12]), "+f"(d[13]), "+f"(d[14]), "+f"(d[15]), "+f"(d[16]), "+f"(d[17]), "+f"(d[18]), "+f"(d[19]), "+f"(d[20]), "+f"(d[21]), "+f"(d[22]), "+f"(d[23]), "+f"(d[24]), "+f"(d[25]), "+f"(d[26]), "+f"(d[27]), "+f"(d[28]), "+f"(d[29]), "+f"(d[30]), "+f"(d[31]) : "r"(a0), "r"(a1), "r"(a2), "r"(a3), "l"(db));
}
__device__ __forceinline__ void wg_n64_first(float* d, uint32_t a0, uint32_t a1, uint32_t a2, uint32_t a3, uint64_t db) {
    asm volatile("wgmma.mma_async.sync.aligned.m64n64k16.f32.bf16.bf16 {%0, %1, %2, %3, %4, %5, %6, %7, %8, %9, %10, %11, %12, %13, %14, %15, %16, %17, %18, %19, %20, %21, %22, %23, %24, %25, %26, %27, %28, %29, %30, %31}, {%32, %33, %34, %35}, %36, 0, 1, 1, 0;"
                 : "=f"(d[0]), "=f"(d[1]), "=f"(d[2]), "=f"(d[3]), "=f"(d[4]), "=f"(d[5]), "=f"(d[6]), "=f"(d[7]), "=f"(d[8]), "=f"(d[9]), "=f"(d[10]), "=f"(d[11]), "=f"(d[12]), "=f"(d[13]), "=f"(d[14]), "=f"(d[15]), "=f"(d[16]), "=f"(d[17]), "=f"(d[18]), "=f"(d[19]), "=f"(d[20]), "=f"(d[21]), "=f"(d[22]), "=f"(d[23]), "=f"(d[24]), "=f"(d[25]), "=f"(d[26]), "=f"(d[27]), "=f"(d[28]), "=f"(d[29]), "=f"(d[30]), "=f"(d[31]) : "r"(a0), "r"(a1), "r"(a2), "r"(a3), "l"(db));
}

__device__ __forceinline__ void wg_n32t(float* d, uint32_t a0, uint32_t a1, uint32_t a2, uint32_t a3, uint64_t db) {
    asm volatile("wgmma.mma_async.sync.aligned.m64n32k16.f32.bf16.bf16 {%0, %1, %2, %3, %4, %5, %6, %7, %8, %9, %10, %11, %12, %13, %14, %15}, {%16, %17, %18, %19}, %20, 1, 1, 1, 1;"
                 : "+f"(d[0]), "+f"(d[1]), "+f"(d[2]), "+f"(d[3]), "+f"(d[4]), "+f"(d[5]), "+f"(d[6]), "+f"(d[7]), "+f"(d[8]), "+f"(d[9]), "+f"(d[10]), "+f"(d[11]), "+f"(d[12]), "+f"(d[13]), "+f"(d[14]), "+f"(d[15]) : "r"(a0), "r"(a1), "r"(a2), "r"(a3), "l"(db));
}
__device__ __forceinline__ void wg_n32t_first(float* d, uint32_t a0, uint32_t a1, uint32_t a2, uint32_t a3, uint64_t db) {
    asm volatile("wgmma.mma_async.sync.aligned.m64n32k16.f32.bf16.bf16 {%0, %1, %2, %3, %4, %5, %6, %7, %8, %9, %10, %11, %12, %13, %14, %15}, {%16, %17, %18, %19}, %20, 0, 1, 1, 1;"
                 : "=f"(d[0]), "=f"(d[1]), "=f"(d[2]), "=f"(d[3]), "=f"(d[4]), "=f"(d[5]), "=f"(d[6]), "=f"(d[7]), "=f"(d[8]), "=f"(d[9]), "=f"(d[10]), "=f"(d[11]), "=f"(d[12]), "=f"(d[13]), "=f"(d[14]), "=f"(d[15]) : "r"(a0), "r"(a1), "r"(a2), "r"(a3), "l"(db));
}
__device__ __forceinline__ void wg_n32t_sfirst(float* d, uint64_t da, uint64_t db) {
    asm volatile("wgmma.mma_async.sync.aligned.m64n32k16.f32.bf16.bf16 {%0, %1, %2, %3, %4, %5, %6, %7, %8, %9, %10, %11, %12, %13, %14, %15}, %16, %17, 0, 1, 1, 1, 1;"
                 : "=f"(d[0]), "=f"(d[1]), "=f"(d[2]), "=f"(d[3]), "=f"(d[4]), "=f"(d[5]), "=f"(d[6]), "=f"(d[7]), "=f"(d[8]), "=f"(d[9]), "=f"(d[10]), "=f"(d[11]), "=f"(d[12]), "=f"(d[13]), "=f"(d[14]), "=f"(d[15]) : "l"(da), "l"(db));
}
__device__ __forceinline__ void wg_n32t_s(float* d, uint64_t da, uint64_t db) {
    asm volatile("wgmma.mma_async.sync.aligned.m64n32k16.f32.bf16.bf16 {%0, %1, %2, %3, %4, %5, %6, %7, %8, %9, %10, %11, %12, %13, %14, %15}, %16, %17, 1, 1, 1, 1, 1;"
                 : "+f"(d[0]), "+f"(d[1]), "+f"(d[2]), "+f"(d[3]), "+f"(d[4]), "+f"(d[5]), "+f"(d[6]), "+f"(d[7]), "+f"(d[8]), "+f"(d[9]), "+f"(d[10]), "+f"(d[11]), "+f"(d[12]), "+f"(d[13]), "+f"(d[14]), "+f"(d[15]) : "l"(da), "l"(db));
}

__device__ __forceinline__ void wg_n32_kk(float* d, uint64_t da, uint64_t db) {
    asm volatile("wgmma.mma_async.sync.aligned.m64n32k16.f32.bf16.bf16 {%0, %1, %2, %3, %4, %5, %6, %7, %8, %9, %10, %11, %12, %13, %14, %15}, %16, %17, 1, 1, 1, 0, 0;"
                 : "+f"(d[0]), "+f"(d[1]), "+f"(d[2]), "+f"(d[3]), "+f"(d[4]), "+f"(d[5]), "+f"(d[6]), "+f"(d[7]), "+f"(d[8]), "+f"(d[9]), "+f"(d[10]), "+f"(d[11]), "+f"(d[12]), "+f"(d[13]), "+f"(d[14]), "+f"(d[15]) : "l"(da), "l"(db));
}

}

namespace ws {
#define LAGT 4
constexpr int LAG = LAGT, NT = NSEG + LAG, NCL = 7;
#define P1A 24
#define P1C 10
#define XD 350
#define TPV_PAUSE 1
#define OT_LATE 1
#define H1_LATE 2
#define O_BULK 0
#define O_DLY 0
#define BP 0
#define REG_G 200
#define REG_T 72
#define REG_X 40
#define PDA 8
#define PDC 8
template <int V> struct IC { static constexpr int value = V; };
#define HBYTES 5120
#define POST_NS 20
#define OP_NS 20
#define LN0_AHEAD 8
#define PRE_PDL 0
#define PRE_PF 0
#define OP_LATE 0
#define G_DLY 0
#define QUIET 0
constexpr int NB4 = QUIET ? 480 : 384;
#define TG_STEPS 40
#define NO_X 0
#define WTA 3
constexpr int WTC = 10 - 2 * WTA;
#define WR 4
#define OBK 2
#define TPVW 1
#define OBRES 1
#define O0_EARLY 1
#define BNS 0
#define SKEW 0
#define XS 250
#define WGRP 4
#define WFLY 2
#define XDUP 1
#define TPV_LATE 0
#define WVOL 1
#define WK3 0
#define W_SKIP 0
#define POST_DRY 0
#define CONV_DRY 0
#define SPIN 0
#define H_NS 20
#define CV_YIELD 0
#define NL2 2
#define XFD 250
#define SELF_LOCAL 0
constexpr int XRS = 3;
constexpr int O_H = 0, O_MEM = 81920, O_RED = 102400, O_BAR = 110080, O_TAB = O_BAR + 192, O_BT = O_TAB + 128, O_TR = O_BAR + 512, O_X = O_TR + 1024;
constexpr int O_QRY = O_X, O_KEY = O_X + 10240, O_OBA = O_KEY + 10240, O_ST = O_OBA + 4096;
constexpr int O_VT = O_X, O_VM = O_VT + 32768, O_SM = O_VM + 4096, O_PB = O_SM + 3072;
constexpr int O_AS = 228352, O_WO = O_AS - 65536, HEAD_SMEM = O_AS + 4096, O_STG = 40960;
static_assert(O_ST + 8192 <= O_WO && O_PB + 10240 <= O_WO && O_AS % 1024 == 0 && O_STG + 163840 <= O_AS && HEAD_SMEM <= 232448, "smem");
constexpr int O_BUSY = O_BT + 128;
constexpr int B_MEM = 0, B_RED = 64, B_SM = 88, B_ST = 96, B_OB = 104, B_HF = 112, B_HE = 128, B_OTF = 144, B_OTE = 160;

constexpr int F_H = 0, F_O = 128, F_P = 256, F_U = 384, F_CV = 392, F_XL = 398, F_Z = 399, NFLAG = 400;
__device__ int g_flags[NFLAG * 8];
#define FLG(i) (g_flags + (i) * 8)
#define RING 16
__device__ __forceinline__ int rslot(int l, int seg) { return l * RING + (seg & (RING - 1)); }
__device__ uint4 g_ht[2 * RING * 2560];
__device__ uint4 g_ot[2 * RING * 256 * 64];
__device__ uint4 g_pt[2 * RING * 5120];
__device__ uint4 g_Y[80 * S_LEN];
__device__ uint4 g_U[DM * S_LEN / 8];
__device__ bf16 g_x[RING * SEG * DM];
__device__ int g_epoch;
__device__ uint4 g_xc[XRS * 16 * 3 * 8 * 32];
#define GT(cond, i)
#define SC(cond, i)
#define SD(x)
#define TS(i)
#define TV(i, v)

}

namespace ws {
__device__ __forceinline__ uint32_t bmul2(uint32_t a, uint32_t b) { uint32_t r; asm("mul.rn.bf16x2 %0, %1, %2;" : "=r"(r) : "r"(a), "r"(b)); return r; }
__device__ __forceinline__ uint32_t bmax2(uint32_t a, uint32_t b) { uint32_t r; asm("max.bf16x2 %0, %1, %2;" : "=r"(r) : "r"(a), "r"(b)); return r; }
__device__ __forceinline__ void flag_wait(const int* f, int tgt, int ns) {
    int guard = 0;
    while (ld_relaxed(f) < tgt) { if (++guard > 4000000) __trap(); __nanosleep(ns); }
}
template <int STRIDE> __device__ __forceinline__ void ld5(uint32_t* w, const void* p) {
#pragma unroll
    for (int r = 0; r < 5; r++) { const uint2 v = __ldcg(reinterpret_cast<const uint2*>(reinterpret_cast<const char*>(p) + r * STRIDE)); w[2 * r] = v.x; w[2 * r + 1] = v.y; }
}
template <int STRIDE> __device__ __forceinline__ void st5(void* p, const uint32_t* w) {
#pragma unroll
    for (int r = 0; r < 5; r++) *reinterpret_cast<uint2*>(reinterpret_cast<char*>(p) + r * STRIDE) = make_uint2(w[2 * r], w[2 * r + 1]);
}
__device__ __forceinline__ void ln_row(const uint32_t* x, uint32_t* y) {
    const float c = blo(__shfl_sync(0xffffffffu, x[0], 0));
    float s0 = 0.f, s1 = 0.f, q0 = 0.f, q1 = 0.f;
#pragma unroll
    for (int i = 0; i < 10; i++) { const float d0 = blo(x[i]) - c, d1 = bhi(x[i]) - c; s0 += d0; s1 += d1; q0 = fmaf(d0, d0, q0); q1 = fmaf(d1, d1, q1); }
    float s = s0 + s1, q = q0 + q1;
#pragma unroll
    for (int o = 16; o > 0; o >>= 1) { s += __shfl_xor_sync(0xffffffffu, s, o); q += __shfl_xor_sync(0xffffffffu, q, o); }
    s *= 1.0f / DM;
    const float mean = c + s;
    q = fmaxf(fmaf(q, 1.0f / DM, -s * s), 0.f);
    const uint32_t nm = pack2(-mean, -mean);
    float sq;
    asm("sqrt.approx.ftz.f32 %0, %1;" : "=f"(sq) : "f"(rbf(rbf(q) + 1e-5f)));
    const float rd = rcpf(rbf(sq));
#pragma unroll
    for (int i = 0; i < 10; i++) { const uint32_t d = badd(x[i], nm); y[i] = pack2(blo(d) * rd, bhi(d) * rd); }
}
__device__ __forceinline__ void clear_acc(int l, int seg, int tok, int lane) {
    uint4* pz = g_pt + rslot(l, seg) * 5120 + (lane >> 4) * 512 + tok * 16 + (lane & 15);
#pragma unroll
    for (int i = 0; i < 5; i++) pz[i * 1024] = make_uint4(0, 0, 0, 0);
}
__device__ __forceinline__ void put_h(int l, int seg, int tok, int lane, const uint32_t* n) {
    st5<8192>(reinterpret_cast<char*>(g_ht + rslot(l, seg) * 2560) + (lane >> 2) * 1024 + tok * 32 + (((lane & 3) * 8) ^ ((tok & 4) << 2)), n);
}
__device__ __forceinline__ void ln0_row(const bf16* x, int seg, int tok, int lane) {
    uint32_t v[10];
    ld5<256>(v, x + (size_t)(seg * SEG + tok) * DM + lane * 4);
    clear_acc(0, seg, tok, lane);
    ln_row(v, v);
    put_h(0, seg, tok, lane, v);
    __syncwarp();
    if (lane == 0) red_release(FLG(F_H + seg), 1);
}
__device__ __forceinline__ void post_row(int l, int seg, int tok, int lane, const bf16* xin, bf16* xout, int ep) {
    const bool dry = ep == 0;
    uint32_t x[10], y[10], n[10];
    const int row = seg * SEG + tok;
    SC(tr, tb);
    const bool first = seg == 0;
    if (seg == 8 || ((seg & 15) == 0 && seg)) flag_wait(FLG(F_CV + (seg >> 4) + 1), 80 * ep, 50);
    const char* yp = dry ? reinterpret_cast<const char*>(xin) + lane * 8 : reinterpret_cast<const char*>(g_Y) + ((size_t)(lane >> 1) * S_LEN + row) * 16 + (lane & 1) * 8;
    SC(tr, tb + 1);
    if (!first) ld5<16 * S_LEN * 16>(y, yp);
    bf16* xm = g_x + ((seg & (RING - 1)) * SEG + tok) * DM + lane * 4;
    if (l == 0) {
        ld5<256>(x, xin + (size_t)row * DM + lane * 4);
        if (!dry) clear_acc(1, seg, tok, lane);
    } else {
        if (!dry) flag_wait(seg + 1 < NSEG ? FLG(F_H + 65 + seg) : FLG(F_XL), 32 * ep, 50);
        ld5<256>(x, dry ? xin + lane * 4 : xm);
    }
    if (!dry) flag_wait(FLG(F_P + l * 64 + seg), 40 * ep, POST_NS);
    SC(tr, tb + 2);
    const uint4* pp = dry ? reinterpret_cast<const uint4*>(xin) + lane : g_pt + rslot(l, seg) * 5120 + (lane >> 4) * 512 + tok * 16 + ((lane & 15) ^ ((tok >> 3) << 1));
    {
        uint4 a[5];
#pragma unroll
        for (int i = 0; i < 5; i++) a[i] = __ldcg(pp + i * 1024);
#pragma unroll
        for (int i = 0; i < 5; i++) {
            x[2 * i] = badd(x[2 * i], pack2(__uint_as_float(a[i].x), __uint_as_float(a[i].y)));
            x[2 * i + 1] = badd(x[2 * i + 1], pack2(__uint_as_float(a[i].z), __uint_as_float(a[i].w)));
        }
    }
    SC(tr && x[0] != 0x12345, tb + 3);
    if (first) { if (!dry) flag_wait(FLG(F_CV), 80 * ep, 50); ld5<16 * S_LEN * 16>(y, yp); }
    ln_row(x, n);
#pragma unroll
    for (int i = 0; i < 10; i++) x[i] = badd(x[i], bmul2(n[i], y[i]));
    SC(tr && x[0] != 0x12345, tb + 4);
    if (l) { if (!dry) st5<256>(xout + (size_t)row * DM + lane * 4, x); }
    else {
        ln_row(x, n);
        SC(tr && n[0] != 0x12345, tb + 5);
        if (!dry) put_h(1, seg, tok, lane, n);
        __syncwarp();
        if (lane == 0 && !dry) red_release(FLG(F_H + 64 + seg), 1);
        SC(tr, tb + 6);
        if (!dry) st5<256>(xm, x);
        if (seg == NSEG - 1) { __syncwarp(); if (lane == 0) red_release(FLG(F_XL), 1); }
    }
}
__device__ __forceinline__ void u_half(const bf16* Bk, const bf16* Bv, const bf16* shiftk, int unit, int lane) {
    const int odd = lane & 1, t0 = (unit / 20) * 16 + odd * 8, cp = (unit % 20) * 16 + (lane >> 1);
    uint32_t kk[11], vv[8];
    const uint32_t* pk = reinterpret_cast<const uint32_t*>(Bk + (size_t)t0 * DM) + cp;
    const uint32_t* pv = reinterpret_cast<const uint32_t*>(Bv + (size_t)t0 * DM) + cp;
#pragma unroll
    for (int i = 0; i < 11; i++) kk[i] = (i >= 3 || t0 > 0) ? __ldg(pk + (i - 3) * (DM / 2)) : 0u;
#pragma unroll
    for (int i = 0; i < 8; i++) vv[i] = __ldg(pv + i * (DM / 2));
    const uint4 sh0 = __ldg(reinterpret_cast<const uint4*>(shiftk + cp * 8));
    const uint32_t s0 = __byte_perm(sh0.x, sh0.z, 0x5410), s1 = __byte_perm(sh0.x, sh0.z, 0x7632), s2 = __byte_perm(sh0.y, sh0.w, 0x5410), s3 = __byte_perm(sh0.y, sh0.w, 0x7632);
#pragma unroll
    for (int t = 0; t < 8; t++)
        vv[t] = bmul2(badd(badd(badd(bmul2(kk[t], s3), bmul2(kk[t + 1], s2)), bmul2(kk[t + 2], s1)), bmul2(kk[t + 3], s0)), vv[t]);
    uint4* d = g_U + (size_t)(cp * 2) * (S_LEN / 8) + (t0 >> 6) * 8 + ((((t0 ^ 56) & 63) >> 3) ^ ((t0 >> 6) & 7));
#pragma unroll
    for (int c = 0; c < 2; c++) {
        const uint32_t sel = c ? 0x7632 : 0x5410;
        d[c * (S_LEN / 8)] = make_uint4(__byte_perm(vv[7], vv[6], sel), __byte_perm(vv[5], vv[4], sel), __byte_perm(vv[3], vv[2], sel), __byte_perm(vv[1], vv[0], sel));
    }
}
constexpr int CV_E = 4224, CV_W = 2 * 4096 + 3 * CV_E + 128, CV_HI = O_X, CV_Y = CV_HI + 4 * CV_W, CV_T = CV_Y + 16384, CV_Z = CV_T + 16384;
static_assert(4 * CV_W <= O_RED && CV_W % 128 == 0 && CV_Z + 128 <= HEAD_SMEM, "conv buffers");
__device__ __forceinline__ void conv_unit(uint32_t ub, uint32_t e0, uint32_t e1, uint32_t zrow, uint32_t tt, uint32_t Dv, int rg, int nq, int lane, uint32_t zero, uint32_t busy, int tb) {
    const int g7 = 7 - (lane >> 2), tq = lane & 3;
    SC(tb >= 0, tb + 3);
    for (int i = lane; i < 32 * nq + 8; i += 32) {
        const uint4 v = lds128(e0 + i * 16);
        const uint32_t nx = lds32(e0 + i * 16 + 16);
        sts128(e1 + i * 16, __byte_perm(v.x, v.y, 0x5432), __byte_perm(v.y, v.z, 0x5432), __byte_perm(v.z, v.w, 0x5432), __byte_perm(v.w, nx, 0x5432));
    }
    __syncwarp();
    SC(tb >= 0, tb + 4);
    float acc[4][4];
#pragma unroll
    for (int i = 0; i < 16; i++) (&acc[0][0])[i] = 0.f;
    uint32_t wb = (g7 & 1) ? e0 + (1 + g7 + 2 * tq) * 2 : e1 + (g7 + 2 * tq) * 2;
    int row = 8 * rg + (lane & 7);
    auto ldb = [&](uint4* b) {
        const uint32_t x = row < 0 ? zrow : ub + row * 128 + (((lane >> 3) ^ (row & 7)) << 4);
        b[0] = ldsm4(x); b[1] = ldsm4(x ^ 64);
        row--;
    };
    uint4 Q[16], b[2][2];
    Q[15].w = lds32(wb);
    auto ldq = [&](int q, int o) { Q[q].y = lds32(wb + o * 32 + 16); Q[q].w = lds32(wb + o * 32 + 32); };
    auto cpq = [&](int q) { Q[q].x = Q[(q + 15) & 15].w + zero; Q[q].z = Q[q].y + zero; };
#pragma unroll
    for (int q = 0; q < 11; q++) ldq(q, q);
#pragma unroll
    for (int q = 0; q < 7; q++) cpq(q);
    ldb(b[0]);
#pragma unroll 1
    for (int D0 = nq; D0 > 0; D0--) {
#pragma unroll
        for (int d = 0; d < 4; d++) {
            if (CV_YIELD && (CV_YIELD == 1 || !(d & 1))) while (lds32(busy)) __nanosleep(40);
            ldb(b[(d + 1) & 1]);
#pragma unroll
            for (int q = 11; q < 15; q++) ldq((4 * d + q) & 15, 4 * d + q);
#pragma unroll
            for (int ks = 0; ks < 4; ks++) {
                const uint4& bb_ = b[d & 1][ks >> 1];
#pragma unroll
                for (int m = 0; m < 4; m++) {
                    const uint4& a = Q[(4 * d + m + ks) & 15];
                    mmav(acc[m], a.x, a.y, a.z, a.w, (ks & 1) ? bb_.z : bb_.x, (ks & 1) ? bb_.w : bb_.y);
                }
                cpq((4 * d + 7 + ks) & 15);
            }
        }
        wb += 512;
    }
    SC(tb >= 0 && acc[0][0] != 1.2345f, tb + 5);
    const uint32_t ua = ub + (8 * rg + (lane & 7)) * 128 + (((lane >> 3) ^ (lane & 7)) << 4);
    const uint4 u0 = ldsm4t(ua), u1 = ldsm4t(ua ^ 64);
    auto y = [&](int m, int hf, uint32_t u) { return badd(pack2(acc[m][2 * hf], acc[m][2 * hf + 1]), bmul2(u, Dv)); };
    stsm4t(tt, y(0, 0, u1.w), y(0, 1, u1.z), y(1, 0, u1.y), y(1, 1, u1.x));
    stsm4t(tt ^ 64, y(2, 0, u0.w), y(2, 1, u0.z), y(3, 0, u0.y), y(3, 1, u0.x));
}
}

namespace ws {
struct HeadArgs { const bf16 *x, *mem0, *Wq, *Wk, *Wv, *Wo, *Bk, *Bv, *shiftk, *ssmk, *ssmD; bf16* out; int h_target; };

__global__ void __launch_bounds__(512, 1) head_kernel(const __grid_constant__ HeadArgs A) {
    extern __shared__ __align__(1024) unsigned char smem_raw[];
    const int tid = threadIdx.x, warp = __shfl_sync(0xffffffffu, tid >> 5, 0), lane = tid & 31;
    const int cq = blockIdx.x >> 4, r = blockIdx.x & 15;
    const int nh = cq < 4 ? 5 : 4, hi = r / 3, role = r - hi * 3;
    const bool head = r < 3 * nh;
    const int p0 = ((r >> 1) - SELF_LOCAL) & 7;
    const int h = (cq < 4 ? 5 * cq : 4 * cq + 4) + hi;
    const uint32_t sb = smem_u32(smem_raw), bb = sb + O_BAR;
    GT(tid == 0, 1);
    const int sp = cq < 4 ? cq : 4 * cq + r - 24;
    if (tid == 0) {
        if ((sb & 0xFFFFFFu) != 1024) __trap();
        for (int i = 0; i < 12; i++) mbar_init(bb + i * 8, SELF_LOCAL && head && i == 7 ? 4 : 1);
        mbar_init(bb + B_ST, role == 2 ? 1 : 5);
        mbar_init(bb + B_OB, 1); mbar_init(bb + B_OB + 64, 1);
        mbar_init(bb + B_HF, 1); mbar_init(bb + B_HF + 8, 1);
        mbar_init(bb + B_HE, 6 * nh);
        sts32(sb + O_BUSY, 0u);
        mbar_init(bb + B_OTF, head ? 4 : 8); mbar_init(bb + B_OTE, 1); mbar_init(bb + B_OTF + 8, head ? 4 : 8); mbar_init(bb + B_OTE + 16, 1);
        asm volatile("fence.mbarrier_init.release.cluster;" ::: "memory");
        mbar_expect_tx(bb + B_RED, nh * 1280);
        mbar_expect_tx(bb + B_SM, 3072); mbar_expect_tx(bb + B_ST, role == 2 ? 5120 : 4096);
        if (role != 2) { mbar_expect_tx(bb + B_OB, 2048); mbar_expect_tx(bb + B_OB + 64, 2048); }
        mbar_expect_tx(bb + B_HF, 8 * HBYTES); mbar_expect_tx(bb + B_HF + 8, 8 * HBYTES);
    }
    asm volatile("griddepcontrol.launch_dependents;");
    __syncwarp();
    cluster_arrive_relaxed();
    if (warp < 8) {
        asm volatile("setmaxnreg.inc.sync.aligned.u32 %0;" ::"n"(REG_G));
        const int wg = warp >> 2, w4 = warp & 3;
        if (head) {
            const bf16* W = (role == 2 ? A.Wv + wg * 64 : (wg ? A.Wk : A.Wq) + role * 64) + h * DH;
            const uint32_t stg = sb + O_STG + wg * 81920;
            const int t7 = tid & 127;
            if (G_DLY) delay(G_DLY);
            GT(tid == 0, 80);
#pragma unroll 1
            for (int i0 = 0; i0 < 40; i0 += WGRP) {
#pragma unroll
                for (int i = i0; i < i0 + WGRP; i++) {
                    const int row = i * 16 + (t7 >> 3), ch = t7 & 7;
                    cp_async16(stg + row * 128 + ((ch ^ (row & 7)) << 4), W + (size_t)row * HD + ch * 8);
                }
                cp_commit();
                cp_wait<WFLY>();
            }
            GT(tid == 0, 81);
        }
        if (head) {
            cluster_wait();
            GT(tid == 0, 82);
            uint32_t wa[40][4];
            cp_wait<0>();
            GT(tid == 0, 83);
            named_bar(8 + wg, 128);
            {
                const uint32_t la = sb + O_STG + wg * 81920 + ((lane & 7) + (lane >> 4) * 8) * 128 + (((w4 * 2 + ((lane >> 3) & 1)) ^ (lane & 7)) << 4);
                { const uint4 v = lds128(sb + O_STG + wg * 81920 + p0 * 10240 + (tid & 127) * 16); sts128(sb + O_AS + wg * 2048 + (tid & 127) * 16, v.x, v.y, v.z, v.w); }
#pragma unroll
                for (int j = 1; j < 40; j++) {
                    const int kk = ((p0 - j / 5) & 7) * 5 + j % 5;
                    const uint4 v = ldsm4t(la + kk * 2048);
                    wa[j][0] = v.x; wa[j][1] = v.y; wa[j][2] = v.z; wa[j][3] = v.w;
                }
            }
            named_bar(10, 384);
            GT(tid == 0, 2);
            fence_async_smem();
            named_bar(8 + wg, 128);
            cluster_arrive_relaxed();
            float acc[16];
            const uint32_t ep_q = role == 2 ? sb + O_VM + warp * 512 + (lane ^ ((lane >> 3) & 1)) * 16
                                            : sb + O_QRY + wg * 10240 + ((lane >> 1) & 1) * 5120 + (4 * (lane >> 4) + 2 * ((lane >> 2) & 1) + (lane & 1)) * 128 +
                                                  (((2 * w4 + ((lane >> 3) & 1)) ^ (4 * (lane >> 4) + 2 * ((lane >> 2) & 1) + (lane & 1)) ^ ((lane & 2) << 1)) << 4);
            const uint32_t ep_t = role == 2 ? sb + O_VT + warp * 1024 + ((lane >> 3) & 1) * 512 + (lane >> 4) * 128 + (lane & 7) * 16
                                            : sb + O_QRY + wg * 10240 + (8 + 8 * (lane >> 4) + (lane & 7)) * 128 + (((2 * w4 + ((lane >> 3) & 1)) ^ (lane & 7)) << 4);
                        const int pz = role == 2 ? P1C : P1A;
            const uint32_t ab = (1024 + O_AS + wg * 2048) >> 4;
            uint32_t ok = 1;
            const uint32_t tidk = __shfl_sync(0xffffffffu, tid, lane);
            auto token_gemm = [&](auto ll, const bool pause, const uint32_t vo, const uint32_t nbar, const uint32_t npar, const int t) {
                constexpr int l = decltype(ll)::value;
                constexpr uint32_t hb = ((1024 + O_H + l * 40960) >> 4) | (1u << 16);
                const uint32_t pr = opq(p0);
                if (l) TS(15); else TS(14);
                wg_fence();
#pragma unroll
                for (int j = 0; j < 40; j++) {
                    const uint64_t db = mkdesc(hb + ((pr - j / 5) & 7) * 320 + (j % 5) * 64, 0xC0000010u);
                    if (j == 0) wg_n32_sfirst(acc, mkdesc(ab, 0x40000040u), db);
                    else if (j < TG_STEPS) wg_n32(acc, wa[j][0], wa[j][1], wa[j][2], wa[j][3], db);
                    if (l == 0 && (j + 1 == P1A || j + 1 == P1C)) {
                        if (pause && pz == j + 1) {
                            wg_commit();
                            if (role == 2) mwait(bb + B_OTE, vo >> 14);
                            wg_wait<0>();
                            named_arrive(3, 384);
                            named_bar(4, NB4);
                            if (SKEW && wg) delay(SKEW);
                            wg_fence();
                        }
                    }
                }
                wg_commit();
                ok = mtest(nbar, npar);
                wg_wait<0>();
                uint32_t pk[8];
#pragma unroll
                for (int i = 0; i < 8; i++) pk[i] = pack2(acc[2 * i], acc[2 * i + 1]);
                if (role == 2) {
                    stsm4(ep_t + l * 8192 + vo, pk[0], pk[1], pk[2], pk[3]);
                    stsm4(ep_t + l * 8192 + vo + 256, pk[4], pk[5], pk[6], pk[7]);
                } else {
                    stsm4t((ep_t ^ (l << 6)) + l * 5120, pk[0], pk[1], pk[2], pk[3]);
                    stsm4t((ep_t ^ (l << 6)) + l * 5120 + 2048, pk[4], pk[5], pk[6], pk[7]);
                }
                asm volatile("{\n.reg .pred p, q;\nsetp.eq.u32 p, %0, 0;\nsetp.eq.u32 q, %1, 0;\n"
                             "@p mbarrier.arrive.expect_tx.shared::cta.b64 _, [%2], %3;\n@q mbarrier.arrive.shared::cluster.b64 _, [%4];\n}"
                             ::"r"(tidk), "r"(tidk & 127), "r"(bb + B_HF + l * 8), "r"(8 * HBYTES), "r"(mapa(bb + B_HE, l)) : "memory");
            };
            GT(tid == 0, 86);
            mwait(bb + B_HF, 0);
            GT(tid == 0, 87);
            token_gemm(IC<0>{}, false, 0, bb + B_MEM, 1, -1);
            GT(tid == 0, 88);
            named_bar(11, 384);
            cluster_wait();
            named_arrive(13, 384);
#pragma unroll 1
            for (int t = 0; t < NT; t++) {
                GT(tid == 0 && blockIdx.x == 98, 100 + t);
                SC(tid == 0 && blockIdx.x == 98, 160 + t);
                TS(0);
                const uint32_t mp = (t & 1) ^ 1;
                const bool tg0 = t + 1 < NSEG, tg1 = t + 1 >= LAG;
                constexpr uint32_t mb = ((1024 + O_MEM) >> 4) | (16u << 16);
#pragma unroll
                for (int G = 0; G < 8; G++) {
                    if (__builtin_expect(!ok, 0)) { if (SPIN & 8) mspin(bb + B_MEM + G * 8, mp); else mwait(bb + B_MEM + G * 8, mp); }
                    ok = mtest(G < 7 ? bb + B_MEM + (G + 1) * 8 : bb + B_HF, mp);
                    if (G == 0) { TS(1); wg_fence(); }
                    if (G == 7) TS(2);
                    if (G == 1) TS(8); if (G == 2) TS(9); if (G == 3) TS(10); if (G == 4) TS(11); if (G == 5) TS(12); if (G == 6) TS(13);
#pragma unroll
                    for (int u = 0; u < 5; u++) {
                        const int j = G * 5 + u;
                        const uint64_t db = mkdesc(mb + j * 32, 8);
                        if (j == 0) wg_n16t_sfirst(acc, mkdesc(ab, 0x40000040u), db);
                        else wg_n16t(acc, wa[j][0], wa[j][1], wa[j][2], wa[j][3], db);
                    }
                    wg_commit();
                }
                if (role == 2 && t) named_bar(5, 384);
                wg_wait<0>();
                TS(3);
                if (role == 2) sts128(ep_q, pack2(acc[0], acc[1]), pack2(acc[2], acc[3]), pack2(acc[4], acc[5]), pack2(acc[6], acc[7]));
                else stsm4t(ep_q, pack2(acc[0], acc[1]), pack2(acc[2], acc[3]), pack2(acc[4], acc[5]), pack2(acc[6], acc[7]));
                named_arrive(1, 384);
                if (tidk < 8) mbar_expect_tx(bb + B_MEM + tidk * 8, SELF_LOCAL && tidk == 7 ? 1280 : 2560);
                if (t == NT - 1) break;
                if (tg0) {
                    if (__builtin_expect(!ok, 0)) mwait(bb + B_HF, mp);
                    if (role != 2) named_bar(2, 384);
                    token_gemm(IC<0>{}, true, mp * 16384, tg1 ? bb + B_HF + 8 : bb + B_MEM, tg1 ? (t + 1 - LAG) & 1 : mp ^ 1, t);
                } else {
                    if (role == 2) mwait(bb + B_OTE, mp); else named_bar(2, 384);
                    named_arrive(3, 384); named_bar(4, NB4);
                    ok = 0;
                }
                TS(5);
                if (tg1) {
                    if (__builtin_expect(!ok, 0)) mwait(bb + B_HF + 8, (t + 1 - LAG) & 1);
                    token_gemm(IC<1>{}, false, mp * 16384, bb + B_MEM, mp ^ 1, t);
                }
                TS(6);
                named_arrive(13, 384);
            }
        } else {
            cluster_wait(); cluster_arrive_relaxed();
            const int ep = ld_relaxed(&g_epoch) + 1;
            const uint32_t cb = sb + (warp < 4 ? warp * CV_W : CV_HI + (warp - 4) * CV_W), lb = bb + B_MEM + warp * 8;
            auto fetch = [&](int k) {
                const int ps = k / 5, rg = ps ? ps - 1 : 0, ch = (sp * 5 + k - 5 * ps) * 8 + warp;
                if (k == 5 * ps) { flag_wait(FLG(F_U + ps), (ps > 1 ? 20 : (ps ? 32 : 320)) * ep, 50); fence_async_global(); }
                if (lane == 0) {
                    const uint32_t nb = ps ? ps * 1024 : 512;
                    mbar_expect_tx(lb, 2 * nb);
                    asm volatile("cp.async.bulk.shared::cluster.global.mbarrier::complete_tx::bytes [%0], [%1], %2, [%3];" ::"r"(cb + (k & 1) * 4096), "l"(g_U + ch * (S_LEN / 8)), "r"(nb), "r"(lb) : "memory");
                    asm volatile("cp.async.bulk.shared::cluster.global.mbarrier::complete_tx::bytes [%0], [%1], %2, [%3];" ::"r"(cb + 8192 + (k & 1) * CV_E + 128), "l"(A.ssmk + (size_t)ch * S_LEN), "r"(nb), "r"(lb) : "memory");
                }
                __syncwarp();
            };
            sts32(cb + 8192 + lane * 4, 0u); sts32(cb + 8192 + CV_E + lane * 4, 0u);
            if (warp == 0) sts32(sb + CV_Z + lane * 4, 0u);
            uint32_t dv = 0;
            if (lane < 5) {
                prefetch_l2(A.ssmk + (size_t)((sp * 5 + lane) * 8 + warp) * S_LEN, 1024);
                dv = *reinterpret_cast<const unsigned short*>(A.ssmD + (sp * 5 + lane) * 8 + warp) * 0x10001u;
            }
            named_bar(8, 256);
            if (!CONV_DRY) fetch(0);
#pragma unroll 1
            for (int k = CONV_DRY ? -1 : 0; k < 25; k++) {
                const int ps = k < 0 ? 0 : k / 5, rg = ps ? ps - 1 : 0;
                const uint32_t Dv = __shfl_sync(0xffffffffu, dv, k - 5 * ps);
                const int tb = sp == 0 && tid == 0 && k >= -1 && k < 7 ? 72 + k * 8 : -1;
                SC(tb >= 0, tb);
                if (k >= 0) {
                    mwait(lb, k & 1);
                    SC(tb >= 0, tb + 1);
                    if (k - 5 * ps < 4) { fence_async_smem(); fetch(k + 1); }
                    SC(tb >= 0, tb + 2);
                }
                const uint32_t tt = sb + CV_T + (k & 1) * 8192;
                conv_unit(cb + (k & 1) * 4096, cb + 8192 + (k & 1) * CV_E, cb + 8192 + 2 * CV_E + 64, sb + CV_Z,
                          tt + warp * 1024 + (lane & 7) * 128 + (((lane >> 3) ^ (lane & 7) ^ warp) & 7) * 16, Dv, rg, ps ? 2 * ps : 1, lane, (uint32_t)A.h_target >> 8, sb + O_BUSY, tb);
                if (k >= 0) mwait(bb + B_OTE + (k & 1) * 16, ((k >> 1) & 1) ^ 1);
                named_bar(8, 256);
                {
                    const uint32_t la = tt + (lane & 7) * 1024 + warp * 128 + (((lane >> 3) ^ (lane & 7) ^ warp) & 7) * 16;
                    const uint4 v0 = ldsm4t(la), v1 = ldsm4t(la ^ 64);
                    const uint32_t ya = sb + CV_Y + (k & 1) * 8192 + (warp * 64 + (lane >> 3) * 8 + 7 - (lane & 7)) * 16;
                    stsm4(ya, v0.x, v0.y, v0.z, v0.w);
                    stsm4(ya + 512, v1.x, v1.y, v1.z, v1.w);
                }
                SC(tb >= 0, tb + 6);
                fence_async_smem();
                __syncwarp();
                if (k >= 0 && lane == 0) mbar_arrive(bb + B_OTF + (k & 1) * 8);
                if (k < 0 || (k - 5 * ps == 4 && k < 24)) fetch(k + 1);
                if (k == 0 && lane < 5) prefetch_l2(A.ssmk + (size_t)((sp * 5 + lane) * 8 + warp) * S_LEN + 512, 3072);
            }
            cluster_wait();
        }
    } else if (warp < 12) {
        asm volatile("setmaxnreg.dec.sync.aligned.u32 %0;" ::"n"(REG_T));
        const int w = warp & 3, c = w >> 1, hh = w & 1;
        const uint32_t lane0 = __shfl_sync(0xffffffffu, tid & 31, tid & 31);
        if (head) {
            const int tile0 = role * 4 * WTA, ntile = role == 2 ? 4 * WTC : 4 * WTA;
            const uint32_t wo = sb + O_WO;
            uint32_t mi[5][4];
#pragma unroll
            for (int i = 0; i < 5; i++)
#pragma unroll
                for (int q = 0; q < 4; q++) {
                    const unsigned short* mp = reinterpret_cast<const unsigned short*>(A.mem0) + 2 * q * DM + i * 128 + (tid & 127);
                    mi[i][q] = mp[0] | (uint32_t)mp[DM] << 16;
                }
            cluster_wait();
            named_bar(10, 384);
#pragma unroll
            for (int i = 0; i < 5; i++) {
                const int col = i * 128 + (tid & 127), kk = col >> 4, pr = (kk * 13) >> 6;
                const uint32_t ma = sb + O_MEM + (((p0 - pr) & 7) * 5 + kk - 5 * pr) * 512 + (col & 8) * 32 + (col & 7) * 16;
                sts128(ma, mi[i][0], mi[i][0], mi[i][1], mi[i][1]);
                sts128(ma + 128, mi[i][2], mi[i][2], mi[i][3], mi[i][3]);
            }
            fence_async_smem();
            named_arrive(11, 384);
            for (int i = tid & 127; i < ntile * 256; i += 128) {
                const int ti = i >> 8, p = (i >> 1) & 127, ch = i & 1;
                const int ks = p >> 4, kh = (p >> 3) & 1, e8 = p & 7;
                const int dim = 64 * (ks >> 2) + 16 * (e8 >> 1) + 8 * (e8 & 1) + 2 * (ks & 3) + kh;
                cp_async16(wo + ti * 4096 + p * 32 + ((ch ^ ((p >> 2) & 1)) << 4), A.Wo + (size_t)(h * DH + dim) * DM + (tile0 + ti) * 16 + ch * 8);
            }
            cp_commit();
            if (lane < 8) {
                const int u = 2 * (tile0 + w + 4 * (lane >> 1)) + (lane & 1), ow = u / 5;
                const int sl = u - 5 * ow;
                sts32(sb + O_TAB + w * 32 + lane * 4, mapa(sb + O_RED + (sl >> 1) * 2560 + (sl & 1) * 256 + hi * (sl < 4 ? 512 : 256), ow & 15));
            }
            cluster_arrive_relaxed(); cluster_wait();
            cp_wait<0>();
            named_bar(7, 128);
            const uint32_t wo_a = wo + w * 4096 + ((lane >> 4) * 8 + (lane & 7)) * 32 + ((((lane >> 3) & 1) ^ ((lane >> 2) & 1)) << 4);
            const uint32_t ob_0 = sb + (role == 2 ? O_PB : O_OBA) + (lane >> 4) * 2048 + ((lane >> 3) & 1) * 128 + ((lane & 7) ^ ((lane >> 1) & 4)) * 16;
            const float cs = 0.08838834764831845f * 1.4426950408889634f;
            auto w_frag = [&](auto four, int i) {
                return ldsm4t(wo_a + (i < 16 || decltype(four)::value == 4 ? (i >> 4) * 32768 + (i & 1) * 16384 + ((i >> 1) & 7) * 512 : 32768 + (i & 1) * 2048 + ((i >> 1) & 7) * 512));
            };
            auto w_pre = [&](auto four, auto pd, uint4* wf) {
#pragma unroll
                for (int i = 0; i < decltype(pd)::value; i++) wf[i] = w_frag(four, i);
            };
            auto w_run = [&](auto four, auto pd, auto rem_, uint4* wf, int t, const uint32_t ob_a, auto&& before_last) {
                constexpr int NTL = decltype(four)::value, PD = decltype(pd)::value, NF = 8 * NTL, NP = NTL > 2 ? 2 : 1;
                constexpr bool REMOTE = decltype(rem_)::value;
                const uint32_t ln = opq(lane0), l8 = (ln & 2) * 64 + (ln >> 2) * 16 + (ln & 1) * 8, rb = (bb + B_RED) & 0xFFFFFFu;
                auto slot = [](int i) { return i < 8 ? i : 8 - WR + (i - 8) % WR; };
                uint4 obr[8];
#pragma unroll
                for (int k = 0; k < 4; k++) obr[k] = ldsm4(ob_a + k * 256);
#pragma unroll
                for (int p = 0; p < NP; p++) {
                    const bool split = p == 1 && NTL == 3;
                    const int nk = split ? 4 : 8;
                    float d[4][4];
                    uint4 ta;
#pragma unroll
                    for (int i = 0; i < 16; i++) (&d[0][0])[i] = 0.f;
#pragma unroll
                    for (int ks = 0; ks < 8; ks++) {
                        if (ks >= nk) continue;
                        if (W_SKIP == 3 || (W_SKIP == 1 && REMOTE) || (W_SKIP == 2 && !REMOTE)) { if (ks == nk - 2) ta = lds128(sb + O_TAB + w * 32 + p * 16); if (REMOTE && p == 0 && ks == OBK) mwait(bb + B_OB + 64, t & 1); continue; }
                        if (p == 0 && ks == OBK) {
                            if (REMOTE) { mwait(bb + B_OB + 64, t & 1); TS(7); }
#pragma unroll
                            for (int k = 4; k < 8; k++) obr[k] = ldsm4(ob_a + k * 256);
                        }
                        if (ks == nk - 2) ta = lds128(sb + O_TAB + w * 32 + p * 16);
#pragma unroll
                        for (int u = 0; u < 2; u++) {
                            const int i = p * 16 + ks * 2 + u;
                            const uint4& o = obr[split && u ? ks + 4 : ks];
                            const uint4& f = wf[slot(i)];
                            if (WVOL) { mmav(d[2 * u], f.x, f.y, f.z, f.w, o.x, o.y); mmav(d[2 * u + 1], f.x, f.y, f.z, f.w, o.z, o.w); }
                            else { mmau(d[2 * u], f, o.x, o.y); mmau(d[2 * u + 1], f, o.z, o.w); }
                            if (i + WR >= 8 && i + WR < NF) wf[slot(i + WR)] = w_frag(four, i + WR);
                        }
                    }
                    if (p) TS(10); else TS(8);
                    if (p == NP - 1) before_last();
                    if (split) {
#pragma unroll
                        for (int i = 0; i < 4; i++) { d[0][i] += d[2][i]; d[1][i] += d[3][i]; }
                    }
                    st_async_v2(ta.x + l8, pack2(d[0][0], d[0][1]), pack2(d[1][0], d[1][1]), (ta.x & 0xFF000000u) | rb);
                    st_async_v2(ta.y + l8, pack2(d[0][2], d[0][3]), pack2(d[1][2], d[1][3]), (ta.y & 0xFF000000u) | rb);
                    if (!split) {
                        st_async_v2(ta.z + l8, pack2(d[2][0], d[2][1]), pack2(d[3][0], d[3][1]), (ta.z & 0xFF000000u) | rb);
                        st_async_v2(ta.w + l8, pack2(d[2][2], d[2][3]), pack2(d[3][2], d[3][3]), (ta.w & 0xFF000000u) | rb);
                    }
                }
            };
            if (role != 2) {
#pragma unroll 1
                for (int t = 0; t < NT; t++) {
                    const uint32_t lane = opq(lane0);
                    const uint32_t dc = mapa(sb, hi * 3 + 2), dp = mapa(sb, hi * 3 + (role ^ 1));
                    const uint32_t qa = sb + O_QRY + c * 5120 + (lane & 7) * 128;
                    const uint32_t sw = (((lane >> 3) ^ (lane & 7)) << 4) ^ (c << 6);
                    {
                        const uint32_t ka = qa + 10240;
                        const uint32_t kt = sb + O_KEY + c * 5120 + (lane & 15) * 128, kx = (((lane >> 4) ^ (lane & 7)) << 4) ^ (c << 6);
                        const uint32_t sd = dc + O_SM + role * 1536 + c * 768 + lane * 4, sbar = dc + O_BAR + B_SM;
                        const uint32_t ta = sb + O_QRY + c * 5120 + (8 + 16 * hh + ((lane & 15) ^ (role * 8))) * 128;
                        uint4 a[4], f[4];
                        named_bar(13, 384);
#pragma unroll
                        for (int i = 0; i < 4; i++) f[i] = ldsm4(kt + 1024 + hh * 2048 + (kx ^ (i << 5) ^ (hh << 6)));
#pragma unroll
                        for (int i = 0; i < 4; i++) a[i] = ldsm4(ta + (kx ^ (i << 5)));
                        const uint32_t kd = ka + (1 + 2 * hh) * 1024 + sw;
                        uint4 k[5];
                        k[1] = ldsm4(kd); k[2] = ldsm4(kd + 1024);
                        {
                            const uint32_t qh = qa + (sw ^ (hh << 6)), kh = kt + (kx ^ (hh << 6));
                            named_bar(1, 384);
                            const uint4 q0 = ldsm4(qh), g0 = ldsm4(kh), g1 = ldsm4(kh ^ 32), q1 = ldsm4(qh ^ 64);
                            float s0[4] = {0.f, 0.f, 0.f, 0.f}, s1[4] = {0.f, 0.f, 0.f, 0.f}, s2[4] = {0.f, 0.f, 0.f, 0.f}, s3[4] = {0.f, 0.f, 0.f, 0.f};
                            mmav(s0, f[0].x, f[0].y, f[0].z, f[0].w, q0.x, q0.y); mmav(s1, f[1].x, f[1].y, f[1].z, f[1].w, q0.z, q0.w);
                            mmav(s2, g0.x, g0.y, g0.z, g0.w, q0.x, q0.y); mmav(s3, g1.x, g1.y, g1.z, g1.w, q0.z, q0.w);
                            mmav(s0, f[2].x, f[2].y, f[2].z, f[2].w, q1.x, q1.y); mmav(s1, f[3].x, f[3].y, f[3].z, f[3].w, q1.z, q1.w);
                            k[0] = ldsm4(ka + sw); k[3] = ldsm4(ka + 1024 + sw); k[4] = ldsm4(ka + 2048 + sw);
                            st_async_b32(sd + hh * 128, pack2(s2[0] + s3[0], s2[1] + s3[1]), sbar);
                            st_async_b32(sd + 256 + hh * 256, pack2(s0[0] + s1[0], s0[1] + s1[1]), sbar);
                            st_async_b32(sd + 384 + hh * 256, pack2(s0[2] + s1[2], s0[3] + s1[3]), sbar);
                        }
                        TS(1);
                        float u[5][4];
#pragma unroll
                        for (int i = 0; i < 20; i++) (&u[0][0])[i] = 0.f;
                        auto half = [&](auto nn, const uint4& a0, const uint4& a1, bool more) {
                            constexpr int NU = decltype(nn)::value;
                            constexpr int ord[5] = {1, 2, 0, 3, 4};
#pragma unroll
                            for (int i = 0; i < NU; i++) mmav(u[ord[i]], a0.x, a0.y, a0.z, a0.w, k[ord[i]].x, k[ord[i]].y);
#pragma unroll
                            for (int i = 0; i < NU; i++) {
                                const int n = ord[i];
                                mmav(u[n], a1.x, a1.y, a1.z, a1.w, k[n].z, k[n].w);
                                if (more) k[n] = ldsm4(((n == 0 ? ka + sw : (n < 3 ? kd + (n - 1) * 1024 : ka + (n - 2) * 1024 + sw))) ^ 64);
                            }
                        };
                        auto fu = [](float x) { return __float_as_uint(x); };
                        const uint32_t so = O_ST + c * 2048 + hh * 768, td = dp + so, tb = dp + O_BAR + B_ST, lo = sb + so + 4096;
                        if (hh) {
                            half(IC<5>{}, a[0], a[1], true); half(IC<5>{}, a[2], a[3], false);
                            st_async_v4(td + lane * 16, fu(u[0][2]), fu(u[0][3]), fu(u[1][2]), fu(u[1][3]), tb);
                            st_async_v4(td + 512 + lane * 16, fu(u[2][2]), fu(u[2][3]), fu(u[3][2]), fu(u[3][3]), tb);
                            st_async_v2(td + 1024 + lane * 8, fu(u[4][2]), fu(u[4][3]), tb);
                            sts128(lo + lane * 16, fu(u[0][0]), fu(u[0][1]), fu(u[1][0]), fu(u[1][1]));
                            sts128(lo + 512 + lane * 16, fu(u[2][0]), fu(u[2][1]), fu(u[3][0]), fu(u[3][1]));
                            sts64(lo + 1024 + lane * 8, fu(u[4][0]), fu(u[4][1]));
                        } else {
                            half(IC<3>{}, a[0], a[1], true); half(IC<3>{}, a[2], a[3], false);
                            st_async_v4(td + lane * 16, fu(u[0][2]), fu(u[0][3]), fu(u[1][2]), fu(u[1][3]), tb);
                            st_async_v2(td + 512 + lane * 8, fu(u[2][2]), fu(u[2][3]), tb);
                            sts128(lo + lane * 16, fu(u[0][0]), fu(u[0][1]), fu(u[1][0]), fu(u[1][1]));
                            sts64(lo + 512 + lane * 8, fu(u[2][0]), fu(u[2][1]));
                        }
                        if (t < NT - 1) named_arrive(2, 384);
                        __syncwarp();
                        if (lane == 0) mbar_arrive(bb + B_ST);
                        TS(2);
                    }
                    if (t == NT - 1) break;
                    uint4 wf[PDA];
                    w_pre(IC<WTA>{}, IC<PDA>{}, wf);
                    if (SPIN & 2) mspin(bb + B_OB, t & 1); else mwait(bb + B_OB, t & 1);
                    TS(3);
                    named_bar(3, 384);
                    w_run(IC<WTA>{}, IC<PDA>{}, IC<1>{}, wf, t, ob_0, []() {});
                    named_arrive(4, NB4);
                    if (w == 0 && lane == 0) { mbar_expect_tx(bb + B_OB, 2048); mbar_expect_tx(bb + B_OB + 64, 2048); }
                    TS(5);
                }
            } else {
#pragma unroll 1
                for (int t = 0; t < NT; t++) {
                    const uint32_t lane = opq(lane0);
                    const int g = lane >> 2, tq = lane & 3;
                    const uint32_t vm_a = sb + O_VM + (g * 4 + 2 * (tq & 1) + (c ^ ((g >> 1) & 1))) * 16 + (tq >> 1) * 8;
                    const uint32_t vt_a = sb + O_VT + (t & 1) * 16384 + ((lane >> 3) & 1) * 512 + (lane >> 4) * 128 + (lane & 7) * 16;
                    named_bar(13, 384);
                    uint4 va[4][2];
#pragma unroll
                    for (int i = 0; i < 4; i++) {
                        va[i][0] = ldsm4(vt_a + c * 8192 + (4 * hh + i) * 1024);
                        va[i][1] = ldsm4(vt_a + c * 8192 + (4 * hh + i) * 1024 + 256);
                    }
                    const uint32_t sa = opq(sb + O_SM + c * 768 + 256 + lane * 16), sa2 = opq(sb + O_SM + c * 768 + (lane & 15) * 16 + (lane >> 4) * 1536), vm_b = opq(vm_a + hh * 2048);
                    named_bar(1, 384);
                    if (__builtin_expect(t < NT - 1, 1)) {
                        uint2 vm[4];
#pragma unroll
                        for (int i = 0; i < 4; i++) vm[i] = lds64(vm_b + i * 512);
                        if (SPIN & 1) mspin(bb + B_SM, t & 1); else mwait(bb + B_SM, t & 1);
                        TS(1);
                        const uint4 x0 = ldsm4t(sa), y0 = ldsm4t(sa + 1536), x1 = ldsm4t(sa2);
                        float s[10];
                        s[2] = blo(x0.x) + blo(y0.x); s[3] = bhi(x0.x) + bhi(y0.x); s[4] = blo(x0.y) + blo(y0.y); s[5] = bhi(x0.y) + bhi(y0.y);
                        s[6] = blo(x0.z) + blo(y0.z); s[7] = bhi(x0.z) + bhi(y0.z); s[8] = blo(x0.w) + blo(y0.w); s[9] = bhi(x0.w) + bhi(y0.w);
                        s[0] = (blo(x1.x) + blo(x1.y)) + (blo(x1.z) + blo(x1.w)); s[1] = (bhi(x1.x) + bhi(x1.y)) + (bhi(x1.z) + bhi(x1.w));
                        float mx = fmaxf(fmaxf(fmaxf(s[0], s[1]), fmaxf(s[2], s[3])), fmaxf(fmaxf(fmaxf(s[4], s[5]), fmaxf(s[6], s[7])), fmaxf(s[8], s[9])));
                        const float m1 = __shfl_xor_sync(0xffffffffu, mx, 1), m2 = __shfl_xor_sync(0xffffffffu, mx, 2), m3 = __shfl_xor_sync(0xffffffffu, mx, 3);
                        mx = fmaxf(fmaxf(mx, m1), fmaxf(m2, m3)) * -cs;
                        uint32_t pb[5];
#pragma unroll
                        for (int i = 0; i < 5; i++) pb[i] = pack2(ex2f(fmaf(s[2 * i], cs, mx)), ex2f(fmaf(s[2 * i + 1], cs, mx)));
                        TS(9);
                        named_bar(3, 384);
                        float o[5][4];
#pragma unroll
                        for (int i = 0; i < 20; i++) (&o[0][0])[i] = 0.f;
                        const uint32_t one2 = 0x3F803F80u;
                        float z[2][4] = {{0.f, 0.f, 0.f, 0.f}, {0.f, 0.f, 0.f, 0.f}};
                        mmav8(o[4], one2, one2, pb[0]);
                        mmav(z[0], one2, one2, one2, one2, pb[1], pb[2]);
                        mmav(z[1], one2, one2, one2, one2, pb[3], pb[4]);
#pragma unroll
                        for (int i = 0; i < 4; i++) mmav8(o[i], vm[i].x, vm[i].y, pb[0]);
#pragma unroll
                        for (int i = 0; i < 4; i++) mmav(o[i], va[i][0].x, va[i][0].y, va[i][0].z, va[i][0].w, pb[1], pb[2]);
#pragma unroll
                        for (int i = 0; i < 4; i++) mmav(o[i], va[i][1].x, va[i][1].y, va[i][1].z, va[i][1].w, pb[3], pb[4]);
                        o[4][0] += z[0][0] + z[1][0]; o[4][1] += z[0][1] + z[1][1];
                        uint4 wf[PDC];
                        w_pre(IC<WTC>{}, IC<PDC>{}, wf);
                        const float r0 = rcpf(o[4][0]), r1 = rcpf(o[4][1]);
                        const uint32_t oo = c * 2048 + hh * 1024 + g * 128 + tq * 16 + (g & 1) * 64;
                        uint32_t e0[4], e1[4];
#pragma unroll
                        for (int i = 0; i < 4; i++) { e0[i] = pack2(o[i][0] * r0, o[i][2] * r0); e1[i] = pack2(o[i][1] * r1, o[i][3] * r1); }
                        sts128(sb + O_PB + (~t & 1) * 5120 + oo, e0[0], e0[1], e0[2], e0[3]);
                        sts128(sb + O_PB + (~t & 1) * 5120 + (oo ^ 64), e1[0], e1[1], e1[2], e1[3]);
                        {
                            const uint32_t da = mapa(sb + O_OBA, r - 2) + oo, ba = mapa(bb + B_OB + hh * 64, r - 2);
                            if (O_DLY) { named_bar(7, 128); if (hh) delay(O_DLY); }
                            st_async_v4(da, e0[0], e0[1], e0[2], e0[3], ba);
                            st_async_v4(da + 0x01000000u, e0[0], e0[1], e0[2], e0[3], ba + 0x01000000u);
                            st_async_v4(da ^ 64, e1[0], e1[1], e1[2], e1[3], ba);
                            st_async_v4((da ^ 64) + 0x01000000u, e1[0], e1[1], e1[2], e1[3], ba + 0x01000000u);
                        }
                        TS(3);
                        if (!O_DLY) named_bar(7, 128);
                        w_run(IC<WTC>{}, IC<PDC>{}, IC<0>{}, wf, t, ob_0 + (~t & 1) * 5120, []() {});
                        named_arrive(4, NB4);
                        mwait(bb + B_ST, t & 1);
                        TS(4);
                    } else { mwait(bb + B_SM, t & 1); mwait(bb + B_ST, t & 1); }
                    TS(5);
                    fence_async_smem();
                    if (TPV_LATE && t < NT - 1) named_bar(6, 224);
#pragma unroll 1
                    for (int l = t < NSEG ? 0 : 1; l < (t >= LAG ? 2 : 1); l++) {
                        const uint32_t pb_ = ((1024 + O_PB) >> 4) + (t & 1) * 320 + l * 160, va_ = (((1024 + O_VT) >> 4) + (t & 1) * 1024 + l * 512) | (8u << 16);
                        const uint32_t oa = sb + O_VT + (t & 1) * 16384 + l * 8192 + w * 1024 + g * 64 + ((tq ^ (g >> 1)) & 3) * 16;
                        const uint32_t vl = (vm_a ^ ((l ^ c) << 4)) + w * 512;
                        const uint2 a0 = lds64(vl), a1 = lds64(vl + 2048);
                        float d[2][16];
                        wg_fence();
                        wg_n32_first(d[0], a0.x, a0.y, 0u, 0u, mkdesc(pb_, 8));
                        wg_n32_first(d[1], a1.x, a1.y, 0u, 0u, mkdesc(pb_, 8));
#pragma unroll
                        for (int i = 0; i < 4; i++) wg_n32_kk(d[i & 1], mkdesc(va_ + (i & 1) * 256 + (i >> 1) * 16, 32), mkdesc(pb_ + 32 + (i >> 1) * 64 + (32u << 16), 8));
                        wg_commit();
                        if (l) TS(13); else TS(11);
                        wg_wait<0>();
                        if (l) TS(14); else TS(12);
                        if (O0_EARLY == 2 && l == (t < NSEG ? 0 : 1)) {
                            uint4* og = g_ot + (rslot(l, t - l * LAG) * 256 + h * 8 + w) * 64 + g * 4 + ((tq ^ (g >> 1)) & 3);
#pragma unroll
                            for (int mt = 0; mt < 2; mt++) {
                                og[mt * 256] = make_uint4(pack2(d[mt][0], d[mt][1]), pack2(d[mt][4], d[mt][5]), pack2(d[mt][8], d[mt][9]), pack2(d[mt][12], d[mt][13]));
                                og[mt * 256 + 32] = make_uint4(pack2(d[mt][2], d[mt][3]), pack2(d[mt][6], d[mt][7]), pack2(d[mt][10], d[mt][11]), pack2(d[mt][14], d[mt][15]));
                            }
                            __syncwarp();
                            if (lane == 0) mbar_arrive(bb + B_OTF + 8);
                            continue;
                        }
#pragma unroll
                        for (int mt = 0; mt < 2; mt++) {
                            sts128(oa + mt * 4096, pack2(d[mt][0], d[mt][1]), pack2(d[mt][4], d[mt][5]), pack2(d[mt][8], d[mt][9]), pack2(d[mt][12], d[mt][13]));
                            sts128(oa + mt * 4096 + 512, pack2(d[mt][2], d[mt][3]), pack2(d[mt][6], d[mt][7]), pack2(d[mt][10], d[mt][11]), pack2(d[mt][14], d[mt][15]));
                        }
                        if (O0_EARLY == 1 && l == 0) {
                            fence_async_smem();
                            __syncwarp();
                            if (lane == 0) mbar_arrive(bb + B_OTF + 8);
                        }
                    }
                    TS(6);
                    if (w == 0 && lane == 0) { mbar_expect_tx(bb + B_ST, 5120); mbar_expect_tx(bb + B_SM, 3072); }
                    fence_async_smem();
                    __syncwarp();
                    if (lane == 0) mbar_arrive(bb + B_OTF);
                    if (t < NT - 1) named_arrive(5, 384);
                }
            }
        } else {
            cluster_wait(); cluster_arrive_relaxed();
            const int wi = sp * 4 + w, half = wi >> 5, tok = wi & 31, ep = ld_relaxed(&g_epoch) + 1;
            GT(lane == 0, 89);
            if (lane < LN0_AHEAD / 2) prefetch_l2(A.x + (size_t)((half + 2 * lane) * SEG + tok) * DM, 1280);
#pragma unroll 1
            for (int k = -LN0_AHEAD / 2; k < NT; k++) {
                const int s0 = k < 0 ? 2 * k + LN0_AHEAD + half : (half ? k + LN0_AHEAD : NSEG);
                if (s0 < NSEG) { ln0_row(A.x, s0, tok, lane); GT(lane == 0 && k < 0, 30 + s0); }
                if (k == -1 && half) {
#pragma unroll 1
                    for (int u = 320 + tok; u < 640; u += 32) u_half(A.Bk, A.Bv, A.shiftk, u, lane);
                    __syncwarp();
                    if (lane == 0) red_release(FLG(F_U + 1), 1);
                }
                const int n = k - half * LAG;
                if ((POST_DRY && k == -LN0_AHEAD / 2 + 1) || (n >= 0 && n < NSEG && k >= 0)) {
                    post_row(half, k < 0 ? 0 : n, tok, lane, A.x, A.out, k < 0 ? 0 : ep);
                    GT(lane == 0 && (n & 3) == 0 && k >= 0, 460 + half * 16 + (n >> 2)); GT(lane == 0 && n == 63 && half, 40);
                }
            }
            cluster_wait();
        }
    } else {
        asm volatile("setmaxnreg.dec.sync.aligned.u32 %0;" ::"n"(REG_X));
        cluster_wait();
        const int s = warp - 12;
        const uint32_t lane0 = __shfl_sync(0xffffffffu, tid & 31, tid & 31);
        if (s < 3) {
            cluster_arrive_relaxed();
            GT(lane == 0, 84);
            if (blockIdx.x * 3 + s < 320) {
                u_half(A.Bk, A.Bv, A.shiftk, blockIdx.x * 3 + s, lane);
                GT(lane == 0, 85);
                __syncwarp();
                if (lane == 0) red_release(FLG(F_U), 1);
                GT(lane == 0, 4);
            }
            const int ztgt = 3 * 16 * NCL * (ld_relaxed(&g_epoch) + 1);
#pragma unroll
            for (int i = 0; i < XRS; i++) st_relaxed_v4(g_xc + ((i * 16 + r) * 3 + s) * 256 + cq * 32 + lane, 0, 0, 0, 0);
            __syncwarp();
            if (lane == 0) red_release(FLG(F_Z), 1);
            cluster_wait();
            constexpr uint32_t XSLOT = 16 * 3 * 4096;
            uint32_t xo_ = (r * 3 + s) * 4096;
            if (s == 0) {
                const uint32_t G = lane >> 1, d = ((r + 2 * (G + SELF_LOCAL)) & 15) ^ (lane & 1);
                if (lane < 16) { sts32(sb + O_BT + lane * 8, (d << 24) + G * 2560); sts32(sb + O_BT + lane * 8 + 4, d < 3 * nh && !(SELF_LOCAL && d == r) ? mapa(bb + B_MEM + G * 8, d) : 0u); }
            }
            while (ld_acquire(FLG(F_Z)) < ztgt) __nanosleep(100);
            named_bar(14, 96);
#pragma unroll 1
            for (int t = 0; t < NT; t++) {
                const uint32_t lane = opq(lane0);
                if (head && role != 2) {
                    auto soft = [&](auto uu, auto vv, int c0, int hh) {
                        constexpr int U = decltype(uu)::value, NV = decltype(vv)::value;
                        const uint32_t dc = mapa(sb, hi * 3 + 2), sa = sb + O_ST + c0 * 2048 + hh * 768;
                        const uint32_t pd = dc + O_PB + (t & 1) * 5120 + c0 * 2560 + (2 * hh + role) * 128 + lane * 4, pbar = dc + O_BAR + B_ST;
                        const int lim = 8 * role + (int)(lane >> 2) - 2 * (int)(lane & 3);
                        auto uf = [](uint32_t x) { return __uint_as_float(x); };
                        mwait(bb + B_ST, t & 1);
                        if (H1_LATE == 2 && r == 1 && U == 2 && t >= LAG - 1 && t < NT - 1) named_arrive(12, 64);
                        uint32_t z[U][NV];
                        auto zz = [](float x, float y) { const uint32_t w = pack2(x, y); return pack2(blo(w) * 0.08838834764831845f, bhi(w) * 0.08838834764831845f); };
#pragma unroll
                        for (int i = 0; i < U; i++) {
                            const uint4 v = lds128(sa + i * 2048 + lane * 16), w = lds128(sa + i * 2048 + 4096 + lane * 16);
                            z[i][0] = zz(uf(v.x) + uf(w.x), uf(v.y) + uf(w.y));
                            z[i][1] = zz(lim < 0 ? -INFINITY : uf(v.z) + uf(w.z), lim < 1 ? -INFINITY : uf(v.w) + uf(w.w));
                            if (NV == 3) {
                                const uint2 x = lds64(sa + i * 2048 + 512 + lane * 8), y = lds64(sa + i * 2048 + 4608 + lane * 8);
                                z[i][2] = zz(lim < 8 ? -INFINITY : uf(x.x) + uf(y.x), lim < 9 ? -INFINITY : uf(x.y) + uf(y.y));
                            } else {
                                const uint4 x = lds128(sa + 512 + lane * 16), y = lds128(sa + 4608 + lane * 16);
                                const uint2 p = lds64(sa + 1024 + lane * 8), q = lds64(sa + 5120 + lane * 8);
                                z[i][2] = zz(lim < 8 ? -INFINITY : uf(x.x) + uf(y.x), lim < 9 ? -INFINITY : uf(x.y) + uf(y.y));
                                z[i][NV - 2] = zz(uf(x.z) + uf(y.z), uf(x.w) + uf(y.w));
                                z[i][NV - 1] = zz(uf(p.x) + uf(q.x), uf(p.y) + uf(q.y));
                            }
                        }
                        const float l2e = 1.4426950408889634f;
                        float e[U][2 * NV], sum[U];
#pragma unroll
                        for (int i = 0; i < U; i++) {
                            uint32_t zm = bmax2(bmax2(z[i][0], z[i][1]), z[i][2]);
                            if (NV == 5) zm = bmax2(zm, bmax2(z[i][NV - 2], z[i][NV - 1]));
                            zm = bmax2(zm, __shfl_xor_sync(0xffffffffu, zm, 1));
                            zm = bmax2(zm, __shfl_xor_sync(0xffffffffu, zm, 2));
                            const float mx = fmaxf(blo(zm), bhi(zm)) * -l2e;
                            sum[i] = 0.f;
#pragma unroll
                            for (int n = 0; n < NV; n++) { e[i][2 * n] = ex2f(fmaf(blo(z[i][n]), l2e, mx)); e[i][2 * n + 1] = ex2f(fmaf(bhi(z[i][n]), l2e, mx)); }
                            sum[i] = ((e[i][0] + e[i][1]) + (e[i][2] + e[i][3])) + (e[i][4] + e[i][5]);
                            if (NV == 5) sum[i] += (e[i][2 * NV - 4] + e[i][2 * NV - 3]) + (e[i][2 * NV - 2] + e[i][2 * NV - 1]);
                            sum[i] += __shfl_xor_sync(0xffffffffu, sum[i], 1);
                            sum[i] += __shfl_xor_sync(0xffffffffu, sum[i], 2);
                            sum[i] = rcpf(sum[i]);
                        }
#pragma unroll
                        for (int i = 0; i < U; i++)
#pragma unroll
                            for (int n = 0; n < 5; n++)
                                st_async_b32(pd + i * 2560 + (n == 0 ? 0 : (NV == 3 ? n : (n < 3 ? n + 2 : n - 2)) * 512), n < NV ? pack2(e[i][2 * n] * sum[i], e[i][2 * n + 1] * sum[i]) : 0u, pbar);
                    };
                    if (s < 2) soft(IC<1>{}, IC<5>{}, s, 1); else soft(IC<2>{}, IC<3>{}, 0, 0);
                    TS(12);
                    named_bar(14, 96);
                    if (s == 0 && lane == 0) mbar_expect_tx(bb + B_ST, 4096);
                    if (H1_LATE == 1 && r == 1 && s == 0 && t >= LAG - 1 && t < NT - 1) named_arrive(12, 64);
                }
                if (t == NT - 1) break;
                uint32_t m0 = 0x80008000u, m1 = 0x80008000u;
                if (t < LAG && cq == 0) {
                    const uint32_t ch = s < 2 ? lane : lane >> 1;
                    const unsigned short* mp = reinterpret_cast<const unsigned short*>(A.mem0) + (((ch >> 3) & 1) * 4 + (s < 2 ? 0 : (lane & 1) * 2)) * DM + (5 * r + 2 * s + (ch >> 4)) * 8 + (ch & 7);
                    m0 = max(mp[0] | (uint32_t)mp[DM] << 16, 1u);
                    if (s < 2) m1 = max(mp[2 * DM] | (uint32_t)mp[3 * DM] << 16, 1u);
                }
                const bool late = t >= LAG;
                auto sum5 = [](uint32_t a, uint32_t b, uint32_t c, uint32_t d, uint32_t e) { return nz(badd(badd(badd(a, b), e), badd(c, d))); };
                auto sum7 = [](uint32_t a, uint32_t b, uint32_t c, uint32_t d, uint32_t e, uint32_t f, uint32_t h_) {
                    return badd(badd(badd(a, b), badd(c, d)), badd(badd(e, f), h_));
                };
                auto min3 = [](uint32_t a, uint32_t b, uint32_t c) { return min(min(a, b), c); };
                auto bcast = [&](auto two, const uint32_t aa, uint32_t x0, uint32_t x1, uint32_t x2, uint32_t x3) {
                    auto send = [&](uint32_t o, uint32_t bar) { if (decltype(two)::value) st_async_v4p(aa + o, x0, x1, x2, x3, bar); else st_async_v2p(aa + o, x0, x1, bar); };
                    uint4 e[5];
                    e[0] = lds128(sb + O_BT);
                    TS(8);
                    send(e[0].x, e[0].y); send(e[0].z, e[0].w);
                    TS(9);
#pragma unroll
                    for (int i = 1; i < 5; i++) e[i] = lds128(sb + O_BT + i * 16);
#pragma unroll
                    for (int i = 1; i < 8; i++) {
                        send(e[(i - 1) % 4 + 1].x, e[(i - 1) % 4 + 1].y); send(e[(i - 1) % 4 + 1].z, e[(i - 1) % 4 + 1].w);
                        if (i < 4) e[i] = lds128(sb + O_BT + (i + 4) * 16);
                    }
                    if (SELF_LOCAL && head) {
                        const uint32_t la = aa + (sb & 0xFF000000u) + 7 * 2560;
                        if (decltype(two)::value) sts128(la, x0, x1, x2, x3); else sts64(la, x0, x1);
                        fence_async_smem();
                        __syncwarp();
                        if (lane == 0) mbar_arrive(bb + B_MEM + 56);
                    }
                };
                const uint32_t ma = (sb + O_MEM + (5 * (r & 1) + 2 * s) * 256) & 0xFFFFFFu;
                int guard = 0;
                if (s < 2) {
                    const uint32_t ra = sb + O_RED + s * 2560 + lane * 16;
                    uint4* xb = reinterpret_cast<uint4*>(reinterpret_cast<char*>(g_xc) + xo_ + lane * 16);
                    uint4* xo = xb + cq * 32;
                    touch(xo); touch(xb);
                    if (SPIN & 4) mspin(bb + B_RED, t & 1); else mwait(bb + B_RED, t & 1);
                    TS(0);
                    uint4 p[5];
#pragma unroll
                    for (int i = 0; i < 5; i++) p[i] = i < 4 || nh == 5 ? lds128(ra + i * 512) : make_uint4(0, 0, 0, 0);
                    const uint32_t u1 = sum5(p[0].y, p[1].y, p[2].y, p[3].y, p[4].y), u3 = sum5(p[0].w, p[1].w, p[2].w, p[3].w, p[4].w);
                    st_relaxed_v4(xo, sum5(p[0].x, p[1].x, p[2].x, p[3].x, p[4].x), late ? u1 : m0, sum5(p[0].z, p[1].z, p[2].z, p[3].z, p[4].z), late ? u3 : m1);
                    TS(1);
                    if (QUIET && head) named_arrive(4, NB4);
                    delay(XD);
                    if (CV_YIELD && !head && s == 0) sts32(sb + O_BUSY, 1u);
                    uint4 x[NCL];
                    while (true) {
                        ld7_relaxed(x, xb);
                        const uint32_t mn = min3(min3(min3(x[0].x, x[0].y, x[0].z), min3(x[0].w, x[1].x, x[1].y), min3(x[1].z, x[1].w, x[2].x)),
                                                 min3(min3(x[2].y, x[2].z, x[2].w), min3(x[3].x, x[3].y, x[3].z), min3(x[3].w, x[4].x, x[4].y)),
                                                 min3(min3(x[4].z, x[4].w, x[5].x), min3(x[5].y, x[5].z, x[5].w), min(min3(x[6].x, x[6].y, x[6].z), x[6].w)));
                        if (NO_X || __all_sync(0xffffffffu, mn != 0)) break;
                        if (++guard > 2000000) __trap();
                    }
                    TS(2);
                    TV(4, guard);
                    bcast(IC<1>{}, ma + lane * 16, sum7(x[0].x, x[1].x, x[2].x, x[3].x, x[4].x, x[5].x, x[6].x), sum7(x[0].y, x[1].y, x[2].y, x[3].y, x[4].y, x[5].y, x[6].y),
                          sum7(x[0].z, x[1].z, x[2].z, x[3].z, x[4].z, x[5].z, x[6].z), sum7(x[0].w, x[1].w, x[2].w, x[3].w, x[4].w, x[5].w, x[6].w));
                } else {
                    const uint32_t ra = sb + O_RED + 5120 + lane * 8;
                    uint2* xb = reinterpret_cast<uint2*>(reinterpret_cast<char*>(g_xc) + xo_ + lane * 8);
                    uint2* xo = xb + cq * 64;
                    touch(xo); touch(xb);
                    if (SPIN & 4) mspin(bb + B_RED, t & 1); else mwait(bb + B_RED, t & 1);
                    TS(0);
                    uint2 p[5];
#pragma unroll
                    for (int i = 0; i < 5; i++) p[i] = i < 4 || nh == 5 ? lds64(ra + i * 256) : make_uint2(0, 0);
                    const uint32_t u1 = sum5(p[0].y, p[1].y, p[2].y, p[3].y, p[4].y);
                    st_relaxed_v2(xo, sum5(p[0].x, p[1].x, p[2].x, p[3].x, p[4].x), late ? u1 : m0);
                    if (lane == 0) mbar_expect_tx(bb + B_RED, nh * 1280);
                    TS(1);
                    if (QUIET && head) named_arrive(4, NB4);
                    delay(XD);
                    uint32_t y0, y1;
                    while (true) {
                        uint2 x[NCL];
                        ld7_relaxed(x, xb);
                        const uint32_t mn = min3(min3(min3(x[0].x, x[0].y, x[1].x), min3(x[1].y, x[2].x, x[2].y), min3(x[3].x, x[3].y, x[4].x)), min3(x[4].y, x[5].x, x[5].y), min(x[6].x, x[6].y));
                        y0 = sum7(x[0].x, x[1].x, x[2].x, x[3].x, x[4].x, x[5].x, x[6].x); y1 = sum7(x[0].y, x[1].y, x[2].y, x[3].y, x[4].y, x[5].y, x[6].y);
                        if (NO_X || __all_sync(0xffffffffu, mn != 0)) break;
                        if (++guard > 2000000) __trap();
                    }
                    TS(2);
                    TV(4, guard);
                    bcast(IC<0>{}, ma + lane * 8, y0, y1, 0u, 0u);
                }
                TS(3);
                if (CV_YIELD && !head) { named_bar(14, 96); if (s == 0) sts32(sb + O_BUSY, 0u); }
                if ((OT_LATE || TPV_LATE) && head && role == 2) named_arrive(6, TPV_LATE ? 224 : 128);
                xo_ += XSLOT; if (xo_ >= XRS * XSLOT) xo_ -= XRS * XSLOT;
                {
                    const uint32_t zo = xo_ + XSLOT >= XRS * XSLOT ? xo_ + XSLOT - XRS * XSLOT : xo_ + XSLOT;
                    char* zp = reinterpret_cast<char*>(g_xc) + zo + cq * 512 + lane * 16;
                    st_relaxed_v4(zp, 0, 0, 0, 0);
                    if (ld_relaxed_v4(zp).x) __trap();
                }
            }
        } else if (r < 2) {
            const uint16_t mask = (uint16_t)((1u << (3 * nh)) - 1u);
            const int htgt = A.h_target * (ld_relaxed(&g_epoch) + 1);
#pragma unroll 1
            for (int n = 0; n < NSEG; n++) {
                if (n == (r == 0 ? 1 : 0)) { cluster_arrive(); cluster_wait(); }
                int guard = 0;
                while (ld_acquire(FLG(F_H + r * 64 + n)) < htgt) { if (++guard > 2000000) __trap(); __nanosleep(H_NS); }
                fence_async_global();
                if (H1_LATE && r == 1) named_bar(12, 64);
                if (n) mwait(bb + B_HE, (n - 1) & 1);
                if (lane < 8)
                    asm volatile("cp.async.bulk.shared::cluster.global.mbarrier::complete_tx::bytes.multicast::cluster [%0], [%1], %2, [%3], %4;" ::"r"(sb + O_H + r * 40960 + lane * 5120),
                                 "l"(g_ht + rslot(r, n) * 2560 + lane * 320), "r"(HBYTES), "r"(bb + B_HF + r * 8), "h"(mask) : "memory");
                __syncwarp();
            }
        } else {
            cluster_arrive(); cluster_wait();
            if (head && role == 2) {
#pragma unroll 1
                for (int t = 0; t < NT; t++) {
                    auto put = [&](int l, int n) {
                        asm volatile("cp.async.bulk.global.shared::cta.bulk_group [%0], [%1], %2;" ::"l"(g_ot + (rslot(l, n) * 256 + h * 8) * 64), "r"(sb + O_VT + (t & 1) * 16384 + l * 8192), "r"(8192) : "memory");
                        asm volatile("cp.async.bulk.commit_group;" ::: "memory");
                    };
                    auto publish = [&](int l, int n) {
                        asm volatile("cp.async.bulk.wait_group 0;" ::: "memory");
                        fence_async_global();
                        red_release(FLG(F_O + l * 64 + n) + (h >> 3), 1);
                        GT(true, 200 + l * 64 + n);
                    };
                    if (O0_EARLY == 2) {
                        const int l = t < NSEG ? 0 : 1;
                        mwait(bb + B_OTF + 8, t & 1);
                        if (lane == 0) { red_release(FLG(F_O + l * 64 + t - l * LAG) + (h >> 3), 1); GT(true, 200 + l * 64 + t - l * LAG); }
                        __syncwarp();
                    }
                    if (O0_EARLY == 1 && t < NSEG) {
                        mwait(bb + B_OTF + 8, t & 1);
                        if (lane == 0) { put(0, t); publish(0, t); }
                        __syncwarp();
                    }
                    mwait(bb + B_OTF, t & 1);
                    if (OT_LATE && !TPV_LATE && t < NT - 1) named_bar(6, 128);
                    const int l = lane & 1, n = t - l * LAG;
                    const bool mine = lane < 2 && n >= 0 && n < NSEG && (l || !O0_EARLY) && (O0_EARLY < 2 || t < NSEG);
                    if (mine) {
                        put(l, n);
                        asm volatile("cp.async.bulk.wait_group.read 0;" ::: "memory");
                    }
                    __syncwarp();
                    if (lane == 0) mbar_arrive(bb + B_OTE);
                    if (mine) publish(l, n);
                    __syncwarp();
                }
            }
            if (!head && lane == 0) {
#pragma unroll 1
                for (int k = 0; k < 25; k++) {
                    const int rg = k / 5, r0 = rg == 1 ? 256 : 0;
                    mwait(bb + B_OTF + (k & 1) * 8, (k >> 1) & 1);
                    asm volatile("cp.async.bulk.global.shared::cta.bulk_group [%0], [%1], %2;" ::"l"(g_Y + (sp * 5 + k - 5 * rg) * S_LEN + (rg ? rg - 1 : 0) * 512 + r0),
                                 "r"(sb + CV_Y + (k & 1) * 8192 + r0 * 16), "r"(rg < 2 ? 4096 : 8192) : "memory");
                    asm volatile("cp.async.bulk.commit_group;" ::: "memory");
                    asm volatile("cp.async.bulk.wait_group 0;" ::: "memory");
                    mbar_arrive(bb + B_OTE + (k & 1) * 16);
                    fence_async_global();
                    red_release(FLG(F_CV + rg), 1);
                    GT(true, 50 + k);
                }
            }
            __syncwarp();
        }
    }
    cluster_arrive(); cluster_wait();
    if (blockIdx.x == 0 && tid == 0) atomicAdd(&g_epoch, 1);
}
}

namespace ws {
constexpr int OP_SS = 17;
constexpr int P_RING = 0, P_AS = 131072, P_STG = P_AS + 2 * OP_SS * 2048, P_BAR = P_STG + 16384, OP_SMEM = P_BAR + 256;
constexpr int PB_FULL = 0, PB_EMPTY = 128, PB_SF = 144, PB_SE = 176;
static_assert(OP_SMEM <= 232448, "smem");

__global__ void __launch_bounds__(384, 1) op_kernel(const bf16* __restrict__ Wo, const bf16* __restrict__ Bk, const bf16* __restrict__ Bv, const bf16* __restrict__ shiftk) {
    extern __shared__ __align__(1024) unsigned char smem_raw[];
    const int tid = threadIdx.x, warp = __shfl_sync(0xffffffffu, tid >> 5, 0), lane = tid & 31;
    const int nb = blockIdx.x % 5, ks = blockIdx.x / 5;
    const uint32_t sb = smem_u32(smem_raw), bb = sb + P_BAR;
    if (tid == 0) {
        if ((sb & 0xFFFFFFu) != 1024) __trap();
        for (int i = 0; i < 16; i++) mbar_init(bb + PB_FULL + i * 8, 1);
        for (int i = 0; i < 2; i++) mbar_init(bb + PB_EMPTY + i * 8, 2);
        for (int i = 0; i < 4; i++) { mbar_init(bb + PB_SF + i * 8, 4); mbar_init(bb + PB_SE + i * 8, 1); }
        asm volatile("fence.mbarrier_init.release.cluster;" ::: "memory");
    }
    GT(tid == 0, 8);
    __syncthreads();
    if (warp < 4) {
        asm volatile("setmaxnreg.dec.sync.aligned.u32 40;");
        if (warp == 0) {
            named_bar(3, 288);
            GT(lane == 0, 3);
            uint32_t it = 0;
            const int otgt = 8 * (ld_relaxed(&g_epoch) + 1);
#pragma unroll 1
            for (int q = 0; q < 2 * NT; q++) {
                const int l = q & 1, n = (q >> 1) - l * LAG;
                if (n < 0 || n >= NSEG) continue;
                int guard = 0;
                while (ld_acquire(FLG(F_O + l * 64 + n) + ks) < otgt) { if (++guard > 4000000) __trap(); __nanosleep(OP_NS); }
                fence_async_global();
                mwait(bb + PB_EMPTY + (it & 1) * 8, ((it >> 1) & 1) ^ 1);
                if (lane < 8) {
                    const uint32_t fb = bb + PB_FULL + ((it & 1) * 8 + lane) * 8;
                    mbar_expect_tx(fb, 8192);
                    asm volatile("cp.async.bulk.shared::cluster.global.mbarrier::complete_tx::bytes [%0], [%1], %2, [%3];" ::"r"(sb + P_RING + (it & 1) * 65536 + lane * 8192),
                                 "l"(g_ot + (rslot(l, n) * 256 + (ks * 8 + lane) * 8) * 64), "r"(8192), "r"(fb) : "memory");
                }
                __syncwarp();
                it++;
            }
        } else if (warp == 3) {
#pragma unroll 1
            for (int rg = 1; rg < 4; rg++) {
#pragma unroll 1
                for (int u = rg * 640 + blockIdx.x; u < rg * 640 + 640; u += 20) u_half(Bk, Bv, shiftk, u, lane);
                __syncwarp();
                if (lane == 0) red_release(FLG(F_U + rg + 1), 1);
                GT(lane == 0 && rg, 4 + rg);
            }
        } else if (lane == 0) {
            const int cw = warp - 1;
            uint32_t it = 0;
#pragma unroll 1
            for (int q = 0; q < 2 * NT; q++) {
                const int l = q & 1, n = (q >> 1) - l * LAG;
                if (n < 0 || n >= NSEG) continue;
                mwait(bb + PB_SF + cw * 8, it & 1);
                asm volatile("cp.reduce.async.bulk.global.shared::cta.bulk_group.add.f32 [%0], [%1], %2;" ::"l"(g_pt + (rslot(l, n) * 10 + nb * 2 + cw) * 512), "r"(sb + P_STG + cw * 8192), "r"(8192) : "memory");
                asm volatile("cp.async.bulk.commit_group;" ::: "memory");
                asm volatile("cp.async.bulk.wait_group.read 0;" ::: "memory");
                mbar_arrive(bb + PB_SE + cw * 8);
                asm volatile("cp.async.bulk.wait_group 0;" ::: "memory");
                fence_async_global();
                red_release(FLG(F_P + l * 64 + n), 1);
                GT(true, 330 + l * 64 + n);
                it++;
            }
        }
    } else {
        asm volatile("setmaxnreg.inc.sync.aligned.u32 232;");
        const int cw = (warp >> 2) - 1, w4 = warp & 3, t7 = tid & 127;
        uint32_t wa[64 - OP_SS][4];
        if (OP_LATE) flag_wait(FLG(F_H), 32 * (ld_relaxed(&g_epoch) + 1), 200);
        {
            const bf16* W = Wo + (size_t)ks * 1024 * DM + nb * 128 + cw * 64 + (t7 & 7) * 8;
            const uint32_t so = (t7 >> 3) * 128 + (((t7 & 7) ^ ((t7 >> 3) & 7)) << 4);
            const uint32_t stg = sb + P_RING + cw * 65536;
            const uint32_t la = stg + ((lane & 7) + (lane >> 4) * 8) * 128 + (((w4 * 2 + ((lane >> 3) & 1)) ^ (lane & 7)) << 4);
#pragma unroll 4
            for (int i = 0; i < 32; i++) cp_async16(stg + i * 2048 + so, W + (size_t)((OP_SS + i) * 16 + (t7 >> 3)) * DM);
            cp_commit();
#pragma unroll 1
            for (int i = 0; i < OP_SS; i++) cp_async16(sb + P_AS + cw * OP_SS * 2048 + i * 2048 + so, W + (size_t)(i * 16 + (t7 >> 3)) * DM);
            cp_commit();
            cp_wait<1>();
            named_bar(1 + cw, 128);
#pragma unroll
            for (int j = 0; j < 32; j++) { const uint4 v = ldsm4t(la + j * 2048); wa[j][0] = v.x; wa[j][1] = v.y; wa[j][2] = v.z; wa[j][3] = v.w; }
            named_bar(1 + cw, 128);
#pragma unroll 1
            for (int i = 0; i < 32 - OP_SS; i++) cp_async16(stg + i * 2048 + so, W + (size_t)((OP_SS + 32 + i) * 16 + (t7 >> 3)) * DM);
            cp_commit();
            cp_wait<0>();
            named_bar(1 + cw, 128);
#pragma unroll
            for (int j = 0; j < 32 - OP_SS; j++) { const uint4 v = ldsm4t(la + j * 2048); wa[32 + j][0] = v.x; wa[32 + j][1] = v.y; wa[32 + j][2] = v.z; wa[32 + j][3] = v.w; }
            fence_async_smem();
            named_bar(3, 288);
        }
        const uint32_t ab = (1024 + P_AS + cw * OP_SS * 2048) >> 4;
        const uint32_t ea = sb + P_STG + cw * 8192 + (lane & 3) * 2048 + (((2 * w4) ^ (lane & 3)) << 5) + (lane >> 2) * 4;
#pragma unroll 1
        for (uint32_t it = 0; it < 2 * NSEG; it++) {
            float acc[16];
            const uint32_t fb = bb + PB_FULL + (it & 1) * 64, par = (it >> 1) & 1;
            const uint32_t ob = opq(((1024 + P_RING) >> 4) + (it & 1) * 4096);
            uint32_t ok = 0;
#pragma unroll
            for (int j = 0; j < 64; j++) {
                if ((j & 7) == 0) {
                    if (j) wg_commit();
                    if (!ok) mslow(fb + j, par);
                    ok = j < 56 ? mtest(fb + j + 8, par) : mtest(bb + PB_SE + cw * 8, (it & 1) ^ 1);
                    if (j == 0) wg_fence();
                }
                const uint64_t db = mkdesc(ob + j * 64, 0x80000020u);
                if (j == 0) wg_n32t_sfirst(acc, mkdesc(ab, 0x40000040u), db);
                else if (j < OP_SS) wg_n32t_s(acc, mkdesc(ab + j * 128, 0x40000040u), db);
                else wg_n32t(acc, wa[j - OP_SS][0], wa[j - OP_SS][1], wa[j - OP_SS][2], wa[j - OP_SS][3], db);
            }
            wg_commit();
            if (!ok) mslow(bb + PB_SE + cw * 8, (it & 1) ^ 1);
            wg_wait<0>();
            if (t7 == 0) mbar_arrive(bb + PB_EMPTY + (it & 1) * 8);
#pragma unroll
            for (int i = 0; i < 16; i++) sts32((ea ^ ((i & 2) << 4)) + ((i >> 2) * 2 + (i & 1)) * 256, __float_as_uint(acc[i]));
            fence_async_smem();
            __syncwarp();
            if (lane == 0) mbar_arrive(bb + PB_SF + cw * 8);
        }
    }
}
}

namespace ws {
static bool usable() {
    static int ok = -1;
    if (ok < 0) {
        cudaFuncSetAttribute(head_kernel, cudaFuncAttributeMaxDynamicSharedMemorySize, HEAD_SMEM);
        cudaFuncSetAttribute(head_kernel, cudaFuncAttributeNonPortableClusterSizeAllowed, 1);
        cudaFuncSetAttribute(op_kernel, cudaFuncAttributeMaxDynamicSharedMemorySize, OP_SMEM);
        cudaLaunchConfig_t cfg = {};
        cfg.gridDim = dim3(NCL * 16); cfg.blockDim = dim3(512); cfg.dynamicSmemBytes = HEAD_SMEM;
        cudaLaunchAttribute at[1];
        at[0].id = cudaLaunchAttributeClusterDimension;
        at[0].val.clusterDim.x = 16; at[0].val.clusterDim.y = 1; at[0].val.clusterDim.z = 1;
        cfg.attrs = at; cfg.numAttrs = 1;
        int n = 0, nsm = 0;
        cudaDeviceGetAttribute(&nsm, cudaDevAttrMultiProcessorCount, 0);
        ok = cudaOccupancyMaxActiveClusters(&n, head_kernel, &cfg) == cudaSuccess && n >= NCL && nsm >= NCL * 16 + 20;
        (void)cudaGetLastError();
    }
    return ok > 0;
}
static void launch_all(void* const* d_in, void* d_out) {
    HeadArgs A;
    A.x = (const bf16*)d_in[0]; A.mem0 = (const bf16*)d_in[1]; A.Wq = (const bf16*)d_in[2]; A.Wk = (const bf16*)d_in[3]; A.Wv = (const bf16*)d_in[4]; A.Wo = (const bf16*)d_in[5];
    A.Bk = (const bf16*)d_in[8]; A.Bv = (const bf16*)d_in[9]; A.shiftk = (const bf16*)d_in[10]; A.ssmk = (const bf16*)d_in[11]; A.ssmD = (const bf16*)d_in[12];
    A.out = (bf16*)d_out; A.h_target = 32;
    cudaStream_t s = cudaStreamPerThread;
    {
        cudaLaunchConfig_t cfg = {};
        cfg.gridDim = dim3(NCL * 16); cfg.blockDim = dim3(512); cfg.dynamicSmemBytes = HEAD_SMEM; cfg.stream = s;
        cudaLaunchAttribute at[2];
        at[0].id = cudaLaunchAttributeClusterDimension;
        at[0].val.clusterDim.x = 16; at[0].val.clusterDim.y = 1; at[0].val.clusterDim.z = 1;
        at[1].id = cudaLaunchAttributeProgrammaticStreamSerialization;
        at[1].val.programmaticStreamSerializationAllowed = 1;
        cfg.attrs = at; cfg.numAttrs = 1;
        cudaLaunchKernelEx(&cfg, head_kernel, A);
    }
    {
        cudaLaunchConfig_t cfg = {};
        cfg.gridDim = dim3(20); cfg.blockDim = dim3(384); cfg.dynamicSmemBytes = OP_SMEM; cfg.stream = s;
        cudaLaunchAttribute at[1];
        at[0].id = cudaLaunchAttributeProgrammaticStreamSerialization;
        at[0].val.programmaticStreamSerializationAllowed = 1;
        cfg.attrs = at; cfg.numAttrs = 1;
        cudaLaunchKernelEx(&cfg, op_kernel, A.Wo, A.Bk, A.Bv, A.shiftk);
    }
}
}

#undef BNS
#undef BP
#undef CONV_DRY
#undef CV_YIELD
#undef FLG
#undef GT
#undef G_DLY
#undef H1_LATE
#undef HBYTES
#undef H_NS
#undef LAGT
#undef LN0_AHEAD
#undef NL2
#undef NO_X
#undef O0_EARLY
#undef OBK
#undef OBRES
#undef OP_LATE
#undef OP_NS
#undef OT_LATE
#undef O_BULK
#undef O_DLY
#undef P1A
#undef P1C
#undef PDA
#undef PDC
#undef POST_DRY
#undef POST_NS
#undef PRE_PDL
#undef PRE_PF
#undef QUIET
#undef REG_G
#undef REG_T
#undef REG_X
#undef RING
#undef SC
#undef SD
#undef SELF_LOCAL
#undef SKEW
#undef SPIN
#undef TG_STEPS
#undef TPVW
#undef TPV_LATE
#undef TPV_PAUSE
#undef TS
#undef TV
#undef UNI
#undef WFLY
#undef WGRP
#undef WK3
#undef WR
#undef WTA
#undef WVOL
#undef W_SKIP
#undef XD
#undef XDUP
#undef XFD
#undef XS
namespace ni {

constexpr int S_LEN = 2048;
constexpr int DM = 640;
constexpr int NH = 32;
constexpr int DH = 128;
constexpr int HD = NH * DH;
constexpr int MEMR = 8;
constexpr int SEG = 32;
constexpr int NSEG = S_LEN / SEG;

__device__ __forceinline__ float bf2f(bf16 v) { return __bfloat162float(v); }
__device__ __forceinline__ bf16 f2bf(float v) { return __float2bfloat16_rn(v); }
__device__ __forceinline__ float rbf(float v) { return __bfloat162float(__float2bfloat16_rn(v)); }
__device__ __forceinline__ uint32_t pack2(float a, float b) {
    __nv_bfloat162 t = __floats2bfloat162_rn(a, b);
    return *reinterpret_cast<uint32_t*>(&t);
}
__device__ __forceinline__ uint32_t smem_u32(const void* p) { return (uint32_t)__cvta_generic_to_shared(p); }
__device__ __forceinline__ void ldsm_x4(uint32_t& r0, uint32_t& r1, uint32_t& r2, uint32_t& r3, uint32_t addr) {
    asm volatile("ldmatrix.sync.aligned.m8n8.x4.shared.b16 {%0,%1,%2,%3}, [%4];"
                 : "=r"(r0), "=r"(r1), "=r"(r2), "=r"(r3) : "r"(addr));
}
__device__ __forceinline__ void ldsm_x2(uint32_t& r0, uint32_t& r1, uint32_t addr) {
    asm volatile("ldmatrix.sync.aligned.m8n8.x2.shared.b16 {%0,%1}, [%2];" : "=r"(r0), "=r"(r1) : "r"(addr));
}
__device__ __forceinline__ void ldsm_x4_t(uint32_t& r0, uint32_t& r1, uint32_t& r2, uint32_t& r3, uint32_t addr) {
    asm volatile("ldmatrix.sync.aligned.m8n8.x4.trans.shared.b16 {%0,%1,%2,%3}, [%4];"
                 : "=r"(r0), "=r"(r1), "=r"(r2), "=r"(r3) : "r"(addr));
}
__device__ __forceinline__ void mma16816(float* c, uint32_t a0, uint32_t a1, uint32_t a2, uint32_t a3,
                                         uint32_t b0, uint32_t b1) {
    asm("mma.sync.aligned.m16n8k16.row.col.f32.bf16.bf16.f32 {%0,%1,%2,%3}, {%4,%5,%6,%7}, {%8,%9}, {%0,%1,%2,%3};"
        : "+f"(c[0]), "+f"(c[1]), "+f"(c[2]), "+f"(c[3])
        : "r"(a0), "r"(a1), "r"(a2), "r"(a3), "r"(b0), "r"(b1));
}
__device__ __forceinline__ void cp_async16(uint32_t dst, const void* src) {
    asm volatile("cp.async.cg.shared.global [%0], [%1], 16;" ::"r"(dst), "l"(src));
}
__device__ __forceinline__ void cp_commit() { asm volatile("cp.async.commit_group;"); }
template <int N> __device__ __forceinline__ void cp_wait() { asm volatile("cp.async.wait_group %0;" ::"n"(N)); }
__device__ __forceinline__ uint4 ld_relaxed_v4(const void* p) {
    uint4 v;
    asm volatile("ld.relaxed.gpu.global.v4.u32 {%0,%1,%2,%3}, [%4];"
                 : "=r"(v.x), "=r"(v.y), "=r"(v.z), "=r"(v.w) : "l"(p) : "memory");
    return v;
}
__device__ __forceinline__ void st_relaxed_v4(void* p, uint32_t a, uint32_t b, uint32_t c, uint32_t d) {
    asm volatile("st.relaxed.gpu.global.v4.u32 [%0], {%1,%2,%3,%4};" ::"l"(p), "r"(a), "r"(b), "r"(c), "r"(d) : "memory");
}
__device__ __forceinline__ int ld_acquire(const int* p) {
    int v;
    asm volatile("ld.acquire.gpu.global.u32 %0, [%1];" : "=r"(v) : "l"(p) : "memory");
    return v;
}
__device__ __forceinline__ void mbar_init(uint32_t bar, int count) {
    asm volatile("mbarrier.init.shared::cta.b64 [%0], %1;" ::"r"(bar), "r"(count));
}
__device__ __forceinline__ void mbar_expect_tx(uint32_t bar, uint32_t bytes) {
    asm volatile("mbarrier.arrive.expect_tx.shared::cta.b64 _, [%0], %1;" ::"r"(bar), "r"(bytes) : "memory");
}
__device__ __forceinline__ void mbar_arrive(uint32_t bar) {
    asm volatile("mbarrier.arrive.shared::cta.b64 _, [%0];" ::"r"(bar) : "memory");
}
constexpr int SPIN_LIMIT = 4000000;
__device__ __forceinline__ void mbar_wait_spin(uint32_t bar, uint32_t parity) {
    uint32_t ok = 0;
    int guard = 0;
    while (!ok && ++guard < SPIN_LIMIT) {
        asm volatile(
            "{\n.reg .pred P1;\n"
            "mbarrier.try_wait.parity.shared::cta.b64 P1, [%1], %2;\n"
            "selp.u32 %0, 1, 0, P1;\n}\n"
            : "=r"(ok) : "r"(bar), "r"(parity) : "memory");
    }
}
__device__ __forceinline__ uint32_t mapa(uint32_t addr, uint32_t rank) {
    uint32_t r;
    asm volatile("mapa.shared::cluster.u32 %0, %1, %2;" : "=r"(r) : "r"(addr), "r"(rank));
    return r;
}
__device__ __forceinline__ void st_async_u32(uint32_t addr, uint32_t v, uint32_t bar) {
    asm volatile("st.async.weak.shared::cluster.mbarrier::complete_tx::bytes.b32 [%0], %1, [%2];" ::"r"(addr), "r"(v), "r"(bar) : "memory");
}
__device__ __forceinline__ void st_async_v2(uint32_t addr, uint32_t a, uint32_t b, uint32_t bar) {
    asm volatile("st.async.weak.shared::cluster.mbarrier::complete_tx::bytes.v2.b32 [%0], {%1,%2}, [%3];" ::"r"(addr), "r"(a), "r"(b), "r"(bar) : "memory");
}
__device__ __forceinline__ void cluster_sync_all() {
    asm volatile("barrier.cluster.arrive.release.aligned;\nbarrier.cluster.wait.acquire.aligned;" ::: "memory");
}
__device__ __forceinline__ void named_bar(int id, int n) { asm volatile("bar.sync %0, %1;" ::"r"(id), "r"(n) : "memory"); }

}

namespace ni {
#define CHAIN_LAG 16
constexpr int CL = 16;
constexpr int OWN = DM / CL;
constexpr int NSRC = CL / 2;
constexpr int NCLU = 64 / CL;
constexpr int CSEG = 4;
constexpr int NCHK = NSEG / CSEG;
constexpr int LAG = CHAIN_LAG;
constexpr int NTICK = NSEG + LAG;

constexpr int F_KV = 0, F_MEM = 32, F_H = 64, F_OP = 96, F_CONV = 128, F_U = 130, F_PROG = 132, F_ZERO = 133, F_CNT = 136;
constexpr int NFLAG = 192;
__device__ int g_flags[NFLAG * 32];
#define FLG(i) (g_flags + (i) * 32)
constexpr int CHAIN_THREADS = 384;
__device__ bf16 g_Y[S_LEN * DM];
__device__ bf16 g_U[DM * S_LEN];
__device__ bf16 g_h[2][S_LEN * DM];
__device__ bf16 g_x[S_LEN * DM];
__device__ bf16 g_kv[2][S_LEN * HD];
#define PRING 4
constexpr int PROWS = PRING * 128, PG = 4;
__device__ bf16 g_part[2 * PROWS * PG * DM];
__device__ uint4 g_kvf[2 * NSEG * NH * 256];
__device__ uint32_t g_xc[2 * 2 * CL * NCLU * 8 * OWN];

#define TVAL(i, v)
#define TSTAMP(i)

#define NRQ 36
#define NRW 8
#define PDQ 4
#define PDW1 0
#define PROBE 2
#define PDW 6
constexpr int NSQ = 60 - NRQ, NSW = 20 - NRW;
__host__ __device__ constexpr bool q_smem(int i) { return ((i + 1) * NSQ) / 60 != (i * NSQ) / 60; }
__host__ __device__ constexpr int q_slot(int i) { return q_smem(i) ? (i * NSQ) / 60 : i - (i * NSQ) / 60; }
__host__ __device__ constexpr int w_tile(int i) { return i < 8 ? ((i & 1) ? 0 : 2) : (i < 16 ? (i & 1) : 1); }
__host__ __device__ constexpr int w_k(int i) { return i < 8 ? i / 2 : (i < 16 ? ((i & 1) ? (i - 8) / 2 : 4 + (i - 8) / 2) : i - 12); }
__host__ __device__ constexpr int w_acc(int i) { return (i >= 16 && (i & 1)) ? 3 : w_tile(i); }
__host__ __device__ constexpr bool w_smem(int i) { return i < PDW || NRW == 0 || ((i - PDW + 1) * NRW) / (20 - PDW) == ((i - PDW) * NRW) / (20 - PDW); }
__host__ __device__ constexpr int w_slot(int i) { return i < PDW ? i : (w_smem(i) ? i - ((i - PDW) * NRW) / (20 - PDW) : ((i - PDW) * NRW) / (20 - PDW)); }
constexpr int O_WQ = 0, O_WW = NSQ * 4096, O_REST = (NSQ + NSW) * 4096;
constexpr int C_TOK = 0, C_MEM = 12288, C_RED = C_MEM + 10240, C_Q = C_RED + 6144, C_K = C_Q + 2048, C_V = C_K + 2048, C_S = C_V + 4096,
              C_BAR = C_S + 3072, C_SIZE = 40960;
constexpr int S_BYTES = 3072 + 4096;
constexpr int B_S = 64, B_R = 72, B_T = 96, B_F = 104;
static_assert(C_BAR + 112 <= C_SIZE, "chain block");
constexpr int O_STB = O_REST - 61440;
static_assert((45 * NSQ) / 60 * 4096 <= O_STB && NSQ <= 32, "staging");
struct ChainSmem { unsigned char b[O_REST + 81920 + 1536]; };
static_assert(sizeof(ChainSmem) <= 232448, "smem");

struct ChainArgs {
    CUtensorMap tk[2], tv[2];
    const bf16 *x, *mem0, *Wq, *Wk, *Wv, *Wo;
    int kv_target;
};
__device__ __forceinline__ uint32_t movmat(uint32_t v) {
    uint32_t r;
    asm volatile("movmatrix.sync.aligned.m8n8.trans.b16 %0, %1;" : "=r"(r) : "r"(v));
    return r;
}
__device__ __forceinline__ void named_arrive(int id, int n) { asm volatile("bar.arrive %0, %1;" ::"r"(id), "r"(n) : "memory"); }
__device__ __forceinline__ void red_release(int* p, int v) { asm volatile("red.release.gpu.global.add.u32 [%0], %1;" ::"l"(p), "r"(v) : "memory"); }

#define CVT(i)
__device__ __forceinline__ uint4 lds128(uint32_t a) {
    uint4 v;
    asm volatile("ld.shared.v4.u32 {%0,%1,%2,%3}, [%4];" : "=r"(v.x), "=r"(v.y), "=r"(v.z), "=r"(v.w) : "r"(a));
    return v;
}
__device__ __forceinline__ uint2 lds64(uint32_t a) {
    uint2 v;
    asm volatile("ld.shared.v2.u32 {%0,%1}, [%2];" : "=r"(v.x), "=r"(v.y) : "r"(a));
    return v;
}
__device__ __forceinline__ uint32_t lds32(uint32_t a) {
    uint32_t v;
    asm volatile("ld.shared.u32 %0, [%1];" : "=r"(v) : "r"(a));
    return v;
}
__device__ __forceinline__ void sts64(uint32_t a, uint32_t x, uint32_t y) { asm volatile("st.shared.v2.u32 [%0], {%1,%2};" ::"r"(a), "r"(x), "r"(y) : "memory"); }
__device__ __forceinline__ void sts128(uint32_t a, uint32_t x, uint32_t y, uint32_t z, uint32_t w) {
    asm volatile("st.shared.v4.u32 [%0], {%1,%2,%3,%4};" ::"r"(a), "r"(x), "r"(y), "r"(z), "r"(w) : "memory");
}
__device__ __forceinline__ void st_async_v4(uint32_t addr, uint32_t a, uint32_t b, uint32_t c, uint32_t d, uint32_t bar) {
    asm volatile("st.async.weak.shared::cluster.mbarrier::complete_tx::bytes.v4.b32 [%0], {%1,%2,%3,%4}, [%5];" ::"r"(addr), "r"(a), "r"(b), "r"(c), "r"(d), "r"(bar) : "memory");
}
__device__ __forceinline__ uint2 ld_relaxed_v2(const void* p) {
    uint2 v;
    asm volatile("ld.relaxed.gpu.global.v2.u32 {%0,%1}, [%2];" : "=r"(v.x), "=r"(v.y) : "l"(p) : "memory");
    return v;
}
__device__ __forceinline__ void st_relaxed_v2(void* p, uint32_t a, uint32_t b) {
    asm volatile("st.relaxed.gpu.global.v2.u32 [%0], {%1,%2};" ::"l"(p), "r"(a), "r"(b) : "memory");
}
__device__ __forceinline__ float blo(uint32_t v) { return __uint_as_float(v << 16); }
__device__ __forceinline__ float bhi(uint32_t v) { return __uint_as_float(v & 0xffff0000u); }
__device__ __forceinline__ uint32_t badd2(uint32_t a, uint32_t b) {
    __nv_bfloat162 r = __hadd2(*reinterpret_cast<__nv_bfloat162*>(&a), *reinterpret_cast<__nv_bfloat162*>(&b));
    return *reinterpret_cast<uint32_t*>(&r);
}
__device__ __forceinline__ void mmau(float* c, const uint4& a, uint32_t b0, uint32_t b1) { mma16816(c, a.x, a.y, a.z, a.w, b0, b1); }

__device__ __forceinline__ void stsm_x4_t(uint32_t a, uint32_t r0, uint32_t r1, uint32_t r2, uint32_t r3) {
    asm volatile("stmatrix.sync.aligned.m8n8.x4.trans.shared.b16 [%0], {%1,%2,%3,%4};" ::"r"(a), "r"(r0), "r"(r1), "r"(r2), "r"(r3) : "memory");
}
__device__ __forceinline__ uint4 ldsm4(uint32_t a) { uint4 v; ldsm_x4(v.x, v.y, v.z, v.w, a); return v; }
__device__ __forceinline__ float ex2f(float x) { float y; asm("ex2.approx.ftz.f32 %0, %1;" : "=f"(y) : "f"(x)); return y; }
__device__ __forceinline__ float rcpf(float x) { float y; asm("rcp.approx.ftz.f32 %0, %1;" : "=f"(y) : "f"(x)); return y; }
#define XD 300
__device__ __forceinline__ void xdelay() {
    uint32_t t0, t1;
    asm volatile("mov.u32 %0, %clock;" : "=r"(t0));
    do { asm volatile("mov.u32 %0, %clock;" : "=r"(t1)); } while (t1 - t0 < XD);
}
template <int V> struct IC { static constexpr int value = V; };
__device__ __forceinline__ uint32_t opq(uint32_t x) { uint32_t y; asm volatile("mov.u32 %0, %1;" : "=r"(y) : "r"(x)); return y; }
#define UNI(x) __shfl_sync(0xffffffffu, (uint32_t)(x), 0)
__device__ __forceinline__ uint32_t mtest(uint32_t bar, uint32_t parity) {
    uint32_t ok;
    asm volatile("{\n.reg .pred P1;\nmbarrier.test_wait.parity.shared::cta.b64 P1, [%1], %2;\nselp.u32 %0, 1, 0, P1;\n}\n" : "=r"(ok) : "r"(bar), "r"(parity) : "memory");
    return ok;
}
__device__ __forceinline__ void mwait(uint32_t bar, uint32_t parity) {
    asm volatile(
        "{\n.reg .pred P1;\n.reg .u32 cnt;\n"
        "mbarrier.try_wait.parity.shared::cta.b64 P1, [%0], %1;\n"
        "@P1 bra DONE;\n"
        "mov.u32 cnt, 0;\n"
        "LAB_WAIT:\n"
        "mbarrier.try_wait.parity.shared::cta.b64 P1, [%0], %1;\n"
        "@P1 bra DONE;\n"
        "add.u32 cnt, cnt, 1;\n"
        "setp.lt.u32 P1, cnt, 4000000;\n"
        "@P1 bra LAB_WAIT;\n"
        "DONE:\n}\n" ::"r"(bar), "r"(parity) : "memory");
}

__global__ void __launch_bounds__(CHAIN_THREADS, 1) chain_kernel(const __grid_constant__ ChainArgs A) {
    extern __shared__ __align__(1024) unsigned char smem_raw[];
    const int tid = threadIdx.x, warp = __shfl_sync(0xffffffffu, tid >> 5, 0), lane = tid & 31;
    const int cq = blockIdx.x / CL, r = blockIdx.x % CL;
    const int h = cq * NSRC + (r >> 1), hf = r & 1;
    const uint32_t sb = smem_u32(smem_raw);
    asm volatile("griddepcontrol.launch_dependents;");
    CVT(0);
    if (warp == 8) {
        if (lane < 8) asm volatile("cp.async.bulk.prefetch.L2.global [%0], %1;" ::"l"(A.x + (size_t)(blockIdx.x * 8 + lane) * 2560), "r"(5120) : "memory");
        asm volatile("cp.async.bulk.prefetch.L2.global [%0], %1;" ::"l"((lane < 16 ? A.Wk : A.Wv) + (size_t)(blockIdx.x * 16 + (lane & 15)) * 2560), "r"(5120) : "memory");
        asm volatile("cp.async.bulk.prefetch.L2.global [%0], %1;" ::"l"((lane < 16 ? A.Wq : A.Wo) + (size_t)(blockIdx.x * 16 + (lane & 15)) * 2560), "r"(5120) : "memory");
    }
    CVT(1);
    if (warp < 8) {
        asm volatile("setmaxnreg.inc.sync.aligned.u32 232;");
        const int j = warp & 3, kh = warp >> 2;
        uint4 wr[NRQ + NRW];
        {
            auto load_round = [&](int gi) {
                const uint32_t buf = sb + ((gi & 1) ? O_STB : O_REST);
#pragma unroll
                for (int it = 0; it < 15; it++) {
                    const int i = tid + it * 256;
                    const int pc = i / 1920, rem = i % 1920, row = rem / 24, ch = rem % 24;
                    const int mat = ch >> 3, pi = ((r >> 1) - (2 * gi + pc)) & 7;
                    const bf16* W = mat == 0 ? A.Wq : (mat == 1 ? A.Wk : A.Wv);
                    cp_async16(buf + pc * 30720 + row * 384 + ((ch ^ (row & 7)) << 4), W + (size_t)(pi * 80 + row) * HD + h * DH + hf * 64 + (ch & 7) * 8);
                }
                cp_commit();
            };
            load_round(0);
            load_round(1);
#pragma unroll
            for (int gi = 0; gi < 4; gi++) {
                cp_wait<1>();
                named_bar(1, 256);
                const uint32_t pb = sb + ((gi & 1) ? O_STB : O_REST) + kh * 30720;
                uint4 tmp[8];
#pragma unroll
                for (int u = 0; u < 5; u++)
#pragma unroll
                    for (int tt = 0; tt < 3; tt++) {
                        const int row = u * 16 + (lane & 7) + (lane >> 4) * 8;
                        const int ch = tt * 8 + j * 2 + ((lane >> 3) & 1);
                        uint4 v;
                        ldsm_x4_t(v.x, v.y, v.z, v.w, pb + row * 384 + ((ch ^ (row & 7)) << 4));
                        const int i = (gi * 5 + u) * 3 + tt;
                        if (q_smem(i)) {
                            if (gi == 3) tmp[q_slot(i) & 7] = v;
                            else sts128(sb + O_WQ + q_slot(i) * 4096 + tid * 16, v.x, v.y, v.z, v.w);
                        } else wr[q_slot(i)] = v;
                    }
                named_bar(1, 256);
                if (gi == 3) {
#pragma unroll
                    for (int i = 45; i < 60; i++)
                        if (q_smem(i)) { const uint4 v = tmp[q_slot(i) & 7]; sts128(sb + O_WQ + q_slot(i) * 4096 + tid * 16, v.x, v.y, v.z, v.w); }
                }
                if (gi < 2) load_round(gi + 2);
                else if (gi == 2) {
                    for (int i = tid; i < 128 * 40; i += 256) {
                        const int row = i / 40, ch = i % 40;
                        cp_async16(sb + O_REST + row * 640 + ((ch ^ (row & 7)) << 4), A.Wo + ((size_t)h * DH + row) * DM + hf * 320 + ch * 8);
                    }
                    cp_commit();
                }
            }
            cp_wait<0>();
            named_bar(1, 256);
#pragma unroll
            for (int i = 0; i < 20; i++) {
                const int tl = w_tile(i), et = (w_k(i) + 4 * (warp & 1)) & 7;
                const int row = et * 16 + (lane & 7) + (lane >> 4) * 8;
                const int ch = (warp >> 1) * 10 + (tl == 2 ? 8 : (warp & 1) * 4 + tl * 2) + ((lane >> 3) & 1);
                uint4 v;
                ldsm_x4_t(v.x, v.y, v.z, v.w, sb + O_REST + row * 640 + ((ch ^ (row & 7)) << 4));
                if (w_smem(i)) sts128(sb + O_WW + w_slot(i) * 4096 + tid * 16, v.x, v.y, v.z, v.w);
                else wr[NRQ + w_slot(i)] = v;
            }
            named_bar(1, 256);
            for (int i = tid; i < 2560; i += 256) {
                const int ks = i >> 6, ln = (i >> 1) & 31, wd = i & 1;
                const int pi = ((r >> 1) - ks / 5) & 7;
                const uint32_t v = *reinterpret_cast<const uint32_t*>(A.mem0 + (ln >> 2) * DM + pi * 80 + (ks % 5) * 16 + wd * 8 + (ln & 3) * 2);
                const int o = ks % 5 == 4 ? ks * 256 + wd * 128 + ln * 4 : i * 4;
                asm volatile("st.shared.u32 [%0], %1;" ::"r"(sb + O_REST + C_MEM + o), "r"(v) : "memory");
                asm volatile("st.shared.u32 [%0], %1;" ::"r"(sb + O_REST + C_SIZE + C_MEM + o), "r"(v) : "memory");
            }
            if (tid < 2) {
                const uint32_t bb = sb + O_REST + tid * C_SIZE + C_BAR;
                for (int i = 0; i < 13; i++) mbar_init(bb + i * 8, 1);
                mbar_init(bb + B_F, 4);
                asm volatile("fence.mbarrier_init.release.cluster;" ::: "memory");
                mbar_expect_tx(bb + B_S, S_BYTES);
                for (int i = 0; i < 3; i++) mbar_expect_tx(bb + B_R + i * 8, 2048);
            }
            asm volatile("fence.proxy.async;" ::: "memory");
        }
        CVT(2);
        cluster_sync_all();
        const uint32_t wq_a = sb + O_WQ + tid * 16;
        const uint32_t cb0 = sb + O_REST;
        const uint32_t qk_a = cb0 + j * 512 + (lane & 7) * 16 + (lane < 16 ? C_Q + (lane >> 3) * 256 + kh * 128 : C_K + kh * 256 + ((lane >> 3) & 1) * 128);
        const uint32_t pd = UNI(mapa(sb, (uint32_t)(r ^ 1)) - sb), sd = UNI(mapa(sb, (uint32_t)r) - sb);
        const uint32_t od = UNI(mapa(sb, (uint32_t)(hf * 8 + warp)) - sb);
        const uint32_t oe = UNI(mapa(sb, (uint32_t)(hf * 8 + (warp & 6))) - sb), oo = UNI(mapa(sb, (uint32_t)(hf * 8 + (warp | 1))) - sb);
        const uint32_t u_mem = UNI(cb0 + C_MEM + kh * 1280), u_bm = UNI(cb0 + C_BAR + kh * 8);
        const uint32_t u_v = UNI(cb0 + C_V + hf * 2048 + j * 512 + kh * 256);
        const uint32_t u_ra = UNI(cb0 + C_RED + (r >> 1) * 256);
        const uint32_t u_ob0 = UNI(cb0 + C_Q + (warp & 1) * 1024), u_ob1 = UNI(cb0 + C_Q + ((warp & 1) ^ 1) * 1024);
        const uint32_t u_role = UNI(warp < 3 ? cb0 + C_S + hf * 1536 + warp * 512 : cb0 + C_V + j * 1024);
        const uint32_t t_tok = cb0 + C_TOK + ((lane & 7) + (lane >> 4) * 8) * 128 +
                               (warp < 3 ? warp * 2048 + ((((lane >> 3) & 1) ^ (lane & 7)) << 4) : 4096 + (j >> 1) * 4096 + ((((j & 1) * 4 + ((lane >> 3) & 1)) ^ (lane & 7)) << 4));
        uint4 qb[PDQ];
#pragma unroll
        for (int s = 0; s < PDQ; s++) qb[s] = lds128(wq_a + s * 4096);
        auto tick = [&](auto cc, const int n) {
            constexpr int c = decltype(cc)::value;
            constexpr uint32_t CO = c * C_SIZE;
            const uint32_t cb = cb0 + CO;
            const uint32_t par = (uint32_t)(n & 1);
            const uint32_t l4 = opq(lane * 4), l8 = l4 * 2, l16 = l4 * 4;
            float acc[3][4];
#pragma unroll
            for (int a = 0; a < 3; a++)
#pragma unroll
                for (int i = 0; i < 4; i++) acc[a][i] = 0.f;
            {
                const uint32_t mb = u_mem + CO + l8;
                uint2 bf[3];
                uint32_t ok = 1;
                auto ldb = [&](int ks) {
                    if (ks == 0) mwait(u_bm + CO, par ^ 1);
                    else if (ks % 5 == 0) { if (!ok) mwait(u_bm + CO + (ks / 5) * 16, par ^ 1); }
                    if (ks % 5 == PROBE && ks < 15) ok = mtest(u_bm + CO + (ks / 5 + 1) * 16, par ^ 1);
                    if (ks % 5 == 4) {
                        bf[ks % 3].x = lds32(u_mem + CO + l4 + (ks / 5) * 2560 + 1024);
                        bf[ks % 3].y = lds32(u_mem + CO + l4 + (ks / 5) * 2560 + 1152);
                    } else bf[ks % 3] = lds64(mb + (ks / 5) * 2560 + (ks % 5) * 256);
                };
                ldb(0);
                TSTAMP(c * 12 + 0);
                ldb(1);
#pragma unroll
                for (int ks = 0; ks < 20; ks++) {
                    if (ks + 2 < 20) ldb(ks + 2);
#pragma unroll
                    for (int tt = 0; tt < 3; tt++) {
                        const int i = ks * 3 + tt;
                        if (q_smem(i)) {
                            const int s = q_slot(i);
                            mmau(acc[tt], qb[s % PDQ], bf[ks % 3].x, bf[ks % 3].y);
                            if (s + PDQ < NSQ) qb[s % PDQ] = lds128(wq_a + (s + PDQ) * 4096);
                        } else mmau(acc[tt], wr[q_slot(i)], bf[ks % 3].x, bf[ks % 3].y);
                    }
                }
            }
            TSTAMP(c * 12 + 1);
            stsm_x4_t(opq(qk_a) + CO, pack2(acc[0][0], acc[0][1]), pack2(acc[0][2], acc[0][3]), pack2(acc[1][0], acc[1][1]), pack2(acc[1][2], acc[1][3]));
            const uint32_t v0 = pack2(acc[2][0], acc[2][1]), v1 = pack2(acc[2][2], acc[2][3]);
            if (n == NSEG - 1) {
                sts64(u_v + CO + l8, v0, v1);
                named_bar(1, 256);
                if (kh == 1 && lane == 0) mbar_arrive(cb + C_BAR + B_F);
#pragma unroll
                for (int s = 0; s < PDQ; s++) qb[s] = lds128(wq_a + s * 4096);
                return;
            }
            named_arrive(1, 384);
            st_async_v2(u_v + CO + l8 + pd, v0, v1, cb + C_BAR + B_S + pd);
            st_async_v2(u_v + CO + l8 + sd, v0, v1, cb + C_BAR + B_S + sd);
            uint4 wb[PDW];
            const uint32_t ww_a = wq_a + (O_WW - O_WQ);
            if (warp < 3) {
                uint4 kb[4];
                const uint32_t t_tk = opq(t_tok);
                mwait(cb + C_BAR + B_T, par);
#pragma unroll
                for (int i = 0; i < 4; i++) kb[i] = ldsm4((t_tk ^ (i << 5)) + CO);
                named_bar(1, 384);
                uint4 qa[4];
#pragma unroll
                for (int i = 0; i < 4; i++) qa[i] = ldsm4(cb + l16 + C_Q + i * 512);
                if (warp == 2) {
#pragma unroll
                    for (int i = 0; i < 4; i++) kb[i] = ldsm4(cb + l16 + C_K + i * 512);
                }
                float s0[4][4], s1[4][4];
#pragma unroll
                for (int i = 0; i < 4; i++) {
#pragma unroll
                    for (int q = 0; q < 4; q++) s0[i][q] = s1[i][q] = 0.f;
                    mmau(s0[i], qa[i], kb[i].x, kb[i].y);
                    mmau(s1[i], qa[i], kb[i].z, kb[i].w);
                }
                const float a0 = ((s0[0][0] + s0[0][2]) + (s0[1][0] + s0[1][2])) + ((s0[2][0] + s0[2][2]) + (s0[3][0] + s0[3][2]));
                const float a1 = ((s0[0][1] + s0[0][3]) + (s0[1][1] + s0[1][3])) + ((s0[2][1] + s0[2][3]) + (s0[3][1] + s0[3][3]));
                const float b0 = ((s1[0][0] + s1[0][2]) + (s1[1][0] + s1[1][2])) + ((s1[2][0] + s1[2][2]) + (s1[3][0] + s1[3][2]));
                const float b1 = ((s1[0][1] + s1[0][3]) + (s1[1][1] + s1[1][3])) + ((s1[2][1] + s1[2][3]) + (s1[3][1] + s1[3][3]));
                const uint32_t so = u_role + CO + l16, bs = cb + C_BAR + B_S;
                const float c0 = warp == 2 ? a0 + b0 : a0, c1 = warp == 2 ? a1 + b1 : a1;
                st_async_v4(so + pd, __float_as_uint(c0), __float_as_uint(c1), __float_as_uint(b0), __float_as_uint(b1), bs + pd);
                st_async_v4(so + sd, __float_as_uint(c0), __float_as_uint(c1), __float_as_uint(b0), __float_as_uint(b1), bs + sd);
                TSTAMP(c * 12 + 2);
#pragma unroll
                for (int s = 0; s < PDW; s++) wb[s] = lds128(ww_a + s * 4096);
            } else if (warp == 3) {
                named_bar(1, 384);
                if (lane < 8) mbar_expect_tx(cb + C_BAR + l8, 1280);
#pragma unroll
                for (int s = 0; s < PDW; s++) wb[s] = lds128(ww_a + s * 4096);
            } else {
                mwait(cb + C_BAR + B_T, par);
                uint4 va[2][2];
                const uint32_t t_tk = opq(t_tok);
#pragma unroll
                for (int e = 0; e < 2; e++)
#pragma unroll
                    for (int k = 0; k < 2; k++)
                        ldsm_x4_t(va[e][k].x, va[e][k].y, va[e][k].z, va[e][k].w, (t_tk ^ (e << 5)) + CO + k * 2048);
#pragma unroll
                for (int s2 = 0; s2 < PDW1; s2++) wb[s2] = lds128(ww_a + s2 * 4096);
                mwait(cb + C_BAR + B_S, par);
                TSTAMP(c * 12 + 3);
                const uint32_t xa = cb + l16 + C_S;
                const uint4 x0 = lds128(xa), y0 = lds128(xa + 1536), x1 = lds128(xa + 512), y1 = lds128(xa + 512 + 1536);
                const uint2 x2 = lds64(xa + 1024), y2 = lds64(xa + 1024 + 1536);
                const uint32_t fv = u_role + CO + l8;
                const float cs = 0.08838834764831845f * 1.4426950408889634f;
                float s[10];
                s[8] = __uint_as_float(x2.x) + __uint_as_float(y2.x); s[9] = __uint_as_float(x2.y) + __uint_as_float(y2.y);
                s[0] = __uint_as_float(x0.x) + __uint_as_float(y0.x); s[1] = __uint_as_float(x0.y) + __uint_as_float(y0.y);
                s[2] = __uint_as_float(x0.z) + __uint_as_float(y0.z); s[3] = __uint_as_float(x0.w) + __uint_as_float(y0.w);
                s[4] = __uint_as_float(x1.x) + __uint_as_float(y1.x); s[5] = __uint_as_float(x1.y) + __uint_as_float(y1.y);
                s[6] = __uint_as_float(x1.z) + __uint_as_float(y1.z); s[7] = __uint_as_float(x1.w) + __uint_as_float(y1.w);
                float mx = fmaxf(fmaxf(fmaxf(s[0], s[1]), fmaxf(s[2], s[3])), fmaxf(fmaxf(fmaxf(s[4], s[5]), fmaxf(s[6], s[7])), fmaxf(s[8], s[9])));
                const float m1 = __shfl_xor_sync(0xffffffffu, mx, 1), m2 = __shfl_xor_sync(0xffffffffu, mx, 2), m3 = __shfl_xor_sync(0xffffffffu, mx, 3);
                const uint2 vm00 = lds64(fv), vm01 = lds64(fv + 256), vm10 = lds64(fv + 512), vm11 = lds64(fv + 768);
                const uint4 vm0 = make_uint4(vm00.x, vm00.y, vm01.x, vm01.y), vm1 = make_uint4(vm10.x, vm10.y, vm11.x, vm11.y);
                mx = fmaxf(fmaxf(mx, m1), fmaxf(m2, m3)) * -cs;
                uint32_t pb[5];
                pb[4] = pack2(ex2f(fmaf(s[8], cs, mx)), ex2f(fmaf(s[9], cs, mx)));
#pragma unroll
                for (int i = 0; i < 4; i++) pb[i] = pack2(ex2f(fmaf(s[2 * i], cs, mx)), ex2f(fmaf(s[2 * i + 1], cs, mx)));
                float o[3][4];
#pragma unroll
                for (int i = 0; i < 4; i++) { o[0][i] = o[1][i] = o[2][i] = 0.f; }
                const uint32_t one2 = 0x3F803F80u;
                mma16816(o[2], one2, one2, one2, one2, pb[4], 0u);
                mmau(o[0], vm0, pb[4], pb[4]);
                mmau(o[1], vm1, pb[4], pb[4]);
                mma16816(o[2], one2, one2, one2, one2, pb[0], pb[1]);
                mmau(o[0], va[0][0], pb[0], pb[1]);
                mmau(o[1], va[1][0], pb[0], pb[1]);
                mma16816(o[2], one2, one2, one2, one2, pb[2], pb[3]);
                mmau(o[0], va[0][1], pb[2], pb[3]);
                mmau(o[1], va[1][1], pb[2], pb[3]);
                const float r0 = rcpf(o[2][0]), r1 = rcpf(o[2][1]);
                stsm_x4_t(cb + l16 + C_Q + j * 512, pack2(o[0][0] * r0, o[0][1] * r1), pack2(o[0][2] * r0, o[0][3] * r1), pack2(o[1][0] * r0, o[1][1] * r1), pack2(o[1][2] * r0, o[1][3] * r1));
                named_arrive(2, 384);
                TSTAMP(c * 12 + 4);
#pragma unroll
                for (int s2 = PDW1; s2 < PDW; s2++) wb[s2] = lds128(ww_a + s2 * 4096);
                if (lane == 0) mbar_arrive(cb + C_BAR + B_F);
                if (warp == 4 && lane == 0) mbar_expect_tx(cb + C_BAR + B_S, S_BYTES);
            }
            named_bar(2, 384);
            TSTAMP(c * 12 + 5);
            {
                uint4 ob[4];
                ob[0] = ldsm4(u_ob0 + CO + l16); ob[1] = ldsm4(u_ob0 + CO + l16 + 512);
                ob[2] = ldsm4(u_ob1 + CO + l16); ob[3] = ldsm4(u_ob1 + CO + l16 + 512);
                float d[4][4];
#pragma unroll
                for (int a = 0; a < 4; a++)
#pragma unroll
                    for (int i = 0; i < 4; i++) d[a][i] = 0.f;
                const uint32_t ra = u_ra + CO + l8, rb = cb + C_BAR + B_R;
#pragma unroll
                for (int i = 0; i < 20; i++) {
                    const int k = w_k(i), ac = w_acc(i);
                    const uint32_t b0 = (k & 1) ? ob[k >> 1].z : ob[k >> 1].x, b1 = (k & 1) ? ob[k >> 1].w : ob[k >> 1].y;
                    if (w_smem(i)) {
                        const int s = w_slot(i);
                        mmau(d[ac], wb[s % PDW], b0, b1);
                        if (s + PDW < NSW) wb[s % PDW] = lds128(ww_a + (s + PDW) * 4096);
                    } else mmau(d[ac], wr[NRQ + w_slot(i)], b0, b1);
                    if (i == 9) {
                        const uint32_t rs = u_ra + CO + l4 + 4096 + (warp & 1) * 128;
                        st_async_u32(rs + oe, pack2(d[2][0], d[2][1]), rb + 16 + oe);
                        st_async_u32(rs + oo, pack2(d[2][2], d[2][3]), rb + 16 + oo);
                    }
                    if (i == 17) st_async_v2(ra + od, pack2(d[0][0], d[0][1]), pack2(d[0][2], d[0][3]), rb + od);
                }
                st_async_v2(ra + 2048 + od, pack2(d[1][0] + d[3][0], d[1][1] + d[3][1]), pack2(d[1][2] + d[3][2], d[1][3] + d[3][3]), rb + 8 + od);
                TSTAMP(c * 12 + 6);
#pragma unroll
                for (int s = 0; s < PDQ; s++) qb[s] = lds128(wq_a + s * 4096);
            }
        };
#pragma unroll 1
        for (int t = 0; t < NTICK; t++) {
            if (t < NSEG) tick(IC<0>{}, t);
            if (t >= LAG) tick(IC<1>{}, t - LAG);
        }
    } else {
        asm volatile("setmaxnreg.dec.sync.aligned.u32 40;");
        const int s = warp - 8;
        cluster_sync_all();
        if (s < 3) {
#pragma unroll 1
            for (int hs = 0; hs < 2 * NTICK; hs++) {
                const int c = hs & 1, t = hs >> 1;
                const int n = t - c * LAG;
                if (n < 0 || n >= NSEG - 1) continue;
                const uint32_t cb = sb + O_REST + c * C_SIZE;
                const uint32_t par = (uint32_t)(n & 1);
                const uint32_t tag = (uint32_t)(n % 13) + 1u;
                uint32_t* xb = g_xc + (size_t)((c * 2 + par) * CL + r) * (NCLU * 320) + s * 128;
                const uint32_t ra = cb + C_RED + s * 2048 + lane * (s < 2 ? 8 : 4);
                mwait(cb + C_BAR + B_R + s * 8, par);
                TSTAMP(c * 12 + 7);
                uint4 p[4];
                if (s < 2) {
#pragma unroll
                    for (int i = 0; i < 4; i++) {
                        const uint2 a = lds64(ra + i * 512), b = lds64(ra + i * 512 + 256);
                        p[i] = make_uint4(a.x, a.y, b.x, b.y);
                    }
                } else {
#pragma unroll
                    for (int i = 0; i < 4; i++) p[i] = make_uint4(lds32(ra + i * 512), lds32(ra + i * 512 + 128), lds32(ra + i * 512 + 256), lds32(ra + i * 512 + 384));
                }
                if (lane == 0) mbar_expect_tx(cb + C_BAR + B_R + s * 8, 2048);
                uint32_t m0, m1;
                if (s < 2) {
                    float f0 = 0.f, f1 = 0.f, f2 = 0.f, f3 = 0.f;
#pragma unroll
                    for (int i = 0; i < 4; i++) {
                        f0 += blo(p[i].x) + blo(p[i].z); f1 += bhi(p[i].x) + bhi(p[i].z);
                        f2 += blo(p[i].y) + blo(p[i].w); f3 += bhi(p[i].y) + bhi(p[i].w);
                    }
                    xb += lane * 4;
                    const uint32_t u0 = (__float_as_uint(f0) & ~0xFu) | tag, u1 = (__float_as_uint(f1) & ~0xFu) | tag;
                    const uint32_t u2 = (__float_as_uint(f2) & ~0xFu) | tag, u3 = (__float_as_uint(f3) & ~0xFu) | tag;
                    st_relaxed_v4(xb + cq * 320, u0, u1, u2, u3);
                    TSTAMP(c * 12 + 8);
                    xdelay();
                    uint4 x[NCLU];
#pragma unroll
                    for (int k = 0; k < NCLU; k++) x[k] = make_uint4(u0, u1, u2, u3);
                    int guard = 0;
                    bool first = true;
                    while (true) {
                        bool ok = true;
#pragma unroll
                        for (int k = 0; k < NCLU; k++) {
                            const bool okk = k == cq || (!first && ((x[k].x ^ tag) | (x[k].y ^ tag) | (x[k].z ^ tag) | (x[k].w ^ tag)) << 28 == 0);
                            if (!okk) { x[k] = ld_relaxed_v4(xb + k * 320); ok = false; }
                        }
                        first = false;
                        if (__all_sync(0xffffffffu, ok) || ++guard > SPIN_LIMIT) break;
                    }
                    TVAL(c * 12 + 11, guard);
                    f0 = f1 = f2 = f3 = 0.f;
#pragma unroll
                    for (int k = 0; k < NCLU; k++) {
                        f0 += __uint_as_float(x[k].x & ~0xFu); f1 += __uint_as_float(x[k].y & ~0xFu);
                        f2 += __uint_as_float(x[k].z & ~0xFu); f3 += __uint_as_float(x[k].w & ~0xFu);
                    }
                    m0 = movmat(pack2(f0, f1)); m1 = movmat(pack2(f2, f3));
                } else {
                    float f0 = 0.f, f1 = 0.f;
#pragma unroll
                    for (int i = 0; i < 4; i++) {
                        f0 += (blo(p[i].x) + blo(p[i].y)) + (blo(p[i].z) + blo(p[i].w));
                        f1 += (bhi(p[i].x) + bhi(p[i].y)) + (bhi(p[i].z) + bhi(p[i].w));
                    }
                    xb += lane * 2;
                    const uint32_t u0 = (__float_as_uint(f0) & ~0xFu) | tag, u1 = (__float_as_uint(f1) & ~0xFu) | tag;
                    st_relaxed_v2(xb + cq * 320, u0, u1);
                    TSTAMP(c * 12 + 8);
                    xdelay();
                    uint2 x[NCLU];
#pragma unroll
                    for (int k = 0; k < NCLU; k++) x[k] = make_uint2(u0, u1);
                    int guard = 0;
                    bool first = true;
                    while (true) {
                        bool ok = true;
#pragma unroll
                        for (int k = 0; k < NCLU; k++) {
                            const bool okk = k == cq || (!first && ((x[k].x ^ tag) | (x[k].y ^ tag)) << 28 == 0);
                            if (!okk) { x[k] = ld_relaxed_v2(xb + k * 320); ok = false; }
                        }
                        first = false;
                        if (__all_sync(0xffffffffu, ok) || ++guard > SPIN_LIMIT) break;
                    }
                    TVAL(c * 12 + 11, guard);
                    f0 = f1 = 0.f;
#pragma unroll
                    for (int k = 0; k < NCLU; k++) { f0 += __uint_as_float(x[k].x & ~0xFu); f1 += __uint_as_float(x[k].y & ~0xFu); }
                    m0 = movmat(pack2(f0, f1)); m1 = 0;
                }
                TSTAMP(c * 12 + 9);
                const uint32_t ma = cb + C_MEM + (s < 2 ? lane * 8 + (hf * 2 + s) * 256 : 1024 + hf * 128 + lane * 4), bm = cb + C_BAR;
                if (s < 2) {
#pragma unroll
                    for (int G = 0; G < 8; G++)
#pragma unroll
                        for (int b = 0; b < 2; b++) {
                            const uint32_t dd = mapa(sb, (uint32_t)(((r + 2 * G) & 15) ^ b)) - sb;
                            st_async_v2(ma + G * 1280 + dd, m0, m1, bm + G * 8 + dd);
                        }
                } else {
#pragma unroll
                    for (int G = 0; G < 8; G++)
#pragma unroll
                        for (int b = 0; b < 2; b++) {
                            const uint32_t dd = mapa(sb, (uint32_t)(((r + 2 * G) & 15) ^ b)) - sb;
                            st_async_u32(ma + G * 1280 + dd, m0, bm + G * 8 + dd);
                        }
                }
                TSTAMP(c * 12 + 10);
            }
        } else {
            auto fetch = [&](int c, int seg) {
                if (lane == 0) {
                    if (seg % CSEG == 0) {
                        int guard = 0;
                        while (ld_acquire(FLG(F_KV + c * NCHK + seg / CSEG)) < A.kv_target && ++guard < SPIN_LIMIT) __nanosleep(64);
                    }
                    asm volatile("fence.proxy.async;" ::: "memory");
                    const uint32_t cb = sb + O_REST + c * C_SIZE;
                    const uint32_t bt = cb + C_BAR + B_T, d = cb + C_TOK;
                    mbar_expect_tx(bt, 12288);
                    const CUtensorMap* mk = &A.tk[c];
                    const CUtensorMap* mv = &A.tv[c];
                    asm volatile("cp.async.bulk.tensor.2d.shared::cluster.global.mbarrier::complete_tx::bytes [%0], [%1, {%3, %4}], [%2];" ::"r"(d),
                                 "l"(mk), "r"(bt), "r"(h * DH + hf * 64), "r"(seg * SEG) : "memory");
#pragma unroll
                    for (int i = 0; i < 2; i++)
                        asm volatile("cp.async.bulk.tensor.2d.shared::cluster.global.mbarrier::complete_tx::bytes [%0], [%1, {%3, %4}], [%2];" ::"r"(d + 4096 + i * 4096),
                                     "l"(mv), "r"(bt), "r"(h * DH + i * 64), "r"(seg * SEG) : "memory");
                }
                __syncwarp();
            };
            fetch(0, 0);
#pragma unroll 1
            for (int hs = 0; hs < 2 * NTICK; hs++) {
                const int c = hs & 1, t = hs >> 1;
                const int n = t - c * LAG;
                if (n < -1 || n >= NSEG) continue;
                if (n >= 0) {
                    const uint32_t cb = sb + O_REST + c * C_SIZE;
                    mwait(cb + C_BAR + B_F, (uint32_t)(n & 1));
                    uint4* fd = g_kvf + (size_t)((c * NSEG + n) * NH + h) * 256 + hf * 64 + lane;
#pragma unroll
                    for (int i = 0; i < 2; i++) {
                        const uint4 k0 = ldsm4(cb + C_K + i * 1024 + lane * 16), k1 = ldsm4(cb + C_K + i * 1024 + 512 + lane * 16);
                        fd[i * 32] = make_uint4(badd2(k0.x, k0.z), badd2(k0.y, k0.w), badd2(k1.x, k1.z), badd2(k1.y, k1.w));
                        const uint32_t va = cb + C_V + hf * 2048 + i * 1024 + lane * 8;
                        const uint2 v0 = lds64(va), v1 = lds64(va + 256), v2 = lds64(va + 512), v3 = lds64(va + 768);
                        fd[128 + i * 32] = make_uint4(badd2(v0.x, v1.x), badd2(v0.y, v1.y), badd2(v2.x, v3.x), badd2(v2.y, v3.y));
                    }
                    if (blockIdx.x == 0 && lane == 0 && (c == 0 || t >= NSEG)) asm volatile("st.relaxed.gpu.global.u32 [%0], %1;" ::"l"(FLG(F_PROG)), "r"(t + 1) : "memory");
                    if ((n % CSEG) == CSEG - 1) {
                        asm volatile("fence.proxy.async;" ::: "memory");
                        __syncwarp();
                        if (lane == 0) { red_release(FLG(F_MEM + c * NCHK + n / CSEG), 1); }
                    }
                }
                if (n + 1 < NSEG - 1) fetch(c, n + 1);
            }
        }
    }
    cluster_sync_all();
}
}

namespace ni {
constexpr int KV_TGT = 32, MEM_TGT = 64, OP_TGT = 16, CONV_TGT = 80, H_TGT = 128;
constexpr int PDIST = (LAG + 3) / 4;
#define QA_PRE 3
#define KV1_W 5
#define KV1_N 16
static_assert(QA_PRE < 4, "inputs of the chunk must be complete");
#define SPLAN 0x102030
#define URGENT 1
#define POST_NS 40

#define ELECT "{\n.reg .pred p;\nelect.sync _|p, 0xffffffff;\n@p "
__device__ __forceinline__ void tma_load_2d(uint32_t dst, const CUtensorMap* map, uint32_t bar, int c0, int c1) {
    asm volatile(ELECT "cp.async.bulk.tensor.2d.shared::cluster.global.mbarrier::complete_tx::bytes [%0], [%1, {%3, %4}], [%2];\n}" ::"r"(dst),
                 "l"(map), "r"(bar), "r"(c0), "r"(c1) : "memory");
}
__device__ __forceinline__ void tma_load_2d_mc(uint32_t dst, const CUtensorMap* map, uint32_t bar, int c0, int c1) {
    asm volatile(ELECT "cp.async.bulk.tensor.2d.shared::cluster.global.mbarrier::complete_tx::bytes.multicast::cluster [%0], [%1, {%3, %4}], [%2], %5;\n}" ::"r"(dst),
                 "l"(map), "r"(bar), "r"(c0), "r"(c1), "h"((unsigned short)3) : "memory");
}
__device__ __forceinline__ void tma_load_3d(uint32_t dst, const CUtensorMap* map, uint32_t bar, int c1, int c2) {
    asm volatile(ELECT "cp.async.bulk.tensor.3d.shared::cluster.global.mbarrier::complete_tx::bytes [%0], [%1, {%5, %3, %4}], [%2];\n}" ::"r"(dst),
                 "l"(map), "r"(bar), "r"(c1), "r"(c2), "r"(0) : "memory");
}
__device__ __forceinline__ void tma_load_3d_mc(uint32_t dst, const CUtensorMap* map, uint32_t bar, int c1, int c2) {
    asm volatile(ELECT "cp.async.bulk.tensor.3d.shared::cluster.global.mbarrier::complete_tx::bytes.multicast::cluster [%0], [%1, {%6, %3, %4}], [%2], %5;\n}" ::"r"(dst),
                 "l"(map), "r"(bar), "r"(c1), "r"(c2), "h"((unsigned short)3), "r"(0) : "memory");
}
__device__ __forceinline__ void bulk_load(uint32_t dst, const void* src, uint32_t bytes, uint32_t bar) {
    asm volatile(ELECT "cp.async.bulk.shared::cluster.global.mbarrier::complete_tx::bytes [%0], [%1], %2, [%3];\n}" ::"r"(dst), "l"(src), "r"(bytes), "r"(bar) : "memory");
}
__device__ __forceinline__ void expect_tx1(uint32_t bar, uint32_t bytes) {
    asm volatile(ELECT "mbarrier.arrive.expect_tx.shared::cta.b64 _, [%0], %1;\n}" ::"r"(bar), "r"(bytes) : "memory");
}
__device__ __forceinline__ void wg_fence() { asm volatile("wgmma.fence.sync.aligned;" ::: "memory"); }
__device__ __forceinline__ void wg_commit() { asm volatile("wgmma.commit_group.sync.aligned;" ::: "memory"); }
template <int N> __device__ __forceinline__ void wg_wait() { asm volatile("wgmma.wait_group.sync.aligned %0;" ::"n"(N) : "memory"); }
__device__ __forceinline__ uint64_t make_desc(uint32_t addr, uint32_t lbo, uint32_t sbo) {
    return (uint64_t)((addr & 0x3FFFF) >> 4) | ((uint64_t)((lbo & 0x3FFFF) >> 4) << 16) |
           ((uint64_t)((sbo & 0x3FFFF) >> 4) << 32) | (1ull << 62);
}
__device__ __forceinline__ void wgmma_m64n256k16(float* d, uint64_t da, uint64_t db) {
    asm volatile("{\n.reg .pred p;\nsetp.ne.b32 p, 1, 0;\n"
                 "wgmma.mma_async.sync.aligned.m64n256k16.f32.bf16.bf16 {%0, %1, %2, %3, %4, %5, %6, %7, %8, %9, %10, %11, %12, %13, %14, %15, %16, %17, %18, %19, %20, %21, %22, %23, %24, %25, %26, %27, %28, %29, %30, %31, %32, %33, %34, %35, %36, %37, %38, %39, %40, %41, %42, %43, %44, %45, %46, %47, %48, %49, %50, %51, %52, %53, %54, %55, %56, %57, %58, %59, %60, %61, %62, %63, %64, %65, %66, %67, %68, %69, %70, %71, %72, %73, %74, %75, %76, %77, %78, %79, %80, %81, %82, %83, %84, %85, %86, %87, %88, %89, %90, %91, %92, %93, %94, %95, %96, %97, %98, %99, %100, %101, %102, %103, %104, %105, %106, %107, %108, %109, %110, %111, %112, %113, %114, %115, %116, %117, %118, %119, %120, %121, %122, %123, %124, %125, %126, %127}, %128, %129, p, 1, 1, 0, 1;\n}\n"
                 : "+f"(d[0]), "+f"(d[1]), "+f"(d[2]), "+f"(d[3]), "+f"(d[4]), "+f"(d[5]), "+f"(d[6]), "+f"(d[7]), "+f"(d[8]), "+f"(d[9]), "+f"(d[10]), "+f"(d[11]), "+f"(d[12]), "+f"(d[13]), "+f"(d[14]), "+f"(d[15]), "+f"(d[16]), "+f"(d[17]), "+f"(d[18]), "+f"(d[19]), "+f"(d[20]), "+f"(d[21]), "+f"(d[22]), "+f"(d[23]), "+f"(d[24]), "+f"(d[25]), "+f"(d[26]), "+f"(d[27]), "+f"(d[28]), "+f"(d[29]), "+f"(d[30]), "+f"(d[31]), "+f"(d[32]), "+f"(d[33]), "+f"(d[34]), "+f"(d[35]), "+f"(d[36]), "+f"(d[37]), "+f"(d[38]), "+f"(d[39]), "+f"(d[40]), "+f"(d[41]), "+f"(d[42]), "+f"(d[43]), "+f"(d[44]), "+f"(d[45]), "+f"(d[46]), "+f"(d[47]), "+f"(d[48]), "+f"(d[49]), "+f"(d[50]), "+f"(d[51]), "+f"(d[52]), "+f"(d[53]), "+f"(d[54]), "+f"(d[55]), "+f"(d[56]), "+f"(d[57]), "+f"(d[58]), "+f"(d[59]), "+f"(d[60]), "+f"(d[61]), "+f"(d[62]), "+f"(d[63]), "+f"(d[64]), "+f"(d[65]), "+f"(d[66]), "+f"(d[67]), "+f"(d[68]), "+f"(d[69]), "+f"(d[70]), "+f"(d[71]), "+f"(d[72]), "+f"(d[73]), "+f"(d[74]), "+f"(d[75]), "+f"(d[76]), "+f"(d[77]), "+f"(d[78]), "+f"(d[79]), "+f"(d[80]), "+f"(d[81]), "+f"(d[82]), "+f"(d[83]), "+f"(d[84]), "+f"(d[85]), "+f"(d[86]), "+f"(d[87]), "+f"(d[88]), "+f"(d[89]), "+f"(d[90]), "+f"(d[91]), "+f"(d[92]), "+f"(d[93]), "+f"(d[94]), "+f"(d[95]), "+f"(d[96]), "+f"(d[97]), "+f"(d[98]), "+f"(d[99]), "+f"(d[100]), "+f"(d[101]), "+f"(d[102]), "+f"(d[103]), "+f"(d[104]), "+f"(d[105]), "+f"(d[106]), "+f"(d[107]), "+f"(d[108]), "+f"(d[109]), "+f"(d[110]), "+f"(d[111]), "+f"(d[112]), "+f"(d[113]), "+f"(d[114]), "+f"(d[115]), "+f"(d[116]), "+f"(d[117]), "+f"(d[118]), "+f"(d[119]), "+f"(d[120]), "+f"(d[121]), "+f"(d[122]), "+f"(d[123]), "+f"(d[124]), "+f"(d[125]), "+f"(d[126]), "+f"(d[127])
                 : "l"(da), "l"(db));
}
__device__ __forceinline__ void wgmma_m64n256k16_first(float* d, uint64_t da, uint64_t db) {
    asm volatile("{\n.reg .pred p;\nsetp.ne.b32 p, 0, 0;\n"
                 "wgmma.mma_async.sync.aligned.m64n256k16.f32.bf16.bf16 {%0, %1, %2, %3, %4, %5, %6, %7, %8, %9, %10, %11, %12, %13, %14, %15, %16, %17, %18, %19, %20, %21, %22, %23, %24, %25, %26, %27, %28, %29, %30, %31, %32, %33, %34, %35, %36, %37, %38, %39, %40, %41, %42, %43, %44, %45, %46, %47, %48, %49, %50, %51, %52, %53, %54, %55, %56, %57, %58, %59, %60, %61, %62, %63, %64, %65, %66, %67, %68, %69, %70, %71, %72, %73, %74, %75, %76, %77, %78, %79, %80, %81, %82, %83, %84, %85, %86, %87, %88, %89, %90, %91, %92, %93, %94, %95, %96, %97, %98, %99, %100, %101, %102, %103, %104, %105, %106, %107, %108, %109, %110, %111, %112, %113, %114, %115, %116, %117, %118, %119, %120, %121, %122, %123, %124, %125, %126, %127}, %128, %129, p, 1, 1, 0, 1;\n}\n"
                 : "=f"(d[0]), "=f"(d[1]), "=f"(d[2]), "=f"(d[3]), "=f"(d[4]), "=f"(d[5]), "=f"(d[6]), "=f"(d[7]), "=f"(d[8]), "=f"(d[9]), "=f"(d[10]), "=f"(d[11]), "=f"(d[12]), "=f"(d[13]), "=f"(d[14]), "=f"(d[15]), "=f"(d[16]), "=f"(d[17]), "=f"(d[18]), "=f"(d[19]), "=f"(d[20]), "=f"(d[21]), "=f"(d[22]), "=f"(d[23]), "=f"(d[24]), "=f"(d[25]), "=f"(d[26]), "=f"(d[27]), "=f"(d[28]), "=f"(d[29]), "=f"(d[30]), "=f"(d[31]), "=f"(d[32]), "=f"(d[33]), "=f"(d[34]), "=f"(d[35]), "=f"(d[36]), "=f"(d[37]), "=f"(d[38]), "=f"(d[39]), "=f"(d[40]), "=f"(d[41]), "=f"(d[42]), "=f"(d[43]), "=f"(d[44]), "=f"(d[45]), "=f"(d[46]), "=f"(d[47]), "=f"(d[48]), "=f"(d[49]), "=f"(d[50]), "=f"(d[51]), "=f"(d[52]), "=f"(d[53]), "=f"(d[54]), "=f"(d[55]), "=f"(d[56]), "=f"(d[57]), "=f"(d[58]), "=f"(d[59]), "=f"(d[60]), "=f"(d[61]), "=f"(d[62]), "=f"(d[63]), "=f"(d[64]), "=f"(d[65]), "=f"(d[66]), "=f"(d[67]), "=f"(d[68]), "=f"(d[69]), "=f"(d[70]), "=f"(d[71]), "=f"(d[72]), "=f"(d[73]), "=f"(d[74]), "=f"(d[75]), "=f"(d[76]), "=f"(d[77]), "=f"(d[78]), "=f"(d[79]), "=f"(d[80]), "=f"(d[81]), "=f"(d[82]), "=f"(d[83]), "=f"(d[84]), "=f"(d[85]), "=f"(d[86]), "=f"(d[87]), "=f"(d[88]), "=f"(d[89]), "=f"(d[90]), "=f"(d[91]), "=f"(d[92]), "=f"(d[93]), "=f"(d[94]), "=f"(d[95]), "=f"(d[96]), "=f"(d[97]), "=f"(d[98]), "=f"(d[99]), "=f"(d[100]), "=f"(d[101]), "=f"(d[102]), "=f"(d[103]), "=f"(d[104]), "=f"(d[105]), "=f"(d[106]), "=f"(d[107]), "=f"(d[108]), "=f"(d[109]), "=f"(d[110]), "=f"(d[111]), "=f"(d[112]), "=f"(d[113]), "=f"(d[114]), "=f"(d[115]), "=f"(d[116]), "=f"(d[117]), "=f"(d[118]), "=f"(d[119]), "=f"(d[120]), "=f"(d[121]), "=f"(d[122]), "=f"(d[123]), "=f"(d[124]), "=f"(d[125]), "=f"(d[126]), "=f"(d[127])
                 : "l"(da), "l"(db));
}
__device__ __forceinline__ void wgmma_rs_m64n128k16(float* d, const uint32_t* a, uint64_t db) {
    asm volatile("{\n.reg .pred p;\nsetp.ne.b32 p, 1, 0;\n"
                 "wgmma.mma_async.sync.aligned.m64n128k16.f32.bf16.bf16 {%0, %1, %2, %3, %4, %5, %6, %7, %8, %9, %10, %11, %12, %13, %14, %15, %16, %17, %18, %19, %20, %21, %22, %23, %24, %25, %26, %27, %28, %29, %30, %31, %32, %33, %34, %35, %36, %37, %38, %39, %40, %41, %42, %43, %44, %45, %46, %47, %48, %49, %50, %51, %52, %53, %54, %55, %56, %57, %58, %59, %60, %61, %62, %63}, {%64, %65, %66, %67}, %68, p, 1, 1, 1;\n}\n"
                 : "+f"(d[0]), "+f"(d[1]), "+f"(d[2]), "+f"(d[3]), "+f"(d[4]), "+f"(d[5]), "+f"(d[6]), "+f"(d[7]), "+f"(d[8]), "+f"(d[9]), "+f"(d[10]), "+f"(d[11]), "+f"(d[12]), "+f"(d[13]), "+f"(d[14]), "+f"(d[15]), "+f"(d[16]), "+f"(d[17]), "+f"(d[18]), "+f"(d[19]), "+f"(d[20]), "+f"(d[21]), "+f"(d[22]), "+f"(d[23]), "+f"(d[24]), "+f"(d[25]), "+f"(d[26]), "+f"(d[27]), "+f"(d[28]), "+f"(d[29]), "+f"(d[30]), "+f"(d[31]), "+f"(d[32]), "+f"(d[33]), "+f"(d[34]), "+f"(d[35]), "+f"(d[36]), "+f"(d[37]), "+f"(d[38]), "+f"(d[39]), "+f"(d[40]), "+f"(d[41]), "+f"(d[42]), "+f"(d[43]), "+f"(d[44]), "+f"(d[45]), "+f"(d[46]), "+f"(d[47]), "+f"(d[48]), "+f"(d[49]), "+f"(d[50]), "+f"(d[51]), "+f"(d[52]), "+f"(d[53]), "+f"(d[54]), "+f"(d[55]), "+f"(d[56]), "+f"(d[57]), "+f"(d[58]), "+f"(d[59]), "+f"(d[60]), "+f"(d[61]), "+f"(d[62]), "+f"(d[63])
                 : "r"(a[0]), "r"(a[1]), "r"(a[2]), "r"(a[3]), "l"(db));
}
__device__ __forceinline__ void wgmma_rs_m64n128k16_first(float* d, const uint32_t* a, uint64_t db) {
    asm volatile("{\n.reg .pred p;\nsetp.ne.b32 p, 0, 0;\n"
                 "wgmma.mma_async.sync.aligned.m64n128k16.f32.bf16.bf16 {%0, %1, %2, %3, %4, %5, %6, %7, %8, %9, %10, %11, %12, %13, %14, %15, %16, %17, %18, %19, %20, %21, %22, %23, %24, %25, %26, %27, %28, %29, %30, %31, %32, %33, %34, %35, %36, %37, %38, %39, %40, %41, %42, %43, %44, %45, %46, %47, %48, %49, %50, %51, %52, %53, %54, %55, %56, %57, %58, %59, %60, %61, %62, %63}, {%64, %65, %66, %67}, %68, p, 1, 1, 1;\n}\n"
                 : "=f"(d[0]), "=f"(d[1]), "=f"(d[2]), "=f"(d[3]), "=f"(d[4]), "=f"(d[5]), "=f"(d[6]), "=f"(d[7]), "=f"(d[8]), "=f"(d[9]), "=f"(d[10]), "=f"(d[11]), "=f"(d[12]), "=f"(d[13]), "=f"(d[14]), "=f"(d[15]), "=f"(d[16]), "=f"(d[17]), "=f"(d[18]), "=f"(d[19]), "=f"(d[20]), "=f"(d[21]), "=f"(d[22]), "=f"(d[23]), "=f"(d[24]), "=f"(d[25]), "=f"(d[26]), "=f"(d[27]), "=f"(d[28]), "=f"(d[29]), "=f"(d[30]), "=f"(d[31]), "=f"(d[32]), "=f"(d[33]), "=f"(d[34]), "=f"(d[35]), "=f"(d[36]), "=f"(d[37]), "=f"(d[38]), "=f"(d[39]), "=f"(d[40]), "=f"(d[41]), "=f"(d[42]), "=f"(d[43]), "=f"(d[44]), "=f"(d[45]), "=f"(d[46]), "=f"(d[47]), "=f"(d[48]), "=f"(d[49]), "=f"(d[50]), "=f"(d[51]), "=f"(d[52]), "=f"(d[53]), "=f"(d[54]), "=f"(d[55]), "=f"(d[56]), "=f"(d[57]), "=f"(d[58]), "=f"(d[59]), "=f"(d[60]), "=f"(d[61]), "=f"(d[62]), "=f"(d[63])
                 : "r"(a[0]), "r"(a[1]), "r"(a[2]), "r"(a[3]), "l"(db));
}

struct BulkMaps { CUtensorMap h, h2, wq, wk, wv, wo, kv, lu; };
struct BulkArgs {
    const bf16 *x, *ssmk, *ssmD, *Bk, *Bv, *shiftk;
    bf16* out;
};
enum { T_KV = 0, T_QA, T_CONV, T_ATT, T_POST, T_LN0 };
constexpr int MAXG = 52, SENT = MAXG - 1;
struct Sched { uint32_t chk[MAXG * 4]; uint32_t info[MAXG]; int sbeg[8]; };

constexpr int BK_STAGES = 4, BK_STAGE_BYTES = 49152, TSLOTS = 4;
struct BulkSmemTail {
    unsigned long long full[BK_STAGES], empty[BK_STAGES], tfull[TSLOTS], tempty[TSLOTS], sfull[4], sempty[4];
    int task[TSLOTS];
    uint32_t tab[MAXG * 5];
};
constexpr int BULK_STG = BK_STAGES * BK_STAGE_BYTES;
constexpr int BULK_TAIL = BULK_STG + 32768;
constexpr int BULK_SMEM = BULK_TAIL + (int)sizeof(BulkSmemTail);
static_assert(BULK_SMEM <= 232448, "bulk smem");
#define PACE 0
#define REG_C 224
#define REG_P 56

#define BT(lead, type, l, c, k)
#define TT(k)
#define FT(k)
#define TTV(k, v)
__device__ __forceinline__ void tma_store_2d(const CUtensorMap* map, uint32_t src, int c0, int c1) {
    asm volatile("cp.async.bulk.tensor.2d.global.shared::cta.bulk_group [%0, {%2, %3}], [%1];" ::"l"(map), "r"(src), "r"(c0), "r"(c1) : "memory");
}
__device__ __forceinline__ void bulk_commit() { asm volatile("cp.async.bulk.commit_group;" ::: "memory"); }
template <int N> __device__ __forceinline__ void bulk_wait_read() { asm volatile("cp.async.bulk.wait_group.read %0;" ::"n"(N) : "memory"); }
template <int N> __device__ __forceinline__ void bulk_wait() { asm volatile("cp.async.bulk.wait_group %0;" ::"n"(N) : "memory"); }
__device__ __forceinline__ void mbar_arrive_cluster(uint32_t bar) {
    asm volatile("mbarrier.arrive.shared::cluster.b64 _, [%0];" ::"r"(bar) : "memory");
}
__device__ __forceinline__ void stsm_x4(uint32_t addr, uint32_t r0, uint32_t r1, uint32_t r2, uint32_t r3) {
    asm volatile("stmatrix.sync.aligned.m8n8.x4.shared.b16 [%0], {%1,%2,%3,%4};" ::"r"(addr), "r"(r0), "r"(r1), "r"(r2), "r"(r3) : "memory");
}
__device__ __forceinline__ void mma1688(float* c, uint32_t a0, uint32_t a1, uint32_t b0) {
    asm("mma.sync.aligned.m16n8k8.row.col.f32.bf16.bf16.f32 {%0,%1,%2,%3}, {%4,%5}, {%6}, {%0,%1,%2,%3};"
        : "+f"(c[0]), "+f"(c[1]), "+f"(c[2]), "+f"(c[3]) : "r"(a0), "r"(a1), "r"(b0));
}
__device__ __forceinline__ int ld_relaxed(const int* p) {
    int v;
    asm volatile("ld.relaxed.gpu.global.u32 %0, [%1];" : "=r"(v) : "l"(p) : "memory");
    return v;
}
__device__ __forceinline__ void flag_wait(const int* f, int tgt, int ns) {
    int guard = 0;
    while (ld_relaxed(f) < tgt && ++guard < 4000000) __nanosleep(ns);
}
__device__ __forceinline__ void fence_async() { asm volatile("fence.proxy.async.global;" ::: "memory"); }
__device__ __forceinline__ uint32_t bmul2(uint32_t a, uint32_t b) { uint32_t r; asm("mul.rn.bf16x2 %0, %1, %2;" : "=r"(r) : "r"(a), "r"(b)); return r; }
__device__ __forceinline__ uint32_t bsum2(uint32_t a, uint32_t b) { uint32_t r; asm("add.rn.bf16x2 %0, %1, %2;" : "=r"(r) : "r"(a), "r"(b)); return r; }
__device__ __forceinline__ uint32_t bmax2(uint32_t a, uint32_t b) { uint32_t r; asm("max.bf16x2 %0, %1, %2;" : "=r"(r) : "r"(a), "r"(b)); return r; }
__device__ __forceinline__ uint32_t rscore(float a, float b) {
    const uint32_t u = pack2(a, b);
    return pack2(blo(u) * 0.08838834764831845f, bhi(u) * 0.08838834764831845f);
}
template <int STRIDE> __device__ __forceinline__ void ld5(uint32_t* w, const bf16* p) {
#pragma unroll
    for (int r = 0; r < 5; r++) { const uint2 v = __ldcg(reinterpret_cast<const uint2*>(p + r * STRIDE)); w[2 * r] = v.x; w[2 * r + 1] = v.y; }
}
__device__ __forceinline__ void st5(bf16* p, const uint32_t* w) {
#pragma unroll
    for (int r = 0; r < 5; r++) *reinterpret_cast<uint2*>(p + r * 128) = make_uint2(w[2 * r], w[2 * r + 1]);
}
__device__ __forceinline__ void ln_row(const uint32_t* x, uint32_t* y) {
    float s = 0.f;
#pragma unroll
    for (int i = 0; i < 10; i++) s += blo(x[i]) + bhi(x[i]);
#pragma unroll
    for (int o = 16; o > 0; o >>= 1) s += __shfl_xor_sync(0xffffffffu, s, o);
    const float mean = s * (1.0f / DM);
    float q = 0.f;
#pragma unroll
    for (int i = 0; i < 10; i++) { const float d0 = blo(x[i]) - mean, d1 = bhi(x[i]) - mean; q = fmaf(d0, d0, q); q = fmaf(d1, d1, q); }
#pragma unroll
    for (int o = 16; o > 0; o >>= 1) q += __shfl_xor_sync(0xffffffffu, q, o);
    const uint32_t nm = pack2(-mean, -mean);
    float sq;
    asm("sqrt.approx.ftz.f32 %0, %1;" : "=f"(sq) : "f"(rbf(rbf(q * (1.0f / DM)) + 1e-5f)));
    const float rd = rcpf(rbf(sq));
#pragma unroll
    for (int i = 0; i < 10; i++) { const uint32_t d = bsum2(x[i], nm); y[i] = pack2(blo(d) * rd, bhi(d) * rd); }
}
__device__ __forceinline__ void red_add8(uint4* p, uint32_t a, uint32_t b, uint32_t c, uint32_t d) {
    asm volatile("red.relaxed.gpu.global.add.noftz.v4.bf16x2 [%0], {%1,%2,%3,%4};" ::"l"(p), "r"(a), "r"(b), "r"(c), "r"(d) : "memory");
}
__device__ __forceinline__ void part_sum(const uint4& v, const uint4& w, int lane, uint32_t& x0, uint32_t& x1) {
    float t[8];
    t[0] = blo(v.x) + blo(w.x); t[1] = bhi(v.x) + bhi(w.x); t[2] = blo(v.y) + blo(w.y); t[3] = bhi(v.y) + bhi(w.y);
    t[4] = blo(v.z) + blo(w.z); t[5] = bhi(v.z) + bhi(w.z); t[6] = blo(v.w) + blo(w.w); t[7] = bhi(v.w) + bhi(w.w);
#pragma unroll
    for (int i = 0; i < 4; i++) t[i] = (lane < 16 ? t[i] : t[4 + i]) + __shfl_xor_sync(0xffffffffu, lane < 16 ? t[4 + i] : t[i], 16);
    const uint32_t r0 = pack2(t[0], t[1]), r1 = pack2(t[2], t[3]);
    const uint32_t ex = __shfl_xor_sync(0xffffffffu, (lane & 1) ? r0 : r1, 1);
    x0 = (lane & 1) ? ex : r0; x1 = (lane & 1) ? r1 : ex;
}
__device__ __forceinline__ void post_row(int l, int row, int lane, const bf16* xin, bf16* xout) {
    uint32_t x[10], y[10], n[10];
    const int cl = (lane & 12) * 8 + (lane >> 4) * 16 + (lane & 1) * 8 + (lane & 2) * 2;
    uint4* pp = reinterpret_cast<uint4*>(g_part + (size_t)(l * PROWS + (row & (PROWS - 1))) * (PG * DM)) + (lane & 15) + (lane >> 4) * 80;
    int* f = FLG(F_OP + l * NCHK + (row >> 7));
    flag_wait(FLG(F_CONV + (row >> 10)), CONV_TGT, 200);
    ld5<128>(x, xin + (size_t)row * DM + cl);
    flag_wait(f + 4, OP_TGT, POST_NS);
    {
        uint4 v[10];
#pragma unroll
        for (int i = 0; i < 10; i++) v[i] = __ldcg(pp + (i >> 1) * 16 + (i & 1) * 160);
#pragma unroll
        for (int r = 0; r < 5; r++) {
            uint32_t s0, s1;
            part_sum(v[2 * r], v[2 * r + 1], lane, s0, s1);
            if (r == 1) ld5<16 * S_LEN * 8>(y, g_Y + ((size_t)(cl >> 3) * S_LEN + (row ^ ((row >> 6) & 7))) * 8 + (cl & 4));
            x[2 * r] = bsum2(x[2 * r], s0); x[2 * r + 1] = bsum2(x[2 * r + 1], s1);
        }
    }
    ln_row(x, n);
#pragma unroll
    for (int i = 0; i < 10; i++) x[i] = bsum2(x[i], bmul2(n[i], y[i]));
    if (l == 0) {
        ln_row(x, n);
        st5(g_h[1] + (size_t)row * DM + cl, n);
        __syncwarp();
        if (lane == 0) red_release(FLG(F_H + NCHK + (row >> 7)), 1);
    }
#pragma unroll
    for (int i = 0; i < 10; i++) pp[(i >> 1) * 16 + (i & 1) * 160] = make_uint4(0, 0, 0, 0);
    st5(xout + (size_t)row * DM + cl, x);
    __syncwarp();
    if (l && lane == 0) red_release(f + 5, 1);
}
__device__ __forceinline__ void u_unit(const bf16* Bk, const bf16* Bv, const bf16* shiftk, int unit, int lane) {
    const int t0 = (unit / 10) * 16, cp = (unit % 10) * 32 + lane;
    uint32_t kk[19], vv[16];
    const uint32_t* pk = reinterpret_cast<const uint32_t*>(Bk + (size_t)t0 * DM) + cp;
    const uint32_t* pv = reinterpret_cast<const uint32_t*>(Bv + (size_t)t0 * DM) + cp;
#pragma unroll
    for (int i = 0; i < 19; i++) kk[i] = (i >= 3 || t0 > 0) ? __ldg(pk + (i - 3) * (DM / 2)) : 0u;
#pragma unroll
    for (int i = 0; i < 16; i++) vv[i] = __ldg(pv + i * (DM / 2));
    const uint4 sh0 = __ldg(reinterpret_cast<const uint4*>(shiftk + cp * 8));
    const uint32_t s0 = __byte_perm(sh0.x, sh0.z, 0x5410), s1 = __byte_perm(sh0.x, sh0.z, 0x7632), s2 = __byte_perm(sh0.y, sh0.w, 0x5410), s3 = __byte_perm(sh0.y, sh0.w, 0x7632);
#pragma unroll
    for (int t = 0; t < 16; t++)
        vv[t] = bmul2(bsum2(bsum2(bsum2(bmul2(kk[t], s3), bmul2(kk[t + 1], s2)), bmul2(kk[t + 2], s1)), bmul2(kk[t + 3], s0)), vv[t]);
    uint4* d = reinterpret_cast<uint4*>(g_U + (size_t)(cp * 2) * S_LEN + (t0 ^ 48));
#pragma unroll
    for (int c = 0; c < 2; c++) {
        const uint32_t sel = c ? 0x7632 : 0x5410;
#pragma unroll
        for (int hh = 0; hh < 2; hh++)
            d[c * (S_LEN / 8) + hh] = make_uint4(__byte_perm(vv[15 - hh * 8], vv[14 - hh * 8], sel), __byte_perm(vv[13 - hh * 8], vv[12 - hh * 8], sel),
                                                 __byte_perm(vv[11 - hh * 8], vv[10 - hh * 8], sel), __byte_perm(vv[9 - hh * 8], vv[8 - hh * 8], sel));
    }
}
constexpr int CV_EP = 4224;
template <class F> __device__ __forceinline__ void conv_unit(uint32_t ub, uint32_t e0, uint32_t e1, uint32_t zrow, uint32_t yt, float Dv, int m, int lane, F&& nearly_done) {
    const int g = lane >> 2, tq = lane & 3;
    asm volatile("st.shared.u32 [%0], %1;" ::"r"(e0 + lane * 4), "r"(0) : "memory");
    asm volatile("st.shared.u32 [%0], %1;" ::"r"(zrow + lane * 4), "r"(0) : "memory");
    __syncwarp();
    for (int i = lane; i < CV_EP / 16; i += 32) {
        const uint4 v = lds128(e0 + i * 16);
        const uint32_t nx = i + 1 < CV_EP / 16 ? lds32(e0 + i * 16 + 16) : 0u;
        sts128(e1 + i * 16, __byte_perm(v.x, v.y, 0x5432), __byte_perm(v.y, v.z, 0x5432), __byte_perm(v.z, v.w, 0x5432), __byte_perm(v.w, nx, 0x5432));
    }
    __syncwarp();
    float acc[8][4];
#pragma unroll
    for (int n = 0; n < 8; n++)
#pragma unroll
        for (int i = 0; i < 4; i++) acc[n][i] = 0.f;
    uint32_t wb = (g & 1) ? e0 + (1 + g + 2 * tq) * 2 : e1 + (g + 2 * tq) * 2;
    uint32_t W[16], a[4][4], an[4][4];
    int row = m * 16 + (lane & 15);
    auto lda = [&](uint32_t (*d)[4]) {
        const uint32_t x = row < 0 ? zrow : ub + row * 128 + (((lane >> 4) ^ (row & 7)) << 4);
#pragma unroll
        for (int ks = 0; ks < 4; ks++) ldsm_x4(d[ks][0], d[ks][1], d[ks][2], d[ks][3], x ^ (ks << 5));
        row--;
    };
#pragma unroll
    for (int i = 0; i < 16; i++) W[i] = lds32(wb + i * 16);
    lda(a);
    const int nD = m == 0 ? 16 : 32;
#pragma unroll 2
    for (int D = 0; D < nD; D++) {
        uint32_t Wn[8];
        wb += 128;
        if (D == nD - 6) nearly_done();
        lda(an);
#pragma unroll
        for (int i = 0; i < 8; i++) Wn[i] = lds32(wb + 128 + i * 16);
#pragma unroll
        for (int ks = 0; ks < 4; ks++)
#pragma unroll
            for (int n = 0; n < 8; n++) mma16816(acc[n], a[ks][0], a[ks][1], a[ks][2], a[ks][3], W[2 * ks + n], W[2 * ks + n + 1]);
#pragma unroll
        for (int i = 0; i < 8; i++) { W[i] = W[i + 8]; W[i + 8] = Wn[i]; }
#pragma unroll
        for (int ks = 0; ks < 4; ks++)
#pragma unroll
            for (int i = 0; i < 4; i++) a[ks][i] = an[ks][i];
    }
#pragma unroll
    for (int n = 0; n < 8; n++)
#pragma unroll
        for (int r = 0; r < 2; r++) {
            const int a_ = g + r * 8, b_ = n * 8 + tq * 2;
            const int ar = m * 16 + a_, p = 62 - b_;
            const uint32_t kv = lds32(ub + ar * 128 + (((p >> 3) ^ (ar & 7)) << 4) + (p & 7) * 2);
            const float y0 = rbf(acc[n][2 * r]) + rbf(bhi(kv) * Dv), y1 = rbf(acc[n][2 * r + 1]) + rbf(blo(kv) * Dv);
            const uint32_t pk = pack2(y0, y1);
            asm volatile("st.shared.u16 [%0], %1;" ::"r"(yt + ((a_ * 64 + b_) ^ g) * 16), "h"((unsigned short)(pk & 0xffff)) : "memory");
            asm volatile("st.shared.u16 [%0], %1;" ::"r"(yt + ((a_ * 64 + b_ + 1) ^ g) * 16), "h"((unsigned short)(pk >> 16)) : "memory");
        }
}

__global__ void __launch_bounds__(384, 1) bulk_kernel(const __grid_constant__ BulkMaps M, const __grid_constant__ BulkArgs A,
                                                      const __grid_constant__ Sched SC) {
    extern __shared__ __align__(1024) unsigned char smem_raw[];
    const uint32_t sb0 = smem_u32(smem_raw);
    const uint32_t full0 = sb0 + BULK_TAIL, empty0 = full0 + 32, tfull0 = full0 + 64, tempty0 = full0 + 96, sfull = full0 + 128, sempty = full0 + 160,
                   task0 = full0 + 192, tab0 = full0 + 208;
    const int tid = threadIdx.x, wid = __shfl_sync(0xffffffffu, tid >> 5, 0), lane = tid & 31;
    const int rank = blockIdx.x & 1;
    if (tid == 0) {
        for (int i = 0; i < BK_STAGES; i++) { mbar_init(full0 + 8 * i, 1); mbar_init(empty0 + 8 * i, 4); }
        for (int i = 0; i < TSLOTS; i++) { mbar_init(tfull0 + 8 * i, 1); mbar_init(tempty0 + 8 * i, 19); }
        for (int i = 0; i < 4; i++) { mbar_init(sfull + 8 * i, 8); mbar_init(sempty + 8 * i, 1); }
        asm volatile("fence.mbarrier_init.release.cluster;" ::: "memory");
        if (rank == 1) for (int i = 0; i < TSLOTS; i++) mbar_expect_tx(tfull0 + 8 * i, 4);
        BT(true, T_LN0, 0, 0, 0);
    }
    if (tid < MAXG * 5) asm volatile("st.shared.u32 [%0], %1;" ::"r"(tab0 + tid * 4), "r"(SC.chk[tid]) : "memory");
    cluster_sync_all();
    uint32_t tc = 0, it = 0;
    if (wid < 4) {
        asm volatile("setmaxnreg.dec.sync.aligned.u32 %0;" ::"n"(REG_P));
        if (wid == 0) {
            int head = SC.sbeg[lane >> 3];
            const int hend = SC.sbeg[(lane >> 3) + 1];
            uint32_t chk = 0; int pv = (blockIdx.x >> 1) & 31, grp = (SC.sbeg[3] + (blockIdx.x >> 6)) << 2 | 3, ncode = 0, code = 3 << 6 | 2, guard = 0;
            auto acquire = [&](uint32_t bytes) -> uint32_t {
                const uint32_t s = it & 3;
                mwait(empty0 + 8 * s, ((it >> 2) & 1) ^ 1);
                it++;
                expect_tx1(full0 + 8 * s, bytes);
                return s;
            };
            auto uwait = [&](const int* f, int tgt) {
                int g2 = 0;
                while ((int)UNI(ld_relaxed(f)) < tgt && ++g2 < 4000000) __nanosleep(32);
                fence_async();
            };
#pragma unroll 1
            while (true) {
                const int type = (code >> 6) & 3;
                const int iend = type == T_KV ? 10 : (type == T_QA ? 24 : 31);
                const int jj = code & 63, g0 = (jj & 15) * 4, lc = (code >> 9) & 31;
                const bool lm = (code >> 8) & 1;
                const CUtensorMap* mb = type == T_QA ? &M.wq : (jj < 16 ? &M.wk : &M.wv);
                bool have = false, ok = (code >> 14) & 1;
                int imem = 16;
#pragma unroll 1
                for (int i = type < T_CONV ? 0 : (type == T_CONV ? 24 : 28 + jj); i < iend; i++) {
                    const int sd = (type < T_CONV ? SPLAN : 0x1230) >> 4 * min(iend - i, 7) & 15;
                    if (rank == 0 && sd) {
                        if (sd == 1) {
                            if (type == T_CONV) mwait(empty0 + 8 * (it & 3), ((it >> 2) & 1) ^ 1);
                            const int gi = head + ((lane >> 2) & 1);
                            chk = lds32(tab0 + ((gi < hend ? gi : SENT) * 4 + (lane & 3)) * 4);
                            pv = ld_relaxed(g_flags + (chk & 0xffff));
                        } else if (sd == 2) {
                            const int tgt = (int)(chk >> 16);
                            const uint32_t b = (__ballot_sync(0xffffffffu, (lane & 3) == 0 ? pv < tgt : pv >= tgt) >> (lane & 24)) & 0xff;
                            const uint32_t cand = (b & 1) ? b & 15 : b >> 4;
                            head += (b & 1) ? 0 : ((b & 16) ? 1 : 2);
                            if (head > hend || guard > 4000000) head = hend;
                            const uint32_t req = lane >= 24 ? 1 : 15;
                            grp = (int)__reduce_min_sync(0xffffffffu, (cand & req) == req ? ((uint32_t)head << 2 | (cand ^ req) >> 2 | ((cand ^ req) & 2 ? 0 : 256)) : (head < hend ? 1000u : 1004u));
                            if (grp < 1000) grp &= 255;
                            if (grp < 1000) asm volatile("{\n.reg .pred p;\nsetp.eq.u32 p, %2, 0;\n@p atom.relaxed.gpu.global.inc.u32 %0, [%1], 0x7fffffff;\n}" : "+r"(pv) : "l"(FLG(F_CNT + (grp >> 2))), "r"(lane) : "memory");
                        } else {
                            if (grp < 1000) {
                                const int tk = (int)UNI(pv);
                                have = tk < (int)(UNI(lds32(tab0 + (grp >> 2) * 16)) >> 16);
                                ncode = (int)UNI(lds32(tab0 + MAXG * 16 + (grp & ~3))) | (grp & 3) << 19 | tk;
                            } else if (grp == 1004) { have = true; ncode = -1; }
                            if (have) {
                                const uint32_t o = (tc & 3) * 4;
                                mwait(tempty0 + 2 * o, ((tc >> 2) & 1) ^ 1);
                                asm volatile(ELECT "st.shared.u32 [%0], %1;\n@p mbarrier.arrive.shared::cta.b64 _, [%2];\n"
                                             "@p st.async.weak.shared::cluster.mbarrier::complete_tx::bytes.b32 [%3], %1, [%4];\n}"
                                             ::"r"(task0 + o), "r"(ncode), "r"(tfull0 + 2 * o), "r"(mapa(task0 + o, 1)), "r"(mapa(tfull0 + 2 * o, 1)) : "memory");
                            }
                        }
                    }
                    if (i >= 28) continue;
                    if (i == 8 && type == T_QA) pv = ld_relaxed(FLG((lane & 1 ? F_MEM : F_KV) + lc));
                    if (i == 10) {
                        const uint32_t b = __ballot_sync(0xffffffffu, pv >= (lane & 1 ? MEM_TGT : KV_TGT));
                        if (b & 2) imem = 13;
                        if (!(b & 1)) uwait(FLG(F_KV + lc), KV_TGT);
                        fence_async();
                    }
                    const uint32_t s = acquire(i < 12 ? 49152 : (i == 24 || i == 27 ? 0 : 32768));
                    const uint32_t sa = sb0 + s * BK_STAGE_BYTES, fb = full0 + 8 * s;
                    if (i == 0) TT(3);
                    if (i < 10) {
                        if (lm) {
                            tma_load_3d(sa + 16384, mb, fb, i * 64, g0);
                            tma_load_3d(sa + 32768, mb, fb, i * 64, g0 + 2);
                        } else tma_load_3d_mc(sa + 16384 + rank * 16384, mb, fb, i * 64, g0 + rank * 2);
                        int d = 0;
                        if (!ok) {
                            d = 1;
                            if (i == 3) {
                                uwait(FLG(F_H + lc), H_TGT);
                                ok = true;
                                d = -3;
                                TT(4);
                            }
                        }
#pragma unroll 1
                        for (; d <= 0; d++) {
                            const uint32_t s2 = (s + d) & 3;
                            if (lm) tma_load_2d_mc(sb0 + s2 * BK_STAGE_BYTES + rank * 8192, &M.h, full0 + 8 * s2, (i + d) * 64, lc * 128 + rank * 64);
                            else tma_load_2d(sb0 + s2 * BK_STAGE_BYTES, &M.h2, full0 + 8 * s2, (i + d) * 64, lc * 128);
                        }
                    } else if (i < 13) {
#pragma unroll 1
                        for (int k = 0, bx = (i - 10) * 3; k < 3 && bx < 8; k++, bx++)
                            tma_load_2d(sa + k * 16384, &M.kv, fb, (g0 + (bx & 3)) * 64, (bx >> 2) * S_LEN + (lc & 15) * 128);
                    } else if (i < 24) {
                        const int cn = ((i - 14) >> 1) * 128, ck = g0 * 64 + (i & 1) * 128;
                        if (i > 13) {
                            if (lm) { tma_load_2d(sa, &M.wo, fb, cn, ck); tma_load_2d(sa + 16384, &M.wo, fb, cn + 64, ck); }
                            else tma_load_2d_mc(sa + rank * 16384, &M.wo, fb, cn + rank * 64, ck);
                        }
                        if (i == imem) {
                            TT(5);
                            if (i == 16) uwait(FLG(F_MEM + lc), MEM_TGT);
                            const uint32_t s2 = (s + (i >> 4)) & 3;
#pragma unroll 1
                            for (int k = 0; k < 4; k++)
                                bulk_load(sb0 + s2 * BK_STAGE_BYTES + k * 8192, g_kvf + (size_t)((lc * CSEG + k) * NH + jj * 2) * 256, 8192, full0 + 8 * s2);
                            TT(6);
                        }
                    } else if (i == 25) {
                        tma_load_2d(sa, &M.lu, fb, 0, (2 * jj + rank) * 256);
                    } else if (i == 26) {
#pragma unroll 1
                        for (int k = 0; k < 8; k++)
                            bulk_load(sa + k * CV_EP + 128, A.ssmk + (size_t)((2 * jj + rank) * 8 + k) * S_LEN, 4096, fb);
                    }
                }
                if (type != 3) TT(7);
                if (rank == 0) {
                    if (!have) {
                        if (type == 3) { guard++; __nanosleep(64); }
                        code = 3 << 6;
                        continue;
                    }
                } else {
                    const uint32_t o = (tc & 3) * 4;
                    mwait(tfull0 + 2 * o, (tc >> 2) & 1);
                    ncode = (int)UNI(lds32(task0 + o));
                    asm volatile(ELECT "mbarrier.arrive.expect_tx.shared::cta.b64 _, [%0], 4;\n@p mbarrier.arrive.shared::cluster.b64 _, [%1];\n}" ::"r"(tfull0 + 2 * o), "r"(mapa(tempty0 + 2 * o, 0)) : "memory");
                    __syncwarp();
                }
                tc++;
                if (ncode < 0) break;
                TT(0); TTV(15, ncode);
                code = ((ncode & 256) ? (2 * ncode + rank) & 63 : ncode & 63) | (ncode & 0x1c0) | ((ncode >> (rank ? 14 : 9)) & 31) << 9 | ((ncode >> (19 + rank)) & 1) << 14;
                fence_async();
            }
        } else if (wid == 1) {
            if (lane < 8) asm volatile("prefetch.tensormap [%0];" ::"l"(&M.h + lane) : "memory");
            __syncwarp();
            if (lane == 0) {
                uint32_t rc = 0;
                while (true) {
                    mwait(tfull0 + 8 * (tc & 3), (tc >> 2) & 1);
                    const int code = (int)lds32(task0 + 4 * (tc & 3));
                    mbar_arrive_cluster(mapa(tempty0 + 8 * (tc & 3), 0));
                    tc++;
                    if (code < 0) break;
                    const int type = (code >> 6) & 3;
                    const int lc = (code >> (rank ? 14 : 9)) & 31;
                    mwait(sfull + 8 * (rc & 3), (rc >> 2) & 1);
                    if (type == T_CONV) {
                        asm volatile("cp.async.bulk.global.shared::cta.bulk_group [%0], [%1], %2;" ::"l"(g_Y + (size_t)((2 * (code & 63) + rank) * S_LEN + lc * 1024) * 8), "r"(sb0 + BULK_STG), "r"(16384) : "memory");
                        bulk_commit();
                        bulk_wait<0>();
                    }
                    mbar_arrive(sempty + 8 * (rc & 3));
                    rc++;
                    FT(0);
                    red_release(type == T_QA ? FLG(F_OP + lc) + 4 : FLG((type == T_KV ? F_KV : F_CONV) + lc), 1);
                    FT(1);
                    BT(true, type, lc >> 4, lc & 15, 2);
                }
            }
        } else {
            const int nw = 2 * gridDim.x, idx = (wid - 2) * gridDim.x + blockIdx.x;
#pragma unroll 1
            for (int hh = 0; hh < 2; hh++) {
#pragma unroll 1
                for (int u = hh * 640 + idx; u < hh * 640 + 640; u += nw) u_unit(A.Bk, A.Bv, A.shiftk, u, lane);
                __syncwarp();
                if (lane == 0) red_release(FLG(F_U + hh), 1);
                BT(lane == 0, T_LN0, hh, 0, 2);
            }
#pragma unroll 1
            for (int q = 0; q < 2 * (NCHK + PDIST); q++) {
                const int l = q & 1, c = (q >> 1) - l * PDIST;
                if (c < 0 || c >= NCHK) continue;
#pragma unroll 1
                for (int rr = idx; rr < 128; rr += nw) post_row(l, c * 128 + rr, lane, l ? g_x : A.x, l ? A.out : g_x);
                BT(lane == 0, T_POST, l, c, 2);
            }
        }
    } else {
        asm volatile("setmaxnreg.inc.sync.aligned.u32 %0;" ::"n"(REG_C));
        const int cw = (wid >> 2) - 1, warp = wid & 3;
        const uint32_t wst = sb0 + BULK_STG + (cw * 4 + warp) * 4096;
        uint32_t rc = 0;
        int npend = 0;
        bool urgent = false;
        uint32_t oofs = 0;
        uint32_t qf[16][4];
        auto release = [&](int s) { if ((tid & 127) == 0) { mbar_arrive(empty0 + 8 * s); mbar_arrive_cluster(mapa(empty0 + 8 * s, rank ^ 1)); } };
        auto next = [&]() -> int { const int s = it & 3; mwait(full0 + 8 * s, (it >> 2) & 1); it++; return s; };
        auto wgbar = [&]() { if (cw == 0) named_bar(2, 128); else named_bar(3, 128); };
        auto handoff = [&]() {
            mwait(sempty + 8 * (rc & 3), ((rc >> 2) & 1) ^ 1);
            asm volatile(ELECT "mbarrier.arrive.shared::cta.b64 _, [%0];\n}" ::"r"(sfull + 8 * (rc & 3)) : "memory");
            rc++;
        };
        auto stg_free = [&]() { mwait(sempty + 8 * ((rc - 1) & 3), ((rc - 1) >> 2) & 1); };
        auto round_q = [&]() {
            if (npend > 4) {
                uint4* d = reinterpret_cast<uint4*>(g_part) + oofs;
                if (npend == 6) {
#pragma unroll
                    for (int i = 0; i < 4; i++) red_add8(d + (i >> 1) * 4 + (i & 1) * (8 * PG * DM / 8), qf[i][0], qf[i][1], qf[i][2], qf[i][3]);
                    npend = 5;
                } else {
#pragma unroll
                    for (int i = 4; i < 8; i++) red_add8(d + (i >> 1) * 4 + (i & 1) * (8 * PG * DM / 8), qf[i][0], qf[i][1], qf[i][2], qf[i][3]);
                    npend = 0;
                    handoff();
                }
                return;
            }
            const uint32_t sst = wst + (lane & 15) * 128 + (((lane >> 4) ^ (lane & 7)) << 4) + (npend & 1) * 2048;
#pragma unroll
            for (int q = 0; q < 4; q++)
                if (npend == 4 - q) {
#pragma unroll
                    for (int i = 0; i < 4; i++) stsm_x4(sst ^ (i << 5), qf[q * 4 + i][0], qf[q * 4 + i][1], qf[q * 4 + i][2], qf[q * 4 + i][3]);
                }
            __syncwarp();
            uint4* d = reinterpret_cast<uint4*>(&g_kv[0][0]) + oofs;
            const uint32_t src = wst + (lane >> 3) * 128 + (((lane & 7) ^ (lane >> 3)) << 4) + (npend & 1) * 2048;
#pragma unroll
            for (int i = 0; i < 4; i++) d[i * (4 * HD / 8)] = lds128((src + i * 512) ^ ((i & 1) << 6));
            oofs += 8;
            if (--npend == 0) handoff();
        };
        auto round_a = [&](const float* a, int hh) {
            uint4* d = reinterpret_cast<uint4*>(g_part) + oofs;
#pragma unroll
            for (int i = hh * 4; i < hh * 4 + 4; i++) {
                const float* b = a + (i >> 1) * 16 + (i & 1) * 2;
                red_add8(d + (i >> 1) * 4 + (i & 1) * (8 * PG * DM / 8), pack2(b[0], b[1]), pack2(b[4], b[5]), pack2(b[8], b[9]), pack2(b[12], b[13]));
            }
            if (hh) oofs += 16;
        };
        while (true) {
            tc++; TT(0); tc--;
            int code;
            while (true) {
                if (npend == 0) mwait(tfull0 + 8 * (tc & 3), (tc >> 2) & 1);
                if (npend == 0 || UNI(mtest(tfull0 + 8 * (tc & 3), (tc >> 2) & 1))) {
                    code = (int)UNI(lds32(task0 + 4 * (tc & 3)));
                    if (npend == 0 || ((code & 0x80) == 0 && !urgent && UNI(mtest(full0 + 8 * (it & 3), (it >> 2) & 1)))) break;
                }
                round_q();
            }
            if (lane == 0) mbar_arrive_cluster(mapa(tempty0 + 8 * (tc & 3), 0));
            tc++;
            TT(2);
            if (code < 0) break;
            const int type = (code >> 6) & 3;
            TTV(15, code);
#define BTC(type, k)
            if (type == T_CONV) {
                const int m = (code >> 9) & 1;
                BT((tid & 127) == 0, T_CONV, 0, m, 0);
                const int u = 2 * (code & 63) + rank, ch = cw * 4 + warp;
                int lane = tid & 31;
                asm volatile("" : "+r"(lane));
                const float Dv = bf2f(A.ssmD[u * 8 + ch]);
                const int sd = next(), s0 = next(), s1 = next(), s2 = next();
                TT(3);
                const uint32_t e1 = sb0 + s2 * BK_STAGE_BYTES;
                conv_unit(sb0 + s0 * BK_STAGE_BYTES + ch * 4096, sb0 + s1 * BK_STAGE_BYTES + ch * CV_EP, e1 + 64 + ch * CV_EP, e1 + 40960 + ch * 128, sb0 + BULK_STG + ch * 2, Dv, m, lane,
                          [&]() { release(sd); stg_free(); });
                asm volatile("fence.proxy.async.shared::cta;" ::: "memory");
                __syncwarp();
                handoff();
                TT(5);
                wgbar();
                release(s0); release(s1); release(s2);
                __syncwarp();
#pragma unroll
                for (int i = 0; i < 64; i++) qf[i >> 2][i & 3] = 0;
                continue;
            }
            float acc[128];
            {
                int s = next();
                TT(3); BTC(type, 0); BTC(type, 1);
                uint32_t sa = sb0 + s * BK_STAGE_BYTES + cw * 8192, sb = sb0 + s * BK_STAGE_BYTES + 16384;
                wg_fence();
                wgmma_m64n256k16_first(acc, make_desc(sa, 16, 1024), make_desc(sb, 8192, 1024));
#pragma unroll 1
                for (int kb = 0;;) {
#pragma unroll
                    for (int k = 1; k < 4; k++) wgmma_m64n256k16(acc, make_desc(sa + k * 32, 16, 1024), make_desc(sb + k * 2048, 8192, 1024));
                    wg_commit();
                    if (npend) round_q();
                    if (kb) { wg_wait<1>(); release((s - 1) & 3); }
                    if (++kb == 10) break;
                    s = next();
                    sa = sb0 + s * BK_STAGE_BYTES + cw * 8192; sb = sb0 + s * BK_STAGE_BYTES + 16384;
                    wg_fence();
                    wgmma_m64n256k16(acc, make_desc(sa, 16, 1024), make_desc(sb, 8192, 1024));
                }
            }
            wg_wait<0>();
            TT(4);
            release((it - 1) & 3);
            stg_free();
#pragma unroll
            for (int i = 0; i < 16; i++)
#pragma unroll
                for (int e = 0; e < 4; e++) qf[i][e] = pack2(acc[i * 8 + e * 2], acc[i * 8 + e * 2 + 1]);
            {
                const int cd = (int)lds32(task0 + 4 * ((tc - 1) & 3)), lc = (cd >> (rank ? 14 : 9)) & 31, jj = (cd & 256) ? (2 * cd + rank) & 63 : cd & 63;
                const int r0 = cw * 64 + warp * 16;
                if (type == T_KV) {
                    oofs = ((jj >> 4) * S_LEN + (lc & 15) * 128 + r0 + (lane >> 3)) * (HD / 8) + (jj & 15) * 32 + (lane & 7);
                    npend = 4;
                    urgent = URGENT && (lc < 2 || lc >= 16);
                    continue;
                }
                oofs = (((lc >> 4) * PRING + (lc & (PRING - 1))) * 128 + r0 + (lane >> 2)) * (PG * DM / 8) + (jj & (PG - 1)) * (DM / 8) + (lane & 3);
            }
            const float cs = 1.4426950408889634f;
            int lane = tid & 31;
            asm volatile("" : "+r"(lane));
            const int g = lane >> 2, tq = lane & 3;
            const int sg = cw * 2 + (warp >> 1), hs = warp & 1;
            float mt[2][2], sum[2][2];
            {
                const int x0 = next(), x1 = next();
                TT(5);
                float s[2][4][4];
#pragma unroll
                for (int hd = 0; hd < 2; hd++)
#pragma unroll
                    for (int n = 0; n < 4; n++)
#pragma unroll
                        for (int e = 0; e < 4; e++) s[hd][n][e] = 0.f;
                const uint32_t krow = (sg * 32 + (lane & 7) + (lane >> 4) * 8) * 128 + ((((lane >> 3) & 1) ^ (lane & 7)) << 4);
#pragma unroll
                for (int ii = 0; ii < 16; ii++) {
                    const int i = (ii >> 1) + (ii & 1) * 8;
                    const uint32_t kb = sb0 + (i < 12 ? x0 * BK_STAGE_BYTES + (i >> 2) * 16384 : x1 * BK_STAGE_BYTES) + (krow ^ ((i & 3) << 5));
                    const uint4 k0 = ldsm4(kb), k1 = ldsm4(kb + 2048);
                    mma16816(s[i >> 3][0], qf[i][0], qf[i][1], qf[i][2], qf[i][3], k0.x, k0.y);
                    mma16816(s[i >> 3][1], qf[i][0], qf[i][1], qf[i][2], qf[i][3], k0.z, k0.w);
                    mma16816(s[i >> 3][2], qf[i][0], qf[i][1], qf[i][2], qf[i][3], k1.x, k1.y);
                    mma16816(s[i >> 3][3], qf[i][0], qf[i][1], qf[i][2], qf[i][3], k1.z, k1.w);
                }
#pragma unroll
                for (int i = 0; i < 8; i++) sts128(wst + i * 512 + lane * 16, qf[8 + i][0], qf[8 + i][1], qf[8 + i][2], qf[8 + i][3]);
                wgbar();
                release(x0);
                TT(6);
                uint32_t pa[2][4][2];
#pragma unroll
                for (int hd = 0; hd < 2; hd++) {
                    uint32_t mx[2] = {0xff80ff80u, 0xff80ff80u};
#pragma unroll
                    for (int n = 0; n < 4; n++)
#pragma unroll
                        for (int r = 0; r < 2; r++) {
                            const int d = hs * 16 + g + r * 8 - n * 8 - tq * 2;
                            pa[hd][n][r] = rscore(d < 0 ? -INFINITY : s[hd][n][2 * r], d < 1 ? -INFINITY : s[hd][n][2 * r + 1]);
                            mx[r] = bmax2(mx[r], pa[hd][n][r]);
                        }
#pragma unroll
                    for (int r = 0; r < 2; r++) {
                        mx[r] = bmax2(mx[r], __shfl_xor_sync(0xffffffffu, mx[r], 1));
                        mx[r] = bmax2(mx[r], __shfl_xor_sync(0xffffffffu, mx[r], 2));
                        mt[hd][r] = fmaxf(blo(mx[r]), bhi(mx[r])) * cs;
                        sum[hd][r] = 0.f;
                    }
#pragma unroll
                    for (int n = 0; n < 4; n++)
#pragma unroll
                        for (int r = 0; r < 2; r++) {
                            const float p0 = ex2f(fmaf(blo(pa[hd][n][r]), cs, -mt[hd][r])), p1 = ex2f(fmaf(bhi(pa[hd][n][r]), cs, -mt[hd][r]));
                            sum[hd][r] += p0 + p1;
                            pa[hd][n][r] = pack2(p0, p1);
                        }
                }
                const uint32_t vrow = (sg * 32 + (lane & 15)) * 128 + (((lane >> 4) ^ (lane & 7)) << 4);
                int xv = x1;
#pragma unroll
                for (int hd = 0; hd < 2; hd++) {
                    if (hd == 1) xv = next();
#pragma unroll
                    for (int i = 0; i < 8; i++) {
                        const uint32_t vb = sb0 + xv * BK_STAGE_BYTES + (hd == 0 ? 16384 : 0) + (i >> 2) * 16384 + (vrow ^ ((i & 3) << 5));
                        uint4 v0, v1;
                        ldsm_x4_t(v0.x, v0.y, v0.z, v0.w, vb);
                        ldsm_x4_t(v1.x, v1.y, v1.z, v1.w, vb + 2048);
                        float* o = acc + hd * 64 + i * 8;
#pragma unroll
                        for (int e = 0; e < 8; e++) o[e] = 0.f;
                        mma16816(o, pa[hd][0][0], pa[hd][0][1], pa[hd][1][0], pa[hd][1][1], v0.x, v0.y);
                        mma16816(o + 4, pa[hd][0][0], pa[hd][0][1], pa[hd][1][0], pa[hd][1][1], v0.z, v0.w);
                        mma16816(o, pa[hd][2][0], pa[hd][2][1], pa[hd][3][0], pa[hd][3][1], v1.x, v1.y);
                        mma16816(o + 4, pa[hd][2][0], pa[hd][2][1], pa[hd][3][0], pa[hd][3][1], v1.z, v1.w);
                    }
                    wgbar();
                    release(xv);
                }
            }
            TT(7);
            BTC(T_ATT, 0);
            {
                const int xm = next();
                TT(8);
                BTC(T_ATT, 1);
                const uint32_t mb = sb0 + xm * BK_STAGE_BYTES + sg * 8192 + lane * 16;
                float sm[2][2][4];
#pragma unroll
                for (int i = 0; i < 16; i++) (&sm[0][0][0])[i] = 0.f;
#pragma unroll
                for (int q = 0; q < 4; q++) {
                    const uint4 k0 = lds128(mb + q * 512), k1 = lds128(mb + 4096 + q * 512);
                    const uint4 qa = lds128(wst + q * 1024 + lane * 16), qb = lds128(wst + q * 1024 + 512 + lane * 16);
                    mma16816(sm[0][0], qf[2 * q][0], qf[2 * q][1], qf[2 * q][2], qf[2 * q][3], k0.x, k0.y);
                    mma16816(sm[0][1], qf[2 * q + 1][0], qf[2 * q + 1][1], qf[2 * q + 1][2], qf[2 * q + 1][3], k0.z, k0.w);
                    mmau(sm[1][0], qa, k1.x, k1.y);
                    mmau(sm[1][1], qb, k1.z, k1.w);
                }
                float f[2][2];
                uint32_t pm[2][2];
#pragma unroll
                for (int hd = 0; hd < 2; hd++)
#pragma unroll
                    for (int r = 0; r < 2; r++) {
                        const uint32_t w = rscore(sm[hd][0][2 * r] + sm[hd][1][2 * r], sm[hd][0][2 * r + 1] + sm[hd][1][2 * r + 1]);
                        const float s0 = blo(w) * cs, s1 = bhi(w) * cs;
                        float m = fmaxf(s0, s1);
                        m = fmaxf(m, __shfl_xor_sync(0xffffffffu, m, 1));
                        m = fmaxf(fmaxf(m, __shfl_xor_sync(0xffffffffu, m, 2)), mt[hd][r]);
                        const float a = ex2f(mt[hd][r] - m), p0 = ex2f(s0 - m), p1 = ex2f(s1 - m);
                        float t = fmaf(sum[hd][r], a, p0 + p1);
                        t += __shfl_xor_sync(0xffffffffu, t, 1);
                        t += __shfl_xor_sync(0xffffffffu, t, 2);
                        t = rcpf(t);
                        f[hd][r] = a * t;
                        pm[hd][r] = pack2(p0 * t, p1 * t);
                    }
#pragma unroll
                for (int q = 0; q < 8; q++) {
                    const int hd = q >> 2;
                    const uint4 vm = lds128(mb + hd * 4096 + 2048 + (q & 3) * 512);
                    float* o = acc + q * 16;
#pragma unroll
                    for (int e = 0; e < 16; e++) o[e] *= f[hd][(e >> 1) & 1];
                    mma1688(o, pm[hd][0], pm[hd][1], vm.x);
                    mma1688(o + 4, pm[hd][0], pm[hd][1], vm.y);
                    mma1688(o + 8, pm[hd][0], pm[hd][1], vm.z);
                    mma1688(o + 12, pm[hd][0], pm[hd][1], vm.w);
#pragma unroll
                    for (int e = 0; e < 8; e++) qf[q * 2 + (e >> 2)][e & 3] = pack2(o[2 * e], o[2 * e + 1]);
                }
                wgbar();
                release(xm);
            }
            TT(9);
#pragma unroll
            for (int t = 0; t < 10; t++) {
                const int s = next();
                const uint32_t sb = sb0 + s * BK_STAGE_BYTES;
                float* d = acc + ((t >> 1) & 1) * 64;
                wg_fence();
#pragma unroll
                for (int k = 0; k < 8; k++) {
                    const uint64_t db = make_desc(sb + k * 2048, 16384, 1024);
                    if (k == 0 && !(t & 1)) wgmma_rs_m64n128k16_first(d, qf[k], db);
                    else wgmma_rs_m64n128k16(d, qf[(t & 1) * 8 + k], db);
                }
                wg_commit();
                if (t) {
                    wg_wait<1>();
                    release((s - 1) & 3);
                    if (t > 1) round_a(acc + (((t >> 1) & 1) ^ 1) * 64, t & 1);
                }
            }
            wg_wait<0>();
            release((it - 1) & 3);
            TT(10);
#pragma unroll
            for (int i = 0; i < 32; i++) qf[i >> 2][i & 3] = pack2(acc[(i >> 3) * 16 + (i & 4) / 2 + (i & 3) * 4], acc[(i >> 3) * 16 + (i & 4) / 2 + (i & 3) * 4 + 1]);
            npend = 6;
            urgent = URGENT > 1;
        }
    }
    cluster_sync_all();
}

__global__ void __launch_bounds__(256) reset_kernel(const bf16* x, int g0, int ncl) {
    const int lane = threadIdx.x & 31, row = blockIdx.x * 8 + (threadIdx.x >> 5);
    uint32_t r[10];
    ld5<128>(r, x + (size_t)row * DM + lane * 4);
    if (blockIdx.x == 0)
        for (int i = threadIdx.x; i < NFLAG * 2; i += blockDim.x) reinterpret_cast<uint4*>(FLG(i >> 1))[i & 1] = make_uint4(i == g0 ? min(ncl, 32) : (i == g0 + 2 ? max(ncl - 32, 0) : 0), 0, 0, 0);
    for (int i = blockIdx.x * 256 + threadIdx.x; i < 2 * PROWS * PG * DM / 8; i += S_LEN * 32) reinterpret_cast<uint4*>(g_part)[i] = make_uint4(0, 0, 0, 0);
    ln_row(r, r);
    st5(g_h[0] + (size_t)row * DM + lane * 4, r);
    if (blockIdx.x) return;
}

typedef CUresult (*PFN_encodeTiled)(CUtensorMap*, CUtensorMapDataType, cuuint32_t, void*, const cuuint64_t*, const cuuint64_t*,
                                    const cuuint32_t*, const cuuint32_t*, CUtensorMapInterleave, CUtensorMapSwizzle,
                                    CUtensorMapL2promotion, CUtensorMapFloatOOBfill);
static PFN_encodeTiled get_encode() {
    static PFN_encodeTiled fn = nullptr;
    if (!fn) {
        void* p = nullptr;
        cudaDriverEntryPointQueryResult qr;
        cudaGetDriverEntryPoint("cuTensorMapEncodeTiled", &p, cudaEnableDefault, &qr);
        fn = (PFN_encodeTiled)p;
    }
    return fn;
}
static void make_map(CUtensorMap* m, const void* ptr, uint64_t rows, uint64_t cols, uint32_t box_rows) {
    cuuint64_t dims[2] = {cols, rows};
    cuuint64_t strides[1] = {cols * 2};
    cuuint32_t box[2] = {64u, box_rows};
    cuuint32_t es[2] = {1, 1};
    get_encode()(m, CU_TENSOR_MAP_DATA_TYPE_BFLOAT16, 2, const_cast<void*>(ptr), dims, strides, box, es,
                 CU_TENSOR_MAP_INTERLEAVE_NONE, CU_TENSOR_MAP_SWIZZLE_128B, CU_TENSOR_MAP_L2_PROMOTION_L2_128B,
                 CU_TENSOR_MAP_FLOAT_OOB_FILL_NONE);
}
static void make_map3(CUtensorMap* m, const void* ptr) {
    cuuint64_t dims[3] = {64, DM, HD / 64};
    cuuint64_t strides[2] = {HD * 2, 128};
    cuuint32_t box[3] = {64u, 64u, 2u};
    cuuint32_t es[3] = {1, 1, 1};
    get_encode()(m, CU_TENSOR_MAP_DATA_TYPE_BFLOAT16, 3, const_cast<void*>(ptr), dims, strides, box, es,
                 CU_TENSOR_MAP_INTERLEAVE_NONE, CU_TENSOR_MAP_SWIZZLE_128B, CU_TENSOR_MAP_L2_PROMOTION_L2_128B,
                 CU_TENSOR_MAP_FLOAT_OOB_FILL_NONE);
}
#define QA_PRE0 4
#define KV1_E 1
#define KV1_L 16
#define KV0_X 6
#define CONV0_AT 1
#define CONV1_AT 9
static void build_sched(Sched& S, int naux) {
    int n = 0;
    auto ck = [](int f, int t) { return (uint32_t)(f * 32) | (uint32_t)t << 16; };
    auto add = [&](int lm, int type, int la, int ca, int lb, int cb, int ntask, uint32_t soft) {
        S.info[n] = (uint32_t)(type << 6 | lm << 8 | (la * 16 + ca) << 9 | (lb * 16 + cb) << 14);
        S.chk[n * 4] = ck(F_CNT + n, ntask); S.chk[n * 4 + 1] = soft;
        S.chk[n * 4 + 2] = ck(F_H + la * NCHK + ca, H_TGT); S.chk[n * 4 + 3] = ck(F_H + lb * NCHK + cb, H_TGT);
        n++;
    };
    for (int i = 0; i < MAXG * 4; i++) S.chk[i] = ck(F_ZERO, 0);
    for (int i = 0; i < MAXG; i++) S.info[i] = 0;
    S.sbeg[0] = n;
    for (int i = 0; i < NCHK; i++) {
        add(1, T_KV, 1, i, 1, i, 16, i < KV1_E || i >= KV1_L ? ck(F_OP + i, 14) + 4 : ck(F_H + NCHK + i, KV1_N));
        S.chk[n * 4 - 2] = S.chk[n * 4 - 1] = ck(F_CONV + i / 8, CONV_TGT);
    }
    S.sbeg[1] = n;
    auto addqa = [&]() {
    for (int p = 0; p < NCHK + PDIST; p++) {
        const bool h0 = p < NCHK, h1 = p >= PDIST;
        const int la = h0 ? 0 : 1, ca = h0 ? p : p - PDIST, lb = h1 ? 1 : 0, cb = h1 ? p - PDIST : p;
        const int ta = ca * CSEG + CSEG + la * LAG;
        add(!(h0 && h1), T_QA, la, ca, lb, cb, h0 && h1 ? 16 : 8,
            ck(F_PROG, h1 ? ta - QA_PRE : (ta > QA_PRE0 ? ta - QA_PRE0 : 0)));
        S.info[n - 1] |= 3u << 19;
        S.chk[n * 4 - 2] = h0 && ca >= PRING ? ck(F_H + NCHK + ca - PRING + 1, H_TGT) : ck(F_ZERO, 0);
        S.chk[n * 4 - 1] = !h1 ? ck(F_KV + ca, KV_TGT) : (cb >= PRING ? ck(F_OP + NCHK + cb - PRING, 128) + 5 : ck(F_ZERO, 0));
    }
    };
    auto addkv = [&]() {
    for (int i = 0; i < NCHK; i += 2) add(0, T_KV, 0, i, 0, i + 1, 32, ck(F_PROG, 4 * i > KV0_X + 1 ? 4 * i - KV0_X : 1)), S.chk[n * 4 - 2] = S.chk[n * 4 - 1] = ck(F_ZERO, 0);
    };
    addqa();
    S.sbeg[2] = n;
    for (int m = 0; m < 2; m++) {
        add(0, T_CONV, 0, m, 0, m, 40, ck(F_U + m, naux));
        S.chk[n * 4 - 2] = S.chk[n * 4 - 1] = ck(F_CNT + S.sbeg[2] + 2 + (m ? CONV1_AT : CONV0_AT) / 2, 32);
    }
    S.sbeg[3] = n;
    addkv();
    S.sbeg[4] = n;
}

static void launch_all(void* const* d_in, void* d_out) {
    const bf16* x = (const bf16*)d_in[0];
    const bf16* mem0 = (const bf16*)d_in[1];
    const bf16* Wq = (const bf16*)d_in[2];
    const bf16* Wk = (const bf16*)d_in[3];
    const bf16* Wv = (const bf16*)d_in[4];
    const bf16* Wo = (const bf16*)d_in[5];
    static bool inited = false;
    static int nsm = 132;
    static Sched SC;
    bf16 *p_h, *p_kv, *p_u;
    cudaGetSymbolAddress((void**)&p_h, g_h);
    cudaGetSymbolAddress((void**)&p_kv, g_kv);
    cudaGetSymbolAddress((void**)&p_u, g_U);
    if (!inited) {
        inited = true;
        cudaDeviceGetAttribute(&nsm, cudaDevAttrMultiProcessorCount, 0);
        cudaFuncSetAttribute(chain_kernel, cudaFuncAttributeMaxDynamicSharedMemorySize, (int)sizeof(ChainSmem));
        cudaFuncSetAttribute(chain_kernel, cudaFuncAttributeNonPortableClusterSizeAllowed, 1);
        cudaFuncSetAttribute(bulk_kernel, cudaFuncAttributeMaxDynamicSharedMemorySize, BULK_SMEM);
        build_sched(SC, 2 * ((nsm - 64) & ~1));
    }
    const size_t QS = (size_t)S_LEN * HD;
    BulkMaps M;
    make_map(&M.h, p_h, 2 * S_LEN, DM, 64);
    make_map(&M.h2, p_h, 2 * S_LEN, DM, 128);
    make_map3(&M.wq, Wq);
    make_map3(&M.wk, Wk);
    make_map3(&M.wv, Wv);
    make_map(&M.wo, Wo, HD, DM, 128);
    make_map(&M.kv, p_kv, 2 * S_LEN, HD, 128);
    make_map(&M.lu, p_u, DM * 32, 64, 256);
    BulkArgs BA;
    BA.x = x; BA.out = (bf16*)d_out;
    BA.Bk = (const bf16*)d_in[8]; BA.Bv = (const bf16*)d_in[9]; BA.shiftk = (const bf16*)d_in[10];
    BA.ssmk = (const bf16*)d_in[11]; BA.ssmD = (const bf16*)d_in[12];
    ChainArgs ca;
    for (int l = 0; l < 2; l++) {
        make_map(&ca.tk[l], p_kv, S_LEN, HD, 32);
        make_map(&ca.tv[l], p_kv + QS, S_LEN, HD, 32);
    }
    ca.x = x; ca.mem0 = mem0; ca.Wq = Wq; ca.Wk = Wk; ca.Wv = Wv; ca.Wo = Wo; ca.kv_target = KV_TGT;
    cudaStream_t s = cudaStreamPerThread;
    reset_kernel<<<S_LEN / 8, 256, 0, s>>>(x, 2 * (F_CNT + SC.sbeg[3]), (nsm - 64) / 2);
    {
        cudaLaunchConfig_t cfg = {};
        cfg.gridDim = dim3(64); cfg.blockDim = dim3(CHAIN_THREADS); cfg.dynamicSmemBytes = sizeof(ChainSmem); cfg.stream = s;
        cudaLaunchAttribute at[1];
        at[0].id = cudaLaunchAttributeClusterDimension;
        at[0].val.clusterDim.x = CL; at[0].val.clusterDim.y = 1; at[0].val.clusterDim.z = 1;
        cfg.attrs = at; cfg.numAttrs = 1;
        cudaLaunchKernelEx(&cfg, chain_kernel, ca);
    }
    {
        cudaLaunchConfig_t cfg = {};
        cfg.gridDim = dim3((nsm - 64) & ~1); cfg.blockDim = dim3(384); cfg.dynamicSmemBytes = BULK_SMEM; cfg.stream = s;
        cudaLaunchAttribute at[2];
        at[0].id = cudaLaunchAttributeProgrammaticStreamSerialization;
        at[0].val.programmaticStreamSerializationAllowed = 1;
        at[1].id = cudaLaunchAttributeClusterDimension;
        at[1].val.clusterDim.x = 2; at[1].val.clusterDim.y = 1; at[1].val.clusterDim.z = 1;
        cfg.attrs = at; cfg.numAttrs = 2;
        cudaLaunchKernelEx(&cfg, bulk_kernel, M, BA, SC);
    }
}
}

extern "C" void kernel_launch(void* const* d_in, const int* in_sizes, int n_in, void* d_out, int out_size) {
    (void)in_sizes; (void)n_in; (void)out_size;
    if (ws::usable()) ws::launch_all(d_in, d_out);
    else ni::launch_all(d_in, d_out);
}
```

```cpp
#include <cuda_runtime.h>
#include <cuda_bf16.h>
#include <stdint.h>
#include <cuda.h>

typedef __nv_bfloat16 bf16;
namespace ws {
constexpr int S_LEN = 2048, DM = 640, NH = 32, DH = 128, HD = NH * DH, SEG = 32, NSEG = S_LEN / SEG;

__device__ __forceinline__ float bf2f(bf16 v) { return __bfloat162float(v); }
__device__ __forceinline__ float rbf(float v) { return __bfloat162float(__float2bfloat16_rn(v)); }
__device__ __forceinline__ uint32_t pack2(float a, float b) {
    __nv_bfloat162 t = __floats2bfloat162_rn(a, b);
    return *reinterpret_cast<uint32_t*>(&t);
}
__device__ __forceinline__ float blo(uint32_t v) { return __uint_as_float(v << 16); }
__device__ __forceinline__ float bhi(uint32_t v) { return __uint_as_float(v & 0xffff0000u); }
__device__ __forceinline__ uint32_t badd(uint32_t a, uint32_t b) { uint32_t r; asm("add.rn.bf16x2 %0, %1, %2;" : "=r"(r) : "r"(a), "r"(b)); return r; }
__device__ __forceinline__ uint32_t smem_u32(const void* p) { return (uint32_t)__cvta_generic_to_shared(p); }
__device__ __forceinline__ uint4 ldsm4(uint32_t a) {
    uint4 v;
    asm volatile("ldmatrix.sync.aligned.m8n8.x4.shared.b16 {%0,%1,%2,%3}, [%4];" : "=r"(v.x), "=r"(v.y), "=r"(v.z), "=r"(v.w) : "r"(a));
    return v;
}
__device__ __forceinline__ uint4 ldsm4t(uint32_t a) {
    uint4 v;
    asm volatile("ldmatrix.sync.aligned.m8n8.x4.trans.shared.b16 {%0,%1,%2,%3}, [%4];" : "=r"(v.x), "=r"(v.y), "=r"(v.z), "=r"(v.w) : "r"(a));
    return v;
}
__device__ __forceinline__ uint2 ldsm2t(uint32_t a) {
    uint2 v;
    asm volatile("ldmatrix.sync.aligned.m8n8.x2.trans.shared.b16 {%0,%1}, [%2];" : "=r"(v.x), "=r"(v.y) : "r"(a));
    return v;
}
__device__ __forceinline__ void stsm4(uint32_t a, uint32_t r0, uint32_t r1, uint32_t r2, uint32_t r3) {
    asm volatile("stmatrix.sync.aligned.m8n8.x4.shared.b16 [%0], {%1,%2,%3,%4};" ::"r"(a), "r"(r0), "r"(r1), "r"(r2), "r"(r3) : "memory");
}
__device__ __forceinline__ void stsm2(uint32_t a, uint32_t r0, uint32_t r1) {
    asm volatile("stmatrix.sync.aligned.m8n8.x2.shared.b16 [%0], {%1,%2};" ::"r"(a), "r"(r0), "r"(r1) : "memory");
}
__device__ __forceinline__ void stsm4t(uint32_t a, uint32_t r0, uint32_t r1, uint32_t r2, uint32_t r3) {
    asm volatile("stmatrix.sync.aligned.m8n8.x4.trans.shared.b16 [%0], {%1,%2,%3,%4};" ::"r"(a), "r"(r0), "r"(r1), "r"(r2), "r"(r3) : "memory");
}
__device__ __forceinline__ void mma16816(float* c, uint32_t a0, uint32_t a1, uint32_t a2, uint32_t a3, uint32_t b0, uint32_t b1) {
    asm("mma.sync.aligned.m16n8k16.row.col.f32.bf16.bf16.f32 {%0,%1,%2,%3}, {%4,%5,%6,%7}, {%8,%9}, {%0,%1,%2,%3};"
        : "+f"(c[0]), "+f"(c[1]), "+f"(c[2]), "+f"(c[3]) : "r"(a0), "r"(a1), "r"(a2), "r"(a3), "r"(b0), "r"(b1));
}
__device__ __forceinline__ void mmav(float* c, uint32_t a0, uint32_t a1, uint32_t a2, uint32_t a3, uint32_t b0, uint32_t b1) {
    asm volatile("mma.sync.aligned.m16n8k16.row.col.f32.bf16.bf16.f32 {%0,%1,%2,%3}, {%4,%5,%6,%7}, {%8,%9}, {%0,%1,%2,%3};"
        : "+f"(c[0]), "+f"(c[1]), "+f"(c[2]), "+f"(c[3]) : "r"(a0), "r"(a1), "r"(a2), "r"(a3), "r"(b0), "r"(b1));
}
__device__ __forceinline__ void mmau(float* c, const uint4& a, uint32_t b0, uint32_t b1) { mma16816(c, a.x, a.y, a.z, a.w, b0, b1); }
__device__ __forceinline__ void mma1688(float* c, uint32_t a0, uint32_t a1, uint32_t b0) {
    asm("mma.sync.aligned.m16n8k8.row.col.f32.bf16.bf16.f32 {%0,%1,%2,%3}, {%4,%5}, {%6}, {%0,%1,%2,%3};"
        : "+f"(c[0]), "+f"(c[1]), "+f"(c[2]), "+f"(c[3]) : "r"(a0), "r"(a1), "r"(b0));
}
__device__ __forceinline__ void mmav8(float* c, uint32_t a0, uint32_t a1, uint32_t b0) {
    asm volatile("mma.sync.aligned.m16n8k8.row.col.f32.bf16.bf16.f32 {%0,%1,%2,%3}, {%4,%5}, {%6}, {%0,%1,%2,%3};"
        : "+f"(c[0]), "+f"(c[1]), "+f"(c[2]), "+f"(c[3]) : "r"(a0), "r"(a1), "r"(b0));
}
__device__ __forceinline__ void cp_async16(uint32_t dst, const void* src) { asm volatile("cp.async.cg.shared.global [%0], [%1], 16;" ::"r"(dst), "l"(src)); }
__device__ __forceinline__ void cp_commit() { asm volatile("cp.async.commit_group;"); }
template <int N> __device__ __forceinline__ void cp_wait() { asm volatile("cp.async.wait_group %0;" ::"n"(N)); }
__device__ __forceinline__ uint4 lds128(uint32_t a) {
    uint4 v;
    asm volatile("ld.shared.v4.u32 {%0,%1,%2,%3}, [%4];" : "=r"(v.x), "=r"(v.y), "=r"(v.z), "=r"(v.w) : "r"(a));
    return v;
}
__device__ __forceinline__ uint2 lds64(uint32_t a) {
    uint2 v;
    asm volatile("ld.shared.v2.u32 {%0,%1}, [%2];" : "=r"(v.x), "=r"(v.y) : "r"(a));
    return v;
}
__device__ __forceinline__ uint32_t lds32(uint32_t a) { uint32_t v; asm volatile("ld.shared.u32 %0, [%1];" : "=r"(v) : "r"(a)); return v; }
__device__ __forceinline__ void sts32(uint32_t a, uint32_t x) { asm volatile("st.shared.u32 [%0], %1;" ::"r"(a), "r"(x) : "memory"); }
__device__ __forceinline__ void sts64(uint32_t a, uint32_t x, uint32_t y) { asm volatile("st.shared.v2.u32 [%0], {%1,%2};" ::"r"(a), "r"(x), "r"(y) : "memory"); }
__device__ __forceinline__ void sts128(uint32_t a, uint32_t x, uint32_t y, uint32_t z, uint32_t w) {
    asm volatile("st.shared.v4.u32 [%0], {%1,%2,%3,%4};" ::"r"(a), "r"(x), "r"(y), "r"(z), "r"(w) : "memory");
}
__device__ __forceinline__ uint4 ld_relaxed_v4(const void* p) {
    uint4 v;
    asm volatile("ld.relaxed.gpu.global.v4.u32 {%0,%1,%2,%3}, [%4];" : "=r"(v.x), "=r"(v.y), "=r"(v.z), "=r"(v.w) : "l"(p) : "memory");
    return v;
}
__device__ __forceinline__ uint2 ld_relaxed_v2(const void* p) {
    uint2 v;
    asm volatile("ld.relaxed.gpu.global.v2.u32 {%0,%1}, [%2];" : "=r"(v.x), "=r"(v.y) : "l"(p) : "memory");
    return v;
}
__device__ __forceinline__ void ld7_relaxed(uint4* x, const void* p) {
    asm volatile("ld.relaxed.gpu.global.v4.u32 {%0,%1,%2,%3}, [%28 + 0];\nld.relaxed.gpu.global.v4.u32 {%4,%5,%6,%7}, [%28 + 512];\nld.relaxed.gpu.global.v4.u32 {%8,%9,%10,%11}, [%28 + 1024];\nld.relaxed.gpu.global.v4.u32 {%12,%13,%14,%15}, [%28 + 1536];\nld.relaxed.gpu.global.v4.u32 {%16,%17,%18,%19}, [%28 + 2048];\nld.relaxed.gpu.global.v4.u32 {%20,%21,%22,%23}, [%28 + 2560];\nld.relaxed.gpu.global.v4.u32 {%24,%25,%26,%27}, [%28 + 3072];\n" : "=r"(x[0].x), "=r"(x[0].y), "=r"(x[0].z), "=r"(x[0].w), "=r"(x[1].x), "=r"(x[1].y), "=r"(x[1].z), "=r"(x[1].w), "=r"(x[2].x), "=r"(x[2].y), "=r"(x[2].z), "=r"(x[2].w), "=r"(x[3].x), "=r"(x[3].y), "=r"(x[3].z), "=r"(x[3].w), "=r"(x[4].x), "=r"(x[4].y), "=r"(x[4].z), "=r"(x[4].w), "=r"(x[5].x), "=r"(x[5].y), "=r"(x[5].z), "=r"(x[5].w), "=r"(x[6].x), "=r"(x[6].y), "=r"(x[6].z), "=r"(x[6].w) : "l"(p) : "memory");
}
__device__ __forceinline__ void ld7_relaxed(uint2* x, const void* p) {
    asm volatile("ld.relaxed.gpu.global.v2.u32 {%0,%1}, [%14 + 0];\nld.relaxed.gpu.global.v2.u32 {%2,%3}, [%14 + 512];\nld.relaxed.gpu.global.v2.u32 {%4,%5}, [%14 + 1024];\nld.relaxed.gpu.global.v2.u32 {%6,%7}, [%14 + 1536];\nld.relaxed.gpu.global.v2.u32 {%8,%9}, [%14 + 2048];\nld.relaxed.gpu.global.v2.u32 {%10,%11}, [%14 + 2560];\nld.relaxed.gpu.global.v2.u32 {%12,%13}, [%14 + 3072];\n" : "=r"(x[0].x), "=r"(x[0].y), "=r"(x[1].x), "=r"(x[1].y), "=r"(x[2].x), "=r"(x[2].y), "=r"(x[3].x), "=r"(x[3].y), "=r"(x[4].x), "=r"(x[4].y), "=r"(x[5].x), "=r"(x[5].y), "=r"(x[6].x), "=r"(x[6].y) : "l"(p) : "memory");
}
__device__ __forceinline__ void st_relaxed_v4(void* p, uint32_t a, uint32_t b, uint32_t c, uint32_t d) {
    asm volatile("st.relaxed.gpu.global.v4.u32 [%0], {%1,%2,%3,%4};" ::"l"(p), "r"(a), "r"(b), "r"(c), "r"(d) : "memory");
}
__device__ __forceinline__ void st_relaxed_v2(void* p, uint32_t a, uint32_t b) {
    asm volatile("st.relaxed.gpu.global.v2.u32 [%0], {%1,%2};" ::"l"(p), "r"(a), "r"(b) : "memory");
}
__device__ __forceinline__ uint32_t clear16(void* p) {
    uint32_t r;
    asm volatile("{\n.reg .b128 z, o;\n.reg .b64 a, b;\nmov.b64 a, 0;\nmov.b128 z, {a, a};\natom.relaxed.gpu.global.exch.b128 o, [%1], z;\nmov.b128 {a, b}, o;\ncvt.u32.u64 %0, a;\n}" : "=r"(r) : "l"(p) : "memory");
    return r;
}
__device__ __forceinline__ uint32_t nz(uint32_t v) { uint32_t r; asm("max.u32 %0, %1, 1;" : "=r"(r) : "r"(v)); return r; }
__device__ __forceinline__ void touch(const void* p) { asm volatile("prefetch.global.L2 [%0];" ::"l"(p) : "memory"); }
__device__ __forceinline__ int ld_relaxed(const int* p) {
    int v;
    asm volatile("ld.relaxed.gpu.global.u32 %0, [%1];" : "=r"(v) : "l"(p) : "memory");
    return v;
}
__device__ __forceinline__ int ld_acquire(const int* p) {
    int v;
    asm volatile("ld.acquire.gpu.global.u32 %0, [%1];" : "=r"(v) : "l"(p) : "memory");
    return v;
}
__device__ __forceinline__ void red_release(int* p, int v) { asm volatile("red.release.gpu.global.add.u32 [%0], %1;" ::"l"(p), "r"(v) : "memory"); }
__device__ __forceinline__ void mbar_init(uint32_t bar, int count) { asm volatile("mbarrier.init.shared::cta.b64 [%0], %1;" ::"r"(bar), "r"(count)); }
__device__ __forceinline__ void mbar_expect_tx(uint32_t bar, uint32_t bytes) {
    asm volatile("mbarrier.arrive.expect_tx.shared::cta.b64 _, [%0], %1;" ::"r"(bar), "r"(bytes) : "memory");
}
__device__ __forceinline__ void mbar_arrive(uint32_t bar) { asm volatile("mbarrier.arrive.shared::cta.b64 _, [%0];" ::"r"(bar) : "memory"); }
__device__ __forceinline__ void mbar_arrive_cluster(uint32_t bar) { asm volatile("mbarrier.arrive.shared::cluster.b64 _, [%0];" ::"r"(bar) : "memory"); }
__device__ __forceinline__ bool mtry(uint32_t bar, uint32_t parity) {
    uint32_t ok;
    asm volatile("{\n.reg .pred P1;\nmbarrier.try_wait.parity.shared::cta.b64 P1, [%1], %2;\nselp.u32 %0, 1, 0, P1;\n}\n" : "=r"(ok) : "r"(bar), "r"(parity) : "memory");
    return ok != 0;
}
__device__ __forceinline__ void mslow(uint32_t bar, uint32_t parity) {
    asm volatile(
        "{\n.reg .pred P1;\n.reg .u32 cnt;\n"
        "mov.u32 cnt, 0;\n"
        "LAB_WAIT:\n"
        "mbarrier.try_wait.parity.shared::cta.b64 P1, [%0], %1;\n"
        "@P1 bra DONE;\n"
        "add.u32 cnt, cnt, 1;\n"
        "setp.lt.u32 P1, cnt, 1000000;\n"
        "@P1 bra LAB_WAIT;\n"
        "trap;\n"
        "DONE:\n}\n" ::"r"(bar), "r"(parity) : "memory");
}
__device__ __forceinline__ void mwait(uint32_t bar, uint32_t parity) {
    asm volatile(
        "{\n.reg .pred P1, P2;\n.reg .u32 cnt;\n"
        "mov.u32 cnt, 0;\n"
        "LAB_WAIT:\n"
        "mbarrier.try_wait.parity.shared::cta.b64 P1, [%0], %1;\n"
        "add.u32 cnt, cnt, 1;\n"
        "setp.gt.u32 P2, cnt, 1000000;\n"
        "@P2 trap;\n"
        "@!P1 bra LAB_WAIT;\n"
        "}\n" ::"r"(bar), "r"(parity) : "memory");
}
__device__ __forceinline__ void mspin(uint32_t bar, uint32_t parity) {
    asm volatile(
        "{\n.reg .pred P1, P2;\n.reg .u32 cnt;\n"
        "mov.u32 cnt, 0;\n"
        "LAB_WAIT:\n"
        "mbarrier.test_wait.parity.shared::cta.b64 P1, [%0], %1;\n"
        "add.u32 cnt, cnt, 1;\n"
        "setp.gt.u32 P2, cnt, 40000000;\n"
        "@P2 trap;\n"
        "@!P1 bra LAB_WAIT;\n"
        "}\n" ::"r"(bar), "r"(parity) : "memory");
}
__device__ __forceinline__ uint32_t mtest(uint32_t bar, uint32_t parity) {
    uint32_t ok;
    asm volatile("{\n.reg .pred P1;\nmbarrier.test_wait.parity.shared::cta.b64 P1, [%1], %2;\nselp.u32 %0, 1, 0, P1;\n}\n" : "=r"(ok) : "r"(bar), "r"(parity) : "memory");
    return ok;
}
__device__ __forceinline__ uint32_t mapa(uint32_t addr, uint32_t rank) {
    uint32_t r;
    asm("mapa.shared::cluster.u32 %0, %1, %2;" : "=r"(r) : "r"(addr), "r"(rank));
    return r;
}
__device__ __forceinline__ void st_async_b32(uint32_t addr, uint32_t a, uint32_t bar) {
    asm volatile("st.async.weak.shared::cluster.mbarrier::complete_tx::bytes.b32 [%0], %1, [%2];" ::"r"(addr), "r"(a), "r"(bar) : "memory");
}
__device__ __forceinline__ void st_async_v2(uint32_t addr, uint32_t a, uint32_t b, uint32_t bar) {
    asm volatile("st.async.weak.shared::cluster.mbarrier::complete_tx::bytes.v2.b32 [%0], {%1,%2}, [%3];" ::"r"(addr), "r"(a), "r"(b), "r"(bar) : "memory");
}
__device__ __forceinline__ void st_async_v2_lt(uint32_t addr, uint32_t a, uint32_t b, uint32_t bar, uint32_t x, uint32_t lim) {
    asm volatile("{\n.reg .pred p;\nsetp.lt.u32 p, %4, %5;\n@p st.async.weak.shared::cluster.mbarrier::complete_tx::bytes.v2.b32 [%0], {%1,%2}, [%3];\n}"
                 ::"r"(addr), "r"(a), "r"(b), "r"(bar), "r"(x), "r"(lim) : "memory");
}
__device__ __forceinline__ void st_async_v4(uint32_t addr, uint32_t a, uint32_t b, uint32_t c, uint32_t d, uint32_t bar) {
    asm volatile("st.async.weak.shared::cluster.mbarrier::complete_tx::bytes.v4.b32 [%0], {%1,%2,%3,%4}, [%5];" ::"r"(addr), "r"(a), "r"(b), "r"(c), "r"(d), "r"(bar) : "memory");
}
__device__ __forceinline__ void st_async_v4p(uint32_t addr, uint32_t a, uint32_t b, uint32_t c, uint32_t d, uint32_t bar) {
    asm volatile("{\n.reg .pred p;\nsetp.ne.u32 p, %5, 0;\n@p st.async.weak.shared::cluster.mbarrier::complete_tx::bytes.v4.b32 [%0], {%1,%2,%3,%4}, [%5];\n}"
                 ::"r"(addr), "r"(a), "r"(b), "r"(c), "r"(d), "r"(bar) : "memory");
}
__device__ __forceinline__ void st_async_v2p(uint32_t addr, uint32_t a, uint32_t b, uint32_t bar) {
    asm volatile("{\n.reg .pred p;\nsetp.ne.u32 p, %3, 0;\n@p st.async.weak.shared::cluster.mbarrier::complete_tx::bytes.v2.b32 [%0], {%1,%2}, [%3];\n}"
                 ::"r"(addr), "r"(a), "r"(b), "r"(bar) : "memory");
}
__device__ __forceinline__ void cluster_arrive() { asm volatile("barrier.cluster.arrive.release.aligned;" ::: "memory"); }
__device__ __forceinline__ void cluster_arrive_relaxed() { asm volatile("barrier.cluster.arrive.relaxed.aligned;" ::: "memory"); }
__device__ __forceinline__ void prefetch_l2(const void* p, uint32_t bytes) { asm volatile("cp.async.bulk.prefetch.L2.global [%0], %1;" ::"l"(p), "r"(bytes) : "memory"); }
__device__ __forceinline__ void cluster_wait() { asm volatile("barrier.cluster.wait.acquire.aligned;" ::: "memory"); }
__device__ __forceinline__ void named_bar(int id, int n) { asm volatile("bar.sync %0, %1;" ::"r"(id), "r"(n) : "memory"); }
__device__ __forceinline__ void named_arrive(int id, int n) { asm volatile("bar.arrive %0, %1;" ::"r"(id), "r"(n) : "memory"); }
__device__ __forceinline__ void fence_async_smem() { asm volatile("fence.proxy.async.shared::cta;" ::: "memory"); }
__device__ __forceinline__ void fence_async_global() { asm volatile("fence.proxy.async.global;" ::: "memory"); }
__device__ __forceinline__ void wg_fence() { asm volatile("wgmma.fence.sync.aligned;" ::: "memory"); }
__device__ __forceinline__ void wg_commit() { asm volatile("wgmma.commit_group.sync.aligned;" ::: "memory"); }
template <int N> __device__ __forceinline__ void wg_wait() { asm volatile("wgmma.wait_group.sync.aligned %0;" ::"n"(N) : "memory"); }
__device__ __forceinline__ uint64_t ndesc(uint32_t addr, uint32_t lbo, uint32_t sbo) {
    return (uint64_t)((addr & 0x3FFFF) >> 4) | ((uint64_t)(lbo >> 4) << 16) | ((uint64_t)(sbo >> 4) << 32);
}
__device__ __forceinline__ float ex2f(float x) { float y; asm("ex2.approx.ftz.f32 %0, %1;" : "=f"(y) : "f"(x)); return y; }
__device__ __forceinline__ float rcpf(float x) { float y; asm("rcp.approx.ftz.f32 %0, %1;" : "=f"(y) : "f"(x)); return y; }
__device__ __forceinline__ uint32_t clk32() { uint32_t c; asm volatile("mov.u32 %0, %clock;" : "=r"(c)); return c; }
__device__ __forceinline__ uint32_t opq(uint32_t x) { uint32_t y; asm volatile("mov.u32 %0, %1;" : "=r"(y) : "r"(x)); return y; }
__device__ __forceinline__ uint32_t rem(uint32_t addr, uint32_t rank) { return mapa(addr, rank); }
__device__ __forceinline__ uint64_t mkdesc(uint32_t lo, uint32_t hi) { uint64_t d; asm("mov.b64 %0, {%1,%2};" : "=l"(d) : "r"(lo), "r"(hi)); return d; }
__device__ __forceinline__ void delay(uint32_t n) {
    asm volatile("{\n.reg .pred P;\n.reg .u32 a, b;\nmov.u32 a, %clock;\nadd.u32 a, a, %0;\nDL:\nmov.u32 b, %clock;\nsub.u32 b, b, a;\nsetp.lt.s32 P, b, 0;\n@P bra.uni DL;\n}" ::"r"(n) : "memory");
}
#define UNI(x) __shfl_sync(0xffffffffu, (uint32_t)(x), 0)
__device__ __forceinline__ void wg_n16t(float* d, uint32_t a0, uint32_t a1, uint32_t a2, uint32_t a3, uint64_t db) {
    asm volatile("wgmma.mma_async.sync.aligned.m64n16k16.f32.bf16.bf16 {%0, %1, %2, %3, %4, %5, %6, %7}, {%8, %9, %10, %11}, %12, 1, 1, 1, 1;"
                 : "+f"(d[0]), "+f"(d[1]), "+f"(d[2]), "+f"(d[3]), "+f"(d[4]), "+f"(d[5]), "+f"(d[6]), "+f"(d[7]) : "r"(a0), "r"(a1), "r"(a2), "r"(a3), "l"(db));
}
__device__ __forceinline__ void wg_n16t_first(float* d, uint32_t a0, uint32_t a1, uint32_t a2, uint32_t a3, uint64_t db) {
    asm volatile("wgmma.mma_async.sync.aligned.m64n16k16.f32.bf16.bf16 {%0, %1, %2, %3, %4, %5, %6, %7}, {%8, %9, %10, %11}, %12, 0, 1, 1, 1;"
                 : "=f"(d[0]), "=f"(d[1]), "=f"(d[2]), "=f"(d[3]), "=f"(d[4]), "=f"(d[5]), "=f"(d[6]), "=f"(d[7]) : "r"(a0), "r"(a1), "r"(a2), "r"(a3), "l"(db));
}
__device__ __forceinline__ void wg_n32(float* d, uint32_t a0, uint32_t a1, uint32_t a2, uint32_t a3, uint64_t db) {
    asm volatile("wgmma.mma_async.sync.aligned.m64n32k16.f32.bf16.bf16 {%0, %1, %2, %3, %4, %5, %6, %7, %8, %9, %10, %11, %12, %13, %14, %15}, {%16, %17, %18, %19}, %20, 1, 1, 1, 0;"
                 : "+f"(d[0]), "+f"(d[1]), "+f"(d[2]), "+f"(d[3]), "+f"(d[4]), "+f"(d[5]), "+f"(d[6]), "+f"(d[7]), "+f"(d[8]), "+f"(d[9]), "+f"(d[10]), "+f"(d[11]), "+f"(d[12]), "+f"(d[13]), "+f"(d[14]), "+f"(d[15]) : "r"(a0), "r"(a1), "r"(a2), "r"(a3), "l"(db));
}
__device__ __forceinline__ void wg_n32_first(float* d, uint32_t a0, uint32_t a1, uint32_t a2, uint32_t a3, uint64_t db) {
    asm volatile("wgmma.mma_async.sync.aligned.m64n32k16.f32.bf16.bf16 {%0, %1, %2, %3, %4, %5, %6, %7, %8, %9, %10, %11, %12, %13, %14, %15}, {%16, %17, %18, %19}, %20, 0, 1, 1, 0;"
                 : "=f"(d[0]), "=f"(d[1]), "=f"(d[2]), "=f"(d[3]), "=f"(d[4]), "=f"(d[5]), "=f"(d[6]), "=f"(d[7]), "=f"(d[8]), "=f"(d[9]), "=f"(d[10]), "=f"(d[11]), "=f"(d[12]), "=f"(d[13]), "=f"(d[14]), "=f"(d[15]) : "r"(a0), "r"(a1), "r"(a2), "r"(a3), "l"(db));
}

__device__ __forceinline__ void wg_n16t_sfirst(float* d, uint64_t da, uint64_t db) {
    asm volatile("wgmma.mma_async.sync.aligned.m64n16k16.f32.bf16.bf16 {%0, %1, %2, %3, %4, %5, %6, %7}, %8, %9, 0, 1, 1, 1, 1;"
                 : "=f"(d[0]), "=f"(d[1]), "=f"(d[2]), "=f"(d[3]), "=f"(d[4]), "=f"(d[5]), "=f"(d[6]), "=f"(d[7]) : "l"(da), "l"(db));
}
__device__ __forceinline__ void wg_n32_sfirst(float* d, uint64_t da, uint64_t db) {
    asm volatile("wgmma.mma_async.sync.aligned.m64n32k16.f32.bf16.bf16 {%0, %1, %2, %3, %4, %5, %6, %7, %8, %9, %10, %11, %12, %13, %14, %15}, %16, %17, 0, 1, 1, 1, 0;"
                 : "=f"(d[0]), "=f"(d[1]), "=f"(d[2]), "=f"(d[3]), "=f"(d[4]), "=f"(d[5]), "=f"(d[6]), "=f"(d[7]), "=f"(d[8]), "=f"(d[9]), "=f"(d[10]), "=f"(d[11]), "=f"(d[12]), "=f"(d[13]), "=f"(d[14]), "=f"(d[15]) : "l"(da), "l"(db));
}

__device__ __forceinline__ void wg_n16t_s(float* d, uint64_t da, uint64_t db) {
    asm volatile("wgmma.mma_async.sync.aligned.m64n16k16.f32.bf16.bf16 {%0, %1, %2, %3, %4, %5, %6, %7}, %8, %9, 1, 1, 1, 1, 1;"
                 : "+f"(d[0]), "+f"(d[1]), "+f"(d[2]), "+f"(d[3]), "+f"(d[4]), "+f"(d[5]), "+f"(d[6]), "+f"(d[7]) : "l"(da), "l"(db));
}
__device__ __forceinline__ void wg_n64_sfirst(float* d, uint64_t da, uint64_t db) {
    asm volatile("wgmma.mma_async.sync.aligned.m64n64k16.f32.bf16.bf16 {%0, %1, %2, %3, %4, %5, %6, %7, %8, %9, %10, %11, %12, %13, %14, %15, %16, %17, %18, %19, %20, %21, %22, %23, %24, %25, %26, %27, %28, %29, %30, %31}, %32, %33, 0, 1, 1, 1, 0;"
                 : "=f"(d[0]), "=f"(d[1]), "=f"(d[2]), "=f"(d[3]), "=f"(d[4]), "=f"(d[5]), "=f"(d[6]), "=f"(d[7]), "=f"(d[8]), "=f"(d[9]), "=f"(d[10]), "=f"(d[11]), "=f"(d[12]), "=f"(d[13]), "=f"(d[14]), "=f"(d[15]), "=f"(d[16]), "=f"(d[17]), "=f"(d[18]), "=f"(d[19]), "=f"(d[20]), "=f"(d[21]), "=f"(d[22]), "=f"(d[23]), "=f"(d[24]), "=f"(d[25]), "=f"(d[26]), "=f"(d[27]), "=f"(d[28]), "=f"(d[29]), "=f"(d[30]), "=f"(d[31]) : "l"(da), "l"(db));
}
__device__ __forceinline__ void wg_n64_s(float* d, uint64_t da, uint64_t db) {
    asm volatile("wgmma.mma_async.sync.aligned.m64n64k16.f32.bf16.bf16 {%0, %1, %2, %3, %4, %5, %6, %7, %8, %9, %10, %11, %12, %13, %14, %15, %16, %17, %18, %19, %20, %21, %22, %23, %24, %25, %26, %27, %28, %29, %30, %31}, %32, %33, 1, 1, 1, 1, 0;"
                 : "+f"(d[0]), "+f"(d[1]), "+f"(d[2]), "+f"(d[3]), "+f"(d[4]), "+f"(d[5]), "+f"(d[6]), "+f"(d[7]), "+f"(d[8]), "+f"(d[9]), "+f"(d[10]), "+f"(d[11]), "+f"(d[12]), "+f"(d[13]), "+f"(d[14]), "+f"(d[15]), "+f"(d[16]), "+f"(d[17]), "+f"(d[18]), "+f"(d[19]), "+f"(d[20]), "+f"(d[21]), "+f"(d[22]), "+f"(d[23]), "+f"(d[24]), "+f"(d[25]), "+f"(d[26]), "+f"(d[27]), "+f"(d[28]), "+f"(d[29]), "+f"(d[30]), "+f"(d[31]) : "l"(da), "l"(db));
}
__device__ __forceinline__ void wg_n64(float* d, uint32_t a0, uint32_t a1, uint32_t a2, uint32_t a3, uint64_t db) {
    asm volatile("wgmma.mma_async.sync.aligned.m64n64k16.f32.bf16.bf16 {%0, %1, %2, %3, %4, %5, %6, %7, %8, %9, %10, %11, %12, %13, %14, %15, %16, %17, %18, %19, %20, %21, %22, %23, %24, %25, %26, %27, %28, %29, %30, %31}, {%32, %33, %34, %35}, %36, 1, 1, 1, 0;"
                 : "+f"(d[0]), "+f"(d[1]), "+f"(d[2]), "+f"(d[3]), "+f"(d[4]), "+f"(d[5]), "+f"(d[6]), "+f"(d[7]), "+f"(d[8]), "+f"(d[9]), "+f"(d[10]), "+f"(d[11]), "+f"(d[12]), "+f"(d[13]), "+f"(d[14]), "+f"(d[15]), "+f"(d[16]), "+f"(d[17]), "+f"(d[18]), "+f"(d[19]), "+f"(d[20]), "+f"(d[21]), "+f"(d[22]), "+f"(d[23]), "+f"(d[24]), "+f"(d[25]), "+f"(d[26]), "+f"(d[27]), "+f"(d[28]), "+f"(d[29]), "+f"(d[30]), "+f"(d[31]) : "r"(a0), "r"(a1), "r"(a2), "r"(a3), "l"(db));
}
__device__ __forceinline__ void wg_n64_first(float* d, uint32_t a0, uint32_t a1, uint32_t a2, uint32_t a3, uint64_t db) {
    asm volatile("wgmma.mma_async.sync.aligned.m64n64k16.f32.bf16.bf16 {%0, %1, %2, %3, %4, %5, %6, %7, %8, %9, %10, %11, %12, %13, %14, %15, %16, %17, %18, %19, %20, %21, %22, %23, %24, %25, %26, %27, %28, %29, %30, %31}, {%32, %33, %34, %35}, %36, 0, 1, 1, 0;"
                 : "=f"(d[0]), "=f"(d[1]), "=f"(d[2]), "=f"(d[3]), "=f"(d[4]), "=f"(d[5]), "=f"(d[6]), "=f"(d[7]), "=f"(d[8]), "=f"(d[9]), "=f"(d[10]), "=f"(d[11]), "=f"(d[12]), "=f"(d[13]), "=f"(d[14]), "=f"(d[15]), "=f"(d[16]), "=f"(d[17]), "=f"(d[18]), "=f"(d[19]), "=f"(d[20]), "=f"(d[21]), "=f"(d[22]), "=f"(d[23]), "=f"(d[24]), "=f"(d[25]), "=f"(d[26]), "=f"(d[27]), "=f"(d[28]), "=f"(d[29]), "=f"(d[30]), "=f"(d[31]) : "r"(a0), "r"(a1), "r"(a2), "r"(a3), "l"(db));
}

__device__ __forceinline__ void wg_n32t(float* d, uint32_t a0, uint32_t a1, uint32_t a2, uint32_t a3, uint64_t db) {
    asm volatile("wgmma.mma_async.sync.aligned.m64n32k16.f32.bf16.bf16 {%0, %1, %2, %3, %4, %5, %6, %7, %8, %9, %10, %11, %12, %13, %14, %15}, {%16, %17, %18, %19}, %20, 1, 1, 1, 1;"
                 : "+f"(d[0]), "+f"(d[1]), "+f"(d[2]), "+f"(d[3]), "+f"(d[4]), "+f"(d[5]), "+f"(d[6]), "+f"(d[7]), "+f"(d[8]), "+f"(d[9]), "+f"(d[10]), "+f"(d[11]), "+f"(d[12]), "+f"(d[13]), "+f"(d[14]), "+f"(d[15]) : "r"(a0), "r"(a1), "r"(a2), "r"(a3), "l"(db));
}
__device__ __forceinline__ void wg_n32t_first(float* d, uint32_t a0, uint32_t a1, uint32_t a2, uint32_t a3, uint64_t db) {
    asm volatile("wgmma.mma_async.sync.aligned.m64n32k16.f32.bf16.bf16 {%0, %1, %2, %3, %4, %5, %6, %7, %8, %9, %10, %11, %12, %13, %14, %15}, {%16, %17, %18, %19}, %20, 0, 1, 1, 1;"
                 : "=f"(d[0]), "=f"(d[1]), "=f"(d[2]), "=f"(d[3]), "=f"(d[4]), "=f"(d[5]), "=f"(d[6]), "=f"(d[7]), "=f"(d[8]), "=f"(d[9]), "=f"(d[10]), "=f"(d[11]), "=f"(d[12]), "=f"(d[13]), "=f"(d[14]), "=f"(d[15]) : "r"(a0), "r"(a1), "r"(a2), "r"(a3), "l"(db));
}
__device__ __forceinline__ void wg_n32t_sfirst(float* d, uint64_t da, uint64_t db) {
    asm volatile("wgmma.mma_async.sync.aligned.m64n32k16.f32.bf16.bf16 {%0, %1, %2, %3, %4, %5, %6, %7, %8, %9, %10, %11, %12, %13, %14, %15}, %16, %17, 0, 1, 1, 1, 1;"
                 : "=f"(d[0]), "=f"(d[1]), "=f"(d[2]), "=f"(d[3]), "=f"(d[4]), "=f"(d[5]), "=f"(d[6]), "=f"(d[7]), "=f"(d[8]), "=f"(d[9]), "=f"(d[10]), "=f"(d[11]), "=f"(d[12]), "=f"(d[13]), "=f"(d[14]), "=f"(d[15]) : "l"(da), "l"(db));
}
__device__ __forceinline__ void wg_n32t_s(float* d, uint64_t da, uint64_t db) {
    asm volatile("wgmma.mma_async.sync.aligned.m64n32k16.f32.bf16.bf16 {%0, %1, %2, %3, %4, %5, %6, %7, %8, %9, %10, %11, %12, %13, %14, %15}, %16, %17, 1, 1, 1, 1, 1;"
                 : "+f"(d[0]), "+f"(d[1]), "+f"(d[2]), "+f"(d[3]), "+f"(d[4]), "+f"(d[5]), "+f"(d[6]), "+f"(d[7]), "+f"(d[8]), "+f"(d[9]), "+f"(d[10]), "+f"(d[11]), "+f"(d[12]), "+f"(d[13]), "+f"(d[14]), "+f"(d[15]) : "l"(da), "l"(db));
}

__device__ __forceinline__ void wg_n32_kk(float* d, uint64_t da, uint64_t db) {
    asm volatile("wgmma.mma_async.sync.aligned.m64n32k16.f32.bf16.bf16 {%0, %1, %2, %3, %4, %5, %6, %7, %8, %9, %10, %11, %12, %13, %14, %15}, %16, %17, 1, 1, 1, 0, 0;"
                 : "+f"(d[0]), "+f"(d[1]), "+f"(d[2]), "+f"(d[3]), "+f"(d[4]), "+f"(d[5]), "+f"(d[6]), "+f"(d[7]), "+f"(d[8]), "+f"(d[9]), "+f"(d[10]), "+f"(d[11]), "+f"(d[12]), "+f"(d[13]), "+f"(d[14]), "+f"(d[15]) : "l"(da), "l"(db));
}

}

namespace ws {
#define LAGT 4
constexpr int LAG = LAGT, NT = NSEG + LAG, NCL = 7;
#define P1A 24
#define P1C 10
#define XD 350
#define TPV_PAUSE 1
#define OT_LATE 1
#define H1_LATE 2
#define O_BULK 0
#define O_DLY 0
#define BP 0
#define REG_G 200
#define REG_T 72
#define REG_X 40
#define PDA 8
#define PDC 8
template <int V> struct IC { static constexpr int value = V; };
#define HBYTES 5120
#define POST_NS 20
#define OP_NS 20
#define LN0_AHEAD 8
#define PRE_PDL 0
#define PRE_PF 0
#define OP_LATE 0
#define G_DLY 0
#define QUIET 0
constexpr int NB4 = QUIET ? 480 : 384;
#define TG_STEPS 40
#define NO_X 0
#define WTA 3
constexpr int WTC = 10 - 2 * WTA;
#define WR 4
#define OBK 2
#define TPVW 1
#define OBRES 1
#define O0_EARLY 1
#define BNS 0
#define SKEW 0
#define XS 250
#define WGRP 4
#define WFLY 2
#define XDUP 1
#define TPV_LATE 0
#define WVOL 1
#define WK3 0
#define W_SKIP 0
#define POST_DRY 0
#define CONV_DRY 0
#define SPIN 0
#define H_NS 20
#define CV_YIELD 0
#define NL2 2
#define XFD 250
#define SELF_LOCAL 0
#define U0_SPARE 0
constexpr int XRS = 3;
constexpr int O_H = 0, O_MEM = 81920, O_RED = 102400, O_BAR = 110080, O_TAB = O_BAR + 192, O_BT = O_TAB + 128, O_TR = O_BAR + 512, O_X = O_TR + 1024;
constexpr int O_QRY = O_X, O_KEY = O_X + 10240, O_OBA = O_KEY + 10240, O_ST = O_OBA + 4096;
constexpr int O_VT = O_X, O_VM = O_VT + 32768, O_SM = O_VM + 4096, O_PB = O_SM + 3072;
constexpr int O_AS = 228352, O_WO = O_AS - 65536, HEAD_SMEM = O_AS + 4096, O_STG = 40960;
static_assert(O_ST + 8192 <= O_WO && O_PB + 10240 <= O_WO && O_AS % 1024 == 0 && O_STG + 163840 <= O_AS && HEAD_SMEM <= 232448, "smem");
constexpr int O_BUSY = O_BT + 128;
constexpr int B_MEM = 0, B_RED = 64, B_SM = 88, B_ST = 96, B_OB = 104, B_HF = 112, B_HE = 128, B_OTF = 144, B_OTE = 160;

constexpr int F_H = 0, F_O = 128, F_P = 256, F_U = 384, F_CV = 392, F_XL = 398, F_Z = 399, NFLAG = 400;
__device__ int g_flags[NFLAG * 8];
#define FLG(i) (g_flags + (i) * 8)
#define RING 16
__device__ __forceinline__ int rslot(int l, int seg) { return l * RING + (seg & (RING - 1)); }
__device__ uint4 g_ht[2 * RING * 2560];
__device__ uint4 g_ot[2 * RING * 256 * 64];
__device__ uint4 g_pt[2 * RING * 5120];
__device__ uint4 g_Y[80 * S_LEN];
__device__ uint4 g_U[DM * S_LEN / 8];
__device__ bf16 g_x[RING * SEG * DM];
__device__ int g_epoch;
__device__ uint4 g_xc[XRS * 16 * 3 * 8 * 32];
#define GT(cond, i)
#define SC(cond, i)
#define SD(x)
#define TS(i)
#define TV(i, v)

}

namespace ws {
__device__ __forceinline__ uint32_t bmul2(uint32_t a, uint32_t b) { uint32_t r; asm("mul.rn.bf16x2 %0, %1, %2;" : "=r"(r) : "r"(a), "r"(b)); return r; }
__device__ __forceinline__ uint32_t bmax2(uint32_t a, uint32_t b) { uint32_t r; asm("max.bf16x2 %0, %1, %2;" : "=r"(r) : "r"(a), "r"(b)); return r; }
__device__ __forceinline__ void flag_wait(const int* f, int tgt, int ns) {
    int guard = 0;
    while (ld_relaxed(f) < tgt) { if (++guard > 4000000) __trap(); __nanosleep(ns); }
}
template <int STRIDE> __device__ __forceinline__ void ld5(uint32_t* w, const void* p) {
#pragma unroll
    for (int r = 0; r < 5; r++) { const uint2 v = __ldcg(reinterpret_cast<const uint2*>(reinterpret_cast<const char*>(p) + r * STRIDE)); w[2 * r] = v.x; w[2 * r + 1] = v.y; }
}
template <int STRIDE> __device__ __forceinline__ void st5(void* p, const uint32_t* w) {
#pragma unroll
    for (int r = 0; r < 5; r++) *reinterpret_cast<uint2*>(reinterpret_cast<char*>(p) + r * STRIDE) = make_uint2(w[2 * r], w[2 * r + 1]);
}
__device__ __forceinline__ void ln_row(const uint32_t* x, uint32_t* y) {
    const float c = blo(__shfl_sync(0xffffffffu, x[0], 0));
    float s0 = 0.f, s1 = 0.f, q0 = 0.f, q1 = 0.f;
#pragma unroll
    for (int i = 0; i < 10; i++) { const float d0 = blo(x[i]) - c, d1 = bhi(x[i]) - c; s0 += d0; s1 += d1; q0 = fmaf(d0, d0, q0); q1 = fmaf(d1, d1, q1); }
    float s = s0 + s1, q = q0 + q1;
#pragma unroll
    for (int o = 16; o > 0; o >>= 1) { s += __shfl_xor_sync(0xffffffffu, s, o); q += __shfl_xor_sync(0xffffffffu, q, o); }
    s *= 1.0f / DM;
    const float mean = c + s;
    q = fmaxf(fmaf(q, 1.0f / DM, -s * s), 0.f);
    const uint32_t nm = pack2(-mean, -mean);
    float sq;
    asm("sqrt.approx.ftz.f32 %0, %1;" : "=f"(sq) : "f"(rbf(rbf(q) + 1e-5f)));
    const float rd = rcpf(rbf(sq));
#pragma unroll
    for (int i = 0; i < 10; i++) { const uint32_t d = badd(x[i], nm); y[i] = pack2(blo(d) * rd, bhi(d) * rd); }
}
__device__ __forceinline__ void clear_acc(int l, int seg, int tok, int lane) {
    uint4* pz = g_pt + rslot(l, seg) * 5120 + (lane >> 4) * 512 + tok * 16 + (lane & 15);
#pragma unroll
    for (int i = 0; i < 5; i++) pz[i * 1024] = make_uint4(0, 0, 0, 0);
}
__device__ __forceinline__ void put_h(int l, int seg, int tok, int lane, const uint32_t* n) {
    st5<8192>(reinterpret_cast<char*>(g_ht + rslot(l, seg) * 2560) + (lane >> 2) * 1024 + tok * 32 + (((lane & 3) * 8) ^ ((tok & 4) << 2)), n);
}
__device__ __forceinline__ void ln0_row(const bf16* x, int seg, int tok, int lane) {
    uint32_t v[10];
    ld5<256>(v, x + (size_t)(seg * SEG + tok) * DM + lane * 4);
    clear_acc(0, seg, tok, lane);
    ln_row(v, v);
    put_h(0, seg, tok, lane, v);
    __syncwarp();
    if (lane == 0) red_release(FLG(F_H + seg), 1);
}
__device__ __forceinline__ void post_row(int l, int seg, int tok, int lane, const bf16* xin, bf16* xout, int ep) {
    const bool dry = ep == 0;
    uint32_t x[10], y[10], n[10];
    const int row = seg * SEG + tok;
    SC(tr, tb);
    const bool first = seg == 0;
    if (seg == 8 || ((seg & 15) == 0 && seg)) flag_wait(FLG(F_CV + (seg >> 4) + 1), 80 * ep, 50);
    const char* yp = dry ? reinterpret_cast<const char*>(xin) + lane * 8 : reinterpret_cast<const char*>(g_Y) + ((size_t)(lane >> 1) * S_LEN + row) * 16 + (lane & 1) * 8;
    SC(tr, tb + 1);
    if (!first) ld5<16 * S_LEN * 16>(y, yp);
    bf16* xm = g_x + ((seg & (RING - 1)) * SEG + tok) * DM + lane * 4;
    if (l == 0) {
        ld5<256>(x, xin + (size_t)row * DM + lane * 4);
        if (!dry) clear_acc(1, seg, tok, lane);
    } else {
        if (!dry) flag_wait(seg + 1 < NSEG ? FLG(F_H + 65 + seg) : FLG(F_XL), 32 * ep, 50);
        ld5<256>(x, dry ? xin + lane * 4 : xm);
    }
    if (!dry) flag_wait(FLG(F_P + l * 64 + seg), 40 * ep, POST_NS);
    SC(tr, tb + 2);
    const uint4* pp = dry ? reinterpret_cast<const uint4*>(xin) + lane : g_pt + rslot(l, seg) * 5120 + (lane >> 4) * 512 + tok * 16 + ((lane & 15) ^ ((tok >> 3) << 1));
    {
        uint4 a[5];
#pragma unroll
        for (int i = 0; i < 5; i++) a[i] = __ldcg(pp + i * 1024);
#pragma unroll
        for (int i = 0; i < 5; i++) {
            x[2 * i] = badd(x[2 * i], pack2(__uint_as_float(a[i].x), __uint_as_float(a[i].y)));
            x[2 * i + 1] = badd(x[2 * i + 1], pack2(__uint_as_float(a[i].z), __uint_as_float(a[i].w)));
        }
    }
    SC(tr && x[0] != 0x12345, tb + 3);
    if (first) { if (!dry) flag_wait(FLG(F_CV), 80 * ep, 50); ld5<16 * S_LEN * 16>(y, yp); }
    ln_row(x, n);
#pragma unroll
    for (int i = 0; i < 10; i++) x[i] = badd(x[i], bmul2(n[i], y[i]));
    SC(tr && x[0] != 0x12345, tb + 4);
    if (l) { if (!dry) st5<256>(xout + (size_t)row * DM + lane * 4, x); }
    else {
        ln_row(x, n);
        SC(tr && n[0] != 0x12345, tb + 5);
        if (!dry) put_h(1, seg, tok, lane, n);
        __syncwarp();
        if (lane == 0 && !dry) red_release(FLG(F_H + 64 + seg), 1);
        SC(tr, tb + 6);
        if (!dry) st5<256>(xm, x);
        if (seg == NSEG - 1) { __syncwarp(); if (lane == 0) red_release(FLG(F_XL), 1); }
    }
}
__device__ __forceinline__ void u_piece(const bf16* Bk, const bf16* Bv, const bf16* shiftk, int t0, int cp, uint4* o) {
    uint32_t kk[11], vv[8];
    const uint32_t* pk = reinterpret_cast<const uint32_t*>(Bk + (size_t)t0 * DM) + cp;
    const uint32_t* pv = reinterpret_cast<const uint32_t*>(Bv + (size_t)t0 * DM) + cp;
#pragma unroll
    for (int i = 0; i < 11; i++) kk[i] = (i >= 3 || t0 > 0) ? __ldg(pk + (i - 3) * (DM / 2)) : 0u;
#pragma unroll
    for (int i = 0; i < 8; i++) vv[i] = __ldg(pv + i * (DM / 2));
    const uint4 sh0 = __ldg(reinterpret_cast<const uint4*>(shiftk + cp * 8));
    const uint32_t s0 = __byte_perm(sh0.x, sh0.z, 0x5410), s1 = __byte_perm(sh0.x, sh0.z, 0x7632), s2 = __byte_perm(sh0.y, sh0.w, 0x5410), s3 = __byte_perm(sh0.y, sh0.w, 0x7632);
#pragma unroll
    for (int t = 0; t < 8; t++)
        vv[t] = bmul2(badd(badd(badd(bmul2(kk[t], s3), bmul2(kk[t + 1], s2)), bmul2(kk[t + 2], s1)), bmul2(kk[t + 3], s0)), vv[t]);
#pragma unroll
    for (int c = 0; c < 2; c++) {
        const uint32_t sel = c ? 0x7632 : 0x5410;
        o[c] = make_uint4(__byte_perm(vv[7], vv[6], sel), __byte_perm(vv[5], vv[4], sel), __byte_perm(vv[3], vv[2], sel), __byte_perm(vv[1], vv[0], sel));
    }
}
__device__ __forceinline__ int u_pos(int t0) { return (t0 >> 6) * 8 + ((((t0 ^ 56) & 63) >> 3) ^ ((t0 >> 6) & 7)); }
__device__ __forceinline__ void u_half(const bf16* Bk, const bf16* Bv, const bf16* shiftk, int unit, int lane) {
    const int t0 = (unit / 20) * 16 + (lane & 1) * 8, cp = (unit % 20) * 16 + (lane >> 1);
    uint4 o[2];
    u_piece(Bk, Bv, shiftk, t0, cp, o);
    uint4* d = g_U + (size_t)(cp * 2) * (S_LEN / 8) + u_pos(t0);
    d[0] = o[0]; d[S_LEN / 8] = o[1];
}
constexpr int CV_E = 4224, CV_W = 2 * 4096 + 3 * CV_E + 128, CV_HI = O_X, CV_Y = CV_HI + 4 * CV_W, CV_T = CV_Y + 16384, CV_Z = CV_T + 16384;
static_assert(4 * CV_W <= O_RED && CV_W % 128 == 0 && CV_Z + 128 <= HEAD_SMEM, "conv buffers");
__device__ __forceinline__ void conv_unit(uint32_t ub, uint32_t e0, uint32_t e1, uint32_t zrow, uint32_t tt, uint32_t Dv, int rg, int nq, int lane, uint32_t zero, uint32_t busy, int tb) {
    const int g7 = 7 - (lane >> 2), tq = lane & 3;
    SC(tb >= 0, tb + 3);
    for (int i = lane; i < 32 * nq + 8; i += 32) {
        const uint4 v = lds128(e0 + i * 16);
        const uint32_t nx = lds32(e0 + i * 16 + 16);
        sts128(e1 + i * 16, __byte_perm(v.x, v.y, 0x5432), __byte_perm(v.y, v.z, 0x5432), __byte_perm(v.z, v.w, 0x5432), __byte_perm(v.w, nx, 0x5432));
    }
    __syncwarp();
    SC(tb >= 0, tb + 4);
    float acc[4][4];
#pragma unroll
    for (int i = 0; i < 16; i++) (&acc[0][0])[i] = 0.f;
    uint32_t wb = (g7 & 1) ? e0 + (1 + g7 + 2 * tq) * 2 : e1 + (g7 + 2 * tq) * 2;
    int row = 8 * rg + (lane & 7);
    auto ldb = [&](uint4* b) {
        const uint32_t x = row < 0 ? zrow : ub + row * 128 + (((lane >> 3) ^ (row & 7)) << 4);
        b[0] = ldsm4(x); b[1] = ldsm4(x ^ 64);
        row--;
    };
    uint4 Q[16], b[2][2];
    Q[15].w = lds32(wb);
    auto ldq = [&](int q, int o) { Q[q].y = lds32(wb + o * 32 + 16); Q[q].w = lds32(wb + o * 32 + 32); };
    auto cpq = [&](int q) { Q[q].x = Q[(q + 15) & 15].w + zero; Q[q].z = Q[q].y + zero; };
#pragma unroll
    for (int q = 0; q < 11; q++) ldq(q, q);
#pragma unroll
    for (int q = 0; q < 7; q++) cpq(q);
    ldb(b[0]);
#pragma unroll 1
    for (int D0 = nq; D0 > 0; D0--) {
#pragma unroll
        for (int d = 0; d < 4; d++) {
            if (CV_YIELD && (CV_YIELD == 1 || !(d & 1))) while (lds32(busy)) __nanosleep(40);
            ldb(b[(d + 1) & 1]);
#pragma unroll
            for (int q = 11; q < 15; q++) ldq((4 * d + q) & 15, 4 * d + q);
#pragma unroll
            for (int ks = 0; ks < 4; ks++) {
                const uint4& bb_ = b[d & 1][ks >> 1];
#pragma unroll
                for (int m = 0; m < 4; m++) {
                    const uint4& a = Q[(4 * d + m + ks) & 15];
                    mmav(acc[m], a.x, a.y, a.z, a.w, (ks & 1) ? bb_.z : bb_.x, (ks & 1) ? bb_.w : bb_.y);
                }
                cpq((4 * d + 7 + ks) & 15);
            }
        }
        wb += 512;
    }
    SC(tb >= 0 && acc[0][0] != 1.2345f, tb + 5);
    const uint32_t ua = ub + (8 * rg + (lane & 7)) * 128 + (((lane >> 3) ^ (lane & 7)) << 4);
    const uint4 u0 = ldsm4t(ua), u1 = ldsm4t(ua ^ 64);
    auto y = [&](int m, int hf, uint32_t u) { return badd(pack2(acc[m][2 * hf], acc[m][2 * hf + 1]), bmul2(u, Dv)); };
    stsm4t(tt, y(0, 0, u1.w), y(0, 1, u1.z), y(1, 0, u1.y), y(1, 1, u1.x));
    stsm4t(tt ^ 64, y(2, 0, u0.w), y(2, 1, u0.z), y(3, 0, u0.y), y(3, 1, u0.x));
}
}

namespace ws {
struct HeadArgs { const bf16 *x, *mem0, *Wq, *Wk, *Wv, *Wo, *Bk, *Bv, *shiftk, *ssmk, *ssmD; bf16* out; int h_target; };

__global__ void __launch_bounds__(512, 1) head_kernel(const __grid_constant__ HeadArgs A) {
    extern __shared__ __align__(1024) unsigned char smem_raw[];
    const int tid = threadIdx.x, warp = __shfl_sync(0xffffffffu, tid >> 5, 0), lane = tid & 31;
    const int cq = blockIdx.x >> 4, r = blockIdx.x & 15;
    const int nh = cq < 4 ? 5 : 4, hi = r / 3, role = r - hi * 3;
    const bool head = r < 3 * nh;
    const int p0 = ((r >> 1) - SELF_LOCAL) & 7;
    const int h = (cq < 4 ? 5 * cq : 4 * cq + 4) + hi;
    const uint32_t sb = smem_u32(smem_raw), bb = sb + O_BAR;
    GT(tid == 0, 1);
    const int sp = cq < 4 ? cq : 4 * cq + r - 24;
    if (tid == 0) {
        if ((sb & 0xFFFFFFu) != 1024) __trap();
        for (int i = 0; i < 12; i++) mbar_init(bb + i * 8, SELF_LOCAL && head && i == 7 ? 4 : 1);
        mbar_init(bb + B_ST, role == 2 ? 1 : 5);
        mbar_init(bb + B_OB, 1); mbar_init(bb + B_OB + 64, 1);
        mbar_init(bb + B_HF, 1); mbar_init(bb + B_HF + 8, 1);
        mbar_init(bb + B_HE, 6 * nh);
        sts32(sb + O_BUSY, 0u);
        mbar_init(bb + B_OTF, head ? 4 : 8); mbar_init(bb + B_OTE, 1); mbar_init(bb + B_OTF + 8, head ? 4 : 8); mbar_init(bb + B_OTE + 16, 1);
        asm volatile("fence.mbarrier_init.release.cluster;" ::: "memory");
        mbar_expect_tx(bb + B_RED, nh * 1280);
        mbar_expect_tx(bb + B_SM, 3072); mbar_expect_tx(bb + B_ST, role == 2 ? 5120 : 4096);
        if (role != 2) { mbar_expect_tx(bb + B_OB, 2048); mbar_expect_tx(bb + B_OB + 64, 2048); }
        mbar_expect_tx(bb + B_HF, 8 * HBYTES); mbar_expect_tx(bb + B_HF + 8, 8 * HBYTES);
    }
    asm volatile("griddepcontrol.launch_dependents;");
    __syncwarp();
    cluster_arrive_relaxed();
    if (warp < 8) {
        asm volatile("setmaxnreg.inc.sync.aligned.u32 %0;" ::"n"(REG_G));
        const int wg = warp >> 2, w4 = warp & 3;
        if (head) {
            uint32_t wa[40][4];
            {
                const int t7 = tid & 127;
                const bf16* W = (role == 2 ? A.Wv + wg * 64 : (wg ? A.Wk : A.Wq) + role * 64) + h * DH + (size_t)(t7 >> 3) * HD + (t7 & 7) * 8;
                const uint32_t so = (t7 >> 3) * 128 + (((t7 & 7) ^ ((t7 >> 3) & 7)) << 4), stg = sb + O_STG + wg * 81920;
                const uint32_t la = stg + ((lane & 7) + (lane >> 4) * 8) * 128 + (((w4 * 2 + ((lane >> 3) & 1)) ^ (lane & 7)) << 4);
                GT(tid == 0, 80);
#pragma unroll
                for (int gi = 0; gi < 8 + WFLY; gi++) {
                    if (gi < 8) {
                        const bf16* Wg = W + (size_t)(((p0 - gi) & 7) * 80) * HD;
#pragma unroll
                        for (int u = 0; u < 5; u++) cp_async16((gi == 0 && u == 0 ? sb + O_AS + wg * 2048 : stg + (gi * 5 + u) * 2048) + so, Wg + (size_t)u * 16 * HD);
                    }
                    cp_commit();
                    if (gi >= WFLY) {
                        cp_wait<WFLY>();
                        named_bar(8 + wg, 128);
#pragma unroll
                        for (int u = 0; u < 5; u++) {
                            const int j = (gi - WFLY) * 5 + u;
                            if (j) { const uint4 v = ldsm4t(la + j * 2048); wa[j][0] = v.x; wa[j][1] = v.y; wa[j][2] = v.z; wa[j][3] = v.w; }
                        }
                    }
                }
                GT(tid == 0, 83);
                cluster_wait();
            }
            named_bar(10, 384);
            GT(tid == 0, 2);
            fence_async_smem();
            named_bar(8 + wg, 128);
            cluster_arrive_relaxed();
            float acc[16];
            const uint32_t ep_q = role == 2 ? sb + O_VM + warp * 512 + (lane ^ ((lane >> 3) & 1)) * 16
                                            : sb + O_QRY + wg * 10240 + ((lane >> 1) & 1) * 5120 + (4 * (lane >> 4) + 2 * ((lane >> 2) & 1) + (lane & 1)) * 128 +
                                                  (((2 * w4 + ((lane >> 3) & 1)) ^ (4 * (lane >> 4) + 2 * ((lane >> 2) & 1) + (lane & 1)) ^ ((lane & 2) << 1)) << 4);
            const uint32_t ep_t = role == 2 ? sb + O_VT + warp * 1024 + ((lane >> 3) & 1) * 512 + (lane >> 4) * 128 + (lane & 7) * 16
                                            : sb + O_QRY + wg * 10240 + (8 + 8 * (lane >> 4) + (lane & 7)) * 128 + (((2 * w4 + ((lane >> 3) & 1)) ^ (lane & 7)) << 4);
                        const int pz = role == 2 ? P1C : P1A;
            const uint32_t ab = (1024 + O_AS + wg * 2048) >> 4;
            uint32_t ok = 1;
            const uint32_t tidk = __shfl_sync(0xffffffffu, tid, lane);
            auto token_gemm = [&](auto ll, const bool pause, const uint32_t vo, const uint32_t nbar, const uint32_t npar, const int t) {
                constexpr int l = decltype(ll)::value;
                constexpr uint32_t hb = ((1024 + O_H + l * 40960) >> 4) | (1u << 16);
                const uint32_t pr = opq(p0);
                if (l) TS(15); else TS(14);
                wg_fence();
#pragma unroll
                for (int j = 0; j < 40; j++) {
                    const uint64_t db = mkdesc(hb + ((pr - j / 5) & 7) * 320 + (j % 5) * 64, 0xC0000010u);
                    if (j == 0) wg_n32_sfirst(acc, mkdesc(ab, 0x40000040u), db);
                    else if (j < TG_STEPS) wg_n32(acc, wa[j][0], wa[j][1], wa[j][2], wa[j][3], db);
                    if (l == 0 && (j + 1 == P1A || j + 1 == P1C)) {
                        if (pause && pz == j + 1) {
                            wg_commit();
                            if (role == 2) mwait(bb + B_OTE, vo >> 14);
                            wg_wait<0>();
                            named_arrive(3, 384);
                            named_bar(4, NB4);
                            if (SKEW && wg) delay(SKEW);
                            wg_fence();
                        }
                    }
                }
                wg_commit();
                ok = mtest(nbar, npar);
                wg_wait<0>();
                uint32_t pk[8];
#pragma unroll
                for (int i = 0; i < 8; i++) pk[i] = pack2(acc[2 * i], acc[2 * i + 1]);
                if (role == 2) {
                    stsm4(ep_t + l * 8192 + vo, pk[0], pk[1], pk[2], pk[3]);
                    stsm4(ep_t + l * 8192 + vo + 256, pk[4], pk[5], pk[6], pk[7]);
                } else {
                    stsm4t((ep_t ^ (l << 6)) + l * 5120, pk[0], pk[1], pk[2], pk[3]);
                    stsm4t((ep_t ^ (l << 6)) + l * 5120 + 2048, pk[4], pk[5], pk[6], pk[7]);
                }
                asm volatile("{\n.reg .pred p, q;\nsetp.eq.u32 p, %0, 0;\nsetp.eq.u32 q, %1, 0;\n"
                             "@p mbarrier.arrive.expect_tx.shared::cta.b64 _, [%2], %3;\n@q mbarrier.arrive.shared::cluster.b64 _, [%4];\n}"
                             ::"r"(tidk), "r"(tidk & 127), "r"(bb + B_HF + l * 8), "r"(8 * HBYTES), "r"(mapa(bb + B_HE, l)) : "memory");
            };
            GT(tid == 0, 86);
            mwait(bb + B_HF, 0);
            GT(tid == 0, 87);
            token_gemm(IC<0>{}, false, 0, bb + B_MEM, 1, -1);
            GT(tid == 0, 88);
            named_bar(11, 384);
            cluster_wait();
            named_arrive(13, 384);
#pragma unroll 1
            for (int t = 0; t < NT; t++) {
                GT(tid == 0 && blockIdx.x == 98, 100 + t);
                SC(tid == 0 && blockIdx.x == 98, 160 + t);
                TS(0);
                const uint32_t mp = (t & 1) ^ 1;
                const bool tg0 = t + 1 < NSEG, tg1 = t + 1 >= LAG;
                constexpr uint32_t mb = ((1024 + O_MEM) >> 4) | (16u << 16);
#pragma unroll
                for (int G = 0; G < 8; G++) {
                    if (__builtin_expect(!ok, 0)) { if (SPIN & 8) mspin(bb + B_MEM + G * 8, mp); else mwait(bb + B_MEM + G * 8, mp); }
                    ok = mtest(G < 7 ? bb + B_MEM + (G + 1) * 8 : bb + B_HF, mp);
                    if (G == 0) { TS(1); wg_fence(); }
                    if (G == 7) TS(2);
                    if (G == 1) TS(8); if (G == 2) TS(9); if (G == 3) TS(10); if (G == 4) TS(11); if (G == 5) TS(12); if (G == 6) TS(13);
#pragma unroll
                    for (int u = 0; u < 5; u++) {
                        const int j = G * 5 + u;
                        const uint64_t db = mkdesc(mb + j * 32, 8);
                        if (j == 0) wg_n16t_sfirst(acc, mkdesc(ab, 0x40000040u), db);
                        else wg_n16t(acc, wa[j][0], wa[j][1], wa[j][2], wa[j][3], db);
                    }
                    wg_commit();
                }
                if (role == 2 && t) named_bar(5, 384);
                wg_wait<0>();
                TS(3);
                if (role == 2) sts128(ep_q, pack2(acc[0], acc[1]), pack2(acc[2], acc[3]), pack2(acc[4], acc[5]), pack2(acc[6], acc[7]));
                else stsm4t(ep_q, pack2(acc[0], acc[1]), pack2(acc[2], acc[3]), pack2(acc[4], acc[5]), pack2(acc[6], acc[7]));
                named_arrive(1, 384);
                if (tidk < 8) mbar_expect_tx(bb + B_MEM + tidk * 8, SELF_LOCAL && tidk == 7 ? 1280 : 2560);
                if (t == NT - 1) break;
                if (tg0) {
                    if (__builtin_expect(!ok, 0)) mwait(bb + B_HF, mp);
                    if (role != 2) named_bar(2, 384);
                    token_gemm(IC<0>{}, true, mp * 16384, tg1 ? bb + B_HF + 8 : bb + B_MEM, tg1 ? (t + 1 - LAG) & 1 : mp ^ 1, t);
                } else {
                    if (role == 2) mwait(bb + B_OTE, mp); else named_bar(2, 384);
                    named_arrive(3, 384); named_bar(4, NB4);
                    ok = 0;
                }
                TS(5);
                if (tg1) {
                    if (__builtin_expect(!ok, 0)) mwait(bb + B_HF + 8, (t + 1 - LAG) & 1);
                    token_gemm(IC<1>{}, false, mp * 16384, bb + B_MEM, mp ^ 1, t);
                }
                TS(6);
                named_arrive(13, 384);
            }
        } else {
            cluster_wait(); cluster_arrive_relaxed();
            const int ep = ld_relaxed(&g_epoch) + 1;
            const uint32_t cb = sb + (warp < 4 ? warp * CV_W : CV_HI + (warp - 4) * CV_W), lb = bb + B_MEM + warp * 8;
            auto fetch = [&](int k) {
                const int ps = k / 5, rg = ps ? ps - 1 : 0, ch = (sp * 5 + k - 5 * ps) * 8 + warp;
                if (k == 5 * ps) { flag_wait(FLG(F_U + ps), (ps > 1 ? 20 : (ps ? 32 : (U0_SPARE ? 128 : 320))) * ep, 50); fence_async_global(); }
                if (lane == 0) {
                    const uint32_t nb = ps ? ps * 1024 : 512;
                    mbar_expect_tx(lb, 2 * nb);
                    asm volatile("cp.async.bulk.shared::cluster.global.mbarrier::complete_tx::bytes [%0], [%1], %2, [%3];" ::"r"(cb + (k & 1) * 4096), "l"(g_U + ch * (S_LEN / 8)), "r"(nb), "r"(lb) : "memory");
                    asm volatile("cp.async.bulk.shared::cluster.global.mbarrier::complete_tx::bytes [%0], [%1], %2, [%3];" ::"r"(cb + 8192 + (k & 1) * CV_E + 128), "l"(A.ssmk + (size_t)ch * S_LEN), "r"(nb), "r"(lb) : "memory");
                }
                __syncwarp();
            };
            sts32(cb + 8192 + lane * 4, 0u); sts32(cb + 8192 + CV_E + lane * 4, 0u);
            if (warp == 0) sts32(sb + CV_Z + lane * 4, 0u);
            uint32_t dv = 0;
            if (lane < 5) {
                prefetch_l2(A.ssmk + (size_t)((sp * 5 + lane) * 8 + warp) * S_LEN, 1024);
                dv = *reinterpret_cast<const unsigned short*>(A.ssmD + (sp * 5 + lane) * 8 + warp) * 0x10001u;
            }
#pragma unroll
            for (int i = 1; i < 5; i++) sts32(cb + 8192 + i * 768 + lane * 4, 0u);
            named_bar(8, 256);
            flag_wait(FLG(F_U), (U0_SPARE ? 128 : 320) * ep, 50);
            fence_async_global();
            if (lane == 0) mbar_expect_tx(lb, 5120);
            __syncwarp();
            if (lane < 10) {
                const int j = lane >> 1, ch = (sp * 5 + j) * 8 + warp;
                asm volatile("cp.async.bulk.shared::cluster.global.mbarrier::complete_tx::bytes [%0], [%1], %2, [%3];" ::"r"((lane & 1) ? cb + j * 512 : cb + 8192 + j * 768 + 128),
                             "l"((lane & 1) ? (const void*)(g_U + ch * (S_LEN / 8)) : (const void*)(A.ssmk + (size_t)ch * S_LEN)), "r"(512), "r"(lb) : "memory");
            }
            __syncwarp();
#pragma unroll 1
            for (int k = 0; k < 25; k++) {
                const int ps = k / 5, rg = ps ? ps - 1 : 0;
                const uint32_t Dv = __shfl_sync(0xffffffffu, dv, k - 5 * ps);
                const int tb = sp == 0 && tid == 0 && k >= -1 && k < 7 ? 72 + k * 8 : -1;
                SC(tb >= 0, tb);
                if (k == 0 || ps) {
                    mwait(lb, k & 1);
                    SC(tb >= 0, tb + 1);
                    if (ps && k - 5 * ps < 4) { fence_async_smem(); fetch(k + 1); }
                    SC(tb >= 0, tb + 2);
                }
                const uint32_t tt = sb + CV_T + (k & 1) * 8192;
                conv_unit(cb + (ps ? (k & 1) * 4096 : k * 512), cb + 8192 + (ps ? (k & 1) * CV_E : k * 768), cb + 8192 + 2 * CV_E + 64, sb + CV_Z,
                          tt + warp * 1024 + (lane & 7) * 128 + (((lane >> 3) ^ (lane & 7) ^ warp) & 7) * 16, Dv, rg, ps ? 2 * ps : 1, lane, (uint32_t)A.h_target >> 8, sb + O_BUSY, tb);
                mwait(bb + B_OTE + (k & 1) * 16, ((k >> 1) & 1) ^ 1);
                named_bar(8, 256);
                {
                    const uint32_t la = tt + (lane & 7) * 1024 + warp * 128 + (((lane >> 3) ^ (lane & 7) ^ warp) & 7) * 16;
                    const uint4 v0 = ldsm4t(la), v1 = ldsm4t(la ^ 64);
                    const uint32_t ya = sb + CV_Y + (k & 1) * 8192 + (warp * 64 + (lane >> 3) * 8 + 7 - (lane & 7)) * 16;
                    stsm4(ya, v0.x, v0.y, v0.z, v0.w);
                    stsm4(ya + 512, v1.x, v1.y, v1.z, v1.w);
                }
                SC(tb >= 0, tb + 6);
                fence_async_smem();
                __syncwarp();
                if (lane == 0) mbar_arrive(bb + B_OTF + (k & 1) * 8);
                if (k - 5 * ps == 4 && k < 24) fetch(k + 1);
                if (k == 0 && lane < 5) prefetch_l2(A.ssmk + (size_t)((sp * 5 + lane) * 8 + warp) * S_LEN + 512, 3072);
            }
            cluster_wait();
        }
    } else if (warp < 12) {
        asm volatile("setmaxnreg.dec.sync.aligned.u32 %0;" ::"n"(REG_T));
        const int w = warp & 3, c = w >> 1, hh = w & 1;
        const uint32_t lane0 = __shfl_sync(0xffffffffu, tid & 31, tid & 31);
        if (head) {
            const int tile0 = role * 4 * WTA, ntile = role == 2 ? 4 * WTC : 4 * WTA;
            const uint32_t wo = sb + O_WO;
            uint32_t mi[5][4];
#pragma unroll
            for (int i = 0; i < 5; i++)
#pragma unroll
                for (int q = 0; q < 4; q++) {
                    const unsigned short* mp = reinterpret_cast<const unsigned short*>(A.mem0) + 2 * q * DM + i * 128 + (tid & 127);
                    mi[i][q] = mp[0] | (uint32_t)mp[DM] << 16;
                }
            cluster_wait();
            named_bar(10, 384);
#pragma unroll
            for (int i = 0; i < 5; i++) {
                const int col = i * 128 + (tid & 127), kk = col >> 4, pr = (kk * 13) >> 6;
                const uint32_t ma = sb + O_MEM + (((p0 - pr) & 7) * 5 + kk - 5 * pr) * 512 + (col & 8) * 32 + (col & 7) * 16;
                sts128(ma, mi[i][0], mi[i][0], mi[i][1], mi[i][1]);
                sts128(ma + 128, mi[i][2], mi[i][2], mi[i][3], mi[i][3]);
            }
            fence_async_smem();
            named_arrive(11, 384);
            for (int i = tid & 127; i < ntile * 256; i += 128) {
                const int ti = i >> 8, p = (i >> 1) & 127, ch = i & 1;
                const int ks = p >> 4, kh = (p >> 3) & 1, e8 = p & 7;
                const int dim = 64 * (ks >> 2) + 16 * (e8 >> 1) + 8 * (e8 & 1) + 2 * (ks & 3) + kh;
                cp_async16(wo + ti * 4096 + p * 32 + ((ch ^ ((p >> 2) & 1)) << 4), A.Wo + (size_t)(h * DH + dim) * DM + (tile0 + ti) * 16 + ch * 8);
            }
            cp_commit();
            if (lane < 8) {
                const int u = 2 * (tile0 + w + 4 * (lane >> 1)) + (lane & 1), ow = u / 5;
                const int sl = u - 5 * ow;
                sts32(sb + O_TAB + w * 32 + lane * 4, mapa(sb + O_RED + (sl >> 1) * 2560 + (sl & 1) * 256 + hi * (sl < 4 ? 512 : 256), ow & 15));
            }
            cluster_arrive_relaxed(); cluster_wait();
            cp_wait<0>();
            named_bar(7, 128);
            const uint32_t wo_a = wo + w * 4096 + ((lane >> 4) * 8 + (lane & 7)) * 32 + ((((lane >> 3) & 1) ^ ((lane >> 2) & 1)) << 4);
            const uint32_t ob_0 = sb + (role == 2 ? O_PB : O_OBA) + (lane >> 4) * 2048 + ((lane >> 3) & 1) * 128 + ((lane & 7) ^ ((lane >> 1) & 4)) * 16;
            const float cs = 0.08838834764831845f * 1.4426950408889634f;
            auto w_frag = [&](auto four, int i) {
                return ldsm4t(wo_a + (i < 16 || decltype(four)::value == 4 ? (i >> 4) * 32768 + (i & 1) * 16384 + ((i >> 1) & 7) * 512 : 32768 + (i & 1) * 2048 + ((i >> 1) & 7) * 512));
            };
            auto w_pre = [&](auto four, auto pd, uint4* wf) {
#pragma unroll
                for (int i = 0; i < decltype(pd)::value; i++) wf[i] = w_frag(four, i);
            };
            auto w_run = [&](auto four, auto pd, auto rem_, uint4* wf, int t, const uint32_t ob_a, auto&& before_last) {
                constexpr int NTL = decltype(four)::value, PD = decltype(pd)::value, NF = 8 * NTL, NP = NTL > 2 ? 2 : 1;
                constexpr bool REMOTE = decltype(rem_)::value;
                const uint32_t ln = opq(lane0), l8 = (ln & 2) * 64 + (ln >> 2) * 16 + (ln & 1) * 8, rb = (bb + B_RED) & 0xFFFFFFu;
                auto slot = [](int i) { return i < 8 ? i : 8 - WR + (i - 8) % WR; };
                uint4 obr[8];
#pragma unroll
                for (int k = 0; k < 4; k++) obr[k] = ldsm4(ob_a + k * 256);
#pragma unroll
                for (int p = 0; p < NP; p++) {
                    const bool split = p == 1 && NTL == 3;
                    const int nk = split ? 4 : 8;
                    float d[4][4];
                    uint4 ta;
#pragma unroll
                    for (int i = 0; i < 16; i++) (&d[0][0])[i] = 0.f;
#pragma unroll
                    for (int ks = 0; ks < 8; ks++) {
                        if (ks >= nk) continue;
                        if (W_SKIP == 3 || (W_SKIP == 1 && REMOTE) || (W_SKIP == 2 && !REMOTE)) { if (ks == nk - 2) ta = lds128(sb + O_TAB + w * 32 + p * 16); if (REMOTE && p == 0 && ks == OBK) mwait(bb + B_OB + 64, t & 1); continue; }
                        if (p == 0 && ks == OBK) {
                            if (REMOTE) { mwait(bb + B_OB + 64, t & 1); TS(7); }
#pragma unroll
                            for (int k = 4; k < 8; k++) obr[k] = ldsm4(ob_a + k * 256);
                        }
                        if (ks == nk - 2) ta = lds128(sb + O_TAB + w * 32 + p * 16);
#pragma unroll
                        for (int u = 0; u < 2; u++) {
                            const int i = p * 16 + ks * 2 + u;
                            const uint4& o = obr[split && u ? ks + 4 : ks];
                            const uint4& f = wf[slot(i)];
                            if (WVOL) { mmav(d[2 * u], f.x, f.y, f.z, f.w, o.x, o.y); mmav(d[2 * u + 1], f.x, f.y, f.z, f.w, o.z, o.w); }
                            else { mmau(d[2 * u], f, o.x, o.y); mmau(d[2 * u + 1], f, o.z, o.w); }
                            if (i + WR >= 8 && i + WR < NF) wf[slot(i + WR)] = w_frag(four, i + WR);
                        }
                    }
                    if (p) TS(10); else TS(8);
                    if (p == NP - 1) before_last();
                    if (split) {
#pragma unroll
                        for (int i = 0; i < 4; i++) { d[0][i] += d[2][i]; d[1][i] += d[3][i]; }
                    }
                    st_async_v2(ta.x + l8, pack2(d[0][0], d[0][1]), pack2(d[1][0], d[1][1]), (ta.x & 0xFF000000u) | rb);
                    st_async_v2(ta.y + l8, pack2(d[0][2], d[0][3]), pack2(d[1][2], d[1][3]), (ta.y & 0xFF000000u) | rb);
                    if (!split) {
                        st_async_v2(ta.z + l8, pack2(d[2][0], d[2][1]), pack2(d[3][0], d[3][1]), (ta.z & 0xFF000000u) | rb);
                        st_async_v2(ta.w + l8, pack2(d[2][2], d[2][3]), pack2(d[3][2], d[3][3]), (ta.w & 0xFF000000u) | rb);
                    }
                }
            };
            if (role != 2) {
#pragma unroll 1
                for (int t = 0; t < NT; t++) {
                    const uint32_t lane = opq(lane0);
                    const uint32_t dc = mapa(sb, hi * 3 + 2), dp = mapa(sb, hi * 3 + (role ^ 1));
                    const uint32_t qa = sb + O_QRY + c * 5120 + (lane & 7) * 128;
                    const uint32_t sw = (((lane >> 3) ^ (lane & 7)) << 4) ^ (c << 6);
                    {
                        const uint32_t ka = qa + 10240;
                        const uint32_t kt = sb + O_KEY + c * 5120 + (lane & 15) * 128, kx = (((lane >> 4) ^ (lane & 7)) << 4) ^ (c << 6);
                        const uint32_t sd = dc + O_SM + role * 1536 + c * 768 + lane * 4, sbar = dc + O_BAR + B_SM;
                        const uint32_t ta = sb + O_QRY + c * 5120 + (8 + 16 * hh + ((lane & 15) ^ (role * 8))) * 128;
                        uint4 a[4], f[4];
                        named_bar(13, 384);
#pragma unroll
                        for (int i = 0; i < 4; i++) f[i] = ldsm4(kt + 1024 + hh * 2048 + (kx ^ (i << 5) ^ (hh << 6)));
#pragma unroll
                        for (int i = 0; i < 4; i++) a[i] = ldsm4(ta + (kx ^ (i << 5)));
                        const uint32_t kd = ka + (1 + 2 * hh) * 1024 + sw;
                        uint4 k[5];
                        k[1] = ldsm4(kd); k[2] = ldsm4(kd + 1024);
                        {
                            const uint32_t qh = qa + (sw ^ (hh << 6)), kh = kt + (kx ^ (hh << 6));
                            named_bar(1, 384);
                            const uint4 q0 = ldsm4(qh), g0 = ldsm4(kh), g1 = ldsm4(kh ^ 32), q1 = ldsm4(qh ^ 64);
                            float s0[4] = {0.f, 0.f, 0.f, 0.f}, s1[4] = {0.f, 0.f, 0.f, 0.f}, s2[4] = {0.f, 0.f, 0.f, 0.f}, s3[4] = {0.f, 0.f, 0.f, 0.f};
                            mmav(s0, f[0].x, f[0].y, f[0].z, f[0].w, q0.x, q0.y); mmav(s1, f[1].x, f[1].y, f[1].z, f[1].w, q0.z, q0.w);
                            mmav(s2, g0.x, g0.y, g0.z, g0.w, q0.x, q0.y); mmav(s3, g1.x, g1.y, g1.z, g1.w, q0.z, q0.w);
                            mmav(s0, f[2].x, f[2].y, f[2].z, f[2].w, q1.x, q1.y); mmav(s1, f[3].x, f[3].y, f[3].z, f[3].w, q1.z, q1.w);
                            k[0] = ldsm4(ka + sw); k[3] = ldsm4(ka + 1024 + sw); k[4] = ldsm4(ka + 2048 + sw);
                            st_async_b32(sd + hh * 128, pack2(s2[0] + s3[0], s2[1] + s3[1]), sbar);
                            st_async_b32(sd + 256 + hh * 256, pack2(s0[0] + s1[0], s0[1] + s1[1]), sbar);
                            st_async_b32(sd + 384 + hh * 256, pack2(s0[2] + s1[2], s0[3] + s1[3]), sbar);
                        }
                        TS(1);
                        float u[5][4];
#pragma unroll
                        for (int i = 0; i < 20; i++) (&u[0][0])[i] = 0.f;
                        auto half = [&](auto nn, const uint4& a0, const uint4& a1, bool more) {
                            constexpr int NU = decltype(nn)::value;
                            constexpr int ord[5] = {1, 2, 0, 3, 4};
#pragma unroll
                            for (int i = 0; i < NU; i++) mmav(u[ord[i]], a0.x, a0.y, a0.z, a0.w, k[ord[i]].x, k[ord[i]].y);
#pragma unroll
                            for (int i = 0; i < NU; i++) {
                                const int n = ord[i];
                                mmav(u[n], a1.x, a1.y, a1.z, a1.w, k[n].z, k[n].w);
                                if (more) k[n] = ldsm4(((n == 0 ? ka + sw : (n < 3 ? kd + (n - 1) * 1024 : ka + (n - 2) * 1024 + sw))) ^ 64);
                            }
                        };
                        auto fu = [](float x) { return __float_as_uint(x); };
                        const uint32_t so = O_ST + c * 2048 + hh * 768, td = dp + so, tb = dp + O_BAR + B_ST, lo = sb + so + 4096;
                        if (hh) {
                            half(IC<5>{}, a[0], a[1], true); half(IC<5>{}, a[2], a[3], false);
                            st_async_v4(td + lane * 16, fu(u[0][2]), fu(u[0][3]), fu(u[1][2]), fu(u[1][3]), tb);
                            st_async_v4(td + 512 + lane * 16, fu(u[2][2]), fu(u[2][3]), fu(u[3][2]), fu(u[3][3]), tb);
                            st_async_v2(td + 1024 + lane * 8, fu(u[4][2]), fu(u[4][3]), tb);
                            sts128(lo + lane * 16, fu(u[0][0]), fu(u[0][1]), fu(u[1][0]), fu(u[1][1]));
                            sts128(lo + 512 + lane * 16, fu(u[2][0]), fu(u[2][1]), fu(u[3][0]), fu(u[3][1]));
                            sts64(lo + 1024 + lane * 8, fu(u[4][0]), fu(u[4][1]));
                        } else {
                            half(IC<3>{}, a[0], a[1], true); half(IC<3>{}, a[2], a[3], false);
                            st_async_v4(td + lane * 16, fu(u[0][2]), fu(u[0][3]), fu(u[1][2]), fu(u[1][3]), tb);
                            st_async_v2(td + 512 + lane * 8, fu(u[2][2]), fu(u[2][3]), tb);
                            sts128(lo + lane * 16, fu(u[0][0]), fu(u[0][1]), fu(u[1][0]), fu(u[1][1]));
                            sts64(lo + 512 + lane * 8, fu(u[2][0]), fu(u[2][1]));
                        }
                        if (t < NT - 1) named_arrive(2, 384);
                        __syncwarp();
                        if (lane == 0) mbar_arrive(bb + B_ST);
                        TS(2);
                    }
                    if (t == NT - 1) break;
                    uint4 wf[PDA];
                    w_pre(IC<WTA>{}, IC<PDA>{}, wf);
                    if (SPIN & 2) mspin(bb + B_OB, t & 1); else mwait(bb + B_OB, t & 1);
                    TS(3);
                    named_bar(3, 384);
                    w_run(IC<WTA>{}, IC<PDA>{}, IC<1>{}, wf, t, ob_0, []() {});
                    named_arrive(4, NB4);
                    if (w == 0 && lane == 0) { mbar_expect_tx(bb + B_OB, 2048); mbar_expect_tx(bb + B_OB + 64, 2048); }
                    TS(5);
                }
            } else {
#pragma unroll 1
                for (int t = 0; t < NT; t++) {
                    const uint32_t lane = opq(lane0);
                    const int g = lane >> 2, tq = lane & 3;
                    const uint32_t vm_a = sb + O_VM + (g * 4 + 2 * (tq & 1) + (c ^ ((g >> 1) & 1))) * 16 + (tq >> 1) * 8;
                    const uint32_t vt_a = sb + O_VT + (t & 1) * 16384 + ((lane >> 3) & 1) * 512 + (lane >> 4) * 128 + (lane & 7) * 16;
                    named_bar(13, 384);
                    uint4 va[4][2];
#pragma unroll
                    for (int i = 0; i < 4; i++) {
                        va[i][0] = ldsm4(vt_a + c * 8192 + (4 * hh + i) * 1024);
                        va[i][1] = ldsm4(vt_a + c * 8192 + (4 * hh + i) * 1024 + 256);
                    }
                    const uint32_t sa = opq(sb + O_SM + c * 768 + 256 + lane * 16), sa2 = opq(sb + O_SM + c * 768 + (lane & 15) * 16 + (lane >> 4) * 1536), vm_b = opq(vm_a + hh * 2048);
                    named_bar(1, 384);
                    if (__builtin_expect(t < NT - 1, 1)) {
                        uint2 vm[4];
#pragma unroll
                        for (int i = 0; i < 4; i++) vm[i] = lds64(vm_b + i * 512);
                        if (SPIN & 1) mspin(bb + B_SM, t & 1); else mwait(bb + B_SM, t & 1);
                        TS(1);
                        const uint4 x0 = ldsm4t(sa), y0 = ldsm4t(sa + 1536), x1 = ldsm4t(sa2);
                        float s[10];
                        s[2] = blo(x0.x) + blo(y0.x); s[3] = bhi(x0.x) + bhi(y0.x); s[4] = blo(x0.y) + blo(y0.y); s[5] = bhi(x0.y) + bhi(y0.y);
                        s[6] = blo(x0.z) + blo(y0.z); s[7] = bhi(x0.z) + bhi(y0.z); s[8] = blo(x0.w) + blo(y0.w); s[9] = bhi(x0.w) + bhi(y0.w);
                        s[0] = (blo(x1.x) + blo(x1.y)) + (blo(x1.z) + blo(x1.w)); s[1] = (bhi(x1.x) + bhi(x1.y)) + (bhi(x1.z) + bhi(x1.w));
                        float mx = fmaxf(fmaxf(fmaxf(s[0], s[1]), fmaxf(s[2], s[3])), fmaxf(fmaxf(fmaxf(s[4], s[5]), fmaxf(s[6], s[7])), fmaxf(s[8], s[9])));
                        const float m1 = __shfl_xor_sync(0xffffffffu, mx, 1), m2 = __shfl_xor_sync(0xffffffffu, mx, 2), m3 = __shfl_xor_sync(0xffffffffu, mx, 3);
                        mx = fmaxf(fmaxf(mx, m1), fmaxf(m2, m3)) * -cs;
                        uint32_t pb[5];
#pragma unroll
                        for (int i = 0; i < 5; i++) pb[i] = pack2(ex2f(fmaf(s[2 * i], cs, mx)), ex2f(fmaf(s[2 * i + 1], cs, mx)));
                        TS(9);
                        named_bar(3, 384);
                        float o[5][4];
#pragma unroll
                        for (int i = 0; i < 20; i++) (&o[0][0])[i] = 0.f;
                        const uint32_t one2 = 0x3F803F80u;
                        float z[2][4] = {{0.f, 0.f, 0.f, 0.f}, {0.f, 0.f, 0.f, 0.f}};
                        mmav8(o[4], one2, one2, pb[0]);
                        mmav(z[0], one2, one2, one2, one2, pb[1], pb[2]);
                        mmav(z[1], one2, one2, one2, one2, pb[3], pb[4]);
#pragma unroll
                        for (int i = 0; i < 4; i++) mmav8(o[i], vm[i].x, vm[i].y, pb[0]);
#pragma unroll
                        for (int i = 0; i < 4; i++) mmav(o[i], va[i][0].x, va[i][0].y, va[i][0].z, va[i][0].w, pb[1], pb[2]);
#pragma unroll
                        for (int i = 0; i < 4; i++) mmav(o[i], va[i][1].x, va[i][1].y, va[i][1].z, va[i][1].w, pb[3], pb[4]);
                        o[4][0] += z[0][0] + z[1][0]; o[4][1] += z[0][1] + z[1][1];
                        uint4 wf[PDC];
                        w_pre(IC<WTC>{}, IC<PDC>{}, wf);
                        const float r0 = rcpf(o[4][0]), r1 = rcpf(o[4][1]);
                        const uint32_t oo = c * 2048 + hh * 1024 + g * 128 + tq * 16 + (g & 1) * 64;
                        uint32_t e0[4], e1[4];
#pragma unroll
                        for (int i = 0; i < 4; i++) { e0[i] = pack2(o[i][0] * r0, o[i][2] * r0); e1[i] = pack2(o[i][1] * r1, o[i][3] * r1); }
                        sts128(sb + O_PB + (~t & 1) * 5120 + oo, e0[0], e0[1], e0[2], e0[3]);
                        sts128(sb + O_PB + (~t & 1) * 5120 + (oo ^ 64), e1[0], e1[1], e1[2], e1[3]);
                        {
                            const uint32_t da = mapa(sb + O_OBA, r - 2) + oo, ba = mapa(bb + B_OB + hh * 64, r - 2);
                            if (O_DLY) { named_bar(7, 128); if (hh) delay(O_DLY); }
                            st_async_v4(da, e0[0], e0[1], e0[2], e0[3], ba);
                            st_async_v4(da + 0x01000000u, e0[0], e0[1], e0[2], e0[3], ba + 0x01000000u);
                            st_async_v4(da ^ 64, e1[0], e1[1], e1[2], e1[3], ba);
                            st_async_v4((da ^ 64) + 0x01000000u, e1[0], e1[1], e1[2], e1[3], ba + 0x01000000u);
                        }
                        TS(3);
                        if (!O_DLY) named_bar(7, 128);
                        w_run(IC<WTC>{}, IC<PDC>{}, IC<0>{}, wf, t, ob_0 + (~t & 1) * 5120, []() {});
                        named_arrive(4, NB4);
                        mwait(bb + B_ST, t & 1);
                        TS(4);
                    } else { mwait(bb + B_SM, t & 1); mwait(bb + B_ST, t & 1); }
                    TS(5);
                    fence_async_smem();
                    if (TPV_LATE && t < NT - 1) named_bar(6, 224);
#pragma unroll 1
                    for (int l = t < NSEG ? 0 : 1; l < (t >= LAG ? 2 : 1); l++) {
                        const uint32_t pb_ = ((1024 + O_PB) >> 4) + (t & 1) * 320 + l * 160, va_ = (((1024 + O_VT) >> 4) + (t & 1) * 1024 + l * 512) | (8u << 16);
                        const uint32_t oa = sb + O_VT + (t & 1) * 16384 + l * 8192 + w * 1024 + g * 64 + ((tq ^ (g >> 1)) & 3) * 16;
                        const uint32_t vl = (vm_a ^ ((l ^ c) << 4)) + w * 512;
                        const uint2 a0 = lds64(vl), a1 = lds64(vl + 2048);
                        float d[2][16];
                        wg_fence();
                        wg_n32_first(d[0], a0.x, a0.y, 0u, 0u, mkdesc(pb_, 8));
                        wg_n32_first(d[1], a1.x, a1.y, 0u, 0u, mkdesc(pb_, 8));
#pragma unroll
                        for (int i = 0; i < 4; i++) wg_n32_kk(d[i & 1], mkdesc(va_ + (i & 1) * 256 + (i >> 1) * 16, 32), mkdesc(pb_ + 32 + (i >> 1) * 64 + (32u << 16), 8));
                        wg_commit();
                        if (l) TS(13); else TS(11);
                        wg_wait<0>();
                        if (l) TS(14); else TS(12);
                        if (O0_EARLY == 2 && l == (t < NSEG ? 0 : 1)) {
                            uint4* og = g_ot + (rslot(l, t - l * LAG) * 256 + h * 8 + w) * 64 + g * 4 + ((tq ^ (g >> 1)) & 3);
#pragma unroll
                            for (int mt = 0; mt < 2; mt++) {
                                og[mt * 256] = make_uint4(pack2(d[mt][0], d[mt][1]), pack2(d[mt][4], d[mt][5]), pack2(d[mt][8], d[mt][9]), pack2(d[mt][12], d[mt][13]));
                                og[mt * 256 + 32] = make_uint4(pack2(d[mt][2], d[mt][3]), pack2(d[mt][6], d[mt][7]), pack2(d[mt][10], d[mt][11]), pack2(d[mt][14], d[mt][15]));
                            }
                            __syncwarp();
                            if (lane == 0) mbar_arrive(bb + B_OTF + 8);
                            continue;
                        }
#pragma unroll
                        for (int mt = 0; mt < 2; mt++) {
                            sts128(oa + mt * 4096, pack2(d[mt][0], d[mt][1]), pack2(d[mt][4], d[mt][5]), pack2(d[mt][8], d[mt][9]), pack2(d[mt][12], d[mt][13]));
                            sts128(oa + mt * 4096 + 512, pack2(d[mt][2], d[mt][3]), pack2(d[mt][6], d[mt][7]), pack2(d[mt][10], d[mt][11]), pack2(d[mt][14], d[mt][15]));
                        }
                        if (O0_EARLY == 1 && l == 0) {
                            fence_async_smem();
                            __syncwarp();
                            if (lane == 0) mbar_arrive(bb + B_OTF + 8);
                        }
                    }
                    TS(6);
                    if (w == 0 && lane == 0) { mbar_expect_tx(bb + B_ST, 5120); mbar_expect_tx(bb + B_SM, 3072); }
                    fence_async_smem();
                    __syncwarp();
                    if (lane == 0) mbar_arrive(bb + B_OTF);
                    if (t < NT - 1) named_arrive(5, 384);
                }
            }
        } else {
            cluster_wait(); cluster_arrive_relaxed();
            const int wi = sp * 4 + w, half = wi >> 5, tok = wi & 31, ep = ld_relaxed(&g_epoch) + 1;
            GT(lane == 0, 89);
            if (lane < LN0_AHEAD / 2) prefetch_l2(A.x + (size_t)((half + 2 * lane) * SEG + tok) * DM, 1280);
#pragma unroll 1
            for (int k = -LN0_AHEAD / 2; k < NT; k++) {
                const int s0 = k < 0 ? 2 * k + LN0_AHEAD + half : (half ? k + LN0_AHEAD : NSEG);
                if (s0 < NSEG) { ln0_row(A.x, s0, tok, lane); GT(lane == 0 && k < 0, 30 + s0); }
                if (k == -1 && half) {
#pragma unroll 1
                    for (int u = 320 + tok; u < 640; u += 32) u_half(A.Bk, A.Bv, A.shiftk, u, lane);
                    __syncwarp();
                    if (lane == 0) red_release(FLG(F_U + 1), 1);
                }
                const int n = k - half * LAG;
                if ((POST_DRY && k == -LN0_AHEAD / 2 + 1) || (n >= 0 && n < NSEG && k >= 0)) {
                    post_row(half, k < 0 ? 0 : n, tok, lane, A.x, A.out, k < 0 ? 0 : ep);
                    GT(lane == 0 && (n & 3) == 0 && k >= 0, 460 + half * 16 + (n >> 2)); GT(lane == 0 && n == 63 && half, 40);
                }
            }
            cluster_wait();
        }
    } else {
        asm volatile("setmaxnreg.dec.sync.aligned.u32 %0;" ::"n"(REG_X));
        cluster_wait();
        const int s = warp - 12;
        const uint32_t lane0 = __shfl_sync(0xffffffffu, tid & 31, tid & 31);
        if (s < 3) {
            cluster_arrive_relaxed();
            GT(lane == 0, 84);
            if (!U0_SPARE && blockIdx.x * 3 + s < 320) {
                u_half(A.Bk, A.Bv, A.shiftk, blockIdx.x * 3 + s, lane);
                GT(lane == 0, 85);
                __syncwarp();
                if (lane == 0) red_release(FLG(F_U), 1);
                GT(lane == 0, 4);
            }
            const int ztgt = 3 * 16 * NCL * (ld_relaxed(&g_epoch) + 1);
#pragma unroll
            for (int i = 0; i < XRS; i++) st_relaxed_v4(g_xc + ((i * 16 + r) * 3 + s) * 256 + cq * 32 + lane, 0, 0, 0, 0);
            __syncwarp();
            if (lane == 0) red_release(FLG(F_Z), 1);
            cluster_wait();
            constexpr uint32_t XSLOT = 16 * 3 * 4096;
            uint32_t xo_ = (r * 3 + s) * 4096;
            if (s == 0) {
                const uint32_t G = lane >> 1, d = ((r + 2 * (G + SELF_LOCAL)) & 15) ^ (lane & 1);
                if (lane < 16) { sts32(sb + O_BT + lane * 8, (d << 24) + G * 2560); sts32(sb + O_BT + lane * 8 + 4, d < 3 * nh && !(SELF_LOCAL && d == r) ? mapa(bb + B_MEM + G * 8, d) : 0u); }
            }
            while (ld_acquire(FLG(F_Z)) < ztgt) __nanosleep(100);
            named_bar(14, 96);
#pragma unroll 1
            for (int t = 0; t < NT; t++) {
                const uint32_t lane = opq(lane0);
                if (head && role != 2) {
                    auto soft = [&](auto uu, auto vv, int c0, int hh) {
                        constexpr int U = decltype(uu)::value, NV = decltype(vv)::value;
                        const uint32_t dc = mapa(sb, hi * 3 + 2), sa = sb + O_ST + c0 * 2048 + hh * 768;
                        const uint32_t pd = dc + O_PB + (t & 1) * 5120 + c0 * 2560 + (2 * hh + role) * 128 + lane * 4, pbar = dc + O_BAR + B_ST;
                        const int lim = 8 * role + (int)(lane >> 2) - 2 * (int)(lane & 3);
                        auto uf = [](uint32_t x) { return __uint_as_float(x); };
                        mwait(bb + B_ST, t & 1);
                        if (H1_LATE == 2 && r == 1 && U == 2 && t >= LAG - 1 && t < NT - 1) named_arrive(12, 64);
                        uint32_t z[U][NV];
                        auto zz = [](float x, float y) { const uint32_t w = pack2(x, y); return pack2(blo(w) * 0.08838834764831845f, bhi(w) * 0.08838834764831845f); };
#pragma unroll
                        for (int i = 0; i < U; i++) {
                            const uint4 v = lds128(sa + i * 2048 + lane * 16), w = lds128(sa + i * 2048 + 4096 + lane * 16);
                            z[i][0] = zz(uf(v.x) + uf(w.x), uf(v.y) + uf(w.y));
                            z[i][1] = zz(lim < 0 ? -INFINITY : uf(v.z) + uf(w.z), lim < 1 ? -INFINITY : uf(v.w) + uf(w.w));
                            if (NV == 3) {
                                const uint2 x = lds64(sa + i * 2048 + 512 + lane * 8), y = lds64(sa + i * 2048 + 4608 + lane * 8);
                                z[i][2] = zz(lim < 8 ? -INFINITY : uf(x.x) + uf(y.x), lim < 9 ? -INFINITY : uf(x.y) + uf(y.y));
                            } else {
                                const uint4 x = lds128(sa + 512 + lane * 16), y = lds128(sa + 4608 + lane * 16);
                                const uint2 p = lds64(sa + 1024 + lane * 8), q = lds64(sa + 5120 + lane * 8);
                                z[i][2] = zz(lim < 8 ? -INFINITY : uf(x.x) + uf(y.x), lim < 9 ? -INFINITY : uf(x.y) + uf(y.y));
                                z[i][NV - 2] = zz(uf(x.z) + uf(y.z), uf(x.w) + uf(y.w));
                                z[i][NV - 1] = zz(uf(p.x) + uf(q.x), uf(p.y) + uf(q.y));
                            }
                        }
                        const float l2e = 1.4426950408889634f;
                        float e[U][2 * NV], sum[U];
#pragma unroll
                        for (int i = 0; i < U; i++) {
                            uint32_t zm = bmax2(bmax2(z[i][0], z[i][1]), z[i][2]);
                            if (NV == 5) zm = bmax2(zm, bmax2(z[i][NV - 2], z[i][NV - 1]));
                            zm = bmax2(zm, __shfl_xor_sync(0xffffffffu, zm, 1));
                            zm = bmax2(zm, __shfl_xor_sync(0xffffffffu, zm, 2));
                            const float mx = fmaxf(blo(zm), bhi(zm)) * -l2e;
                            sum[i] = 0.f;
#pragma unroll
                            for (int n = 0; n < NV; n++) { e[i][2 * n] = ex2f(fmaf(blo(z[i][n]), l2e, mx)); e[i][2 * n + 1] = ex2f(fmaf(bhi(z[i][n]), l2e, mx)); }
                            sum[i] = ((e[i][0] + e[i][1]) + (e[i][2] + e[i][3])) + (e[i][4] + e[i][5]);
                            if (NV == 5) sum[i] += (e[i][2 * NV - 4] + e[i][2 * NV - 3]) + (e[i][2 * NV - 2] + e[i][2 * NV - 1]);
                            sum[i] += __shfl_xor_sync(0xffffffffu, sum[i], 1);
                            sum[i] += __shfl_xor_sync(0xffffffffu, sum[i], 2);
                            sum[i] = rcpf(sum[i]);
                        }
#pragma unroll
                        for (int i = 0; i < U; i++)
#pragma unroll
                            for (int n = 0; n < 5; n++)
                                st_async_b32(pd + i * 2560 + (n == 0 ? 0 : (NV == 3 ? n : (n < 3 ? n + 2 : n - 2)) * 512), n < NV ? pack2(e[i][2 * n] * sum[i], e[i][2 * n + 1] * sum[i]) : 0u, pbar);
                    };
                    if (s < 2) soft(IC<1>{}, IC<5>{}, s, 1); else soft(IC<2>{}, IC<3>{}, 0, 0);
                    TS(12);
                    named_bar(14, 96);
                    if (s == 0 && lane == 0) mbar_expect_tx(bb + B_ST, 4096);
                    if (H1_LATE == 1 && r == 1 && s == 0 && t >= LAG - 1 && t < NT - 1) named_arrive(12, 64);
                }
                if (t == NT - 1) break;
                uint32_t m0 = 0x80008000u, m1 = 0x80008000u;
                if (t < LAG && cq == 0) {
                    const uint32_t ch = s < 2 ? lane : lane >> 1;
                    const unsigned short* mp = reinterpret_cast<const unsigned short*>(A.mem0) + (((ch >> 3) & 1) * 4 + (s < 2 ? 0 : (lane & 1) * 2)) * DM + (5 * r + 2 * s + (ch >> 4)) * 8 + (ch & 7);
                    m0 = max(mp[0] | (uint32_t)mp[DM] << 16, 1u);
                    if (s < 2) m1 = max(mp[2 * DM] | (uint32_t)mp[3 * DM] << 16, 1u);
                }
                const bool late = t >= LAG;
                auto sum5 = [](uint32_t a, uint32_t b, uint32_t c, uint32_t d, uint32_t e) { return nz(badd(badd(badd(a, b), e), badd(c, d))); };
                auto sum7 = [](uint32_t a, uint32_t b, uint32_t c, uint32_t d, uint32_t e, uint32_t f, uint32_t h_) {
                    return badd(badd(badd(a, b), badd(c, d)), badd(badd(e, f), h_));
                };
                auto min3 = [](uint32_t a, uint32_t b, uint32_t c) { return min(min(a, b), c); };
                auto bcast = [&](auto two, const uint32_t aa, uint32_t x0, uint32_t x1, uint32_t x2, uint32_t x3) {
                    auto send = [&](uint32_t o, uint32_t bar) { if (decltype(two)::value) st_async_v4p(aa + o, x0, x1, x2, x3, bar); else st_async_v2p(aa + o, x0, x1, bar); };
                    uint4 e[5];
                    e[0] = lds128(sb + O_BT);
                    TS(8);
                    send(e[0].x, e[0].y); send(e[0].z, e[0].w);
                    TS(9);
#pragma unroll
                    for (int i = 1; i < 5; i++) e[i] = lds128(sb + O_BT + i * 16);
#pragma unroll
                    for (int i = 1; i < 8; i++) {
                        send(e[(i - 1) % 4 + 1].x, e[(i - 1) % 4 + 1].y); send(e[(i - 1) % 4 + 1].z, e[(i - 1) % 4 + 1].w);
                        if (i < 4) e[i] = lds128(sb + O_BT + (i + 4) * 16);
                    }
                    if (SELF_LOCAL && head) {
                        const uint32_t la = aa + (sb & 0xFF000000u) + 7 * 2560;
                        if (decltype(two)::value) sts128(la, x0, x1, x2, x3); else sts64(la, x0, x1);
                        fence_async_smem();
                        __syncwarp();
                        if (lane == 0) mbar_arrive(bb + B_MEM + 56);
                    }
                };
                const uint32_t ma = (sb + O_MEM + (5 * (r & 1) + 2 * s) * 256) & 0xFFFFFFu;
                int guard = 0;
                if (s < 2) {
                    const uint32_t ra = sb + O_RED + s * 2560 + lane * 16;
                    uint4* xb = reinterpret_cast<uint4*>(reinterpret_cast<char*>(g_xc) + xo_ + lane * 16);
                    uint4* xo = xb + cq * 32;
                    touch(xo); touch(xb);
                    if (SPIN & 4) mspin(bb + B_RED, t & 1); else mwait(bb + B_RED, t & 1);
                    TS(0);
                    uint4 p[5];
#pragma unroll
                    for (int i = 0; i < 5; i++) p[i] = i < 4 || nh == 5 ? lds128(ra + i * 512) : make_uint4(0, 0, 0, 0);
                    const uint32_t u1 = sum5(p[0].y, p[1].y, p[2].y, p[3].y, p[4].y), u3 = sum5(p[0].w, p[1].w, p[2].w, p[3].w, p[4].w);
                    st_relaxed_v4(xo, sum5(p[0].x, p[1].x, p[2].x, p[3].x, p[4].x), late ? u1 : m0, sum5(p[0].z, p[1].z, p[2].z, p[3].z, p[4].z), late ? u3 : m1);
                    TS(1);
                    if (QUIET && head) named_arrive(4, NB4);
                    delay(XD);
                    if (CV_YIELD && !head && s == 0) sts32(sb + O_BUSY, 1u);
                    uint4 x[NCL];
                    while (true) {
                        ld7_relaxed(x, xb);
                        const uint32_t mn = min3(min3(min3(x[0].x, x[0].y, x[0].z), min3(x[0].w, x[1].x, x[1].y), min3(x[1].z, x[1].w, x[2].x)),
                                                 min3(min3(x[2].y, x[2].z, x[2].w), min3(x[3].x, x[3].y, x[3].z), min3(x[3].w, x[4].x, x[4].y)),
                                                 min3(min3(x[4].z, x[4].w, x[5].x), min3(x[5].y, x[5].z, x[5].w), min(min3(x[6].x, x[6].y, x[6].z), x[6].w)));
                        if (NO_X || __all_sync(0xffffffffu, mn != 0)) break;
                        if (++guard > 2000000) __trap();
                    }
                    TS(2);
                    TV(4, guard);
                    bcast(IC<1>{}, ma + lane * 16, sum7(x[0].x, x[1].x, x[2].x, x[3].x, x[4].x, x[5].x, x[6].x), sum7(x[0].y, x[1].y, x[2].y, x[3].y, x[4].y, x[5].y, x[6].y),
                          sum7(x[0].z, x[1].z, x[2].z, x[3].z, x[4].z, x[5].z, x[6].z), sum7(x[0].w, x[1].w, x[2].w, x[3].w, x[4].w, x[5].w, x[6].w));
                } else {
                    const uint32_t ra = sb + O_RED + 5120 + lane * 8;
                    uint2* xb = reinterpret_cast<uint2*>(reinterpret_cast<char*>(g_xc) + xo_ + lane * 8);
                    uint2* xo = xb + cq * 64;
                    touch(xo); touch(xb);
                    if (SPIN & 4) mspin(bb + B_RED, t & 1); else mwait(bb + B_RED, t & 1);
                    TS(0);
                    uint2 p[5];
#pragma unroll
                    for (int i = 0; i < 5; i++) p[i] = i < 4 || nh == 5 ? lds64(ra + i * 256) : make_uint2(0, 0);
                    const uint32_t u1 = sum5(p[0].y, p[1].y, p[2].y, p[3].y, p[4].y);
                    st_relaxed_v2(xo, sum5(p[0].x, p[1].x, p[2].x, p[3].x, p[4].x), late ? u1 : m0);
                    if (lane == 0) mbar_expect_tx(bb + B_RED, nh * 1280);
                    TS(1);
                    if (QUIET && head) named_arrive(4, NB4);
                    delay(XD);
                    uint32_t y0, y1;
                    while (true) {
                        uint2 x[NCL];
                        ld7_relaxed(x, xb);
                        const uint32_t mn = min3(min3(min3(x[0].x, x[0].y, x[1].x), min3(x[1].y, x[2].x, x[2].y), min3(x[3].x, x[3].y, x[4].x)), min3(x[4].y, x[5].x, x[5].y), min(x[6].x, x[6].y));
                        y0 = sum7(x[0].x, x[1].x, x[2].x, x[3].x, x[4].x, x[5].x, x[6].x); y1 = sum7(x[0].y, x[1].y, x[2].y, x[3].y, x[4].y, x[5].y, x[6].y);
                        if (NO_X || __all_sync(0xffffffffu, mn != 0)) break;
                        if (++guard > 2000000) __trap();
                    }
                    TS(2);
                    TV(4, guard);
                    bcast(IC<0>{}, ma + lane * 8, y0, y1, 0u, 0u);
                }
                TS(3);
                if (CV_YIELD && !head) { named_bar(14, 96); if (s == 0) sts32(sb + O_BUSY, 0u); }
                if ((OT_LATE || TPV_LATE) && head && role == 2) named_arrive(6, TPV_LATE ? 224 : 128);
                xo_ += XSLOT; if (xo_ >= XRS * XSLOT) xo_ -= XRS * XSLOT;
                {
                    const uint32_t zo = xo_ + XSLOT >= XRS * XSLOT ? xo_ + XSLOT - XRS * XSLOT : xo_ + XSLOT;
                    char* zp = reinterpret_cast<char*>(g_xc) + zo + cq * 512 + lane * 16;
                    st_relaxed_v4(zp, 0, 0, 0, 0);
                    if (ld_relaxed_v4(zp).x) __trap();
                }
            }
        } else if (r < 2) {
            const uint16_t mask = (uint16_t)((1u << (3 * nh)) - 1u);
            const int htgt = A.h_target * (ld_relaxed(&g_epoch) + 1);
#pragma unroll 1
            for (int n = 0; n < NSEG; n++) {
                if (n == (r == 0 ? 1 : 0)) { cluster_arrive(); cluster_wait(); }
                int guard = 0;
                while (ld_acquire(FLG(F_H + r * 64 + n)) < htgt) { if (++guard > 2000000) __trap(); __nanosleep(H_NS); }
                fence_async_global();
                if (H1_LATE && r == 1) named_bar(12, 64);
                if (n) mwait(bb + B_HE, (n - 1) & 1);
                if (lane < 8)
                    asm volatile("cp.async.bulk.shared::cluster.global.mbarrier::complete_tx::bytes.multicast::cluster [%0], [%1], %2, [%3], %4;" ::"r"(sb + O_H + r * 40960 + lane * 5120),
                                 "l"(g_ht + rslot(r, n) * 2560 + lane * 320), "r"(HBYTES), "r"(bb + B_HF + r * 8), "h"(mask) : "memory");
                __syncwarp();
            }
        } else {
            cluster_arrive(); cluster_wait();
            if (head && role == 2) {
#pragma unroll 1
                for (int t = 0; t < NT; t++) {
                    auto put = [&](int l, int n) {
                        asm volatile("cp.async.bulk.global.shared::cta.bulk_group [%0], [%1], %2;" ::"l"(g_ot + (rslot(l, n) * 256 + h * 8) * 64), "r"(sb + O_VT + (t & 1) * 16384 + l * 8192), "r"(8192) : "memory");
                        asm volatile("cp.async.bulk.commit_group;" ::: "memory");
                    };
                    auto publish = [&](int l, int n) {
                        asm volatile("cp.async.bulk.wait_group 0;" ::: "memory");
                        fence_async_global();
                        red_release(FLG(F_O + l * 64 + n) + (h >> 3), 1);
                        GT(true, 200 + l * 64 + n);
                    };
                    if (O0_EARLY == 2) {
                        const int l = t < NSEG ? 0 : 1;
                        mwait(bb + B_OTF + 8, t & 1);
                        if (lane == 0) { red_release(FLG(F_O + l * 64 + t - l * LAG) + (h >> 3), 1); GT(true, 200 + l * 64 + t - l * LAG); }
                        __syncwarp();
                    }
                    if (O0_EARLY == 1 && t < NSEG) {
                        mwait(bb + B_OTF + 8, t & 1);
                        if (lane == 0) { put(0, t); publish(0, t); }
                        __syncwarp();
                    }
                    mwait(bb + B_OTF, t & 1);
                    if (OT_LATE && !TPV_LATE && t < NT - 1) named_bar(6, 128);
                    const int l = lane & 1, n = t - l * LAG;
                    const bool mine = lane < 2 && n >= 0 && n < NSEG && (l || !O0_EARLY) && (O0_EARLY < 2 || t < NSEG);
                    if (mine) {
                        put(l, n);
                        asm volatile("cp.async.bulk.wait_group.read 0;" ::: "memory");
                    }
                    __syncwarp();
                    if (lane == 0) mbar_arrive(bb + B_OTE);
                    if (mine) publish(l, n);
                    __syncwarp();
                }
            }
            if (!head && lane == 0) {
#pragma unroll 1
                for (int k = 0; k < 25; k++) {
                    const int rg = k / 5, r0 = rg == 1 ? 256 : 0;
                    mwait(bb + B_OTF + (k & 1) * 8, (k >> 1) & 1);
                    asm volatile("cp.async.bulk.global.shared::cta.bulk_group [%0], [%1], %2;" ::"l"(g_Y + (sp * 5 + k - 5 * rg) * S_LEN + (rg ? rg - 1 : 0) * 512 + r0),
                                 "r"(sb + CV_Y + (k & 1) * 8192 + r0 * 16), "r"(rg < 2 ? 4096 : 8192) : "memory");
                    asm volatile("cp.async.bulk.commit_group;" ::: "memory");
                    asm volatile("cp.async.bulk.wait_group 0;" ::: "memory");
                    mbar_arrive(bb + B_OTE + (k & 1) * 16);
                    fence_async_global();
                    red_release(FLG(F_CV + rg), 1);
                    GT(true, 50 + k);
                }
            }
            __syncwarp();
        }
    }
    cluster_arrive(); cluster_wait();
    if (blockIdx.x == 0 && tid == 0) atomicAdd(&g_epoch, 1);
}
}

namespace ws {
constexpr int OP_SS = 17;
constexpr int P_RING = 0, P_AS = 131072, P_STG = P_AS + 2 * OP_SS * 2048, P_BAR = P_STG + 16384, OP_SMEM = P_BAR + 256;
constexpr int PB_FULL = 0, PB_EMPTY = 128, PB_SF = 144, PB_SE = 176;
static_assert(OP_SMEM <= 232448, "smem");

__global__ void __launch_bounds__(384, 1) op_kernel(const bf16* __restrict__ Wo, const bf16* __restrict__ Bk, const bf16* __restrict__ Bv, const bf16* __restrict__ shiftk) {
    extern __shared__ __align__(1024) unsigned char smem_raw[];
    const int tid = threadIdx.x, warp = __shfl_sync(0xffffffffu, tid >> 5, 0), lane = tid & 31;
    const int nb = blockIdx.x % 5, ks = blockIdx.x / 5;
    const uint32_t sb = smem_u32(smem_raw), bb = sb + P_BAR;
    if (tid == 0) {
        if ((sb & 0xFFFFFFu) != 1024) __trap();
        for (int i = 0; i < 16; i++) mbar_init(bb + PB_FULL + i * 8, 1);
        for (int i = 0; i < 2; i++) mbar_init(bb + PB_EMPTY + i * 8, 2);
        for (int i = 0; i < 4; i++) { mbar_init(bb + PB_SF + i * 8, 4); mbar_init(bb + PB_SE + i * 8, 1); }
        asm volatile("fence.mbarrier_init.release.cluster;" ::: "memory");
    }
    GT(tid == 0, 8);
    __syncthreads();
    if (warp < 4) {
        asm volatile("setmaxnreg.dec.sync.aligned.u32 40;");
        if (warp == 0) {
            named_bar(3, 288);
            GT(lane == 0, 3);
            uint32_t it = 0;
            const int otgt = 8 * (ld_relaxed(&g_epoch) + 1);
#pragma unroll 1
            for (int q = 0; q < 2 * NT; q++) {
                const int l = q & 1, n = (q >> 1) - l * LAG;
                if (n < 0 || n >= NSEG) continue;
                int guard = 0;
                while (ld_acquire(FLG(F_O + l * 64 + n) + ks) < otgt) { if (++guard > 4000000) __trap(); __nanosleep(OP_NS); }
                fence_async_global();
                mwait(bb + PB_EMPTY + (it & 1) * 8, ((it >> 1) & 1) ^ 1);
                if (lane < 8) {
                    const uint32_t fb = bb + PB_FULL + ((it & 1) * 8 + lane) * 8;
                    mbar_expect_tx(fb, 8192);
                    asm volatile("cp.async.bulk.shared::cluster.global.mbarrier::complete_tx::bytes [%0], [%1], %2, [%3];" ::"r"(sb + P_RING + (it & 1) * 65536 + lane * 8192),
                                 "l"(g_ot + (rslot(l, n) * 256 + (ks * 8 + lane) * 8) * 64), "r"(8192), "r"(fb) : "memory");
                }
                __syncwarp();
                it++;
            }
        } else if (warp == 3) {
#pragma unroll 1
            for (int rg = 1; rg < 4; rg++) {
#pragma unroll 1
                for (int u = rg * 640 + blockIdx.x; u < rg * 640 + 640; u += 20) u_half(Bk, Bv, shiftk, u, lane);
                __syncwarp();
                if (lane == 0) red_release(FLG(F_U + rg + 1), 1);
                GT(lane == 0 && rg, 4 + rg);
            }
        } else if (lane == 0) {
            const int cw = warp - 1;
            uint32_t it = 0;
#pragma unroll 1
            for (int q = 0; q < 2 * NT; q++) {
                const int l = q & 1, n = (q >> 1) - l * LAG;
                if (n < 0 || n >= NSEG) continue;
                mwait(bb + PB_SF + cw * 8, it & 1);
                asm volatile("cp.reduce.async.bulk.global.shared::cta.bulk_group.add.f32 [%0], [%1], %2;" ::"l"(g_pt + (rslot(l, n) * 10 + nb * 2 + cw) * 512), "r"(sb + P_STG + cw * 8192), "r"(8192) : "memory");
                asm volatile("cp.async.bulk.commit_group;" ::: "memory");
                asm volatile("cp.async.bulk.wait_group.read 0;" ::: "memory");
                mbar_arrive(bb + PB_SE + cw * 8);
                asm volatile("cp.async.bulk.wait_group 0;" ::: "memory");
                fence_async_global();
                red_release(FLG(F_P + l * 64 + n), 1);
                GT(true, 330 + l * 64 + n);
                it++;
            }
        }
    } else {
        asm volatile("setmaxnreg.inc.sync.aligned.u32 232;");
        const int cw = (warp >> 2) - 1, w4 = warp & 3, t7 = tid & 127;
        uint32_t wa[64 - OP_SS][4];
        if (OP_LATE) flag_wait(FLG(F_H), 32 * (ld_relaxed(&g_epoch) + 1), 200);
        {
            const bf16* W = Wo + (size_t)ks * 1024 * DM + nb * 128 + cw * 64 + (t7 & 7) * 8;
            const uint32_t so = (t7 >> 3) * 128 + (((t7 & 7) ^ ((t7 >> 3) & 7)) << 4);
            const uint32_t stg = sb + P_RING + cw * 65536;
            const uint32_t la = stg + ((lane & 7) + (lane >> 4) * 8) * 128 + (((w4 * 2 + ((lane >> 3) & 1)) ^ (lane & 7)) << 4);
#pragma unroll 4
            for (int i = 0; i < 32; i++) cp_async16(stg + i * 2048 + so, W + (size_t)((OP_SS + i) * 16 + (t7 >> 3)) * DM);
            cp_commit();
#pragma unroll 1
            for (int i = 0; i < OP_SS; i++) cp_async16(sb + P_AS + cw * OP_SS * 2048 + i * 2048 + so, W + (size_t)(i * 16 + (t7 >> 3)) * DM);
            cp_commit();
            cp_wait<1>();
            named_bar(1 + cw, 128);
#pragma unroll
            for (int j = 0; j < 32; j++) { const uint4 v = ldsm4t(la + j * 2048); wa[j][0] = v.x; wa[j][1] = v.y; wa[j][2] = v.z; wa[j][3] = v.w; }
            named_bar(1 + cw, 128);
#pragma unroll 1
            for (int i = 0; i < 32 - OP_SS; i++) cp_async16(stg + i * 2048 + so, W + (size_t)((OP_SS + 32 + i) * 16 + (t7 >> 3)) * DM);
            cp_commit();
            cp_wait<0>();
            named_bar(1 + cw, 128);
#pragma unroll
            for (int j = 0; j < 32 - OP_SS; j++) { const uint4 v = ldsm4t(la + j * 2048); wa[32 + j][0] = v.x; wa[32 + j][1] = v.y; wa[32 + j][2] = v.z; wa[32 + j][3] = v.w; }
            fence_async_smem();
            named_bar(3, 288);
        }
        const uint32_t ab = (1024 + P_AS + cw * OP_SS * 2048) >> 4;
        const uint32_t ea = sb + P_STG + cw * 8192 + (lane & 3) * 2048 + (((2 * w4) ^ (lane & 3)) << 5) + (lane >> 2) * 4;
#pragma unroll 1
        for (uint32_t it = 0; it < 2 * NSEG; it++) {
            float acc[16];
            const uint32_t fb = bb + PB_FULL + (it & 1) * 64, par = (it >> 1) & 1;
            const uint32_t ob = opq(((1024 + P_RING) >> 4) + (it & 1) * 4096);
            uint32_t ok = 0;
#pragma unroll
            for (int j = 0; j < 64; j++) {
                if ((j & 7) == 0) {
                    if (j) wg_commit();
                    if (!ok) mslow(fb + j, par);
                    ok = j < 56 ? mtest(fb + j + 8, par) : mtest(bb + PB_SE + cw * 8, (it & 1) ^ 1);
                    if (j == 0) wg_fence();
                }
                const uint64_t db = mkdesc(ob + j * 64, 0x80000020u);
                if (j == 0) wg_n32t_sfirst(acc, mkdesc(ab, 0x40000040u), db);
                else if (j < OP_SS) wg_n32t_s(acc, mkdesc(ab + j * 128, 0x40000040u), db);
                else wg_n32t(acc, wa[j - OP_SS][0], wa[j - OP_SS][1], wa[j - OP_SS][2], wa[j - OP_SS][3], db);
            }
            wg_commit();
            if (!ok) mslow(bb + PB_SE + cw * 8, (it & 1) ^ 1);
            wg_wait<0>();
            if (t7 == 0) mbar_arrive(bb + PB_EMPTY + (it & 1) * 8);
#pragma unroll
            for (int i = 0; i < 16; i++) sts32((ea ^ ((i & 2) << 4)) + ((i >> 2) * 2 + (i & 1)) * 256, __float_as_uint(acc[i]));
            fence_async_smem();
            __syncwarp();
            if (lane == 0) mbar_arrive(bb + PB_SF + cw * 8);
        }
    }
}
}

namespace ws {
static bool usable() {
    static int ok = -1;
    if (ok < 0) {
        cudaFuncSetAttribute(head_kernel, cudaFuncAttributeMaxDynamicSharedMemorySize, HEAD_SMEM);
        cudaFuncSetAttribute(head_kernel, cudaFuncAttributeNonPortableClusterSizeAllowed, 1);
        cudaFuncSetAttribute(op_kernel, cudaFuncAttributeMaxDynamicSharedMemorySize, OP_SMEM);
        cudaLaunchConfig_t cfg = {};
        cfg.gridDim = dim3(NCL * 16); cfg.blockDim = dim3(512); cfg.dynamicSmemBytes = HEAD_SMEM;
        cudaLaunchAttribute at[1];
        at[0].id = cudaLaunchAttributeClusterDimension;
        at[0].val.clusterDim.x = 16; at[0].val.clusterDim.y = 1; at[0].val.clusterDim.z = 1;
        cfg.attrs = at; cfg.numAttrs = 1;
        int n = 0, nsm = 0;
        cudaDeviceGetAttribute(&nsm, cudaDevAttrMultiProcessorCount, 0);
        ok = cudaOccupancyMaxActiveClusters(&n, head_kernel, &cfg) == cudaSuccess && n >= NCL && nsm >= NCL * 16 + 20;
        (void)cudaGetLastError();
    }
    return ok > 0;
}
static void launch_all(void* const* d_in, void* d_out) {
    HeadArgs A;
    A.x = (const bf16*)d_in[0]; A.mem0 = (const bf16*)d_in[1]; A.Wq = (const bf16*)d_in[2]; A.Wk = (const bf16*)d_in[3]; A.Wv = (const bf16*)d_in[4]; A.Wo = (const bf16*)d_in[5];
    A.Bk = (const bf16*)d_in[8]; A.Bv = (const bf16*)d_in[9]; A.shiftk = (const bf16*)d_in[10]; A.ssmk = (const bf16*)d_in[11]; A.ssmD = (const bf16*)d_in[12];
    A.out = (bf16*)d_out; A.h_target = 32;
    cudaStream_t s = cudaStreamPerThread;
    {
        cudaLaunchConfig_t cfg = {};
        cfg.gridDim = dim3(NCL * 16); cfg.blockDim = dim3(512); cfg.dynamicSmemBytes = HEAD_SMEM; cfg.stream = s;
        cudaLaunchAttribute at[2];
        at[0].id = cudaLaunchAttributeClusterDimension;
        at[0].val.clusterDim.x = 16; at[0].val.clusterDim.y = 1; at[0].val.clusterDim.z = 1;
        at[1].id = cudaLaunchAttributeProgrammaticStreamSerialization;
        at[1].val.programmaticStreamSerializationAllowed = 1;
        cfg.attrs = at; cfg.numAttrs = 1;
        cudaLaunchKernelEx(&cfg, head_kernel, A);
    }
    {
        cudaLaunchConfig_t cfg = {};
        cfg.gridDim = dim3(20); cfg.blockDim = dim3(384); cfg.dynamicSmemBytes = OP_SMEM; cfg.stream = s;
        cudaLaunchAttribute at[1];
        at[0].id = cudaLaunchAttributeProgrammaticStreamSerialization;
        at[0].val.programmaticStreamSerializationAllowed = 1;
        cfg.attrs = at; cfg.numAttrs = 1;
        cudaLaunchKernelEx(&cfg, op_kernel, A.Wo, A.Bk, A.Bv, A.shiftk);
    }
}
}

#undef BNS
#undef BP
#undef CONV_DRY
#undef CV_YIELD
#undef FLG
#undef GT
#undef G_DLY
#undef H1_LATE
#undef HBYTES
#undef H_NS
#undef LAGT
#undef LN0_AHEAD
#undef NL2
#undef NO_X
#undef O0_EARLY
#undef OBK
#undef OBRES
#undef OP_LATE
#undef OP_NS
#undef OT_LATE
#undef O_BULK
#undef O_DLY
#undef P1A
#undef P1C
#undef PDA
#undef PDC
#undef POST_DRY
#undef POST_NS
#undef PRE_PDL
#undef PRE_PF
#undef QUIET
#undef REG_G
#undef REG_T
#undef REG_X
#undef RING
#undef SC
#undef SD
#undef SELF_LOCAL
#undef SKEW
#undef SPIN
#undef TG_STEPS
#undef TPVW
#undef TPV_LATE
#undef TPV_PAUSE
#undef TS
#undef TV
#undef U0_SPARE
#undef UNI
#undef WFLY
#undef WGRP
#undef WK3
#undef WR
#undef WTA
#undef WVOL
#undef W_SKIP
#undef XD
#undef XDUP
#undef XFD
#undef XS
namespace ni {

constexpr int S_LEN = 2048;
constexpr int DM = 640;
constexpr int NH = 32;
constexpr int DH = 128;
constexpr int HD = NH * DH;
constexpr int MEMR = 8;
constexpr int SEG = 32;
constexpr int NSEG = S_LEN / SEG;

__device__ __forceinline__ float bf2f(bf16 v) { return __bfloat162float(v); }
__device__ __forceinline__ bf16 f2bf(float v) { return __float2bfloat16_rn(v); }
__device__ __forceinline__ float rbf(float v) { return __bfloat162float(__float2bfloat16_rn(v)); }
__device__ __forceinline__ uint32_t pack2(float a, float b) {
    __nv_bfloat162 t = __floats2bfloat162_rn(a, b);
    return *reinterpret_cast<uint32_t*>(&t);
}
__device__ __forceinline__ uint32_t smem_u32(const void* p) { return (uint32_t)__cvta_generic_to_shared(p); }
__device__ __forceinline__ void ldsm_x4(uint32_t& r0, uint32_t& r1, uint32_t& r2, uint32_t& r3, uint32_t addr) {
    asm volatile("ldmatrix.sync.aligned.m8n8.x4.shared.b16 {%0,%1,%2,%3}, [%4];"
                 : "=r"(r0), "=r"(r1), "=r"(r2), "=r"(r3) : "r"(addr));
}
__device__ __forceinline__ void ldsm_x2(uint32_t& r0, uint32_t& r1, uint32_t addr) {
    asm volatile("ldmatrix.sync.aligned.m8n8.x2.shared.b16 {%0,%1}, [%2];" : "=r"(r0), "=r"(r1) : "r"(addr));
}
__device__ __forceinline__ void ldsm_x4_t(uint32_t& r0, uint32_t& r1, uint32_t& r2, uint32_t& r3, uint32_t addr) {
    asm volatile("ldmatrix.sync.aligned.m8n8.x4.trans.shared.b16 {%0,%1,%2,%3}, [%4];"
                 : "=r"(r0), "=r"(r1), "=r"(r2), "=r"(r3) : "r"(addr));
}
__device__ __forceinline__ void mma16816(float* c, uint32_t a0, uint32_t a1, uint32_t a2, uint32_t a3,
                                         uint32_t b0, uint32_t b1) {
    asm("mma.sync.aligned.m16n8k16.row.col.f32.bf16.bf16.f32 {%0,%1,%2,%3}, {%4,%5,%6,%7}, {%8,%9}, {%0,%1,%2,%3};"
        : "+f"(c[0]), "+f"(c[1]), "+f"(c[2]), "+f"(c[3])
        : "r"(a0), "r"(a1), "r"(a2), "r"(a3), "r"(b0), "r"(b1));
}
__device__ __forceinline__ void cp_async16(uint32_t dst, const void* src) {
    asm volatile("cp.async.cg.shared.global [%0], [%1], 16;" ::"r"(dst), "l"(src));
}
__device__ __forceinline__ void cp_commit() { asm volatile("cp.async.commit_group;"); }
template <int N> __device__ __forceinline__ void cp_wait() { asm volatile("cp.async.wait_group %0;" ::"n"(N)); }
__device__ __forceinline__ uint4 ld_relaxed_v4(const void* p) {
    uint4 v;
    asm volatile("ld.relaxed.gpu.global.v4.u32 {%0,%1,%2,%3}, [%4];"
                 : "=r"(v.x), "=r"(v.y), "=r"(v.z), "=r"(v.w) : "l"(p) : "memory");
    return v;
}
__device__ __forceinline__ void st_relaxed_v4(void* p, uint32_t a, uint32_t b, uint32_t c, uint32_t d) {
    asm volatile("st.relaxed.gpu.global.v4.u32 [%0], {%1,%2,%3,%4};" ::"l"(p), "r"(a), "r"(b), "r"(c), "r"(d) : "memory");
}
__device__ __forceinline__ int ld_acquire(const int* p) {
    int v;
    asm volatile("ld.acquire.gpu.global.u32 %0, [%1];" : "=r"(v) : "l"(p) : "memory");
    return v;
}
__device__ __forceinline__ void mbar_init(uint32_t bar, int count) {
    asm volatile("mbarrier.init.shared::cta.b64 [%0], %1;" ::"r"(bar), "r"(count));
}
__device__ __forceinline__ void mbar_expect_tx(uint32_t bar, uint32_t bytes) {
    asm volatile("mbarrier.arrive.expect_tx.shared::cta.b64 _, [%0], %1;" ::"r"(bar), "r"(bytes) : "memory");
}
__device__ __forceinline__ void mbar_arrive(uint32_t bar) {
    asm volatile("mbarrier.arrive.shared::cta.b64 _, [%0];" ::"r"(bar) : "memory");
}
constexpr int SPIN_LIMIT = 4000000;
__device__ __forceinline__ void mbar_wait_spin(uint32_t bar, uint32_t parity) {
    uint32_t ok = 0;
    int guard = 0;
    while (!ok && ++guard < SPIN_LIMIT) {
        asm volatile(
            "{\n.reg .pred P1;\n"
            "mbarrier.try_wait.parity.shared::cta.b64 P1, [%1], %2;\n"
            "selp.u32 %0, 1, 0, P1;\n}\n"
            : "=r"(ok) : "r"(bar), "r"(parity) : "memory");
    }
}
__device__ __forceinline__ uint32_t mapa(uint32_t addr, uint32_t rank) {
    uint32_t r;
    asm volatile("mapa.shared::cluster.u32 %0, %1, %2;" : "=r"(r) : "r"(addr), "r"(rank));
    return r;
}
__device__ __forceinline__ void st_async_u32(uint32_t addr, uint32_t v, uint32_t bar) {
    asm volatile("st.async.weak.shared::cluster.mbarrier::complete_tx::bytes.b32 [%0], %1, [%2];" ::"r"(addr), "r"(v), "r"(bar) : "memory");
}
__device__ __forceinline__ void st_async_v2(uint32_t addr, uint32_t a, uint32_t b, uint32_t bar) {
    asm volatile("st.async.weak.shared::cluster.mbarrier::complete_tx::bytes.v2.b32 [%0], {%1,%2}, [%3];" ::"r"(addr), "r"(a), "r"(b), "r"(bar) : "memory");
}
__device__ __forceinline__ void cluster_sync_all() {
    asm volatile("barrier.cluster.arrive.release.aligned;\nbarrier.cluster.wait.acquire.aligned;" ::: "memory");
}
__device__ __forceinline__ void named_bar(int id, int n) { asm volatile("bar.sync %0, %1;" ::"r"(id), "r"(n) : "memory"); }

}

namespace ni {
#define CHAIN_LAG 16
constexpr int CL = 16;
constexpr int OWN = DM / CL;
constexpr int NSRC = CL / 2;
constexpr int NCLU = 64 / CL;
constexpr int CSEG = 4;
constexpr int NCHK = NSEG / CSEG;
constexpr int LAG = CHAIN_LAG;
constexpr int NTICK = NSEG + LAG;

constexpr int F_KV = 0, F_MEM = 32, F_H = 64, F_OP = 96, F_CONV = 128, F_U = 130, F_PROG = 132, F_ZERO = 133, F_CNT = 136;
constexpr int NFLAG = 192;
__device__ int g_flags[NFLAG * 32];
#define FLG(i) (g_flags + (i) * 32)
constexpr int CHAIN_THREADS = 384;
__device__ bf16 g_Y[S_LEN * DM];
__device__ bf16 g_U[DM * S_LEN];
__device__ bf16 g_h[2][S_LEN * DM];
__device__ bf16 g_x[S_LEN * DM];
__device__ bf16 g_kv[2][S_LEN * HD];
#define PRING 4
constexpr int PROWS = PRING * 128, PG = 4;
__device__ bf16 g_part[2 * PROWS * PG * DM];
__device__ uint4 g_kvf[2 * NSEG * NH * 256];
__device__ uint32_t g_xc[2 * 2 * CL * NCLU * 8 * OWN];

#define TVAL(i, v)
#define TSTAMP(i)

#define NRQ 36
#define NRW 8
#define PDQ 4
#define PDW1 0
#define PROBE 2
#define PDW 6
constexpr int NSQ = 60 - NRQ, NSW = 20 - NRW;
__host__ __device__ constexpr bool q_smem(int i) { return ((i + 1) * NSQ) / 60 != (i * NSQ) / 60; }
__host__ __device__ constexpr int q_slot(int i) { return q_smem(i) ? (i * NSQ) / 60 : i - (i * NSQ) / 60; }
__host__ __device__ constexpr int w_tile(int i) { return i < 8 ? ((i & 1) ? 0 : 2) : (i < 16 ? (i & 1) : 1); }
__host__ __device__ constexpr int w_k(int i) { return i < 8 ? i / 2 : (i < 16 ? ((i & 1) ? (i - 8) / 2 : 4 + (i - 8) / 2) : i - 12); }
__host__ __device__ constexpr int w_acc(int i) { return (i >= 16 && (i & 1)) ? 3 : w_tile(i); }
__host__ __device__ constexpr bool w_smem(int i) { return i < PDW || NRW == 0 || ((i - PDW + 1) * NRW) / (20 - PDW) == ((i - PDW) * NRW) / (20 - PDW); }
__host__ __device__ constexpr int w_slot(int i) { return i < PDW ? i : (w_smem(i) ? i - ((i - PDW) * NRW) / (20 - PDW) : ((i - PDW) * NRW) / (20 - PDW)); }
constexpr int O_WQ = 0, O_WW = NSQ * 4096, O_REST = (NSQ + NSW) * 4096;
constexpr int C_TOK = 0, C_MEM = 12288, C_RED = C_MEM + 10240, C_Q = C_RED + 6144, C_K = C_Q + 2048, C_V = C_K + 2048, C_S = C_V + 4096,
              C_BAR = C_S + 3072, C_SIZE = 40960;
constexpr int S_BYTES = 3072 + 4096;
constexpr int B_S = 64, B_R = 72, B_T = 96, B_F = 104;
static_assert(C_BAR + 112 <= C_SIZE, "chain block");
constexpr int O_STB = O_REST - 61440;
static_assert((45 * NSQ) / 60 * 4096 <= O_STB && NSQ <= 32, "staging");
struct ChainSmem { unsigned char b[O_REST + 81920 + 1536]; };
static_assert(sizeof(ChainSmem) <= 232448, "smem");

struct ChainArgs {
    CUtensorMap tk[2], tv[2];
    const bf16 *x, *mem0, *Wq, *Wk, *Wv, *Wo;
    int kv_target;
};
__device__ __forceinline__ uint32_t movmat(uint32_t v) {
    uint32_t r;
    asm volatile("movmatrix.sync.aligned.m8n8.trans.b16 %0, %1;" : "=r"(r) : "r"(v));
    return r;
}
__device__ __forceinline__ void named_arrive(int id, int n) { asm volatile("bar.arrive %0, %1;" ::"r"(id), "r"(n) : "memory"); }
__device__ __forceinline__ void red_release(int* p, int v) { asm volatile("red.release.gpu.global.add.u32 [%0], %1;" ::"l"(p), "r"(v) : "memory"); }

#define CVT(i)
__device__ __forceinline__ uint4 lds128(uint32_t a) {
    uint4 v;
    asm volatile("ld.shared.v4.u32 {%0,%1,%2,%3}, [%4];" : "=r"(v.x), "=r"(v.y), "=r"(v.z), "=r"(v.w) : "r"(a));
    return v;
}
__device__ __forceinline__ uint2 lds64(uint32_t a) {
    uint2 v;
    asm volatile("ld.shared.v2.u32 {%0,%1}, [%2];" : "=r"(v.x), "=r"(v.y) : "r"(a));
    return v;
}
__device__ __forceinline__ uint32_t lds32(uint32_t a) {
    uint32_t v;
    asm volatile("ld.shared.u32 %0, [%1];" : "=r"(v) : "r"(a));
    return v;
}
__device__ __forceinline__ void sts64(uint32_t a, uint32_t x, uint32_t y) { asm volatile("st.shared.v2.u32 [%0], {%1,%2};" ::"r"(a), "r"(x), "r"(y) : "memory"); }
__device__ __forceinline__ void sts128(uint32_t a, uint32_t x, uint32_t y, uint32_t z, uint32_t w) {
    asm volatile("st.shared.v4.u32 [%0], {%1,%2,%3,%4};" ::"r"(a), "r"(x), "r"(y), "r"(z), "r"(w) : "memory");
}
__device__ __forceinline__ void st_async_v4(uint32_t addr, uint32_t a, uint32_t b, uint32_t c, uint32_t d, uint32_t bar) {
    asm volatile("st.async.weak.shared::cluster.mbarrier::complete_tx::bytes.v4.b32 [%0], {%1,%2,%3,%4}, [%5];" ::"r"(addr), "r"(a), "r"(b), "r"(c), "r"(d), "r"(bar) : "memory");
}
__device__ __forceinline__ uint2 ld_relaxed_v2(const void* p) {
    uint2 v;
    asm volatile("ld.relaxed.gpu.global.v2.u32 {%0,%1}, [%2];" : "=r"(v.x), "=r"(v.y) : "l"(p) : "memory");
    return v;
}
__device__ __forceinline__ void st_relaxed_v2(void* p, uint32_t a, uint32_t b) {
    asm volatile("st.relaxed.gpu.global.v2.u32 [%0], {%1,%2};" ::"l"(p), "r"(a), "r"(b) : "memory");
}
__device__ __forceinline__ float blo(uint32_t v) { return __uint_as_float(v << 16); }
__device__ __forceinline__ float bhi(uint32_t v) { return __uint_as_float(v & 0xffff0000u); }
__device__ __forceinline__ uint32_t badd2(uint32_t a, uint32_t b) {
    __nv_bfloat162 r = __hadd2(*reinterpret_cast<__nv_bfloat162*>(&a), *reinterpret_cast<__nv_bfloat162*>(&b));
    return *reinterpret_cast<uint32_t*>(&r);
}
__device__ __forceinline__ void mmau(float* c, const uint4& a, uint32_t b0, uint32_t b1) { mma16816(c, a.x, a.y, a.z, a.w, b0, b1); }

__device__ __forceinline__ void stsm_x4_t(uint32_t a, uint32_t r0, uint32_t r1, uint32_t r2, uint32_t r3) {
    asm volatile("stmatrix.sync.aligned.m8n8.x4.trans.shared.b16 [%0], {%1,%2,%3,%4};" ::"r"(a), "r"(r0), "r"(r1), "r"(r2), "r"(r3) : "memory");
}
__device__ __forceinline__ uint4 ldsm4(uint32_t a) { uint4 v; ldsm_x4(v.x, v.y, v.z, v.w, a); return v; }
__device__ __forceinline__ float ex2f(float x) { float y; asm("ex2.approx.ftz.f32 %0, %1;" : "=f"(y) : "f"(x)); return y; }
__device__ __forceinline__ float rcpf(float x) { float y; asm("rcp.approx.ftz.f32 %0, %1;" : "=f"(y) : "f"(x)); return y; }
#define XD 300
__device__ __forceinline__ void xdelay() {
    uint32_t t0, t1;
    asm volatile("mov.u32 %0, %clock;" : "=r"(t0));
    do { asm volatile("mov.u32 %0, %clock;" : "=r"(t1)); } while (t1 - t0 < XD);
}
template <int V> struct IC { static constexpr int value = V; };
__device__ __forceinline__ uint32_t opq(uint32_t x) { uint32_t y; asm volatile("mov.u32 %0, %1;" : "=r"(y) : "r"(x)); return y; }
#define UNI(x) __shfl_sync(0xffffffffu, (uint32_t)(x), 0)
__device__ __forceinline__ uint32_t mtest(uint32_t bar, uint32_t parity) {
    uint32_t ok;
    asm volatile("{\n.reg .pred P1;\nmbarrier.test_wait.parity.shared::cta.b64 P1, [%1], %2;\nselp.u32 %0, 1, 0, P1;\n}\n" : "=r"(ok) : "r"(bar), "r"(parity) : "memory");
    return ok;
}
__device__ __forceinline__ void mwait(uint32_t bar, uint32_t parity) {
    asm volatile(
        "{\n.reg .pred P1;\n.reg .u32 cnt;\n"
        "mbarrier.try_wait.parity.shared::cta.b64 P1, [%0], %1;\n"
        "@P1 bra DONE;\n"
        "mov.u32 cnt, 0;\n"
        "LAB_WAIT:\n"
        "mbarrier.try_wait.parity.shared::cta.b64 P1, [%0], %1;\n"
        "@P1 bra DONE;\n"
        "add.u32 cnt, cnt, 1;\n"
        "setp.lt.u32 P1, cnt, 4000000;\n"
        "@P1 bra LAB_WAIT;\n"
        "DONE:\n}\n" ::"r"(bar), "r"(parity) : "memory");
}

__global__ void __launch_bounds__(CHAIN_THREADS, 1) chain_kernel(const __grid_constant__ ChainArgs A) {
    extern __shared__ __align__(1024) unsigned char smem_raw[];
    const int tid = threadIdx.x, warp = __shfl_sync(0xffffffffu, tid >> 5, 0), lane = tid & 31;
    const int cq = blockIdx.x / CL, r = blockIdx.x % CL;
    const int h = cq * NSRC + (r >> 1), hf = r & 1;
    const uint32_t sb = smem_u32(smem_raw);
    asm volatile("griddepcontrol.launch_dependents;");
    CVT(0);
    if (warp == 8) {
        if (lane < 8) asm volatile("cp.async.bulk.prefetch.L2.global [%0], %1;" ::"l"(A.x + (size_t)(blockIdx.x * 8 + lane) * 2560), "r"(5120) : "memory");
        asm volatile("cp.async.bulk.prefetch.L2.global [%0], %1;" ::"l"((lane < 16 ? A.Wk : A.Wv) + (size_t)(blockIdx.x * 16 + (lane & 15)) * 2560), "r"(5120) : "memory");
        asm volatile("cp.async.bulk.prefetch.L2.global [%0], %1;" ::"l"((lane < 16 ? A.Wq : A.Wo) + (size_t)(blockIdx.x * 16 + (lane & 15)) * 2560), "r"(5120) : "memory");
    }
    CVT(1);
    if (warp < 8) {
        asm volatile("setmaxnreg.inc.sync.aligned.u32 232;");
        const int j = warp & 3, kh = warp >> 2;
        uint4 wr[NRQ + NRW];
        {
            auto load_round = [&](int gi) {
                const uint32_t buf = sb + ((gi & 1) ? O_STB : O_REST);
#pragma unroll
                for (int it = 0; it < 15; it++) {
                    const int i = tid + it * 256;
                    const int pc = i / 1920, rem = i % 1920, row = rem / 24, ch = rem % 24;
                    const int mat = ch >> 3, pi = ((r >> 1) - (2 * gi + pc)) & 7;
                    const bf16* W = mat == 0 ? A.Wq : (mat == 1 ? A.Wk : A.Wv);
                    cp_async16(buf + pc * 30720 + row * 384 + ((ch ^ (row & 7)) << 4), W + (size_t)(pi * 80 + row) * HD + h * DH + hf * 64 + (ch & 7) * 8);
                }
                cp_commit();
            };
            load_round(0);
            load_round(1);
#pragma unroll
            for (int gi = 0; gi < 4; gi++) {
                cp_wait<1>();
                named_bar(1, 256);
                const uint32_t pb = sb + ((gi & 1) ? O_STB : O_REST) + kh * 30720;
                uint4 tmp[8];
#pragma unroll
                for (int u = 0; u < 5; u++)
#pragma unroll
                    for (int tt = 0; tt < 3; tt++) {
                        const int row = u * 16 + (lane & 7) + (lane >> 4) * 8;
                        const int ch = tt * 8 + j * 2 + ((lane >> 3) & 1);
                        uint4 v;
                        ldsm_x4_t(v.x, v.y, v.z, v.w, pb + row * 384 + ((ch ^ (row & 7)) << 4));
                        const int i = (gi * 5 + u) * 3 + tt;
                        if (q_smem(i)) {
                            if (gi == 3) tmp[q_slot(i) & 7] = v;
                            else sts128(sb + O_WQ + q_slot(i) * 4096 + tid * 16, v.x, v.y, v.z, v.w);
                        } else wr[q_slot(i)] = v;
                    }
                named_bar(1, 256);
                if (gi == 3) {
#pragma unroll
                    for (int i = 45; i < 60; i++)
                        if (q_smem(i)) { const uint4 v = tmp[q_slot(i) & 7]; sts128(sb + O_WQ + q_slot(i) * 4096 + tid * 16, v.x, v.y, v.z, v.w); }
                }
                if (gi < 2) load_round(gi + 2);
                else if (gi == 2) {
                    for (int i = tid; i < 128 * 40; i += 256) {
                        const int row = i / 40, ch = i % 40;
                        cp_async16(sb + O_REST + row * 640 + ((ch ^ (row & 7)) << 4), A.Wo + ((size_t)h * DH + row) * DM + hf * 320 + ch * 8);
                    }
                    cp_commit();
                }
            }
            cp_wait<0>();
            named_bar(1, 256);
#pragma unroll
            for (int i = 0; i < 20; i++) {
                const int tl = w_tile(i), et = (w_k(i) + 4 * (warp & 1)) & 7;
                const int row = et * 16 + (lane & 7) + (lane >> 4) * 8;
                const int ch = (warp >> 1) * 10 + (tl == 2 ? 8 : (warp & 1) * 4 + tl * 2) + ((lane >> 3) & 1);
                uint4 v;
                ldsm_x4_t(v.x, v.y, v.z, v.w, sb + O_REST + row * 640 + ((ch ^ (row & 7)) << 4));
                if (w_smem(i)) sts128(sb + O_WW + w_slot(i) * 4096 + tid * 16, v.x, v.y, v.z, v.w);
                else wr[NRQ + w_slot(i)] = v;
            }
            named_bar(1, 256);
            for (int i = tid; i < 2560; i += 256) {
                const int ks = i >> 6, ln = (i >> 1) & 31, wd = i & 1;
                const int pi = ((r >> 1) - ks / 5) & 7;
                const uint32_t v = *reinterpret_cast<const uint32_t*>(A.mem0 + (ln >> 2) * DM + pi * 80 + (ks % 5) * 16 + wd * 8 + (ln & 3) * 2);
                const int o = ks % 5 == 4 ? ks * 256 + wd * 128 + ln * 4 : i * 4;
                asm volatile("st.shared.u32 [%0], %1;" ::"r"(sb + O_REST + C_MEM + o), "r"(v) : "memory");
                asm volatile("st.shared.u32 [%0], %1;" ::"r"(sb + O_REST + C_SIZE + C_MEM + o), "r"(v) : "memory");
            }
            if (tid < 2) {
                const uint32_t bb = sb + O_REST + tid * C_SIZE + C_BAR;
                for (int i = 0; i < 13; i++) mbar_init(bb + i * 8, 1);
                mbar_init(bb + B_F, 4);
                asm volatile("fence.mbarrier_init.release.cluster;" ::: "memory");
                mbar_expect_tx(bb + B_S, S_BYTES);
                for (int i = 0; i < 3; i++) mbar_expect_tx(bb + B_R + i * 8, 2048);
            }
            asm volatile("fence.proxy.async;" ::: "memory");
        }
        CVT(2);
        cluster_sync_all();
        const uint32_t wq_a = sb + O_WQ + tid * 16;
        const uint32_t cb0 = sb + O_REST;
        const uint32_t qk_a = cb0 + j * 512 + (lane & 7) * 16 + (lane < 16 ? C_Q + (lane >> 3) * 256 + kh * 128 : C_K + kh * 256 + ((lane >> 3) & 1) * 128);
        const uint32_t pd = UNI(mapa(sb, (uint32_t)(r ^ 1)) - sb), sd = UNI(mapa(sb, (uint32_t)r) - sb);
        const uint32_t od = UNI(mapa(sb, (uint32_t)(hf * 8 + warp)) - sb);
        const uint32_t oe = UNI(mapa(sb, (uint32_t)(hf * 8 + (warp & 6))) - sb), oo = UNI(mapa(sb, (uint32_t)(hf * 8 + (warp | 1))) - sb);
        const uint32_t u_mem = UNI(cb0 + C_MEM + kh * 1280), u_bm = UNI(cb0 + C_BAR + kh * 8);
        const uint32_t u_v = UNI(cb0 + C_V + hf * 2048 + j * 512 + kh * 256);
        const uint32_t u_ra = UNI(cb0 + C_RED + (r >> 1) * 256);
        const uint32_t u_ob0 = UNI(cb0 + C_Q + (warp & 1) * 1024), u_ob1 = UNI(cb0 + C_Q + ((warp & 1) ^ 1) * 1024);
        const uint32_t u_role = UNI(warp < 3 ? cb0 + C_S + hf * 1536 + warp * 512 : cb0 + C_V + j * 1024);
        const uint32_t t_tok = cb0 + C_TOK + ((lane & 7) + (lane >> 4) * 8) * 128 +
                               (warp < 3 ? warp * 2048 + ((((lane >> 3) & 1) ^ (lane & 7)) << 4) : 4096 + (j >> 1) * 4096 + ((((j & 1) * 4 + ((lane >> 3) & 1)) ^ (lane & 7)) << 4));
        uint4 qb[PDQ];
#pragma unroll
        for (int s = 0; s < PDQ; s++) qb[s] = lds128(wq_a + s * 4096);
        auto tick = [&](auto cc, const int n) {
            constexpr int c = decltype(cc)::value;
            constexpr uint32_t CO = c * C_SIZE;
            const uint32_t cb = cb0 + CO;
            const uint32_t par = (uint32_t)(n & 1);
            const uint32_t l4 = opq(lane * 4), l8 = l4 * 2, l16 = l4 * 4;
            float acc[3][4];
#pragma unroll
            for (int a = 0; a < 3; a++)
#pragma unroll
                for (int i = 0; i < 4; i++) acc[a][i] = 0.f;
            {
                const uint32_t mb = u_mem + CO + l8;
                uint2 bf[3];
                uint32_t ok = 1;
                auto ldb = [&](int ks) {
                    if (ks == 0) mwait(u_bm + CO, par ^ 1);
                    else if (ks % 5 == 0) { if (!ok) mwait(u_bm + CO + (ks / 5) * 16, par ^ 1); }
                    if (ks % 5 == PROBE && ks < 15) ok = mtest(u_bm + CO + (ks / 5 + 1) * 16, par ^ 1);
                    if (ks % 5 == 4) {
                        bf[ks % 3].x = lds32(u_mem + CO + l4 + (ks / 5) * 2560 + 1024);
                        bf[ks % 3].y = lds32(u_mem + CO + l4 + (ks / 5) * 2560 + 1152);
                    } else bf[ks % 3] = lds64(mb + (ks / 5) * 2560 + (ks % 5) * 256);
                };
                ldb(0);
                TSTAMP(c * 12 + 0);
                ldb(1);
#pragma unroll
                for (int ks = 0; ks < 20; ks++) {
                    if (ks + 2 < 20) ldb(ks + 2);
#pragma unroll
                    for (int tt = 0; tt < 3; tt++) {
                        const int i = ks * 3 + tt;
                        if (q_smem(i)) {
                            const int s = q_slot(i);
                            mmau(acc[tt], qb[s % PDQ], bf[ks % 3].x, bf[ks % 3].y);
                            if (s + PDQ < NSQ) qb[s % PDQ] = lds128(wq_a + (s + PDQ) * 4096);
                        } else mmau(acc[tt], wr[q_slot(i)], bf[ks % 3].x, bf[ks % 3].y);
                    }
                }
            }
            TSTAMP(c * 12 + 1);
            stsm_x4_t(opq(qk_a) + CO, pack2(acc[0][0], acc[0][1]), pack2(acc[0][2], acc[0][3]), pack2(acc[1][0], acc[1][1]), pack2(acc[1][2], acc[1][3]));
            const uint32_t v0 = pack2(acc[2][0], acc[2][1]), v1 = pack2(acc[2][2], acc[2][3]);
            if (n == NSEG - 1) {
                sts64(u_v + CO + l8, v0, v1);
                named_bar(1, 256);
                if (kh == 1 && lane == 0) mbar_arrive(cb + C_BAR + B_F);
#pragma unroll
                for (int s = 0; s < PDQ; s++) qb[s] = lds128(wq_a + s * 4096);
                return;
            }
            named_arrive(1, 384);
            st_async_v2(u_v + CO + l8 + pd, v0, v1, cb + C_BAR + B_S + pd);
            st_async_v2(u_v + CO + l8 + sd, v0, v1, cb + C_BAR + B_S + sd);
            uint4 wb[PDW];
            const uint32_t ww_a = wq_a + (O_WW - O_WQ);
            if (warp < 3) {
                uint4 kb[4];
                const uint32_t t_tk = opq(t_tok);
                mwait(cb + C_BAR + B_T, par);
#pragma unroll
                for (int i = 0; i < 4; i++) kb[i] = ldsm4((t_tk ^ (i << 5)) + CO);
                named_bar(1, 384);
                uint4 qa[4];
#pragma unroll
                for (int i = 0; i < 4; i++) qa[i] = ldsm4(cb + l16 + C_Q + i * 512);
                if (warp == 2) {
#pragma unroll
                    for (int i = 0; i < 4; i++) kb[i] = ldsm4(cb + l16 + C_K + i * 512);
                }
                float s0[4][4], s1[4][4];
#pragma unroll
                for (int i = 0; i < 4; i++) {
#pragma unroll
                    for (int q = 0; q < 4; q++) s0[i][q] = s1[i][q] = 0.f;
                    mmau(s0[i], qa[i], kb[i].x, kb[i].y);
                    mmau(s1[i], qa[i], kb[i].z, kb[i].w);
                }
                const float a0 = ((s0[0][0] + s0[0][2]) + (s0[1][0] + s0[1][2])) + ((s0[2][0] + s0[2][2]) + (s0[3][0] + s0[3][2]));
                const float a1 = ((s0[0][1] + s0[0][3]) + (s0[1][1] + s0[1][3])) + ((s0[2][1] + s0[2][3]) + (s0[3][1] + s0[3][3]));
                const float b0 = ((s1[0][0] + s1[0][2]) + (s1[1][0] + s1[1][2])) + ((s1[2][0] + s1[2][2]) + (s1[3][0] + s1[3][2]));
                const float b1 = ((s1[0][1] + s1[0][3]) + (s1[1][1] + s1[1][3])) + ((s1[2][1] + s1[2][3]) + (s1[3][1] + s1[3][3]));
                const uint32_t so = u_role + CO + l16, bs = cb + C_BAR + B_S;
                const float c0 = warp == 2 ? a0 + b0 : a0, c1 = warp == 2 ? a1 + b1 : a1;
                st_async_v4(so + pd, __float_as_uint(c0), __float_as_uint(c1), __float_as_uint(b0), __float_as_uint(b1), bs + pd);
                st_async_v4(so + sd, __float_as_uint(c0), __float_as_uint(c1), __float_as_uint(b0), __float_as_uint(b1), bs + sd);
                TSTAMP(c * 12 + 2);
#pragma unroll
                for (int s = 0; s < PDW; s++) wb[s] = lds128(ww_a + s * 4096);
            } else if (warp == 3) {
                named_bar(1, 384);
                if (lane < 8) mbar_expect_tx(cb + C_BAR + l8, 1280);
#pragma unroll
                for (int s = 0; s < PDW; s++) wb[s] = lds128(ww_a + s * 4096);
            } else {
                mwait(cb + C_BAR + B_T, par);
                uint4 va[2][2];
                const uint32_t t_tk = opq(t_tok);
#pragma unroll
                for (int e = 0; e < 2; e++)
#pragma unroll
                    for (int k = 0; k < 2; k++)
                        ldsm_x4_t(va[e][k].x, va[e][k].y, va[e][k].z, va[e][k].w, (t_tk ^ (e << 5)) + CO + k * 2048);
#pragma unroll
                for (int s2 = 0; s2 < PDW1; s2++) wb[s2] = lds128(ww_a + s2 * 4096);
                mwait(cb + C_BAR + B_S, par);
                TSTAMP(c * 12 + 3);
                const uint32_t xa = cb + l16 + C_S;
                const uint4 x0 = lds128(xa), y0 = lds128(xa + 1536), x1 = lds128(xa + 512), y1 = lds128(xa + 512 + 1536);
                const uint2 x2 = lds64(xa + 1024), y2 = lds64(xa + 1024 + 1536);
                const uint32_t fv = u_role + CO + l8;
                const float cs = 0.08838834764831845f * 1.4426950408889634f;
                float s[10];
                s[8] = __uint_as_float(x2.x) + __uint_as_float(y2.x); s[9] = __uint_as_float(x2.y) + __uint_as_float(y2.y);
                s[0] = __uint_as_float(x0.x) + __uint_as_float(y0.x); s[1] = __uint_as_float(x0.y) + __uint_as_float(y0.y);
                s[2] = __uint_as_float(x0.z) + __uint_as_float(y0.z); s[3] = __uint_as_float(x0.w) + __uint_as_float(y0.w);
                s[4] = __uint_as_float(x1.x) + __uint_as_float(y1.x); s[5] = __uint_as_float(x1.y) + __uint_as_float(y1.y);
                s[6] = __uint_as_float(x1.z) + __uint_as_float(y1.z); s[7] = __uint_as_float(x1.w) + __uint_as_float(y1.w);
                float mx = fmaxf(fmaxf(fmaxf(s[0], s[1]), fmaxf(s[2], s[3])), fmaxf(fmaxf(fmaxf(s[4], s[5]), fmaxf(s[6], s[7])), fmaxf(s[8], s[9])));
                const float m1 = __shfl_xor_sync(0xffffffffu, mx, 1), m2 = __shfl_xor_sync(0xffffffffu, mx, 2), m3 = __shfl_xor_sync(0xffffffffu, mx, 3);
                const uint2 vm00 = lds64(fv), vm01 = lds64(fv + 256), vm10 = lds64(fv + 512), vm11 = lds64(fv + 768);
                const uint4 vm0 = make_uint4(vm00.x, vm00.y, vm01.x, vm01.y), vm1 = make_uint4(vm10.x, vm10.y, vm11.x, vm11.y);
                mx = fmaxf(fmaxf(mx, m1), fmaxf(m2, m3)) * -cs;
                uint32_t pb[5];
                pb[4] = pack2(ex2f(fmaf(s[8], cs, mx)), ex2f(fmaf(s[9], cs, mx)));
#pragma unroll
                for (int i = 0; i < 4; i++) pb[i] = pack2(ex2f(fmaf(s[2 * i], cs, mx)), ex2f(fmaf(s[2 * i + 1], cs, mx)));
                float o[3][4];
#pragma unroll
                for (int i = 0; i < 4; i++) { o[0][i] = o[1][i] = o[2][i] = 0.f; }
                const uint32_t one2 = 0x3F803F80u;
                mma16816(o[2], one2, one2, one2, one2, pb[4], 0u);
                mmau(o[0], vm0, pb[4], pb[4]);
                mmau(o[1], vm1, pb[4], pb[4]);
                mma16816(o[2], one2, one2, one2, one2, pb[0], pb[1]);
                mmau(o[0], va[0][0], pb[0], pb[1]);
                mmau(o[1], va[1][0], pb[0], pb[1]);
                mma16816(o[2], one2, one2, one2, one2, pb[2], pb[3]);
                mmau(o[0], va[0][1], pb[2], pb[3]);
                mmau(o[1], va[1][1], pb[2], pb[3]);
                const float r0 = rcpf(o[2][0]), r1 = rcpf(o[2][1]);
                stsm_x4_t(cb + l16 + C_Q + j * 512, pack2(o[0][0] * r0, o[0][1] * r1), pack2(o[0][2] * r0, o[0][3] * r1), pack2(o[1][0] * r0, o[1][1] * r1), pack2(o[1][2] * r0, o[1][3] * r1));
                named_arrive(2, 384);
                TSTAMP(c * 12 + 4);
#pragma unroll
                for (int s2 = PDW1; s2 < PDW; s2++) wb[s2] = lds128(ww_a + s2 * 4096);
                if (lane == 0) mbar_arrive(cb + C_BAR + B_F);
                if (warp == 4 && lane == 0) mbar_expect_tx(cb + C_BAR + B_S, S_BYTES);
            }
            named_bar(2, 384);
            TSTAMP(c * 12 + 5);
            {
                uint4 ob[4];
                ob[0] = ldsm4(u_ob0 + CO + l16); ob[1] = ldsm4(u_ob0 + CO + l16 + 512);
                ob[2] = ldsm4(u_ob1 + CO + l16); ob[3] = ldsm4(u_ob1 + CO + l16 + 512);
                float d[4][4];
#pragma unroll
                for (int a = 0; a < 4; a++)
#pragma unroll
                    for (int i = 0; i < 4; i++) d[a][i] = 0.f;
                const uint32_t ra = u_ra + CO + l8, rb = cb + C_BAR + B_R;
#pragma unroll
                for (int i = 0; i < 20; i++) {
                    const int k = w_k(i), ac = w_acc(i);
                    const uint32_t b0 = (k & 1) ? ob[k >> 1].z : ob[k >> 1].x, b1 = (k & 1) ? ob[k >> 1].w : ob[k >> 1].y;
                    if (w_smem(i)) {
                        const int s = w_slot(i);
                        mmau(d[ac], wb[s % PDW], b0, b1);
                        if (s + PDW < NSW) wb[s % PDW] = lds128(ww_a + (s + PDW) * 4096);
                    } else mmau(d[ac], wr[NRQ + w_slot(i)], b0, b1);
                    if (i == 9) {
                        const uint32_t rs = u_ra + CO + l4 + 4096 + (warp & 1) * 128;
                        st_async_u32(rs + oe, pack2(d[2][0], d[2][1]), rb + 16 + oe);
                        st_async_u32(rs + oo, pack2(d[2][2], d[2][3]), rb + 16 + oo);
                    }
                    if (i == 17) st_async_v2(ra + od, pack2(d[0][0], d[0][1]), pack2(d[0][2], d[0][3]), rb + od);
                }
                st_async_v2(ra + 2048 + od, pack2(d[1][0] + d[3][0], d[1][1] + d[3][1]), pack2(d[1][2] + d[3][2], d[1][3] + d[3][3]), rb + 8 + od);
                TSTAMP(c * 12 + 6);
#pragma unroll
                for (int s = 0; s < PDQ; s++) qb[s] = lds128(wq_a + s * 4096);
            }
        };
#pragma unroll 1
        for (int t = 0; t < NTICK; t++) {
            if (t < NSEG) tick(IC<0>{}, t);
            if (t >= LAG) tick(IC<1>{}, t - LAG);
        }
    } else {
        asm volatile("setmaxnreg.dec.sync.aligned.u32 40;");
        const int s = warp - 8;
        cluster_sync_all();
        if (s < 3) {
#pragma unroll 1
            for (int hs = 0; hs < 2 * NTICK; hs++) {
                const int c = hs & 1, t = hs >> 1;
                const int n = t - c * LAG;
                if (n < 0 || n >= NSEG - 1) continue;
                const uint32_t cb = sb + O_REST + c * C_SIZE;
                const uint32_t par = (uint32_t)(n & 1);
                const uint32_t tag = (uint32_t)(n % 13) + 1u;
                uint32_t* xb = g_xc + (size_t)((c * 2 + par) * CL + r) * (NCLU * 320) + s * 128;
                const uint32_t ra = cb + C_RED + s * 2048 + lane * (s < 2 ? 8 : 4);
                mwait(cb + C_BAR + B_R + s * 8, par);
                TSTAMP(c * 12 + 7);
                uint4 p[4];
                if (s < 2) {
#pragma unroll
                    for (int i = 0; i < 4; i++) {
                        const uint2 a = lds64(ra + i * 512), b = lds64(ra + i * 512 + 256);
                        p[i] = make_uint4(a.x, a.y, b.x, b.y);
                    }
                } else {
#pragma unroll
                    for (int i = 0; i < 4; i++) p[i] = make_uint4(lds32(ra + i * 512), lds32(ra + i * 512 + 128), lds32(ra + i * 512 + 256), lds32(ra + i * 512 + 384));
                }
                if (lane == 0) mbar_expect_tx(cb + C_BAR + B_R + s * 8, 2048);
                uint32_t m0, m1;
                if (s < 2) {
                    float f0 = 0.f, f1 = 0.f, f2 = 0.f, f3 = 0.f;
#pragma unroll
                    for (int i = 0; i < 4; i++) {
                        f0 += blo(p[i].x) + blo(p[i].z); f1 += bhi(p[i].x) + bhi(p[i].z);
                        f2 += blo(p[i].y) + blo(p[i].w); f3 += bhi(p[i].y) + bhi(p[i].w);
                    }
                    xb += lane * 4;
                    const uint32_t u0 = (__float_as_uint(f0) & ~0xFu) | tag, u1 = (__float_as_uint(f1) & ~0xFu) | tag;
                    const uint32_t u2 = (__float_as_uint(f2) & ~0xFu) | tag, u3 = (__float_as_uint(f3) & ~0xFu) | tag;
                    st_relaxed_v4(xb + cq * 320, u0, u1, u2, u3);
                    TSTAMP(c * 12 + 8);
                    xdelay();
                    uint4 x[NCLU];
#pragma unroll
                    for (int k = 0; k < NCLU; k++) x[k] = make_uint4(u0, u1, u2, u3);
                    int guard = 0;
                    bool first = true;
                    while (true) {
                        bool ok = true;
#pragma unroll
                        for (int k = 0; k < NCLU; k++) {
                            const bool okk = k == cq || (!first && ((x[k].x ^ tag) | (x[k].y ^ tag) | (x[k].z ^ tag) | (x[k].w ^ tag)) << 28 == 0);
                            if (!okk) { x[k] = ld_relaxed_v4(xb + k * 320); ok = false; }
                        }
                        first = false;
                        if (__all_sync(0xffffffffu, ok) || ++guard > SPIN_LIMIT) break;
                    }
                    TVAL(c * 12 + 11, guard);
                    f0 = f1 = f2 = f3 = 0.f;
#pragma unroll
                    for (int k = 0; k < NCLU; k++) {
                        f0 += __uint_as_float(x[k].x & ~0xFu); f1 += __uint_as_float(x[k].y & ~0xFu);
                        f2 += __uint_as_float(x[k].z & ~0xFu); f3 += __uint_as_float(x[k].w & ~0xFu);
                    }
                    m0 = movmat(pack2(f0, f1)); m1 = movmat(pack2(f2, f3));
                } else {
                    float f0 = 0.f, f1 = 0.f;
#pragma unroll
                    for (int i = 0; i < 4; i++) {
                        f0 += (blo(p[i].x) + blo(p[i].y)) + (blo(p[i].z) + blo(p[i].w));
                        f1 += (bhi(p[i].x) + bhi(p[i].y)) + (bhi(p[i].z) + bhi(p[i].w));
                    }
                    xb += lane * 2;
                    const uint32_t u0 = (__float_as_uint(f0) & ~0xFu) | tag, u1 = (__float_as_uint(f1) & ~0xFu) | tag;
                    st_relaxed_v2(xb + cq * 320, u0, u1);
                    TSTAMP(c * 12 + 8);
                    xdelay();
                    uint2 x[NCLU];
#pragma unroll
                    for (int k = 0; k < NCLU; k++) x[k] = make_uint2(u0, u1);
                    int guard = 0;
                    bool first = true;
                    while (true) {
                        bool ok = true;
#pragma unroll
                        for (int k = 0; k < NCLU; k++) {
                            const bool okk = k == cq || (!first && ((x[k].x ^ tag) | (x[k].y ^ tag)) << 28 == 0);
                            if (!okk) { x[k] = ld_relaxed_v2(xb + k * 320); ok = false; }
                        }
                        first = false;
                        if (__all_sync(0xffffffffu, ok) || ++guard > SPIN_LIMIT) break;
                    }
                    TVAL(c * 12 + 11, guard);
                    f0 = f1 = 0.f;
#pragma unroll
                    for (int k = 0; k < NCLU; k++) { f0 += __uint_as_float(x[k].x & ~0xFu); f1 += __uint_as_float(x[k].y & ~0xFu); }
                    m0 = movmat(pack2(f0, f1)); m1 = 0;
                }
                TSTAMP(c * 12 + 9);
                const uint32_t ma = cb + C_MEM + (s < 2 ? lane * 8 + (hf * 2 + s) * 256 : 1024 + hf * 128 + lane * 4), bm = cb + C_BAR;
                if (s < 2) {
#pragma unroll
                    for (int G = 0; G < 8; G++)
#pragma unroll
                        for (int b = 0; b < 2; b++) {
                            const uint32_t dd = mapa(sb, (uint32_t)(((r + 2 * G) & 15) ^ b)) - sb;
                            st_async_v2(ma + G * 1280 + dd, m0, m1, bm + G * 8 + dd);
                        }
                } else {
#pragma unroll
                    for (int G = 0; G < 8; G++)
#pragma unroll
                        for (int b = 0; b < 2; b++) {
                            const uint32_t dd = mapa(sb, (uint32_t)(((r + 2 * G) & 15) ^ b)) - sb;
                            st_async_u32(ma + G * 1280 + dd, m0, bm + G * 8 + dd);
                        }
                }
                TSTAMP(c * 12 + 10);
            }
        } else {
            auto fetch = [&](int c, int seg) {
                if (lane == 0) {
                    if (seg % CSEG == 0) {
                        int guard = 0;
                        while (ld_acquire(FLG(F_KV + c * NCHK + seg / CSEG)) < A.kv_target && ++guard < SPIN_LIMIT) __nanosleep(64);
                    }
                    asm volatile("fence.proxy.async;" ::: "memory");
                    const uint32_t cb = sb + O_REST + c * C_SIZE;
                    const uint32_t bt = cb + C_BAR + B_T, d = cb + C_TOK;
                    mbar_expect_tx(bt, 12288);
                    const CUtensorMap* mk = &A.tk[c];
                    const CUtensorMap* mv = &A.tv[c];
                    asm volatile("cp.async.bulk.tensor.2d.shared::cluster.global.mbarrier::complete_tx::bytes [%0], [%1, {%3, %4}], [%2];" ::"r"(d),
                                 "l"(mk), "r"(bt), "r"(h * DH + hf * 64), "r"(seg * SEG) : "memory");
#pragma unroll
                    for (int i = 0; i < 2; i++)
                        asm volatile("cp.async.bulk.tensor.2d.shared::cluster.global.mbarrier::complete_tx::bytes [%0], [%1, {%3, %4}], [%2];" ::"r"(d + 4096 + i * 4096),
                                     "l"(mv), "r"(bt), "r"(h * DH + i * 64), "r"(seg * SEG) : "memory");
                }
                __syncwarp();
            };
            fetch(0, 0);
#pragma unroll 1
            for (int hs = 0; hs < 2 * NTICK; hs++) {
                const int c = hs & 1, t = hs >> 1;
                const int n = t - c * LAG;
                if (n < -1 || n >= NSEG) continue;
                if (n >= 0) {
                    const uint32_t cb = sb + O_REST + c * C_SIZE;
                    mwait(cb + C_BAR + B_F, (uint32_t)(n & 1));
                    uint4* fd = g_kvf + (size_t)((c * NSEG + n) * NH + h) * 256 + hf * 64 + lane;
#pragma unroll
                    for (int i = 0; i < 2; i++) {
                        const uint4 k0 = ldsm4(cb + C_K + i * 1024 + lane * 16), k1 = ldsm4(cb + C_K + i * 1024 + 512 + lane * 16);
                        fd[i * 32] = make_uint4(badd2(k0.x, k0.z), badd2(k0.y, k0.w), badd2(k1.x, k1.z), badd2(k1.y, k1.w));
                        const uint32_t va = cb + C_V + hf * 2048 + i * 1024 + lane * 8;
                        const uint2 v0 = lds64(va), v1 = lds64(va + 256), v2 = lds64(va + 512), v3 = lds64(va + 768);
                        fd[128 + i * 32] = make_uint4(badd2(v0.x, v1.x), badd2(v0.y, v1.y), badd2(v2.x, v3.x), badd2(v2.y, v3.y));
                    }
                    if (blockIdx.x == 0 && lane == 0 && (c == 0 || t >= NSEG)) asm volatile("st.relaxed.gpu.global.u32 [%0], %1;" ::"l"(FLG(F_PROG)), "r"(t + 1) : "memory");
                    if ((n % CSEG) == CSEG - 1) {
                        asm volatile("fence.proxy.async;" ::: "memory");
                        __syncwarp();
                        if (lane == 0) { red_release(FLG(F_MEM + c * NCHK + n / CSEG), 1); }
                    }
                }
                if (n + 1 < NSEG - 1) fetch(c, n + 1);
            }
        }
    }
    cluster_sync_all();
}
}

namespace ni {
constexpr int KV_TGT = 32, MEM_TGT = 64, OP_TGT = 16, CONV_TGT = 80, H_TGT = 128;
constexpr int PDIST = (LAG + 3) / 4;
#define QA_PRE 3
#define KV1_W 5
#define KV1_N 16
static_assert(QA_PRE < 4, "inputs of the chunk must be complete");
#define SPLAN 0x102030
#define URGENT 1
#define POST_NS 40

#define ELECT "{\n.reg .pred p;\nelect.sync _|p, 0xffffffff;\n@p "
__device__ __forceinline__ void tma_load_2d(uint32_t dst, const CUtensorMap* map, uint32_t bar, int c0, int c1) {
    asm volatile(ELECT "cp.async.bulk.tensor.2d.shared::cluster.global.mbarrier::complete_tx::bytes [%0], [%1, {%3, %4}], [%2];\n}" ::"r"(dst),
                 "l"(map), "r"(bar), "r"(c0), "r"(c1) : "memory");
}
__device__ __forceinline__ void tma_load_2d_mc(uint32_t dst, const CUtensorMap* map, uint32_t bar, int c0, int c1) {
    asm volatile(ELECT "cp.async.bulk.tensor.2d.shared::cluster.global.mbarrier::complete_tx::bytes.multicast::cluster [%0], [%1, {%3, %4}], [%2], %5;\n}" ::"r"(dst),
                 "l"(map), "r"(bar), "r"(c0), "r"(c1), "h"((unsigned short)3) : "memory");
}
__device__ __forceinline__ void tma_load_3d(uint32_t dst, const CUtensorMap* map, uint32_t bar, int c1, int c2) {
    asm volatile(ELECT "cp.async.bulk.tensor.3d.shared::cluster.global.mbarrier::complete_tx::bytes [%0], [%1, {%5, %3, %4}], [%2];\n}" ::"r"(dst),
                 "l"(map), "r"(bar), "r"(c1), "r"(c2), "r"(0) : "memory");
}
__device__ __forceinline__ void tma_load_3d_mc(uint32_t dst, const CUtensorMap* map, uint32_t bar, int c1, int c2) {
    asm volatile(ELECT "cp.async.bulk.tensor.3d.shared::cluster.global.mbarrier::complete_tx::bytes.multicast::cluster [%0], [%1, {%6, %3, %4}], [%2], %5;\n}" ::"r"(dst),
                 "l"(map), "r"(bar), "r"(c1), "r"(c2), "h"((unsigned short)3), "r"(0) : "memory");
}
__device__ __forceinline__ void bulk_load(uint32_t dst, const void* src, uint32_t bytes, uint32_t bar) {
    asm volatile(ELECT "cp.async.bulk.shared::cluster.global.mbarrier::complete_tx::bytes [%0], [%1], %2, [%3];\n}" ::"r"(dst), "l"(src), "r"(bytes), "r"(bar) : "memory");
}
__device__ __forceinline__ void expect_tx1(uint32_t bar, uint32_t bytes) {
    asm volatile(ELECT "mbarrier.arrive.expect_tx.shared::cta.b64 _, [%0], %1;\n}" ::"r"(bar), "r"(bytes) : "memory");
}
__device__ __forceinline__ void wg_fence() { asm volatile("wgmma.fence.sync.aligned;" ::: "memory"); }
__device__ __forceinline__ void wg_commit() { asm volatile("wgmma.commit_group.sync.aligned;" ::: "memory"); }
template <int N> __device__ __forceinline__ void wg_wait() { asm volatile("wgmma.wait_group.sync.aligned %0;" ::"n"(N) : "memory"); }
__device__ __forceinline__ uint64_t make_desc(uint32_t addr, uint32_t lbo, uint32_t sbo) {
    return (uint64_t)((addr & 0x3FFFF) >> 4) | ((uint64_t)((lbo & 0x3FFFF) >> 4) << 16) |
           ((uint64_t)((sbo & 0x3FFFF) >> 4) << 32) | (1ull << 62);
}
__device__ __forceinline__ void wgmma_m64n256k16(float* d, uint64_t da, uint64_t db) {
    asm volatile("{\n.reg .pred p;\nsetp.ne.b32 p, 1, 0;\n"
                 "wgmma.mma_async.sync.aligned.m64n256k16.f32.bf16.bf16 {%0, %1, %2, %3, %4, %5, %6, %7, %8, %9, %10, %11, %12, %13, %14, %15, %16, %17, %18, %19, %20, %21, %22, %23, %24, %25, %26, %27, %28, %29, %30, %31, %32, %33, %34, %35, %36, %37, %38, %39, %40, %41, %42, %43, %44, %45, %46, %47, %48, %49, %50, %51, %52, %53, %54, %55, %56, %57, %58, %59, %60, %61, %62, %63, %64, %65, %66, %67, %68, %69, %70, %71, %72, %73, %74, %75, %76, %77, %78, %79, %80, %81, %82, %83, %84, %85, %86, %87, %88, %89, %90, %91, %92, %93, %94, %95, %96, %97, %98, %99, %100, %101, %102, %103, %104, %105, %106, %107, %108, %109, %110, %111, %112, %113, %114, %115, %116, %117, %118, %119, %120, %121, %122, %123, %124, %125, %126, %127}, %128, %129, p, 1, 1, 0, 1;\n}\n"
                 : "+f"(d[0]), "+f"(d[1]), "+f"(d[2]), "+f"(d[3]), "+f"(d[4]), "+f"(d[5]), "+f"(d[6]), "+f"(d[7]), "+f"(d[8]), "+f"(d[9]), "+f"(d[10]), "+f"(d[11]), "+f"(d[12]), "+f"(d[13]), "+f"(d[14]), "+f"(d[15]), "+f"(d[16]), "+f"(d[17]), "+f"(d[18]), "+f"(d[19]), "+f"(d[20]), "+f"(d[21]), "+f"(d[22]), "+f"(d[23]), "+f"(d[24]), "+f"(d[25]), "+f"(d[26]), "+f"(d[27]), "+f"(d[28]), "+f"(d[29]), "+f"(d[30]), "+f"(d[31]), "+f"(d[32]), "+f"(d[33]), "+f"(d[34]), "+f"(d[35]), "+f"(d[36]), "+f"(d[37]), "+f"(d[38]), "+f"(d[39]), "+f"(d[40]), "+f"(d[41]), "+f"(d[42]), "+f"(d[43]), "+f"(d[44]), "+f"(d[45]), "+f"(d[46]), "+f"(d[47]), "+f"(d[48]), "+f"(d[49]), "+f"(d[50]), "+f"(d[51]), "+f"(d[52]), "+f"(d[53]), "+f"(d[54]), "+f"(d[55]), "+f"(d[56]), "+f"(d[57]), "+f"(d[58]), "+f"(d[59]), "+f"(d[60]), "+f"(d[61]), "+f"(d[62]), "+f"(d[63]), "+f"(d[64]), "+f"(d[65]), "+f"(d[66]), "+f"(d[67]), "+f"(d[68]), "+f"(d[69]), "+f"(d[70]), "+f"(d[71]), "+f"(d[72]), "+f"(d[73]), "+f"(d[74]), "+f"(d[75]), "+f"(d[76]), "+f"(d[77]), "+f"(d[78]), "+f"(d[79]), "+f"(d[80]), "+f"(d[81]), "+f"(d[82]), "+f"(d[83]), "+f"(d[84]), "+f"(d[85]), "+f"(d[86]), "+f"(d[87]), "+f"(d[88]), "+f"(d[89]), "+f"(d[90]), "+f"(d[91]), "+f"(d[92]), "+f"(d[93]), "+f"(d[94]), "+f"(d[95]), "+f"(d[96]), "+f"(d[97]), "+f"(d[98]), "+f"(d[99]), "+f"(d[100]), "+f"(d[101]), "+f"(d[102]), "+f"(d[103]), "+f"(d[104]), "+f"(d[105]), "+f"(d[106]), "+f"(d[107]), "+f"(d[108]), "+f"(d[109]), "+f"(d[110]), "+f"(d[111]), "+f"(d[112]), "+f"(d[113]), "+f"(d[114]), "+f"(d[115]), "+f"(d[116]), "+f"(d[117]), "+f"(d[118]), "+f"(d[119]), "+f"(d[120]), "+f"(d[121]), "+f"(d[122]), "+f"(d[123]), "+f"(d[124]), "+f"(d[125]), "+f"(d[126]), "+f"(d[127])
                 : "l"(da), "l"(db));
}
__device__ __forceinline__ void wgmma_m64n256k16_first(float* d, uint64_t da, uint64_t db) {
    asm volatile("{\n.reg .pred p;\nsetp.ne.b32 p, 0, 0;\n"
                 "wgmma.mma_async.sync.aligned.m64n256k16.f32.bf16.bf16 {%0, %1, %2, %3, %4, %5, %6, %7, %8, %9, %10, %11, %12, %13, %14, %15, %16, %17, %18, %19, %20, %21, %22, %23, %24, %25, %26, %27, %28, %29, %30, %31, %32, %33, %34, %35, %36, %37, %38, %39, %40, %41, %42, %43, %44, %45, %46, %47, %48, %49, %50, %51, %52, %53, %54, %55, %56, %57, %58, %59, %60, %61, %62, %63, %64, %65, %66, %67, %68, %69, %70, %71, %72, %73, %74, %75, %76, %77, %78, %79, %80, %81, %82, %83, %84, %85, %86, %87, %88, %89, %90, %91, %92, %93, %94, %95, %96, %97, %98, %99, %100, %101, %102, %103, %104, %105, %106, %107, %108, %109, %110, %111, %112, %113, %114, %115, %116, %117, %118, %119, %120, %121, %122, %123, %124, %125, %126, %127}, %128, %129, p, 1, 1, 0, 1;\n}\n"
                 : "=f"(d[0]), "=f"(d[1]), "=f"(d[2]), "=f"(d[3]), "=f"(d[4]), "=f"(d[5]), "=f"(d[6]), "=f"(d[7]), "=f"(d[8]), "=f"(d[9]), "=f"(d[10]), "=f"(d[11]), "=f"(d[12]), "=f"(d[13]), "=f"(d[14]), "=f"(d[15]), "=f"(d[16]), "=f"(d[17]), "=f"(d[18]), "=f"(d[19]), "=f"(d[20]), "=f"(d[21]), "=f"(d[22]), "=f"(d[23]), "=f"(d[24]), "=f"(d[25]), "=f"(d[26]), "=f"(d[27]), "=f"(d[28]), "=f"(d[29]), "=f"(d[30]), "=f"(d[31]), "=f"(d[32]), "=f"(d[33]), "=f"(d[34]), "=f"(d[35]), "=f"(d[36]), "=f"(d[37]), "=f"(d[38]), "=f"(d[39]), "=f"(d[40]), "=f"(d[41]), "=f"(d[42]), "=f"(d[43]), "=f"(d[44]), "=f"(d[45]), "=f"(d[46]), "=f"(d[47]), "=f"(d[48]), "=f"(d[49]), "=f"(d[50]), "=f"(d[51]), "=f"(d[52]), "=f"(d[53]), "=f"(d[54]), "=f"(d[55]), "=f"(d[56]), "=f"(d[57]), "=f"(d[58]), "=f"(d[59]), "=f"(d[60]), "=f"(d[61]), "=f"(d[62]), "=f"(d[63]), "=f"(d[64]), "=f"(d[65]), "=f"(d[66]), "=f"(d[67]), "=f"(d[68]), "=f"(d[69]), "=f"(d[70]), "=f"(d[71]), "=f"(d[72]), "=f"(d[73]), "=f"(d[74]), "=f"(d[75]), "=f"(d[76]), "=f"(d[77]), "=f"(d[78]), "=f"(d[79]), "=f"(d[80]), "=f"(d[81]), "=f"(d[82]), "=f"(d[83]), "=f"(d[84]), "=f"(d[85]), "=f"(d[86]), "=f"(d[87]), "=f"(d[88]), "=f"(d[89]), "=f"(d[90]), "=f"(d[91]), "=f"(d[92]), "=f"(d[93]), "=f"(d[94]), "=f"(d[95]), "=f"(d[96]), "=f"(d[97]), "=f"(d[98]), "=f"(d[99]), "=f"(d[100]), "=f"(d[101]), "=f"(d[102]), "=f"(d[103]), "=f"(d[104]), "=f"(d[105]), "=f"(d[106]), "=f"(d[107]), "=f"(d[108]), "=f"(d[109]), "=f"(d[110]), "=f"(d[111]), "=f"(d[112]), "=f"(d[113]), "=f"(d[114]), "=f"(d[115]), "=f"(d[116]), "=f"(d[117]), "=f"(d[118]), "=f"(d[119]), "=f"(d[120]), "=f"(d[121]), "=f"(d[122]), "=f"(d[123]), "=f"(d[124]), "=f"(d[125]), "=f"(d[126]), "=f"(d[127])
                 : "l"(da), "l"(db));
}
__device__ __forceinline__ void wgmma_rs_m64n128k16(float* d, const uint32_t* a, uint64_t db) {
    asm volatile("{\n.reg .pred p;\nsetp.ne.b32 p, 1, 0;\n"
                 "wgmma.mma_async.sync.aligned.m64n128k16.f32.bf16.bf16 {%0, %1, %2, %3, %4, %5, %6, %7, %8, %9, %10, %11, %12, %13, %14, %15, %16, %17, %18, %19, %20, %21, %22, %23, %24, %25, %26, %27, %28, %29, %30, %31, %32, %33, %34, %35, %36, %37, %38, %39, %40, %41, %42, %43, %44, %45, %46, %47, %48, %49, %50, %51, %52, %53, %54, %55, %56, %57, %58, %59, %60, %61, %62, %63}, {%64, %65, %66, %67}, %68, p, 1, 1, 1;\n}\n"
                 : "+f"(d[0]), "+f"(d[1]), "+f"(d[2]), "+f"(d[3]), "+f"(d[4]), "+f"(d[5]), "+f"(d[6]), "+f"(d[7]), "+f"(d[8]), "+f"(d[9]), "+f"(d[10]), "+f"(d[11]), "+f"(d[12]), "+f"(d[13]), "+f"(d[14]), "+f"(d[15]), "+f"(d[16]), "+f"(d[17]), "+f"(d[18]), "+f"(d[19]), "+f"(d[20]), "+f"(d[21]), "+f"(d[22]), "+f"(d[23]), "+f"(d[24]), "+f"(d[25]), "+f"(d[26]), "+f"(d[27]), "+f"(d[28]), "+f"(d[29]), "+f"(d[30]), "+f"(d[31]), "+f"(d[32]), "+f"(d[33]), "+f"(d[34]), "+f"(d[35]), "+f"(d[36]), "+f"(d[37]), "+f"(d[38]), "+f"(d[39]), "+f"(d[40]), "+f"(d[41]), "+f"(d[42]), "+f"(d[43]), "+f"(d[44]), "+f"(d[45]), "+f"(d[46]), "+f"(d[47]), "+f"(d[48]), "+f"(d[49]), "+f"(d[50]), "+f"(d[51]), "+f"(d[52]), "+f"(d[53]), "+f"(d[54]), "+f"(d[55]), "+f"(d[56]), "+f"(d[57]), "+f"(d[58]), "+f"(d[59]), "+f"(d[60]), "+f"(d[61]), "+f"(d[62]), "+f"(d[63])
                 : "r"(a[0]), "r"(a[1]), "r"(a[2]), "r"(a[3]), "l"(db));
}
__device__ __forceinline__ void wgmma_rs_m64n128k16_first(float* d, const uint32_t* a, uint64_t db) {
    asm volatile("{\n.reg .pred p;\nsetp.ne.b32 p, 0, 0;\n"
                 "wgmma.mma_async.sync.aligned.m64n128k16.f32.bf16.bf16 {%0, %1, %2, %3, %4, %5, %6, %7, %8, %9, %10, %11, %12, %13, %14, %15, %16, %17, %18, %19, %20, %21, %22, %23, %24, %25, %26, %27, %28, %29, %30, %31, %32, %33, %34, %35, %36, %37, %38, %39, %40, %41, %42, %43, %44, %45, %46, %47, %48, %49, %50, %51, %52, %53, %54, %55, %56, %57, %58, %59, %60, %61, %62, %63}, {%64, %65, %66, %67}, %68, p, 1, 1, 1;\n}\n"
                 : "=f"(d[0]), "=f"(d[1]), "=f"(d[2]), "=f"(d[3]), "=f"(d[4]), "=f"(d[5]), "=f"(d[6]), "=f"(d[7]), "=f"(d[8]), "=f"(d[9]), "=f"(d[10]), "=f"(d[11]), "=f"(d[12]), "=f"(d[13]), "=f"(d[14]), "=f"(d[15]), "=f"(d[16]), "=f"(d[17]), "=f"(d[18]), "=f"(d[19]), "=f"(d[20]), "=f"(d[21]), "=f"(d[22]), "=f"(d[23]), "=f"(d[24]), "=f"(d[25]), "=f"(d[26]), "=f"(d[27]), "=f"(d[28]), "=f"(d[29]), "=f"(d[30]), "=f"(d[31]), "=f"(d[32]), "=f"(d[33]), "=f"(d[34]), "=f"(d[35]), "=f"(d[36]), "=f"(d[37]), "=f"(d[38]), "=f"(d[39]), "=f"(d[40]), "=f"(d[41]), "=f"(d[42]), "=f"(d[43]), "=f"(d[44]), "=f"(d[45]), "=f"(d[46]), "=f"(d[47]), "=f"(d[48]), "=f"(d[49]), "=f"(d[50]), "=f"(d[51]), "=f"(d[52]), "=f"(d[53]), "=f"(d[54]), "=f"(d[55]), "=f"(d[56]), "=f"(d[57]), "=f"(d[58]), "=f"(d[59]), "=f"(d[60]), "=f"(d[61]), "=f"(d[62]), "=f"(d[63])
                 : "r"(a[0]), "r"(a[1]), "r"(a[2]), "r"(a[3]), "l"(db));
}

struct BulkMaps { CUtensorMap h, h2, wq, wk, wv, wo, kv, lu; };
struct BulkArgs {
    const bf16 *x, *ssmk, *ssmD, *Bk, *Bv, *shiftk;
    bf16* out;
};
enum { T_KV = 0, T_QA, T_CONV, T_ATT, T_POST, T_LN0 };
constexpr int MAXG = 52, SENT = MAXG - 1;
struct Sched { uint32_t chk[MAXG * 4]; uint32_t info[MAXG]; int sbeg[8]; };

constexpr int BK_STAGES = 4, BK_STAGE_BYTES = 49152, TSLOTS = 4;
struct BulkSmemTail {
    unsigned long long full[BK_STAGES], empty[BK_STAGES], tfull[TSLOTS], tempty[TSLOTS], sfull[4], sempty[4];
    int task[TSLOTS];
    uint32_t tab[MAXG * 5];
};
constexpr int BULK_STG = BK_STAGES * BK_STAGE_BYTES;
constexpr int BULK_TAIL = BULK_STG + 32768;
constexpr int BULK_SMEM = BULK_TAIL + (int)sizeof(BulkSmemTail);
static_assert(BULK_SMEM <= 232448, "bulk smem");
#define PACE 0
#define REG_C 224
#define REG_P 56

#define BT(lead, type, l, c, k)
#define TT(k)
#define FT(k)
#define TTV(k, v)
__device__ __forceinline__ void tma_store_2d(const CUtensorMap* map, uint32_t src, int c0, int c1) {
    asm volatile("cp.async.bulk.tensor.2d.global.shared::cta.bulk_group [%0, {%2, %3}], [%1];" ::"l"(map), "r"(src), "r"(c0), "r"(c1) : "memory");
}
__device__ __forceinline__ void bulk_commit() { asm volatile("cp.async.bulk.commit_group;" ::: "memory"); }
template <int N> __device__ __forceinline__ void bulk_wait_read() { asm volatile("cp.async.bulk.wait_group.read %0;" ::"n"(N) : "memory"); }
template <int N> __device__ __forceinline__ void bulk_wait() { asm volatile("cp.async.bulk.wait_group %0;" ::"n"(N) : "memory"); }
__device__ __forceinline__ void mbar_arrive_cluster(uint32_t bar) {
    asm volatile("mbarrier.arrive.shared::cluster.b64 _, [%0];" ::"r"(bar) : "memory");
}
__device__ __forceinline__ void stsm_x4(uint32_t addr, uint32_t r0, uint32_t r1, uint32_t r2, uint32_t r3) {
    asm volatile("stmatrix.sync.aligned.m8n8.x4.shared.b16 [%0], {%1,%2,%3,%4};" ::"r"(addr), "r"(r0), "r"(r1), "r"(r2), "r"(r3) : "memory");
}
__device__ __forceinline__ void mma1688(float* c, uint32_t a0, uint32_t a1, uint32_t b0) {
    asm("mma.sync.aligned.m16n8k8.row.col.f32.bf16.bf16.f32 {%0,%1,%2,%3}, {%4,%5}, {%6}, {%0,%1,%2,%3};"
        : "+f"(c[0]), "+f"(c[1]), "+f"(c[2]), "+f"(c[3]) : "r"(a0), "r"(a1), "r"(b0));
}
__device__ __forceinline__ int ld_relaxed(const int* p) {
    int v;
    asm volatile("ld.relaxed.gpu.global.u32 %0, [%1];" : "=r"(v) : "l"(p) : "memory");
    return v;
}
__device__ __forceinline__ void flag_wait(const int* f, int tgt, int ns) {
    int guard = 0;
    while (ld_relaxed(f) < tgt && ++guard < 4000000) __nanosleep(ns);
}
__device__ __forceinline__ void fence_async() { asm volatile("fence.proxy.async.global;" ::: "memory"); }
__device__ __forceinline__ uint32_t bmul2(uint32_t a, uint32_t b) { uint32_t r; asm("mul.rn.bf16x2 %0, %1, %2;" : "=r"(r) : "r"(a), "r"(b)); return r; }
__device__ __forceinline__ uint32_t bsum2(uint32_t a, uint32_t b) { uint32_t r; asm("add.rn.bf16x2 %0, %1, %2;" : "=r"(r) : "r"(a), "r"(b)); return r; }
__device__ __forceinline__ uint32_t bmax2(uint32_t a, uint32_t b) { uint32_t r; asm("max.bf16x2 %0, %1, %2;" : "=r"(r) : "r"(a), "r"(b)); return r; }
__device__ __forceinline__ uint32_t rscore(float a, float b) {
    const uint32_t u = pack2(a, b);
    return pack2(blo(u) * 0.08838834764831845f, bhi(u) * 0.08838834764831845f);
}
template <int STRIDE> __device__ __forceinline__ void ld5(uint32_t* w, const bf16* p) {
#pragma unroll
    for (int r = 0; r < 5; r++) { const uint2 v = __ldcg(reinterpret_cast<const uint2*>(p + r * STRIDE)); w[2 * r] = v.x; w[2 * r + 1] = v.y; }
}
__device__ __forceinline__ void st5(bf16* p, const uint32_t* w) {
#pragma unroll
    for (int r = 0; r < 5; r++) *reinterpret_cast<uint2*>(p + r * 128) = make_uint2(w[2 * r], w[2 * r + 1]);
}
__device__ __forceinline__ void ln_row(const uint32_t* x, uint32_t* y) {
    float s = 0.f;
#pragma unroll
    for (int i = 0; i < 10; i++) s += blo(x[i]) + bhi(x[i]);
#pragma unroll
    for (int o = 16; o > 0; o >>= 1) s += __shfl_xor_sync(0xffffffffu, s, o);
    const float mean = s * (1.0f / DM);
    float q = 0.f;
#pragma unroll
    for (int i = 0; i < 10; i++) { const float d0 = blo(x[i]) - mean, d1 = bhi(x[i]) - mean; q = fmaf(d0, d0, q); q = fmaf(d1, d1, q); }
#pragma unroll
    for (int o = 16; o > 0; o >>= 1) q += __shfl_xor_sync(0xffffffffu, q, o);
    const uint32_t nm = pack2(-mean, -mean);
    float sq;
    asm("sqrt.approx.ftz.f32 %0, %1;" : "=f"(sq) : "f"(rbf(rbf(q * (1.0f / DM)) + 1e-5f)));
    const float rd = rcpf(rbf(sq));
#pragma unroll
    for (int i = 0; i < 10; i++) { const uint32_t d = bsum2(x[i], nm); y[i] = pack2(blo(d) * rd, bhi(d) * rd); }
}
__device__ __forceinline__ void red_add8(uint4* p, uint32_t a, uint32_t b, uint32_t c, uint32_t d) {
    asm volatile("red.relaxed.gpu.global.add.noftz.v4.bf16x2 [%0], {%1,%2,%3,%4};" ::"l"(p), "r"(a), "r"(b), "r"(c), "r"(d) : "memory");
}
__device__ __forceinline__ void part_sum(const uint4& v, const uint4& w, int lane, uint32_t& x0, uint32_t& x1) {
    float t[8];
    t[0] = blo(v.x) + blo(w.x); t[1] = bhi(v.x) + bhi(w.x); t[2] = blo(v.y) + blo(w.y); t[3] = bhi(v.y) + bhi(w.y);
    t[4] = blo(v.z) + blo(w.z); t[5] = bhi(v.z) + bhi(w.z); t[6] = blo(v.w) + blo(w.w); t[7] = bhi(v.w) + bhi(w.w);
#pragma unroll
    for (int i = 0; i < 4; i++) t[i] = (lane < 16 ? t[i] : t[4 + i]) + __shfl_xor_sync(0xffffffffu, lane < 16 ? t[4 + i] : t[i], 16);
    const uint32_t r0 = pack2(t[0], t[1]), r1 = pack2(t[2], t[3]);
    const uint32_t ex = __shfl_xor_sync(0xffffffffu, (lane & 1) ? r0 : r1, 1);
    x0 = (lane & 1) ? ex : r0; x1 = (lane & 1) ? r1 : ex;
}
__device__ __forceinline__ void post_row(int l, int row, int lane, const bf16* xin, bf16* xout) {
    uint32_t x[10], y[10], n[10];
    const int cl = (lane & 12) * 8 + (lane >> 4) * 16 + (lane & 1) * 8 + (lane & 2) * 2;
    uint4* pp = reinterpret_cast<uint4*>(g_part + (size_t)(l * PROWS + (row & (PROWS - 1))) * (PG * DM)) + (lane & 15) + (lane >> 4) * 80;
    int* f = FLG(F_OP + l * NCHK + (row >> 7));
    flag_wait(FLG(F_CONV + (row >> 10)), CONV_TGT, 200);
    ld5<128>(x, xin + (size_t)row * DM + cl);
    flag_wait(f + 4, OP_TGT, POST_NS);
    {
        uint4 v[10];
#pragma unroll
        for (int i = 0; i < 10; i++) v[i] = __ldcg(pp + (i >> 1) * 16 + (i & 1) * 160);
#pragma unroll
        for (int r = 0; r < 5; r++) {
            uint32_t s0, s1;
            part_sum(v[2 * r], v[2 * r + 1], lane, s0, s1);
            if (r == 1) ld5<16 * S_LEN * 8>(y, g_Y + ((size_t)(cl >> 3) * S_LEN + (row ^ ((row >> 6) & 7))) * 8 + (cl & 4));
            x[2 * r] = bsum2(x[2 * r], s0); x[2 * r + 1] = bsum2(x[2 * r + 1], s1);
        }
    }
    ln_row(x, n);
#pragma unroll
    for (int i = 0; i < 10; i++) x[i] = bsum2(x[i], bmul2(n[i], y[i]));
    if (l == 0) {
        ln_row(x, n);
        st5(g_h[1] + (size_t)row * DM + cl, n);
        __syncwarp();
        if (lane == 0) red_release(FLG(F_H + NCHK + (row >> 7)), 1);
    }
#pragma unroll
    for (int i = 0; i < 10; i++) pp[(i >> 1) * 16 + (i & 1) * 160] = make_uint4(0, 0, 0, 0);
    st5(xout + (size_t)row * DM + cl, x);
    __syncwarp();
    if (l && lane == 0) red_release(f + 5, 1);
}
__device__ __forceinline__ void u_unit(const bf16* Bk, const bf16* Bv, const bf16* shiftk, int unit, int lane) {
    const int t0 = (unit / 10) * 16, cp = (unit % 10) * 32 + lane;
    uint32_t kk[19], vv[16];
    const uint32_t* pk = reinterpret_cast<const uint32_t*>(Bk + (size_t)t0 * DM) + cp;
    const uint32_t* pv = reinterpret_cast<const uint32_t*>(Bv + (size_t)t0 * DM) + cp;
#pragma unroll
    for (int i = 0; i < 19; i++) kk[i] = (i >= 3 || t0 > 0) ? __ldg(pk + (i - 3) * (DM / 2)) : 0u;
#pragma unroll
    for (int i = 0; i < 16; i++) vv[i] = __ldg(pv + i * (DM / 2));
    const uint4 sh0 = __ldg(reinterpret_cast<const uint4*>(shiftk + cp * 8));
    const uint32_t s0 = __byte_perm(sh0.x, sh0.z, 0x5410), s1 = __byte_perm(sh0.x, sh0.z, 0x7632), s2 = __byte_perm(sh0.y, sh0.w, 0x5410), s3 = __byte_perm(sh0.y, sh0.w, 0x7632);
#pragma unroll
    for (int t = 0; t < 16; t++)
        vv[t] = bmul2(bsum2(bsum2(bsum2(bmul2(kk[t], s3), bmul2(kk[t + 1], s2)), bmul2(kk[t + 2], s1)), bmul2(kk[t + 3], s0)), vv[t]);
    uint4* d = reinterpret_cast<uint4*>(g_U + (size_t)(cp * 2) * S_LEN + (t0 ^ 48));
#pragma unroll
    for (int c = 0; c < 2; c++) {
        const uint32_t sel = c ? 0x7632 : 0x5410;
#pragma unroll
        for (int hh = 0; hh < 2; hh++)
            d[c * (S_LEN / 8) + hh] = make_uint4(__byte_perm(vv[15 - hh * 8], vv[14 - hh * 8], sel), __byte_perm(vv[13 - hh * 8], vv[12 - hh * 8], sel),
                                                 __byte_perm(vv[11 - hh * 8], vv[10 - hh * 8], sel), __byte_perm(vv[9 - hh * 8], vv[8 - hh * 8], sel));
    }
}
constexpr int CV_EP = 4224;
template <class F> __device__ __forceinline__ void conv_unit(uint32_t ub, uint32_t e0, uint32_t e1, uint32_t zrow, uint32_t yt, float Dv, int m, int lane, F&& nearly_done) {
    const int g = lane >> 2, tq = lane & 3;
    asm volatile("st.shared.u32 [%0], %1;" ::"r"(e0 + lane * 4), "r"(0) : "memory");
    asm volatile("st.shared.u32 [%0], %1;" ::"r"(zrow + lane * 4), "r"(0) : "memory");
    __syncwarp();
    for (int i = lane; i < CV_EP / 16; i += 32) {
        const uint4 v = lds128(e0 + i * 16);
        const uint32_t nx = i + 1 < CV_EP / 16 ? lds32(e0 + i * 16 + 16) : 0u;
        sts128(e1 + i * 16, __byte_perm(v.x, v.y, 0x5432), __byte_perm(v.y, v.z, 0x5432), __byte_perm(v.z, v.w, 0x5432), __byte_perm(v.w, nx, 0x5432));
    }
    __syncwarp();
    float acc[8][4];
#pragma unroll
    for (int n = 0; n < 8; n++)
#pragma unroll
        for (int i = 0; i < 4; i++) acc[n][i] = 0.f;
    uint32_t wb = (g & 1) ? e0 + (1 + g + 2 * tq) * 2 : e1 + (g + 2 * tq) * 2;
    uint32_t W[16], a[4][4], an[4][4];
    int row = m * 16 + (lane & 15);
    auto lda = [&](uint32_t (*d)[4]) {
        const uint32_t x = row < 0 ? zrow : ub + row * 128 + (((lane >> 4) ^ (row & 7)) << 4);
#pragma unroll
        for (int ks = 0; ks < 4; ks++) ldsm_x4(d[ks][0], d[ks][1], d[ks][2], d[ks][3], x ^ (ks << 5));
        row--;
    };
#pragma unroll
    for (int i = 0; i < 16; i++) W[i] = lds32(wb + i * 16);
    lda(a);
    const int nD = m == 0 ? 16 : 32;
#pragma unroll 2
    for (int D = 0; D < nD; D++) {
        uint32_t Wn[8];
        wb += 128;
        if (D == nD - 6) nearly_done();
        lda(an);
#pragma unroll
        for (int i = 0; i < 8; i++) Wn[i] = lds32(wb + 128 + i * 16);
#pragma unroll
        for (int ks = 0; ks < 4; ks++)
#pragma unroll
            for (int n = 0; n < 8; n++) mma16816(acc[n], a[ks][0], a[ks][1], a[ks][2], a[ks][3], W[2 * ks + n], W[2 * ks + n + 1]);
#pragma unroll
        for (int i = 0; i < 8; i++) { W[i] = W[i + 8]; W[i + 8] = Wn[i]; }
#pragma unroll
        for (int ks = 0; ks < 4; ks++)
#pragma unroll
            for (int i = 0; i < 4; i++) a[ks][i] = an[ks][i];
    }
#pragma unroll
    for (int n = 0; n < 8; n++)
#pragma unroll
        for (int r = 0; r < 2; r++) {
            const int a_ = g + r * 8, b_ = n * 8 + tq * 2;
            const int ar = m * 16 + a_, p = 62 - b_;
            const uint32_t kv = lds32(ub + ar * 128 + (((p >> 3) ^ (ar & 7)) << 4) + (p & 7) * 2);
            const float y0 = rbf(acc[n][2 * r]) + rbf(bhi(kv) * Dv), y1 = rbf(acc[n][2 * r + 1]) + rbf(blo(kv) * Dv);
            const uint32_t pk = pack2(y0, y1);
            asm volatile("st.shared.u16 [%0], %1;" ::"r"(yt + ((a_ * 64 + b_) ^ g) * 16), "h"((unsigned short)(pk & 0xffff)) : "memory");
            asm volatile("st.shared.u16 [%0], %1;" ::"r"(yt + ((a_ * 64 + b_ + 1) ^ g) * 16), "h"((unsigned short)(pk >> 16)) : "memory");
        }
}

__global__ void __launch_bounds__(384, 1) bulk_kernel(const __grid_constant__ BulkMaps M, const __grid_constant__ BulkArgs A,
                                                      const __grid_constant__ Sched SC) {
    extern __shared__ __align__(1024) unsigned char smem_raw[];
    const uint32_t sb0 = smem_u32(smem_raw);
    const uint32_t full0 = sb0 + BULK_TAIL, empty0 = full0 + 32, tfull0 = full0 + 64, tempty0 = full0 + 96, sfull = full0 + 128, sempty = full0 + 160,
                   task0 = full0 + 192, tab0 = full0 + 208;
    const int tid = threadIdx.x, wid = __shfl_sync(0xffffffffu, tid >> 5, 0), lane = tid & 31;
    const int rank = blockIdx.x & 1;
    if (tid == 0) {
        for (int i = 0; i < BK_STAGES; i++) { mbar_init(full0 + 8 * i, 1); mbar_init(empty0 + 8 * i, 4); }
        for (int i = 0; i < TSLOTS; i++) { mbar_init(tfull0 + 8 * i, 1); mbar_init(tempty0 + 8 * i, 19); }
        for (int i = 0; i < 4; i++) { mbar_init(sfull + 8 * i, 8); mbar_init(sempty + 8 * i, 1); }
        asm volatile("fence.mbarrier_init.release.cluster;" ::: "memory");
        if (rank == 1) for (int i = 0; i < TSLOTS; i++) mbar_expect_tx(tfull0 + 8 * i, 4);
        BT(true, T_LN0, 0, 0, 0);
    }
    if (tid < MAXG * 5) asm volatile("st.shared.u32 [%0], %1;" ::"r"(tab0 + tid * 4), "r"(SC.chk[tid]) : "memory");
    cluster_sync_all();
    uint32_t tc = 0, it = 0;
    if (wid < 4) {
        asm volatile("setmaxnreg.dec.sync.aligned.u32 %0;" ::"n"(REG_P));
        if (wid == 0) {
            int head = SC.sbeg[lane >> 3];
            const int hend = SC.sbeg[(lane >> 3) + 1];
            uint32_t chk = 0; int pv = (blockIdx.x >> 1) & 31, grp = (SC.sbeg[3] + (blockIdx.x >> 6)) << 2 | 3, ncode = 0, code = 3 << 6 | 2, guard = 0;
            auto acquire = [&](uint32_t bytes) -> uint32_t {
                const uint32_t s = it & 3;
                mwait(empty0 + 8 * s, ((it >> 2) & 1) ^ 1);
                it++;
                expect_tx1(full0 + 8 * s, bytes);
                return s;
            };
            auto uwait = [&](const int* f, int tgt) {
                int g2 = 0;
                while ((int)UNI(ld_relaxed(f)) < tgt && ++g2 < 4000000) __nanosleep(32);
                fence_async();
            };
#pragma unroll 1
            while (true) {
                const int type = (code >> 6) & 3;
                const int iend = type == T_KV ? 10 : (type == T_QA ? 24 : 31);
                const int jj = code & 63, g0 = (jj & 15) * 4, lc = (code >> 9) & 31;
                const bool lm = (code >> 8) & 1;
                const CUtensorMap* mb = type == T_QA ? &M.wq : (jj < 16 ? &M.wk : &M.wv);
                bool have = false, ok = (code >> 14) & 1;
                int imem = 16;
#pragma unroll 1
                for (int i = type < T_CONV ? 0 : (type == T_CONV ? 24 : 28 + jj); i < iend; i++) {
                    const int sd = (type < T_CONV ? SPLAN : 0x1230) >> 4 * min(iend - i, 7) & 15;
                    if (rank == 0 && sd) {
                        if (sd == 1) {
                            if (type == T_CONV) mwait(empty0 + 8 * (it & 3), ((it >> 2) & 1) ^ 1);
                            const int gi = head + ((lane >> 2) & 1);
                            chk = lds32(tab0 + ((gi < hend ? gi : SENT) * 4 + (lane & 3)) * 4);
                            pv = ld_relaxed(g_flags + (chk & 0xffff));
                        } else if (sd == 2) {
                            const int tgt = (int)(chk >> 16);
                            const uint32_t b = (__ballot_sync(0xffffffffu, (lane & 3) == 0 ? pv < tgt : pv >= tgt) >> (lane & 24)) & 0xff;
                            const uint32_t cand = (b & 1) ? b & 15 : b >> 4;
                            head += (b & 1) ? 0 : ((b & 16) ? 1 : 2);
                            if (head > hend || guard > 4000000) head = hend;
                            const uint32_t req = lane >= 24 ? 1 : 15;
                            grp = (int)__reduce_min_sync(0xffffffffu, (cand & req) == req ? ((uint32_t)head << 2 | (cand ^ req) >> 2 | ((cand ^ req) & 2 ? 0 : 256)) : (head < hend ? 1000u : 1004u));
                            if (grp < 1000) grp &= 255;
                            if (grp < 1000) asm volatile("{\n.reg .pred p;\nsetp.eq.u32 p, %2, 0;\n@p atom.relaxed.gpu.global.inc.u32 %0, [%1], 0x7fffffff;\n}" : "+r"(pv) : "l"(FLG(F_CNT + (grp >> 2))), "r"(lane) : "memory");
                        } else {
                            if (grp < 1000) {
                                const int tk = (int)UNI(pv);
                                have = tk < (int)(UNI(lds32(tab0 + (grp >> 2) * 16)) >> 16);
                                ncode = (int)UNI(lds32(tab0 + MAXG * 16 + (grp & ~3))) | (grp & 3) << 19 | tk;
                            } else if (grp == 1004) { have = true; ncode = -1; }
                            if (have) {
                                const uint32_t o = (tc & 3) * 4;
                                mwait(tempty0 + 2 * o, ((tc >> 2) & 1) ^ 1);
                                asm volatile(ELECT "st.shared.u32 [%0], %1;\n@p mbarrier.arrive.shared::cta.b64 _, [%2];\n"
                                             "@p st.async.weak.shared::cluster.mbarrier::complete_tx::bytes.b32 [%3], %1, [%4];\n}"
                                             ::"r"(task0 + o), "r"(ncode), "r"(tfull0 + 2 * o), "r"(mapa(task0 + o, 1)), "r"(mapa(tfull0 + 2 * o, 1)) : "memory");
                            }
                        }
                    }
                    if (i >= 28) continue;
                    if (i == 8 && type == T_QA) pv = ld_relaxed(FLG((lane & 1 ? F_MEM : F_KV) + lc));
                    if (i == 10) {
                        const uint32_t b = __ballot_sync(0xffffffffu, pv >= (lane & 1 ? MEM_TGT : KV_TGT));
                        if (b & 2) imem = 13;
                        if (!(b & 1)) uwait(FLG(F_KV + lc), KV_TGT);
                        fence_async();
                    }
                    const uint32_t s = acquire(i < 12 ? 49152 : (i == 24 || i == 27 ? 0 : 32768));
                    const uint32_t sa = sb0 + s * BK_STAGE_BYTES, fb = full0 + 8 * s;
                    if (i == 0) TT(3);
                    if (i < 10) {
                        if (lm) {
                            tma_load_3d(sa + 16384, mb, fb, i * 64, g0);
                            tma_load_3d(sa + 32768, mb, fb, i * 64, g0 + 2);
                        } else tma_load_3d_mc(sa + 16384 + rank * 16384, mb, fb, i * 64, g0 + rank * 2);
                        int d = 0;
                        if (!ok) {
                            d = 1;
                            if (i == 3) {
                                uwait(FLG(F_H + lc), H_TGT);
                                ok = true;
                                d = -3;
                                TT(4);
                            }
                        }
#pragma unroll 1
                        for (; d <= 0; d++) {
                            const uint32_t s2 = (s + d) & 3;
                            if (lm) tma_load_2d_mc(sb0 + s2 * BK_STAGE_BYTES + rank * 8192, &M.h, full0 + 8 * s2, (i + d) * 64, lc * 128 + rank * 64);
                            else tma_load_2d(sb0 + s2 * BK_STAGE_BYTES, &M.h2, full0 + 8 * s2, (i + d) * 64, lc * 128);
                        }
                    } else if (i < 13) {
#pragma unroll 1
                        for (int k = 0, bx = (i - 10) * 3; k < 3 && bx < 8; k++, bx++)
                            tma_load_2d(sa + k * 16384, &M.kv, fb, (g0 + (bx & 3)) * 64, (bx >> 2) * S_LEN + (lc & 15) * 128);
                    } else if (i < 24) {
                        const int cn = ((i - 14) >> 1) * 128, ck = g0 * 64 + (i & 1) * 128;
                        if (i > 13) {
                            if (lm) { tma_load_2d(sa, &M.wo, fb, cn, ck); tma_load_2d(sa + 16384, &M.wo, fb, cn + 64, ck); }
                            else tma_load_2d_mc(sa + rank * 16384, &M.wo, fb, cn + rank * 64, ck);
                        }
                        if (i == imem) {
                            TT(5);
                            if (i == 16) uwait(FLG(F_MEM + lc), MEM_TGT);
                            const uint32_t s2 = (s + (i >> 4)) & 3;
#pragma unroll 1
                            for (int k = 0; k < 4; k++)
                                bulk_load(sb0 + s2 * BK_STAGE_BYTES + k * 8192, g_kvf + (size_t)((lc * CSEG + k) * NH + jj * 2) * 256, 8192, full0 + 8 * s2);
                            TT(6);
                        }
                    } else if (i == 25) {
                        tma_load_2d(sa, &M.lu, fb, 0, (2 * jj + rank) * 256);
                    } else if (i == 26) {
#pragma unroll 1
                        for (int k = 0; k < 8; k++)
                            bulk_load(sa + k * CV_EP + 128, A.ssmk + (size_t)((2 * jj + rank) * 8 + k) * S_LEN, 4096, fb);
                    }
                }
                if (type != 3) TT(7);
                if (rank == 0) {
                    if (!have) {
                        if (type == 3) { guard++; __nanosleep(64); }
                        code = 3 << 6;
                        continue;
                    }
                } else {
                    const uint32_t o = (tc & 3) * 4;
                    mwait(tfull0 + 2 * o, (tc >> 2) & 1);
                    ncode = (int)UNI(lds32(task0 + o));
                    asm volatile(ELECT "mbarrier.arrive.expect_tx.shared::cta.b64 _, [%0], 4;\n@p mbarrier.arrive.shared::cluster.b64 _, [%1];\n}" ::"r"(tfull0 + 2 * o), "r"(mapa(tempty0 + 2 * o, 0)) : "memory");
                    __syncwarp();
                }
                tc++;
                if (ncode < 0) break;
                TT(0); TTV(15, ncode);
                code = ((ncode & 256) ? (2 * ncode + rank) & 63 : ncode & 63) | (ncode & 0x1c0) | ((ncode >> (rank ? 14 : 9)) & 31) << 9 | ((ncode >> (19 + rank)) & 1) << 14;
                fence_async();
            }
        } else if (wid == 1) {
            if (lane < 8) asm volatile("prefetch.tensormap [%0];" ::"l"(&M.h + lane) : "memory");
            __syncwarp();
            if (lane == 0) {
                uint32_t rc = 0;
                while (true) {
                    mwait(tfull0 + 8 * (tc & 3), (tc >> 2) & 1);
                    const int code = (int)lds32(task0 + 4 * (tc & 3));
                    mbar_arrive_cluster(mapa(tempty0 + 8 * (tc & 3), 0));
                    tc++;
                    if (code < 0) break;
                    const int type = (code >> 6) & 3;
                    const int lc = (code >> (rank ? 14 : 9)) & 31;
                    mwait(sfull + 8 * (rc & 3), (rc >> 2) & 1);
                    if (type == T_CONV) {
                        asm volatile("cp.async.bulk.global.shared::cta.bulk_group [%0], [%1], %2;" ::"l"(g_Y + (size_t)((2 * (code & 63) + rank) * S_LEN + lc * 1024) * 8), "r"(sb0 + BULK_STG), "r"(16384) : "memory");
                        bulk_commit();
                        bulk_wait<0>();
                    }
                    mbar_arrive(sempty + 8 * (rc & 3));
                    rc++;
                    FT(0);
                    red_release(type == T_QA ? FLG(F_OP + lc) + 4 : FLG((type == T_KV ? F_KV : F_CONV) + lc), 1);
                    FT(1);
                    BT(true, type, lc >> 4, lc & 15, 2);
                }
            }
        } else {
            const int nw = 2 * gridDim.x, idx = (wid - 2) * gridDim.x + blockIdx.x;
#pragma unroll 1
            for (int hh = 0; hh < 2; hh++) {
#pragma unroll 1
                for (int u = hh * 640 + idx; u < hh * 640 + 640; u += nw) u_unit(A.Bk, A.Bv, A.shiftk, u, lane);
                __syncwarp();
                if (lane == 0) red_release(FLG(F_U + hh), 1);
                BT(lane == 0, T_LN0, hh, 0, 2);
            }
#pragma unroll 1
            for (int q = 0; q < 2 * (NCHK + PDIST); q++) {
                const int l = q & 1, c = (q >> 1) - l * PDIST;
                if (c < 0 || c >= NCHK) continue;
#pragma unroll 1
                for (int rr = idx; rr < 128; rr += nw) post_row(l, c * 128 + rr, lane, l ? g_x : A.x, l ? A.out : g_x);
                BT(lane == 0, T_POST, l, c, 2);
            }
        }
    } else {
        asm volatile("setmaxnreg.inc.sync.aligned.u32 %0;" ::"n"(REG_C));
        const int cw = (wid >> 2) - 1, warp = wid & 3;
        const uint32_t wst = sb0 + BULK_STG + (cw * 4 + warp) * 4096;
        uint32_t rc = 0;
        int npend = 0;
        bool urgent = false;
        uint32_t oofs = 0;
        uint32_t qf[16][4];
        auto release = [&](int s) { if ((tid & 127) == 0) { mbar_arrive(empty0 + 8 * s); mbar_arrive_cluster(mapa(empty0 + 8 * s, rank ^ 1)); } };
        auto next = [&]() -> int { const int s = it & 3; mwait(full0 + 8 * s, (it >> 2) & 1); it++; return s; };
        auto wgbar = [&]() { if (cw == 0) named_bar(2, 128); else named_bar(3, 128); };
        auto handoff = [&]() {
            mwait(sempty + 8 * (rc & 3), ((rc >> 2) & 1) ^ 1);
            asm volatile(ELECT "mbarrier.arrive.shared::cta.b64 _, [%0];\n}" ::"r"(sfull + 8 * (rc & 3)) : "memory");
            rc++;
        };
        auto stg_free = [&]() { mwait(sempty + 8 * ((rc - 1) & 3), ((rc - 1) >> 2) & 1); };
        auto round_q = [&]() {
            if (npend > 4) {
                uint4* d = reinterpret_cast<uint4*>(g_part) + oofs;
                if (npend == 6) {
#pragma unroll
                    for (int i = 0; i < 4; i++) red_add8(d + (i >> 1) * 4 + (i & 1) * (8 * PG * DM / 8), qf[i][0], qf[i][1], qf[i][2], qf[i][3]);
                    npend = 5;
                } else {
#pragma unroll
                    for (int i = 4; i < 8; i++) red_add8(d + (i >> 1) * 4 + (i & 1) * (8 * PG * DM / 8), qf[i][0], qf[i][1], qf[i][2], qf[i][3]);
                    npend = 0;
                    handoff();
                }
                return;
            }
            const uint32_t sst = wst + (lane & 15) * 128 + (((lane >> 4) ^ (lane & 7)) << 4) + (npend & 1) * 2048;
#pragma unroll
            for (int q = 0; q < 4; q++)
                if (npend == 4 - q) {
#pragma unroll
                    for (int i = 0; i < 4; i++) stsm_x4(sst ^ (i << 5), qf[q * 4 + i][0], qf[q * 4 + i][1], qf[q * 4 + i][2], qf[q * 4 + i][3]);
                }
            __syncwarp();
            uint4* d = reinterpret_cast<uint4*>(&g_kv[0][0]) + oofs;
            const uint32_t src = wst + (lane >> 3) * 128 + (((lane & 7) ^ (lane >> 3)) << 4) + (npend & 1) * 2048;
#pragma unroll
            for (int i = 0; i < 4; i++) d[i * (4 * HD / 8)] = lds128((src + i * 512) ^ ((i & 1) << 6));
            oofs += 8;
            if (--npend == 0) handoff();
        };
        auto round_a = [&](const float* a, int hh) {
            uint4* d = reinterpret_cast<uint4*>(g_part) + oofs;
#pragma unroll
            for (int i = hh * 4; i < hh * 4 + 4; i++) {
                const float* b = a + (i >> 1) * 16 + (i & 1) * 2;
                red_add8(d + (i >> 1) * 4 + (i & 1) * (8 * PG * DM / 8), pack2(b[0], b[1]), pack2(b[4], b[5]), pack2(b[8], b[9]), pack2(b[12], b[13]));
            }
            if (hh) oofs += 16;
        };
        while (true) {
            tc++; TT(0); tc--;
            int code;
            while (true) {
                if (npend == 0) mwait(tfull0 + 8 * (tc & 3), (tc >> 2) & 1);
                if (npend == 0 || UNI(mtest(tfull0 + 8 * (tc & 3), (tc >> 2) & 1))) {
                    code = (int)UNI(lds32(task0 + 4 * (tc & 3)));
                    if (npend == 0 || ((code & 0x80) == 0 && !urgent && UNI(mtest(full0 + 8 * (it & 3), (it >> 2) & 1)))) break;
                }
                round_q();
            }
            if (lane == 0) mbar_arrive_cluster(mapa(tempty0 + 8 * (tc & 3), 0));
            tc++;
            TT(2);
            if (code < 0) break;
            const int type = (code >> 6) & 3;
            TTV(15, code);
#define BTC(type, k)
            if (type == T_CONV) {
                const int m = (code >> 9) & 1;
                BT((tid & 127) == 0, T_CONV, 0, m, 0);
                const int u = 2 * (code & 63) + rank, ch = cw * 4 + warp;
                int lane = tid & 31;
                asm volatile("" : "+r"(lane));
                const float Dv = bf2f(A.ssmD[u * 8 + ch]);
                const int sd = next(), s0 = next(), s1 = next(), s2 = next();
                TT(3);
                const uint32_t e1 = sb0 + s2 * BK_STAGE_BYTES;
                conv_unit(sb0 + s0 * BK_STAGE_BYTES + ch * 4096, sb0 + s1 * BK_STAGE_BYTES + ch * CV_EP, e1 + 64 + ch * CV_EP, e1 + 40960 + ch * 128, sb0 + BULK_STG + ch * 2, Dv, m, lane,
                          [&]() { release(sd); stg_free(); });
                asm volatile("fence.proxy.async.shared::cta;" ::: "memory");
                __syncwarp();
                handoff();
                TT(5);
                wgbar();
                release(s0); release(s1); release(s2);
                __syncwarp();
#pragma unroll
                for (int i = 0; i < 64; i++) qf[i >> 2][i & 3] = 0;
                continue;
            }
            float acc[128];
            {
                int s = next();
                TT(3); BTC(type, 0); BTC(type, 1);
                uint32_t sa = sb0 + s * BK_STAGE_BYTES + cw * 8192, sb = sb0 + s * BK_STAGE_BYTES + 16384;
                wg_fence();
                wgmma_m64n256k16_first(acc, make_desc(sa, 16, 1024), make_desc(sb, 8192, 1024));
#pragma unroll 1
                for (int kb = 0;;) {
#pragma unroll
                    for (int k = 1; k < 4; k++) wgmma_m64n256k16(acc, make_desc(sa + k * 32, 16, 1024), make_desc(sb + k * 2048, 8192, 1024));
                    wg_commit();
                    if (npend) round_q();
                    if (kb) { wg_wait<1>(); release((s - 1) & 3); }
                    if (++kb == 10) break;
                    s = next();
                    sa = sb0 + s * BK_STAGE_BYTES + cw * 8192; sb = sb0 + s * BK_STAGE_BYTES + 16384;
                    wg_fence();
                    wgmma_m64n256k16(acc, make_desc(sa, 16, 1024), make_desc(sb, 8192, 1024));
                }
            }
            wg_wait<0>();
            TT(4);
            release((it - 1) & 3);
            stg_free();
#pragma unroll
            for (int i = 0; i < 16; i++)
#pragma unroll
                for (int e = 0; e < 4; e++) qf[i][e] = pack2(acc[i * 8 + e * 2], acc[i * 8 + e * 2 + 1]);
            {
                const int cd = (int)lds32(task0 + 4 * ((tc - 1) & 3)), lc = (cd >> (rank ? 14 : 9)) & 31, jj = (cd & 256) ? (2 * cd + rank) & 63 : cd & 63;
                const int r0 = cw * 64 + warp * 16;
                if (type == T_KV) {
                    oofs = ((jj >> 4) * S_LEN + (lc & 15) * 128 + r0 + (lane >> 3)) * (HD / 8) + (jj & 15) * 32 + (lane & 7);
                    npend = 4;
                    urgent = URGENT && (lc < 2 || lc >= 16);
                    continue;
                }
                oofs = (((lc >> 4) * PRING + (lc & (PRING - 1))) * 128 + r0 + (lane >> 2)) * (PG * DM / 8) + (jj & (PG - 1)) * (DM / 8) + (lane & 3);
            }
            const float cs = 1.4426950408889634f;
            int lane = tid & 31;
            asm volatile("" : "+r"(lane));
            const int g = lane >> 2, tq = lane & 3;
            const int sg = cw * 2 + (warp >> 1), hs = warp & 1;
            float mt[2][2], sum[2][2];
            {
                const int x0 = next(), x1 = next();
                TT(5);
                float s[2][4][4];
#pragma unroll
                for (int hd = 0; hd < 2; hd++)
#pragma unroll
                    for (int n = 0; n < 4; n++)
#pragma unroll
                        for (int e = 0; e < 4; e++) s[hd][n][e] = 0.f;
                const uint32_t krow = (sg * 32 + (lane & 7) + (lane >> 4) * 8) * 128 + ((((lane >> 3) & 1) ^ (lane & 7)) << 4);
#pragma unroll
                for (int ii = 0; ii < 16; ii++) {
                    const int i = (ii >> 1) + (ii & 1) * 8;
                    const uint32_t kb = sb0 + (i < 12 ? x0 * BK_STAGE_BYTES + (i >> 2) * 16384 : x1 * BK_STAGE_BYTES) + (krow ^ ((i & 3) << 5));
                    const uint4 k0 = ldsm4(kb), k1 = ldsm4(kb + 2048);
                    mma16816(s[i >> 3][0], qf[i][0], qf[i][1], qf[i][2], qf[i][3], k0.x, k0.y);
                    mma16816(s[i >> 3][1], qf[i][0], qf[i][1], qf[i][2], qf[i][3], k0.z, k0.w);
                    mma16816(s[i >> 3][2], qf[i][0], qf[i][1], qf[i][2], qf[i][3], k1.x, k1.y);
                    mma16816(s[i >> 3][3], qf[i][0], qf[i][1], qf[i][2], qf[i][3], k1.z, k1.w);
                }
#pragma unroll
                for (int i = 0; i < 8; i++) sts128(wst + i * 512 + lane * 16, qf[8 + i][0], qf[8 + i][1], qf[8 + i][2], qf[8 + i][3]);
                wgbar();
                release(x0);
                TT(6);
                uint32_t pa[2][4][2];
#pragma unroll
                for (int hd = 0; hd < 2; hd++) {
                    uint32_t mx[2] = {0xff80ff80u, 0xff80ff80u};
#pragma unroll
                    for (int n = 0; n < 4; n++)
#pragma unroll
                        for (int r = 0; r < 2; r++) {
                            const int d = hs * 16 + g + r * 8 - n * 8 - tq * 2;
                            pa[hd][n][r] = rscore(d < 0 ? -INFINITY : s[hd][n][2 * r], d < 1 ? -INFINITY : s[hd][n][2 * r + 1]);
                            mx[r] = bmax2(mx[r], pa[hd][n][r]);
                        }
#pragma unroll
                    for (int r = 0; r < 2; r++) {
                        mx[r] = bmax2(mx[r], __shfl_xor_sync(0xffffffffu, mx[r], 1));
                        mx[r] = bmax2(mx[r], __shfl_xor_sync(0xffffffffu, mx[r], 2));
                        mt[hd][r] = fmaxf(blo(mx[r]), bhi(mx[r])) * cs;
                        sum[hd][r] = 0.f;
                    }
#pragma unroll
                    for (int n = 0; n < 4; n++)
#pragma unroll
                        for (int r = 0; r < 2; r++) {
                            const float p0 = ex2f(fmaf(blo(pa[hd][n][r]), cs, -mt[hd][r])), p1 = ex2f(fmaf(bhi(pa[hd][n][r]), cs, -mt[hd][r]));
                            sum[hd][r] += p0 + p1;
                            pa[hd][n][r] = pack2(p0, p1);
                        }
                }
                const uint32_t vrow = (sg * 32 + (lane & 15)) * 128 + (((lane >> 4) ^ (lane & 7)) << 4);
                int xv = x1;
#pragma unroll
                for (int hd = 0; hd < 2; hd++) {
                    if (hd == 1) xv = next();
#pragma unroll
                    for (int i = 0; i < 8; i++) {
                        const uint32_t vb = sb0 + xv * BK_STAGE_BYTES + (hd == 0 ? 16384 : 0) + (i >> 2) * 16384 + (vrow ^ ((i & 3) << 5));
                        uint4 v0, v1;
                        ldsm_x4_t(v0.x, v0.y, v0.z, v0.w, vb);
                        ldsm_x4_t(v1.x, v1.y, v1.z, v1.w, vb + 2048);
                        float* o = acc + hd * 64 + i * 8;
#pragma unroll
                        for (int e = 0; e < 8; e++) o[e] = 0.f;
                        mma16816(o, pa[hd][0][0], pa[hd][0][1], pa[hd][1][0], pa[hd][1][1], v0.x, v0.y);
                        mma16816(o + 4, pa[hd][0][0], pa[hd][0][1], pa[hd][1][0], pa[hd][1][1], v0.z, v0.w);
                        mma16816(o, pa[hd][2][0], pa[hd][2][1], pa[hd][3][0], pa[hd][3][1], v1.x, v1.y);
                        mma16816(o + 4, pa[hd][2][0], pa[hd][2][1], pa[hd][3][0], pa[hd][3][1], v1.z, v1.w);
                    }
                    wgbar();
                    release(xv);
                }
            }
            TT(7);
            BTC(T_ATT, 0);
            {
                const int xm = next();
                TT(8);
                BTC(T_ATT, 1);
                const uint32_t mb = sb0 + xm * BK_STAGE_BYTES + sg * 8192 + lane * 16;
                float sm[2][2][4];
#pragma unroll
                for (int i = 0; i < 16; i++) (&sm[0][0][0])[i] = 0.f;
#pragma unroll
                for (int q = 0; q < 4; q++) {
                    const uint4 k0 = lds128(mb + q * 512), k1 = lds128(mb + 4096 + q * 512);
                    const uint4 qa = lds128(wst + q * 1024 + lane * 16), qb = lds128(wst + q * 1024 + 512 + lane * 16);
                    mma16816(sm[0][0], qf[2 * q][0], qf[2 * q][1], qf[2 * q][2], qf[2 * q][3], k0.x, k0.y);
                    mma16816(sm[0][1], qf[2 * q + 1][0], qf[2 * q + 1][1], qf[2 * q + 1][2], qf[2 * q + 1][3], k0.z, k0.w);
                    mmau(sm[1][0], qa, k1.x, k1.y);
                    mmau(sm[1][1], qb, k1.z, k1.w);
                }
                float f[2][2];
                uint32_t pm[2][2];
#pragma unroll
                for (int hd = 0; hd < 2; hd++)
#pragma unroll
                    for (int r = 0; r < 2; r++) {
                        const uint32_t w = rscore(sm[hd][0][2 * r] + sm[hd][1][2 * r], sm[hd][0][2 * r + 1] + sm[hd][1][2 * r + 1]);
                        const float s0 = blo(w) * cs, s1 = bhi(w) * cs;
                        float m = fmaxf(s0, s1);
                        m = fmaxf(m, __shfl_xor_sync(0xffffffffu, m, 1));
                        m = fmaxf(fmaxf(m, __shfl_xor_sync(0xffffffffu, m, 2)), mt[hd][r]);
                        const float a = ex2f(mt[hd][r] - m), p0 = ex2f(s0 - m), p1 = ex2f(s1 - m);
                        float t = fmaf(sum[hd][r], a, p0 + p1);
                        t += __shfl_xor_sync(0xffffffffu, t, 1);
                        t += __shfl_xor_sync(0xffffffffu, t, 2);
                        t = rcpf(t);
                        f[hd][r] = a * t;
                        pm[hd][r] = pack2(p0 * t, p1 * t);
                    }
#pragma unroll
                for (int q = 0; q < 8; q++) {
                    const int hd = q >> 2;
                    const uint4 vm = lds128(mb + hd * 4096 + 2048 + (q & 3) * 512);
                    float* o = acc + q * 16;
#pragma unroll
                    for (int e = 0; e < 16; e++) o[e] *= f[hd][(e >> 1) & 1];
                    mma1688(o, pm[hd][0], pm[hd][1], vm.x);
                    mma1688(o + 4, pm[hd][0], pm[hd][1], vm.y);
                    mma1688(o + 8, pm[hd][0], pm[hd][1], vm.z);
                    mma1688(o + 12, pm[hd][0], pm[hd][1], vm.w);
#pragma unroll
                    for (int e = 0; e < 8; e++) qf[q * 2 + (e >> 2)][e & 3] = pack2(o[2 * e], o[2 * e + 1]);
                }
                wgbar();
                release(xm);
            }
            TT(9);
#pragma unroll
            for (int t = 0; t < 10; t++) {
                const int s = next();
                const uint32_t sb = sb0 + s * BK_STAGE_BYTES;
                float* d = acc + ((t >> 1) & 1) * 64;
                wg_fence();
#pragma unroll
                for (int k = 0; k < 8; k++) {
                    const uint64_t db = make_desc(sb + k * 2048, 16384, 1024);
                    if (k == 0 && !(t & 1)) wgmma_rs_m64n128k16_first(d, qf[k], db);
                    else wgmma_rs_m64n128k16(d, qf[(t & 1) * 8 + k], db);
                }
                wg_commit();
                if (t) {
                    wg_wait<1>();
                    release((s - 1) & 3);
                    if (t > 1) round_a(acc + (((t >> 1) & 1) ^ 1) * 64, t & 1);
                }
            }
            wg_wait<0>();
            release((it - 1) & 3);
            TT(10);
#pragma unroll
            for (int i = 0; i < 32; i++) qf[i >> 2][i & 3] = pack2(acc[(i >> 3) * 16 + (i & 4) / 2 + (i & 3) * 4], acc[(i >> 3) * 16 + (i & 4) / 2 + (i & 3) * 4 + 1]);
            npend = 6;
            urgent = URGENT > 1;
        }
    }
    cluster_sync_all();
}

__global__ void __launch_bounds__(256) reset_kernel(const bf16* x, int g0, int ncl) {
    const int lane = threadIdx.x & 31, row = blockIdx.x * 8 + (threadIdx.x >> 5);
    uint32_t r[10];
    ld5<128>(r, x + (size_t)row * DM + lane * 4);
    if (blockIdx.x == 0)
        for (int i = threadIdx.x; i < NFLAG * 2; i += blockDim.x) reinterpret_cast<uint4*>(FLG(i >> 1))[i & 1] = make_uint4(i == g0 ? min(ncl, 32) : (i == g0 + 2 ? max(ncl - 32, 0) : 0), 0, 0, 0);
    for (int i = blockIdx.x * 256 + threadIdx.x; i < 2 * PROWS * PG * DM / 8; i += S_LEN * 32) reinterpret_cast<uint4*>(g_part)[i] = make_uint4(0, 0, 0, 0);
    ln_row(r, r);
    st5(g_h[0] + (size_t)row * DM + lane * 4, r);
    if (blockIdx.x) return;
}

typedef CUresult (*PFN_encodeTiled)(CUtensorMap*, CUtensorMapDataType, cuuint32_t, void*, const cuuint64_t*, const cuuint64_t*,
                                    const cuuint32_t*, const cuuint32_t*, CUtensorMapInterleave, CUtensorMapSwizzle,
                                    CUtensorMapL2promotion, CUtensorMapFloatOOBfill);
static PFN_encodeTiled get_encode() {
    static PFN_encodeTiled fn = nullptr;
    if (!fn) {
        void* p = nullptr;
        cudaDriverEntryPointQueryResult qr;
        cudaGetDriverEntryPoint("cuTensorMapEncodeTiled", &p, cudaEnableDefault, &qr);
        fn = (PFN_encodeTiled)p;
    }
    return fn;
}
static void make_map(CUtensorMap* m, const void* ptr, uint64_t rows, uint64_t cols, uint32_t box_rows) {
    cuuint64_t dims[2] = {cols, rows};
    cuuint64_t strides[1] = {cols * 2};
    cuuint32_t box[2] = {64u, box_rows};
    cuuint32_t es[2] = {1, 1};
    get_encode()(m, CU_TENSOR_MAP_DATA_TYPE_BFLOAT16, 2, const_cast<void*>(ptr), dims, strides, box, es,
                 CU_TENSOR_MAP_INTERLEAVE_NONE, CU_TENSOR_MAP_SWIZZLE_128B, CU_TENSOR_MAP_L2_PROMOTION_L2_128B,
                 CU_TENSOR_MAP_FLOAT_OOB_FILL_NONE);
}
static void make_map3(CUtensorMap* m, const void* ptr) {
    cuuint64_t dims[3] = {64, DM, HD / 64};
    cuuint64_t strides[2] = {HD * 2, 128};
    cuuint32_t box[3] = {64u, 64u, 2u};
    cuuint32_t es[3] = {1, 1, 1};
    get_encode()(m, CU_TENSOR_MAP_DATA_TYPE_BFLOAT16, 3, const_cast<void*>(ptr), dims, strides, box, es,
                 CU_TENSOR_MAP_INTERLEAVE_NONE, CU_TENSOR_MAP_SWIZZLE_128B, CU_TENSOR_MAP_L2_PROMOTION_L2_128B,
                 CU_TENSOR_MAP_FLOAT_OOB_FILL_NONE);
}
#define QA_PRE0 4
#define KV1_E 1
#define KV1_L 16
#define KV0_X 6
#define CONV0_AT 1
#define CONV1_AT 9
static void build_sched(Sched& S, int naux) {
    int n = 0;
    auto ck = [](int f, int t) { return (uint32_t)(f * 32) | (uint32_t)t << 16; };
    auto add = [&](int lm, int type, int la, int ca, int lb, int cb, int ntask, uint32_t soft) {
        S.info[n] = (uint32_t)(type << 6 | lm << 8 | (la * 16 + ca) << 9 | (lb * 16 + cb) << 14);
        S.chk[n * 4] = ck(F_CNT + n, ntask); S.chk[n * 4 + 1] = soft;
        S.chk[n * 4 + 2] = ck(F_H + la * NCHK + ca, H_TGT); S.chk[n * 4 + 3] = ck(F_H + lb * NCHK + cb, H_TGT);
        n++;
    };
    for (int i = 0; i < MAXG * 4; i++) S.chk[i] = ck(F_ZERO, 0);
    for (int i = 0; i < MAXG; i++) S.info[i] = 0;
    S.sbeg[0] = n;
    for (int i = 0; i < NCHK; i++) {
        add(1, T_KV, 1, i, 1, i, 16, i < KV1_E || i >= KV1_L ? ck(F_OP + i, 14) + 4 : ck(F_H + NCHK + i, KV1_N));
        S.chk[n * 4 - 2] = S.chk[n * 4 - 1] = ck(F_CONV + i / 8, CONV_TGT);
    }
    S.sbeg[1] = n;
    auto addqa = [&]() {
    for (int p = 0; p < NCHK + PDIST; p++) {
        const bool h0 = p < NCHK, h1 = p >= PDIST;
        const int la = h0 ? 0 : 1, ca = h0 ? p : p - PDIST, lb = h1 ? 1 : 0, cb = h1 ? p - PDIST : p;
        const int ta = ca * CSEG + CSEG + la * LAG;
        add(!(h0 && h1), T_QA, la, ca, lb, cb, h0 && h1 ? 16 : 8,
            ck(F_PROG, h1 ? ta - QA_PRE : (ta > QA_PRE0 ? ta - QA_PRE0 : 0)));
        S.info[n - 1] |= 3u << 19;
        S.chk[n * 4 - 2] = h0 && ca >= PRING ? ck(F_H + NCHK + ca - PRING + 1, H_TGT) : ck(F_ZERO, 0);
        S.chk[n * 4 - 1] = !h1 ? ck(F_KV + ca, KV_TGT) : (cb >= PRING ? ck(F_OP + NCHK + cb - PRING, 128) + 5 : ck(F_ZERO, 0));
    }
    };
    auto addkv = [&]() {
    for (int i = 0; i < NCHK; i += 2) add(0, T_KV, 0, i, 0, i + 1, 32, ck(F_PROG, 4 * i > KV0_X + 1 ? 4 * i - KV0_X : 1)), S.chk[n * 4 - 2] = S.chk[n * 4 - 1] = ck(F_ZERO, 0);
    };
    addqa();
    S.sbeg[2] = n;
    for (int m = 0; m < 2; m++) {
        add(0, T_CONV, 0, m, 0, m, 40, ck(F_U + m, naux));
        S.chk[n * 4 - 2] = S.chk[n * 4 - 1] = ck(F_CNT + S.sbeg[2] + 2 + (m ? CONV1_AT : CONV0_AT) / 2, 32);
    }
    S.sbeg[3] = n;
    addkv();
    S.sbeg[4] = n;
}

static void launch_all(void* const* d_in, void* d_out) {
    const bf16* x = (const bf16*)d_in[0];
    const bf16* mem0 = (const bf16*)d_in[1];
    const bf16* Wq = (const bf16*)d_in[2];
    const bf16* Wk = (const bf16*)d_in[3];
    const bf16* Wv = (const bf16*)d_in[4];
    const bf16* Wo = (const bf16*)d_in[5];
    static bool inited = false;
    static int nsm = 132;
    static Sched SC;
    bf16 *p_h, *p_kv, *p_u;
    cudaGetSymbolAddress((void**)&p_h, g_h);
    cudaGetSymbolAddress((void**)&p_kv, g_kv);
    cudaGetSymbolAddress((void**)&p_u, g_U);
    if (!inited) {
        inited = true;
        cudaDeviceGetAttribute(&nsm, cudaDevAttrMultiProcessorCount, 0);
        cudaFuncSetAttribute(chain_kernel, cudaFuncAttributeMaxDynamicSharedMemorySize, (int)sizeof(ChainSmem));
        cudaFuncSetAttribute(chain_kernel, cudaFuncAttributeNonPortableClusterSizeAllowed, 1);
        cudaFuncSetAttribute(bulk_kernel, cudaFuncAttributeMaxDynamicSharedMemorySize, BULK_SMEM);
        build_sched(SC, 2 * ((nsm - 64) & ~1));
    }
    const size_t QS = (size_t)S_LEN * HD;
    BulkMaps M;
    make_map(&M.h, p_h, 2 * S_LEN, DM, 64);
    make_map(&M.h2, p_h, 2 * S_LEN, DM, 128);
    make_map3(&M.wq, Wq);
    make_map3(&M.wk, Wk);
    make_map3(&M.wv, Wv);
    make_map(&M.wo, Wo, HD, DM, 128);
    make_map(&M.kv, p_kv, 2 * S_LEN, HD, 128);
    make_map(&M.lu, p_u, DM * 32, 64, 256);
    BulkArgs BA;
    BA.x = x; BA.out = (bf16*)d_out;
    BA.Bk = (const bf16*)d_in[8]; BA.Bv = (const bf16*)d_in[9]; BA.shiftk = (const bf16*)d_in[10];
    BA.ssmk = (const bf16*)d_in[11]; BA.ssmD = (const bf16*)d_in[12];
    ChainArgs ca;
    for (int l = 0; l < 2; l++) {
        make_map(&ca.tk[l], p_kv, S_LEN, HD, 32);
        make_map(&ca.tv[l], p_kv + QS, S_LEN, HD, 32);
    }
    ca.x = x; ca.mem0 = mem0; ca.Wq = Wq; ca.Wk = Wk; ca.Wv = Wv; ca.Wo = Wo; ca.kv_target = KV_TGT;
    cudaStream_t s = cudaStreamPerThread;
    reset_kernel<<<S_LEN / 8, 256, 0, s>>>(x, 2 * (F_CNT + SC.sbeg[3]), (nsm - 64) / 2);
    {
        cudaLaunchConfig_t cfg = {};
        cfg.gridDim = dim3(64); cfg.blockDim = dim3(CHAIN_THREADS); cfg.dynamicSmemBytes = sizeof(ChainSmem); cfg.stream = s;
        cudaLaunchAttribute at[1];
        at[0].id = cudaLaunchAttributeClusterDimension;
        at[0].val.clusterDim.x = CL; at[0].val.clusterDim.y = 1; at[0].val.clusterDim.z = 1;
        cfg.attrs = at; cfg.numAttrs = 1;
        cudaLaunchKernelEx(&cfg, chain_kernel, ca);
    }
    {
        cudaLaunchConfig_t cfg = {};
        cfg.gridDim = dim3((nsm - 64) & ~1); cfg.blockDim = dim3(384); cfg.dynamicSmemBytes = BULK_SMEM; cfg.stream = s;
        cudaLaunchAttribute at[2];
        at[0].id = cudaLaunchAttributeProgrammaticStreamSerialization;
        at[0].val.programmaticStreamSerializationAllowed = 1;
        at[1].id = cudaLaunchAttributeClusterDimension;
        at[1].val.clusterDim.x = 2; at[1].val.clusterDim.y = 1; at[1].val.clusterDim.z = 1;
        cfg.attrs = at; cfg.numAttrs = 2;
        cudaLaunchKernelEx(&cfg, bulk_kernel, M, BA, SC);
    }
}
}

extern "C" void kernel_launch(void* const* d_in, const int* in_sizes, int n_in, void* d_out, int out_size) {
    (void)in_sizes; (void)n_in; (void)out_size;
    if (ws::usable()) ws::launch_all(d_in, d_out);
    else ni::launch_all(d_in, d_out);
}
```

```cpp
#include <cuda_runtime.h>
#include <cuda_bf16.h>
#include <stdint.h>
#include <cuda.h>

typedef __nv_bfloat16 bf16;
namespace ws {
constexpr int S_LEN = 2048, DM = 640, NH = 32, DH = 128, HD = NH * DH, SEG = 32, NSEG = S_LEN / SEG;

__device__ __forceinline__ float bf2f(bf16 v) { return __bfloat162float(v); }
__device__ __forceinline__ float rbf(float v) { return __bfloat162float(__float2bfloat16_rn(v)); }
__device__ __forceinline__ uint32_t pack2(float a, float b) {
    __nv_bfloat162 t = __floats2bfloat162_rn(a, b);
    return *reinterpret_cast<uint32_t*>(&t);
}
__device__ __forceinline__ float blo(uint32_t v) { return __uint_as_float(v << 16); }
__device__ __forceinline__ float bhi(uint32_t v) { return __uint_as_float(v & 0xffff0000u); }
__device__ __forceinline__ uint32_t badd(uint32_t a, uint32_t b) { uint32_t r; asm("add.rn.bf16x2 %0, %1, %2;" : "=r"(r) : "r"(a), "r"(b)); return r; }
__device__ __forceinline__ uint32_t smem_u32(const void* p) { return (uint32_t)__cvta_generic_to_shared(p); }
__device__ __forceinline__ uint4 ldsm4(uint32_t a) {
    uint4 v;
    asm volatile("ldmatrix.sync.aligned.m8n8.x4.shared.b16 {%0,%1,%2,%3}, [%4];" : "=r"(v.x), "=r"(v.y), "=r"(v.z), "=r"(v.w) : "r"(a));
    return v;
}
__device__ __forceinline__ uint4 ldsm4t(uint32_t a) {
    uint4 v;
    asm volatile("ldmatrix.sync.aligned.m8n8.x4.trans.shared.b16 {%0,%1,%2,%3}, [%4];" : "=r"(v.x), "=r"(v.y), "=r"(v.z), "=r"(v.w) : "r"(a));
    return v;
}
__device__ __forceinline__ void stsm4(uint32_t a, uint32_t r0, uint32_t r1, uint32_t r2, uint32_t r3) {
    asm volatile("stmatrix.sync.aligned.m8n8.x4.shared.b16 [%0], {%1,%2,%3,%4};" ::"r"(a), "r"(r0), "r"(r1), "r"(r2), "r"(r3) : "memory");
}
__device__ __forceinline__ void stsm4t(uint32_t a, uint32_t r0, uint32_t r1, uint32_t r2, uint32_t r3) {
    asm volatile("stmatrix.sync.aligned.m8n8.x4.trans.shared.b16 [%0], {%1,%2,%3,%4};" ::"r"(a), "r"(r0), "r"(r1), "r"(r2), "r"(r3) : "memory");
}
__device__ __forceinline__ void mma16816(float* c, uint32_t a0, uint32_t a1, uint32_t a2, uint32_t a3, uint32_t b0, uint32_t b1) {
    asm("mma.sync.aligned.m16n8k16.row.col.f32.bf16.bf16.f32 {%0,%1,%2,%3}, {%4,%5,%6,%7}, {%8,%9}, {%0,%1,%2,%3};"
        : "+f"(c[0]), "+f"(c[1]), "+f"(c[2]), "+f"(c[3]) : "r"(a0), "r"(a1), "r"(a2), "r"(a3), "r"(b0), "r"(b1));
}
__device__ __forceinline__ void mmav(float* c, uint32_t a0, uint32_t a1, uint32_t a2, uint32_t a3, uint32_t b0, uint32_t b1) {
    asm volatile("mma.sync.aligned.m16n8k16.row.col.f32.bf16.bf16.f32 {%0,%1,%2,%3}, {%4,%5,%6,%7}, {%8,%9}, {%0,%1,%2,%3};"
        : "+f"(c[0]), "+f"(c[1]), "+f"(c[2]), "+f"(c[3]) : "r"(a0), "r"(a1), "r"(a2), "r"(a3), "r"(b0), "r"(b1));
}
__device__ __forceinline__ void mmau(float* c, const uint4& a, uint32_t b0, uint32_t b1) { mma16816(c, a.x, a.y, a.z, a.w, b0, b1); }
__device__ __forceinline__ void mma1688(float* c, uint32_t a0, uint32_t a1, uint32_t b0) {
    asm("mma.sync.aligned.m16n8k8.row.col.f32.bf16.bf16.f32 {%0,%1,%2,%3}, {%4,%5}, {%6}, {%0,%1,%2,%3};"
        : "+f"(c[0]), "+f"(c[1]), "+f"(c[2]), "+f"(c[3]) : "r"(a0), "r"(a1), "r"(b0));
}
__device__ __forceinline__ void mmav8(float* c, uint32_t a0, uint32_t a1, uint32_t b0) {
    asm volatile("mma.sync.aligned.m16n8k8.row.col.f32.bf16.bf16.f32 {%0,%1,%2,%3}, {%4,%5}, {%6}, {%0,%1,%2,%3};"
        : "+f"(c[0]), "+f"(c[1]), "+f"(c[2]), "+f"(c[3]) : "r"(a0), "r"(a1), "r"(b0));
}
__device__ __forceinline__ void cp_async16(uint32_t dst, const void* src) { asm volatile("cp.async.cg.shared.global [%0], [%1], 16;" ::"r"(dst), "l"(src)); }
__device__ __forceinline__ void cp_commit() { asm volatile("cp.async.commit_group;"); }
template <int N> __device__ __forceinline__ void cp_wait() { asm volatile("cp.async.wait_group %0;" ::"n"(N)); }
__device__ __forceinline__ uint4 lds128(uint32_t a) {
    uint4 v;
    asm volatile("ld.shared.v4.u32 {%0,%1,%2,%3}, [%4];" : "=r"(v.x), "=r"(v.y), "=r"(v.z), "=r"(v.w) : "r"(a));
    return v;
}
__device__ __forceinline__ uint2 lds64(uint32_t a) {
    uint2 v;
    asm volatile("ld.shared.v2.u32 {%0,%1}, [%2];" : "=r"(v.x), "=r"(v.y) : "r"(a));
    return v;
}
__device__ __forceinline__ uint32_t lds32(uint32_t a) { uint32_t v; asm volatile("ld.shared.u32 %0, [%1];" : "=r"(v) : "r"(a)); return v; }
__device__ __forceinline__ void sts32(uint32_t a, uint32_t x) { asm volatile("st.shared.u32 [%0], %1;" ::"r"(a), "r"(x) : "memory"); }
__device__ __forceinline__ void sts64(uint32_t a, uint32_t x, uint32_t y) { asm volatile("st.shared.v2.u32 [%0], {%1,%2};" ::"r"(a), "r"(x), "r"(y) : "memory"); }
__device__ __forceinline__ void sts128(uint32_t a, uint32_t x, uint32_t y, uint32_t z, uint32_t w) {
    asm volatile("st.shared.v4.u32 [%0], {%1,%2,%3,%4};" ::"r"(a), "r"(x), "r"(y), "r"(z), "r"(w) : "memory");
}
__device__ __forceinline__ uint4 ld_relaxed_v4(const void* p) {
    uint4 v;
    asm volatile("ld.relaxed.gpu.global.v4.u32 {%0,%1,%2,%3}, [%4];" : "=r"(v.x), "=r"(v.y), "=r"(v.z), "=r"(v.w) : "l"(p) : "memory");
    return v;
}
__device__ __forceinline__ uint2 ld_relaxed_v2(const void* p) {
    uint2 v;
    asm volatile("ld.relaxed.gpu.global.v2.u32 {%0,%1}, [%2];" : "=r"(v.x), "=r"(v.y) : "l"(p) : "memory");
    return v;
}
__device__ __forceinline__ void ld7_relaxed(uint4* x, const void* p) {
    asm volatile("ld.relaxed.gpu.global.v4.u32 {%0,%1,%2,%3}, [%28 + 0];\nld.relaxed.gpu.global.v4.u32 {%4,%5,%6,%7}, [%28 + 512];\nld.relaxed.gpu.global.v4.u32 {%8,%9,%10,%11}, [%28 + 1024];\nld.relaxed.gpu.global.v4.u32 {%12,%13,%14,%15}, [%28 + 1536];\nld.relaxed.gpu.global.v4.u32 {%16,%17,%18,%19}, [%28 + 2048];\nld.relaxed.gpu.global.v4.u32 {%20,%21,%22,%23}, [%28 + 2560];\nld.relaxed.gpu.global.v4.u32 {%24,%25,%26,%27}, [%28 + 3072];\n" : "=r"(x[0].x), "=r"(x[0].y), "=r"(x[0].z), "=r"(x[0].w), "=r"(x[1].x), "=r"(x[1].y), "=r"(x[1].z), "=r"(x[1].w), "=r"(x[2].x), "=r"(x[2].y), "=r"(x[2].z), "=r"(x[2].w), "=r"(x[3].x), "=r"(x[3].y), "=r"(x[3].z), "=r"(x[3].w), "=r"(x[4].x), "=r"(x[4].y), "=r"(x[4].z), "=r"(x[4].w), "=r"(x[5].x), "=r"(x[5].y), "=r"(x[5].z), "=r"(x[5].w), "=r"(x[6].x), "=r"(x[6].y), "=r"(x[6].z), "=r"(x[6].w) : "l"(p) : "memory");
}
__device__ __forceinline__ void ld7_relaxed(uint2* x, const void* p) {
    asm volatile("ld.relaxed.gpu.global.v2.u32 {%0,%1}, [%14 + 0];\nld.relaxed.gpu.global.v2.u32 {%2,%3}, [%14 + 512];\nld.relaxed.gpu.global.v2.u32 {%4,%5}, [%14 + 1024];\nld.relaxed.gpu.global.v2.u32 {%6,%7}, [%14 + 1536];\nld.relaxed.gpu.global.v2.u32 {%8,%9}, [%14 + 2048];\nld.relaxed.gpu.global.v2.u32 {%10,%11}, [%14 + 2560];\nld.relaxed.gpu.global.v2.u32 {%12,%13}, [%14 + 3072];\n" : "=r"(x[0].x), "=r"(x[0].y), "=r"(x[1].x), "=r"(x[1].y), "=r"(x[2].x), "=r"(x[2].y), "=r"(x[3].x), "=r"(x[3].y), "=r"(x[4].x), "=r"(x[4].y), "=r"(x[5].x), "=r"(x[5].y), "=r"(x[6].x), "=r"(x[6].y) : "l"(p) : "memory");
}
__device__ __forceinline__ void st_relaxed_v4(void* p, uint32_t a, uint32_t b, uint32_t c, uint32_t d) {
    asm volatile("st.relaxed.gpu.global.v4.u32 [%0], {%1,%2,%3,%4};" ::"l"(p), "r"(a), "r"(b), "r"(c), "r"(d) : "memory");
}
__device__ __forceinline__ void st_relaxed_v2(void* p, uint32_t a, uint32_t b) {
    asm volatile("st.relaxed.gpu.global.v2.u32 [%0], {%1,%2};" ::"l"(p), "r"(a), "r"(b) : "memory");
}
__device__ __forceinline__ uint32_t nz(uint32_t v) { uint32_t r; asm("max.u32 %0, %1, 1;" : "=r"(r) : "r"(v)); return r; }
__device__ __forceinline__ void touch(const void* p) { asm volatile("prefetch.global.L2 [%0];" ::"l"(p) : "memory"); }
__device__ __forceinline__ int ld_relaxed(const int* p) {
    int v;
    asm volatile("ld.relaxed.gpu.global.u32 %0, [%1];" : "=r"(v) : "l"(p) : "memory");
    return v;
}
__device__ __forceinline__ int ld_acquire(const int* p) {
    int v;
    asm volatile("ld.acquire.gpu.global.u32 %0, [%1];" : "=r"(v) : "l"(p) : "memory");
    return v;
}
__device__ __forceinline__ void red_release(int* p, int v) { asm volatile("red.release.gpu.global.add.u32 [%0], %1;" ::"l"(p), "r"(v) : "memory"); }
__device__ __forceinline__ void mbar_init(uint32_t bar, int count) { asm volatile("mbarrier.init.shared::cta.b64 [%0], %1;" ::"r"(bar), "r"(count)); }
__device__ __forceinline__ void mbar_expect_tx(uint32_t bar, uint32_t bytes) {
    asm volatile("mbarrier.arrive.expect_tx.shared::cta.b64 _, [%0], %1;" ::"r"(bar), "r"(bytes) : "memory");
}
__device__ __forceinline__ void mbar_arrive(uint32_t bar) { asm volatile("mbarrier.arrive.shared::cta.b64 _, [%0];" ::"r"(bar) : "memory"); }
__device__ __forceinline__ void mbar_arrive_cluster(uint32_t bar) { asm volatile("mbarrier.arrive.shared::cluster.b64 _, [%0];" ::"r"(bar) : "memory"); }
__device__ __forceinline__ void mslow(uint32_t bar, uint32_t parity) {
    asm volatile(
        "{\n.reg .pred P1;\n.reg .u32 cnt;\n"
        "mov.u32 cnt, 0;\n"
        "LAB_WAIT:\n"
        "mbarrier.try_wait.parity.shared::cta.b64 P1, [%0], %1;\n"
        "@P1 bra DONE;\n"
        "add.u32 cnt, cnt, 1;\n"
        "setp.lt.u32 P1, cnt, 1000000;\n"
        "@P1 bra LAB_WAIT;\n"
        "trap;\n"
        "DONE:\n}\n" ::"r"(bar), "r"(parity) : "memory");
}
__device__ __forceinline__ void mwait(uint32_t bar, uint32_t parity) {
    asm volatile(
        "{\n.reg .pred P1, P2;\n.reg .u32 cnt;\n"
        "mov.u32 cnt, 0;\n"
        "LAB_WAIT:\n"
        "mbarrier.try_wait.parity.shared::cta.b64 P1, [%0], %1;\n"
        "add.u32 cnt, cnt, 1;\n"
        "setp.gt.u32 P2, cnt, 1000000;\n"
        "@P2 trap;\n"
        "@!P1 bra LAB_WAIT;\n"
        "}\n" ::"r"(bar), "r"(parity) : "memory");
}
__device__ __forceinline__ uint32_t mtest(uint32_t bar, uint32_t parity) {
    uint32_t ok;
    asm volatile("{\n.reg .pred P1;\nmbarrier.test_wait.parity.shared::cta.b64 P1, [%1], %2;\nselp.u32 %0, 1, 0, P1;\n}\n" : "=r"(ok) : "r"(bar), "r"(parity) : "memory");
    return ok;
}
__device__ __forceinline__ uint32_t mapa(uint32_t addr, uint32_t rank) {
    uint32_t r;
    asm("mapa.shared::cluster.u32 %0, %1, %2;" : "=r"(r) : "r"(addr), "r"(rank));
    return r;
}
__device__ __forceinline__ void st_async_b32(uint32_t addr, uint32_t a, uint32_t bar) {
    asm volatile("st.async.weak.shared::cluster.mbarrier::complete_tx::bytes.b32 [%0], %1, [%2];" ::"r"(addr), "r"(a), "r"(bar) : "memory");
}
__device__ __forceinline__ void st_async_v2(uint32_t addr, uint32_t a, uint32_t b, uint32_t bar) {
    asm volatile("st.async.weak.shared::cluster.mbarrier::complete_tx::bytes.v2.b32 [%0], {%1,%2}, [%3];" ::"r"(addr), "r"(a), "r"(b), "r"(bar) : "memory");
}
__device__ __forceinline__ void st_async_v4(uint32_t addr, uint32_t a, uint32_t b, uint32_t c, uint32_t d, uint32_t bar) {
    asm volatile("st.async.weak.shared::cluster.mbarrier::complete_tx::bytes.v4.b32 [%0], {%1,%2,%3,%4}, [%5];" ::"r"(addr), "r"(a), "r"(b), "r"(c), "r"(d), "r"(bar) : "memory");
}
__device__ __forceinline__ void st_async_v4p(uint32_t addr, uint32_t a, uint32_t b, uint32_t c, uint32_t d, uint32_t bar) {
    asm volatile("{\n.reg .pred p;\nsetp.ne.u32 p, %5, 0;\n@p st.async.weak.shared::cluster.mbarrier::complete_tx::bytes.v4.b32 [%0], {%1,%2,%3,%4}, [%5];\n}"
                 ::"r"(addr), "r"(a), "r"(b), "r"(c), "r"(d), "r"(bar) : "memory");
}
__device__ __forceinline__ void st_async_v2p(uint32_t addr, uint32_t a, uint32_t b, uint32_t bar) {
    asm volatile("{\n.reg .pred p;\nsetp.ne.u32 p, %3, 0;\n@p st.async.weak.shared::cluster.mbarrier::complete_tx::bytes.v2.b32 [%0], {%1,%2}, [%3];\n}"
                 ::"r"(addr), "r"(a), "r"(b), "r"(bar) : "memory");
}
__device__ __forceinline__ void cluster_arrive() { asm volatile("barrier.cluster.arrive.release.aligned;" ::: "memory"); }
__device__ __forceinline__ void cluster_arrive_relaxed() { asm volatile("barrier.cluster.arrive.relaxed.aligned;" ::: "memory"); }
__device__ __forceinline__ void prefetch_l2(const void* p, uint32_t bytes) { asm volatile("cp.async.bulk.prefetch.L2.global [%0], %1;" ::"l"(p), "r"(bytes) : "memory"); }
__device__ __forceinline__ void cluster_wait() { asm volatile("barrier.cluster.wait.acquire.aligned;" ::: "memory"); }
__device__ __forceinline__ void named_bar(int id, int n) { asm volatile("bar.sync %0, %1;" ::"r"(id), "r"(n) : "memory"); }
__device__ __forceinline__ void named_arrive(int id, int n) { asm volatile("bar.arrive %0, %1;" ::"r"(id), "r"(n) : "memory"); }
__device__ __forceinline__ void fence_async_smem() { asm volatile("fence.proxy.async.shared::cta;" ::: "memory"); }
__device__ __forceinline__ void fence_async_global() { asm volatile("fence.proxy.async.global;" ::: "memory"); }
__device__ __forceinline__ void wg_fence() { asm volatile("wgmma.fence.sync.aligned;" ::: "memory"); }
__device__ __forceinline__ void wg_commit() { asm volatile("wgmma.commit_group.sync.aligned;" ::: "memory"); }
template <int N> __device__ __forceinline__ void wg_wait() { asm volatile("wgmma.wait_group.sync.aligned %0;" ::"n"(N) : "memory"); }
__device__ __forceinline__ float ex2f(float x) { float y; asm("ex2.approx.ftz.f32 %0, %1;" : "=f"(y) : "f"(x)); return y; }
__device__ __forceinline__ float rcpf(float x) { float y; asm("rcp.approx.ftz.f32 %0, %1;" : "=f"(y) : "f"(x)); return y; }
__device__ __forceinline__ uint32_t clk32() { uint32_t c; asm volatile("mov.u32 %0, %clock;" : "=r"(c)); return c; }
__device__ __forceinline__ uint32_t opq(uint32_t x) { uint32_t y; asm volatile("mov.u32 %0, %1;" : "=r"(y) : "r"(x)); return y; }
__device__ __forceinline__ uint64_t mkdesc(uint32_t lo, uint32_t hi) { uint64_t d; asm("mov.b64 %0, {%1,%2};" : "=l"(d) : "r"(lo), "r"(hi)); return d; }
__device__ __forceinline__ void delay(uint32_t n) {
    asm volatile("{\n.reg .pred P;\n.reg .u32 a, b;\nmov.u32 a, %clock;\nadd.u32 a, a, %0;\nDL:\nmov.u32 b, %clock;\nsub.u32 b, b, a;\nsetp.lt.s32 P, b, 0;\n@P bra.uni DL;\n}" ::"r"(n) : "memory");
}
#define UNI(x) __shfl_sync(0xffffffffu, (uint32_t)(x), 0)
__device__ __forceinline__ void wg_n16t(float* d, uint32_t a0, uint32_t a1, uint32_t a2, uint32_t a3, uint64_t db) {
    asm volatile("wgmma.mma_async.sync.aligned.m64n16k16.f32.bf16.bf16 {%0, %1, %2, %3, %4, %5, %6, %7}, {%8, %9, %10, %11}, %12, 1, 1, 1, 1;"
                 : "+f"(d[0]), "+f"(d[1]), "+f"(d[2]), "+f"(d[3]), "+f"(d[4]), "+f"(d[5]), "+f"(d[6]), "+f"(d[7]) : "r"(a0), "r"(a1), "r"(a2), "r"(a3), "l"(db));
}
__device__ __forceinline__ void wg_n16t_first(float* d, uint32_t a0, uint32_t a1, uint32_t a2, uint32_t a3, uint64_t db) {
    asm volatile("wgmma.mma_async.sync.aligned.m64n16k16.f32.bf16.bf16 {%0, %1, %2, %3, %4, %5, %6, %7}, {%8, %9, %10, %11}, %12, 0, 1, 1, 1;"
                 : "=f"(d[0]), "=f"(d[1]), "=f"(d[2]), "=f"(d[3]), "=f"(d[4]), "=f"(d[5]), "=f"(d[6]), "=f"(d[7]) : "r"(a0), "r"(a1), "r"(a2), "r"(a3), "l"(db));
}
__device__ __forceinline__ void wg_n32(float* d, uint32_t a0, uint32_t a1, uint32_t a2, uint32_t a3, uint64_t db) {
    asm volatile("wgmma.mma_async.sync.aligned.m64n32k16.f32.bf16.bf16 {%0, %1, %2, %3, %4, %5, %6, %7, %8, %9, %10, %11, %12, %13, %14, %15}, {%16, %17, %18, %19}, %20, 1, 1, 1, 0;"
                 : "+f"(d[0]), "+f"(d[1]), "+f"(d[2]), "+f"(d[3]), "+f"(d[4]), "+f"(d[5]), "+f"(d[6]), "+f"(d[7]), "+f"(d[8]), "+f"(d[9]), "+f"(d[10]), "+f"(d[11]), "+f"(d[12]), "+f"(d[13]), "+f"(d[14]), "+f"(d[15]) : "r"(a0), "r"(a1), "r"(a2), "r"(a3), "l"(db));
}
__device__ __forceinline__ void wg_n32_first(float* d, uint32_t a0, uint32_t a1, uint32_t a2, uint32_t a3, uint64_t db) {
    asm volatile("wgmma.mma_async.sync.aligned.m64n32k16.f32.bf16.bf16 {%0, %1, %2, %3, %4, %5, %6, %7, %8, %9, %10, %11, %12, %13, %14, %15}, {%16, %17, %18, %19}, %20, 0, 1, 1, 0;"
                 : "=f"(d[0]), "=f"(d[1]), "=f"(d[2]), "=f"(d[3]), "=f"(d[4]), "=f"(d[5]), "=f"(d[6]), "=f"(d[7]), "=f"(d[8]), "=f"(d[9]), "=f"(d[10]), "=f"(d[11]), "=f"(d[12]), "=f"(d[13]), "=f"(d[14]), "=f"(d[15]) : "r"(a0), "r"(a1), "r"(a2), "r"(a3), "l"(db));
}

__device__ __forceinline__ void wg_n16t_sfirst(float* d, uint64_t da, uint64_t db) {
    asm volatile("wgmma.mma_async.sync.aligned.m64n16k16.f32.bf16.bf16 {%0, %1, %2, %3, %4, %5, %6, %7}, %8, %9, 0, 1, 1, 1, 1;"
                 : "=f"(d[0]), "=f"(d[1]), "=f"(d[2]), "=f"(d[3]), "=f"(d[4]), "=f"(d[5]), "=f"(d[6]), "=f"(d[7]) : "l"(da), "l"(db));
}
__device__ __forceinline__ void wg_n32_sfirst(float* d, uint64_t da, uint64_t db) {
    asm volatile("wgmma.mma_async.sync.aligned.m64n32k16.f32.bf16.bf16 {%0, %1, %2, %3, %4, %5, %6, %7, %8, %9, %10, %11, %12, %13, %14, %15}, %16, %17, 0, 1, 1, 1, 0;"
                 : "=f"(d[0]), "=f"(d[1]), "=f"(d[2]), "=f"(d[3]), "=f"(d[4]), "=f"(d[5]), "=f"(d[6]), "=f"(d[7]), "=f"(d[8]), "=f"(d[9]), "=f"(d[10]), "=f"(d[11]), "=f"(d[12]), "=f"(d[13]), "=f"(d[14]), "=f"(d[15]) : "l"(da), "l"(db));
}

__device__ __forceinline__ void wg_n16t_s(float* d, uint64_t da, uint64_t db) {
    asm volatile("wgmma.mma_async.sync.aligned.m64n16k16.f32.bf16.bf16 {%0, %1, %2, %3, %4, %5, %6, %7}, %8, %9, 1, 1, 1, 1, 1;"
                 : "+f"(d[0]), "+f"(d[1]), "+f"(d[2]), "+f"(d[3]), "+f"(d[4]), "+f"(d[5]), "+f"(d[6]), "+f"(d[7]) : "l"(da), "l"(db));
}
__device__ __forceinline__ void wg_n64_sfirst(float* d, uint64_t da, uint64_t db) {
    asm volatile("wgmma.mma_async.sync.aligned.m64n64k16.f32.bf16.bf16 {%0, %1, %2, %3, %4, %5, %6, %7, %8, %9, %10, %11, %12, %13, %14, %15, %16, %17, %18, %19, %20, %21, %22, %23, %24, %25, %26, %27, %28, %29, %30, %31}, %32, %33, 0, 1, 1, 1, 0;"
                 : "=f"(d[0]), "=f"(d[1]), "=f"(d[2]), "=f"(d[3]), "=f"(d[4]), "=f"(d[5]), "=f"(d[6]), "=f"(d[7]), "=f"(d[8]), "=f"(d[9]), "=f"(d[10]), "=f"(d[11]), "=f"(d[12]), "=f"(d[13]), "=f"(d[14]), "=f"(d[15]), "=f"(d[16]), "=f"(d[17]), "=f"(d[18]), "=f"(d[19]), "=f"(d[20]), "=f"(d[21]), "=f"(d[22]), "=f"(d[23]), "=f"(d[24]), "=f"(d[25]), "=f"(d[26]), "=f"(d[27]), "=f"(d[28]), "=f"(d[29]), "=f"(d[30]), "=f"(d[31]) : "l"(da), "l"(db));
}
__device__ __forceinline__ void wg_n64_s(float* d, uint64_t da, uint64_t db) {
    asm volatile("wgmma.mma_async.sync.aligned.m64n64k16.f32.bf16.bf16 {%0, %1, %2, %3, %4, %5, %6, %7, %8, %9, %10, %11, %12, %13, %14, %15, %16, %17, %18, %19, %20, %21, %22, %23, %24, %25, %26, %27, %28, %29, %30, %31}, %32, %33, 1, 1, 1, 1, 0;"
                 : "+f"(d[0]), "+f"(d[1]), "+f"(d[2]), "+f"(d[3]), "+f"(d[4]), "+f"(d[5]), "+f"(d[6]), "+f"(d[7]), "+f"(d[8]), "+f"(d[9]), "+f"(d[10]), "+f"(d[11]), "+f"(d[12]), "+f"(d[13]), "+f"(d[14]), "+f"(d[15]), "+f"(d[16]), "+f"(d[17]), "+f"(d[18]), "+f"(d[19]), "+f"(d[20]), "+f"(d[21]), "+f"(d[22]), "+f"(d[23]), "+f"(d[24]), "+f"(d[25]), "+f"(d[26]), "+f"(d[27]), "+f"(d[28]), "+f"(d[29]), "+f"(d[30]), "+f"(d[31]) : "l"(da), "l"(db));
}
__device__ __forceinline__ void wg_n64(float* d, uint32_t a0, uint32_t a1, uint32_t a2, uint32_t a3, uint64_t db) {
    asm volatile("wgmma.mma_async.sync.aligned.m64n64k16.f32.bf16.bf16 {%0, %1, %2, %3, %4, %5, %6, %7, %8, %9, %10, %11, %12, %13, %14, %15, %16, %17, %18, %19, %20, %21, %22, %23, %24, %25, %26, %27, %28, %29, %30, %31}, {%32, %33, %34, %35}, %36, 1, 1, 1, 0;"
                 : "+f"(d[0]), "+f"(d[1]), "+f"(d[2]), "+f"(d[3]), "+f"(d[4]), "+f"(d[5]), "+f"(d[6]), "+f"(d[7]), "+f"(d[8]), "+f"(d[9]), "+f"(d[10]), "+f"(d[11]), "+f"(d[12]), "+f"(d[13]), "+f"(d[14]), "+f"(d[15]), "+f"(d[16]), "+f"(d[17]), "+f"(d[18]), "+f"(d[19]), "+f"(d[20]), "+f"(d[21]), "+f"(d[22]), "+f"(d[23]), "+f"(d[24]), "+f"(d[25]), "+f"(d[26]), "+f"(d[27]), "+f"(d[28]), "+f"(d[29]), "+f"(d[30]), "+f"(d[31]) : "r"(a0), "r"(a1), "r"(a2), "r"(a3), "l"(db));
}
__device__ __forceinline__ void wg_n64_first(float* d, uint32_t a0, uint32_t a1, uint32_t a2, uint32_t a3, uint64_t db) {
    asm volatile("wgmma.mma_async.sync.aligned.m64n64k16.f32.bf16.bf16 {%0, %1, %2, %3, %4, %5, %6, %7, %8, %9, %10, %11, %12, %13, %14, %15, %16, %17, %18, %19, %20, %21, %22, %23, %24, %25, %26, %27, %28, %29, %30, %31}, {%32, %33, %34, %35}, %36, 0, 1, 1, 0;"
                 : "=f"(d[0]), "=f"(d[1]), "=f"(d[2]), "=f"(d[3]), "=f"(d[4]), "=f"(d[5]), "=f"(d[6]), "=f"(d[7]), "=f"(d[8]), "=f"(d[9]), "=f"(d[10]), "=f"(d[11]), "=f"(d[12]), "=f"(d[13]), "=f"(d[14]), "=f"(d[15]), "=f"(d[16]), "=f"(d[17]), "=f"(d[18]), "=f"(d[19]), "=f"(d[20]), "=f"(d[21]), "=f"(d[22]), "=f"(d[23]), "=f"(d[24]), "=f"(d[25]), "=f"(d[26]), "=f"(d[27]), "=f"(d[28]), "=f"(d[29]), "=f"(d[30]), "=f"(d[31]) : "r"(a0), "r"(a1), "r"(a2), "r"(a3), "l"(db));
}

__device__ __forceinline__ void wg_n32t(float* d, uint32_t a0, uint32_t a1, uint32_t a2, uint32_t a3, uint64_t db) {
    asm volatile("wgmma.mma_async.sync.aligned.m64n32k16.f32.bf16.bf16 {%0, %1, %2, %3, %4, %5, %6, %7, %8, %9, %10, %11, %12, %13, %14, %15}, {%16, %17, %18, %19}, %20, 1, 1, 1, 1;"
                 : "+f"(d[0]), "+f"(d[1]), "+f"(d[2]), "+f"(d[3]), "+f"(d[4]), "+f"(d[5]), "+f"(d[6]), "+f"(d[7]), "+f"(d[8]), "+f"(d[9]), "+f"(d[10]), "+f"(d[11]), "+f"(d[12]), "+f"(d[13]), "+f"(d[14]), "+f"(d[15]) : "r"(a0), "r"(a1), "r"(a2), "r"(a3), "l"(db));
}
__device__ __forceinline__ void wg_n32t_first(float* d, uint32_t a0, uint32_t a1, uint32_t a2, uint32_t a3, uint64_t db) {
    asm volatile("wgmma.mma_async.sync.aligned.m64n32k16.f32.bf16.bf16 {%0, %1, %2, %3, %4, %5, %6, %7, %8, %9, %10, %11, %12, %13, %14, %15}, {%16, %17, %18, %19}, %20, 0, 1, 1, 1;"
                 : "=f"(d[0]), "=f"(d[1]), "=f"(d[2]), "=f"(d[3]), "=f"(d[4]), "=f"(d[5]), "=f"(d[6]), "=f"(d[7]), "=f"(d[8]), "=f"(d[9]), "=f"(d[10]), "=f"(d[11]), "=f"(d[12]), "=f"(d[13]), "=f"(d[14]), "=f"(d[15]) : "r"(a0), "r"(a1), "r"(a2), "r"(a3), "l"(db));
}
__device__ __forceinline__ void wg_n32t_sfirst(float* d, uint64_t da, uint64_t db) {
    asm volatile("wgmma.mma_async.sync.aligned.m64n32k16.f32.bf16.bf16 {%0, %1, %2, %3, %4, %5, %6, %7, %8, %9, %10, %11, %12, %13, %14, %15}, %16, %17, 0, 1, 1, 1, 1;"
                 : "=f"(d[0]), "=f"(d[1]), "=f"(d[2]), "=f"(d[3]), "=f"(d[4]), "=f"(d[5]), "=f"(d[6]), "=f"(d[7]), "=f"(d[8]), "=f"(d[9]), "=f"(d[10]), "=f"(d[11]), "=f"(d[12]), "=f"(d[13]), "=f"(d[14]), "=f"(d[15]) : "l"(da), "l"(db));
}
__device__ __forceinline__ void wg_n32t_s(float* d, uint64_t da, uint64_t db) {
    asm volatile("wgmma.mma_async.sync.aligned.m64n32k16.f32.bf16.bf16 {%0, %1, %2, %3, %4, %5, %6, %7, %8, %9, %10, %11, %12, %13, %14, %15}, %16, %17, 1, 1, 1, 1, 1;"
                 : "+f"(d[0]), "+f"(d[1]), "+f"(d[2]), "+f"(d[3]), "+f"(d[4]), "+f"(d[5]), "+f"(d[6]), "+f"(d[7]), "+f"(d[8]), "+f"(d[9]), "+f"(d[10]), "+f"(d[11]), "+f"(d[12]), "+f"(d[13]), "+f"(d[14]), "+f"(d[15]) : "l"(da), "l"(db));
}

__device__ __forceinline__ void wg_n32_kk(float* d, uint64_t da, uint64_t db) {
    asm volatile("wgmma.mma_async.sync.aligned.m64n32k16.f32.bf16.bf16 {%0, %1, %2, %3, %4, %5, %6, %7, %8, %9, %10, %11, %12, %13, %14, %15}, %16, %17, 1, 1, 1, 0, 0;"
                 : "+f"(d[0]), "+f"(d[1]), "+f"(d[2]), "+f"(d[3]), "+f"(d[4]), "+f"(d[5]), "+f"(d[6]), "+f"(d[7]), "+f"(d[8]), "+f"(d[9]), "+f"(d[10]), "+f"(d[11]), "+f"(d[12]), "+f"(d[13]), "+f"(d[14]), "+f"(d[15]) : "l"(da), "l"(db));
}

}

namespace ws {
#define LAGT 4
constexpr int LAG = LAGT, NT = NSEG + LAG, NCL = 7;
#define P1A 24
#define P1C 10
#define XD 350
#define REG_G 200
#define REG_T 72
#define REG_X 40
template <int V> struct IC { static constexpr int value = V; };
#define POST_NS 20
#define OP_NS 20
#define LN0_AHEAD 8
#define TG_STEPS 40
#define NO_X 0
#define WTA 3
constexpr int WTC = 10 - 2 * WTA;
#define WR 4
#define OBK 2
#define WFLY 2
#define H_NS 20
constexpr int XRS = 3;
constexpr int O_H = 0, O_MEM = 81920, O_RED = 102400, O_BAR = 110080, O_TAB = O_BAR + 192, O_BT = O_TAB + 128, O_TR = O_BAR + 512, O_X = O_TR + 1024;
constexpr int O_QRY = O_X, O_KEY = O_X + 10240, O_OBA = O_KEY + 10240, O_ST = O_OBA + 4096;
constexpr int O_VT = O_X, O_VM = O_VT + 32768, O_SM = O_VM + 4096, O_PB = O_SM + 3072;
constexpr int O_AS = 228352, O_WO = O_AS - 65536, HEAD_SMEM = O_AS + 4096, O_STG = 40960;
static_assert(O_ST + 8192 <= O_WO && O_PB + 10240 <= O_WO && O_AS % 1024 == 0 && O_STG + 163840 <= O_AS && HEAD_SMEM <= 232448, "smem");
constexpr int B_MEM = 0, B_RED = 64, B_SM = 88, B_ST = 96, B_OB = 104, B_HF = 112, B_HE = 128, B_OTF = 144, B_OTE = 160;

constexpr int F_H = 0, F_O = 128, F_P = 256, F_U = 384, F_CV = 392, F_XL = 398, F_Z = 399, NFLAG = 400;
__device__ int g_flags[NFLAG * 8];
#define FLG(i) (g_flags + (i) * 8)
#define RING 16
__device__ __forceinline__ int rslot(int l, int seg) { return l * RING + (seg & (RING - 1)); }
__device__ uint4 g_ht[2 * RING * 2560];
__device__ uint4 g_ot[2 * RING * 256 * 64];
__device__ uint4 g_pt[2 * RING * 5120];
__device__ uint4 g_Y[80 * S_LEN];
__device__ uint4 g_U[DM * S_LEN / 8];
__device__ bf16 g_x[RING * SEG * DM];
__device__ int g_epoch;
__device__ uint4 g_xc[XRS * 16 * 3 * 8 * 32];
#define GT(cond, i)
#define SC(cond, i)
#define SD(x)
#define TS(i)
#define TV(i, v)

}

namespace ws {
__device__ __forceinline__ uint32_t bmul2(uint32_t a, uint32_t b) { uint32_t r; asm("mul.rn.bf16x2 %0, %1, %2;" : "=r"(r) : "r"(a), "r"(b)); return r; }
__device__ __forceinline__ uint32_t bmax2(uint32_t a, uint32_t b) { uint32_t r; asm("max.bf16x2 %0, %1, %2;" : "=r"(r) : "r"(a), "r"(b)); return r; }
__device__ __forceinline__ void flag_wait(const int* f, int tgt, int ns) {
    int guard = 0;
    while (ld_relaxed(f) < tgt) { if (++guard > 4000000) __trap(); __nanosleep(ns); }
}
template <int STRIDE> __device__ __forceinline__ void ld5(uint32_t* w, const void* p) {
#pragma unroll
    for (int r = 0; r < 5; r++) { const uint2 v = __ldcg(reinterpret_cast<const uint2*>(reinterpret_cast<const char*>(p) + r * STRIDE)); w[2 * r] = v.x; w[2 * r + 1] = v.y; }
}
template <int STRIDE> __device__ __forceinline__ void st5(void* p, const uint32_t* w) {
#pragma unroll
    for (int r = 0; r < 5; r++) *reinterpret_cast<uint2*>(reinterpret_cast<char*>(p) + r * STRIDE) = make_uint2(w[2 * r], w[2 * r + 1]);
}
__device__ __forceinline__ void ln_row(const uint32_t* x, uint32_t* y) {
    const float c = blo(__shfl_sync(0xffffffffu, x[0], 0));
    float s0 = 0.f, s1 = 0.f, q0 = 0.f, q1 = 0.f;
#pragma unroll
    for (int i = 0; i < 10; i++) { const float d0 = blo(x[i]) - c, d1 = bhi(x[i]) - c; s0 += d0; s1 += d1; q0 = fmaf(d0, d0, q0); q1 = fmaf(d1, d1, q1); }
    float s = s0 + s1, q = q0 + q1;
#pragma unroll
    for (int o = 16; o > 0; o >>= 1) { s += __shfl_xor_sync(0xffffffffu, s, o); q += __shfl_xor_sync(0xffffffffu, q, o); }
    s *= 1.0f / DM;
    const float mean = c + s;
    q = fmaxf(fmaf(q, 1.0f / DM, -s * s), 0.f);
    const uint32_t nm = pack2(-mean, -mean);
    float sq;
    asm("sqrt.approx.ftz.f32 %0, %1;" : "=f"(sq) : "f"(rbf(rbf(q) + 1e-5f)));
    const float rd = rcpf(rbf(sq));
#pragma unroll
    for (int i = 0; i < 10; i++) { const uint32_t d = badd(x[i], nm); y[i] = pack2(blo(d) * rd, bhi(d) * rd); }
}
__device__ __forceinline__ void clear_acc(int l, int seg, int tok, int lane) {
    uint4* pz = g_pt + rslot(l, seg) * 5120 + (lane >> 4) * 512 + tok * 16 + (lane & 15);
#pragma unroll
    for (int i = 0; i < 5; i++) pz[i * 1024] = make_uint4(0, 0, 0, 0);
}
__device__ __forceinline__ void put_h(int l, int seg, int tok, int lane, const uint32_t* n) {
    st5<8192>(reinterpret_cast<char*>(g_ht + rslot(l, seg) * 2560) + (lane >> 2) * 1024 + tok * 32 + (((lane & 3) * 8) ^ ((tok & 4) << 2)), n);
}
__device__ __forceinline__ void ln0_row(const bf16* x, int seg, int tok, int lane) {
    uint32_t v[10];
    ld5<256>(v, x + (size_t)(seg * SEG + tok) * DM + lane * 4);
    clear_acc(0, seg, tok, lane);
    ln_row(v, v);
    put_h(0, seg, tok, lane, v);
    __syncwarp();
    if (lane == 0) red_release(FLG(F_H + seg), 1);
}
__device__ __forceinline__ void post_row(int l, int seg, int tok, int lane, const bf16* xin, bf16* xout, int ep) {
    uint32_t x[10], y[10], n[10];
    const int row = seg * SEG + tok;
    SC(tr, tb);
    const bool first = seg == 0;
    if (seg == 8 || ((seg & 15) == 0 && seg)) flag_wait(FLG(F_CV + (seg >> 4) + 1), 80 * ep, 50);
    const char* yp = reinterpret_cast<const char*>(g_Y) + ((size_t)(lane >> 1) * S_LEN + row) * 16 + (lane & 1) * 8;
    SC(tr, tb + 1);
    if (!first) ld5<16 * S_LEN * 16>(y, yp);
    bf16* xm = g_x + ((seg & (RING - 1)) * SEG + tok) * DM + lane * 4;
    if (l == 0) {
        ld5<256>(x, xin + (size_t)row * DM + lane * 4);
        clear_acc(1, seg, tok, lane);
    } else {
        flag_wait(seg + 1 < NSEG ? FLG(F_H + 65 + seg) : FLG(F_XL), 32 * ep, 50);
        ld5<256>(x, xm);
    }
    flag_wait(FLG(F_P + l * 64 + seg), 40 * ep, POST_NS);
    SC(tr, tb + 2);
    const uint4* pp = g_pt + rslot(l, seg) * 5120 + (lane >> 4) * 512 + tok * 16 + ((lane & 15) ^ ((tok >> 3) << 1));
    {
        uint4 a[5];
#pragma unroll
        for (int i = 0; i < 5; i++) a[i] = __ldcg(pp + i * 1024);
#pragma unroll
        for (int i = 0; i < 5; i++) {
            x[2 * i] = badd(x[2 * i], pack2(__uint_as_float(a[i].x), __uint_as_float(a[i].y)));
            x[2 * i + 1] = badd(x[2 * i + 1], pack2(__uint_as_float(a[i].z), __uint_as_float(a[i].w)));
        }
    }
    SC(tr && x[0] != 0x12345, tb + 3);
    if (first) { flag_wait(FLG(F_CV), 80 * ep, 50); ld5<16 * S_LEN * 16>(y, yp); }
    ln_row(x, n);
#pragma unroll
    for (int i = 0; i < 10; i++) x[i] = badd(x[i], bmul2(n[i], y[i]));
    SC(tr && x[0] != 0x12345, tb + 4);
    if (l) st5<256>(xout + (size_t)row * DM + lane * 4, x);
    else {
        ln_row(x, n);
        SC(tr && n[0] != 0x12345, tb + 5);
        put_h(1, seg, tok, lane, n);
        __syncwarp();
        if (lane == 0) red_release(FLG(F_H + 64 + seg), 1);
        SC(tr, tb + 6);
        st5<256>(xm, x);
        if (seg == NSEG - 1) { __syncwarp(); if (lane == 0) red_release(FLG(F_XL), 1); }
    }
}
__device__ __forceinline__ void u_piece(const bf16* Bk, const bf16* Bv, const bf16* shiftk, int t0, int cp, uint4* o) {
    uint32_t kk[11], vv[8];
    const uint32_t* pk = reinterpret_cast<const uint32_t*>(Bk + (size_t)t0 * DM) + cp;
    const uint32_t* pv = reinterpret_cast<const uint32_t*>(Bv + (size_t)t0 * DM) + cp;
#pragma unroll
    for (int i = 0; i < 11; i++) kk[i] = (i >= 3 || t0 > 0) ? __ldg(pk + (i - 3) * (DM / 2)) : 0u;
#pragma unroll
    for (int i = 0; i < 8; i++) vv[i] = __ldg(pv + i * (DM / 2));
    const uint4 sh0 = __ldg(reinterpret_cast<const uint4*>(shiftk + cp * 8));
    const uint32_t s0 = __byte_perm(sh0.x, sh0.z, 0x5410), s1 = __byte_perm(sh0.x, sh0.z, 0x7632), s2 = __byte_perm(sh0.y, sh0.w, 0x5410), s3 = __byte_perm(sh0.y, sh0.w, 0x7632);
#pragma unroll
    for (int t = 0; t < 8; t++)
        vv[t] = bmul2(badd(badd(badd(bmul2(kk[t], s3), bmul2(kk[t + 1], s2)), bmul2(kk[t + 2], s1)), bmul2(kk[t + 3], s0)), vv[t]);
#pragma unroll
    for (int c = 0; c < 2; c++) {
        const uint32_t sel = c ? 0x7632 : 0x5410;
        o[c] = make_uint4(__byte_perm(vv[7], vv[6], sel), __byte_perm(vv[5], vv[4], sel), __byte_perm(vv[3], vv[2], sel), __byte_perm(vv[1], vv[0], sel));
    }
}
__device__ __forceinline__ int u_pos(int t0) { return (t0 >> 6) * 8 + ((((t0 ^ 56) & 63) >> 3) ^ ((t0 >> 6) & 7)); }
__device__ __forceinline__ void u_half(const bf16* Bk, const bf16* Bv, const bf16* shiftk, int unit, int lane) {
    const int t0 = (unit / 20) * 16 + (lane & 1) * 8, cp = (unit % 20) * 16 + (lane >> 1);
    uint4 o[2];
    u_piece(Bk, Bv, shiftk, t0, cp, o);
    uint4* d = g_U + (size_t)(cp * 2) * (S_LEN / 8) + u_pos(t0);
    d[0] = o[0]; d[S_LEN / 8] = o[1];
}
constexpr int CV_E = 4224, CV_W = 2 * 4096 + 3 * CV_E + 128, CV_HI = O_X, CV_Y = CV_HI + 4 * CV_W, CV_T = CV_Y + 16384, CV_Z = CV_T + 16384;
static_assert(4 * CV_W <= O_RED && CV_W % 128 == 0 && CV_Z + 128 <= HEAD_SMEM, "conv buffers");
__device__ __forceinline__ void conv_unit(uint32_t ub, uint32_t e0, uint32_t e1, uint32_t zrow, uint32_t tt, uint32_t Dv, int rg, int nq, int lane, uint32_t zero, int tb) {
    const int g7 = 7 - (lane >> 2), tq = lane & 3;
    SC(tb >= 0, tb + 3);
    for (int i = lane; i < 32 * nq + 8; i += 32) {
        const uint4 v = lds128(e0 + i * 16);
        const uint32_t nx = lds32(e0 + i * 16 + 16);
        sts128(e1 + i * 16, __byte_perm(v.x, v.y, 0x5432), __byte_perm(v.y, v.z, 0x5432), __byte_perm(v.z, v.w, 0x5432), __byte_perm(v.w, nx, 0x5432));
    }
    __syncwarp();
    SC(tb >= 0, tb + 4);
    float acc[4][4];
#pragma unroll
    for (int i = 0; i < 16; i++) (&acc[0][0])[i] = 0.f;
    uint32_t wb = (g7 & 1) ? e0 + (1 + g7 + 2 * tq) * 2 : e1 + (g7 + 2 * tq) * 2;
    int row = 8 * rg + (lane & 7);
    auto ldb = [&](uint4* b) {
        const uint32_t x = row < 0 ? zrow : ub + row * 128 + (((lane >> 3) ^ (row & 7)) << 4);
        b[0] = ldsm4(x); b[1] = ldsm4(x ^ 64);
        row--;
    };
    uint4 Q[16], b[2][2];
    Q[15].w = lds32(wb);
    auto ldq = [&](int q, int o) { Q[q].y = lds32(wb + o * 32 + 16); Q[q].w = lds32(wb + o * 32 + 32); };
    auto cpq = [&](int q) { Q[q].x = Q[(q + 15) & 15].w + zero; Q[q].z = Q[q].y + zero; };
#pragma unroll
    for (int q = 0; q < 11; q++) ldq(q, q);
#pragma unroll
    for (int q = 0; q < 7; q++) cpq(q);
    ldb(b[0]);
#pragma unroll 1
    for (int D0 = nq; D0 > 0; D0--) {
#pragma unroll
        for (int d = 0; d < 4; d++) {
            ldb(b[(d + 1) & 1]);
#pragma unroll
            for (int q = 11; q < 15; q++) ldq((4 * d + q) & 15, 4 * d + q);
#pragma unroll
            for (int ks = 0; ks < 4; ks++) {
                const uint4& bb_ = b[d & 1][ks >> 1];
#pragma unroll
                for (int m = 0; m < 4; m++) {
                    const uint4& a = Q[(4 * d + m + ks) & 15];
                    mmav(acc[m], a.x, a.y, a.z, a.w, (ks & 1) ? bb_.z : bb_.x, (ks & 1) ? bb_.w : bb_.y);
                }
                cpq((4 * d + 7 + ks) & 15);
            }
        }
        wb += 512;
    }
    SC(tb >= 0 && acc[0][0] != 1.2345f, tb + 5);
    const uint32_t ua = ub + (8 * rg + (lane & 7)) * 128 + (((lane >> 3) ^ (lane & 7)) << 4);
    const uint4 u0 = ldsm4t(ua), u1 = ldsm4t(ua ^ 64);
    auto y = [&](int m, int hf, uint32_t u) { return badd(pack2(acc[m][2 * hf], acc[m][2 * hf + 1]), bmul2(u, Dv)); };
    stsm4t(tt, y(0, 0, u1.w), y(0, 1, u1.z), y(1, 0, u1.y), y(1, 1, u1.x));
    stsm4t(tt ^ 64, y(2, 0, u0.w), y(2, 1, u0.z), y(3, 0, u0.y), y(3, 1, u0.x));
}
}

namespace ws {
struct HeadArgs { const bf16 *x, *mem0, *Wq, *Wk, *Wv, *Wo, *Bk, *Bv, *shiftk, *ssmk, *ssmD; bf16* out; int h_target; };

__global__ void __launch_bounds__(512, 1) head_kernel(const __grid_constant__ HeadArgs A) {
    extern __shared__ __align__(1024) unsigned char smem_raw[];
    const int tid = threadIdx.x, warp = __shfl_sync(0xffffffffu, tid >> 5, 0), lane = tid & 31;
    const int cq = blockIdx.x >> 4, r = blockIdx.x & 15;
    const int nh = cq < 4 ? 5 : 4, hi = r / 3, role = r - hi * 3;
    const bool head = r < 3 * nh;
    const int p0 = r >> 1;
    const int h = (cq < 4 ? 5 * cq : 4 * cq + 4) + hi;
    const uint32_t sb = smem_u32(smem_raw), bb = sb + O_BAR;
    GT(tid == 0, 1);
    const int sp = cq < 4 ? cq : 4 * cq + r - 24;
    if (tid == 0) {
        if ((sb & 0xFFFFFFu) != 1024) __trap();
        for (int i = 0; i < 12; i++) mbar_init(bb + i * 8, 1);
        mbar_init(bb + B_ST, role == 2 ? 1 : 5);
        mbar_init(bb + B_OB, 1); mbar_init(bb + B_OB + 64, 1);
        mbar_init(bb + B_HF, 1); mbar_init(bb + B_HF + 8, 1);
        mbar_init(bb + B_HE, 6 * nh);
        mbar_init(bb + B_OTF, head ? 4 : 8); mbar_init(bb + B_OTE, 1); mbar_init(bb + B_OTF + 8, head ? 4 : 8); mbar_init(bb + B_OTE + 16, 1);
        asm volatile("fence.mbarrier_init.release.cluster;" ::: "memory");
        mbar_expect_tx(bb + B_RED, nh * 1280);
        mbar_expect_tx(bb + B_SM, 3072); mbar_expect_tx(bb + B_ST, role == 2 ? 5120 : 4096);
        if (role != 2) { mbar_expect_tx(bb + B_OB, 2048); mbar_expect_tx(bb + B_OB + 64, 2048); }
        mbar_expect_tx(bb + B_HF, 40960); mbar_expect_tx(bb + B_HF + 8, 40960);
    }
    asm volatile("griddepcontrol.launch_dependents;");
    __syncwarp();
    cluster_arrive_relaxed();
    if (warp < 8) {
        asm volatile("setmaxnreg.inc.sync.aligned.u32 %0;" ::"n"(REG_G));
        const int wg = warp >> 2, w4 = warp & 3;
        if (head) {
            uint32_t wa[40][4];
            {
                const int t7 = tid & 127;
                const bf16* W = (role == 2 ? A.Wv + wg * 64 : (wg ? A.Wk : A.Wq) + role * 64) + h * DH + (size_t)(t7 >> 3) * HD + (t7 & 7) * 8;
                const uint32_t so = (t7 >> 3) * 128 + (((t7 & 7) ^ ((t7 >> 3) & 7)) << 4), stg = sb + O_STG + wg * 81920;
                const uint32_t la = stg + ((lane & 7) + (lane >> 4) * 8) * 128 + (((w4 * 2 + ((lane >> 3) & 1)) ^ (lane & 7)) << 4);
                GT(tid == 0, 80);
#pragma unroll
                for (int gi = 0; gi < 8 + WFLY; gi++) {
                    if (gi < 8) {
                        const bf16* Wg = W + (size_t)(((p0 - gi) & 7) * 80) * HD;
#pragma unroll
                        for (int u = 0; u < 5; u++) cp_async16((gi == 0 && u == 0 ? sb + O_AS + wg * 2048 : stg + (gi * 5 + u) * 2048) + so, Wg + (size_t)u * 16 * HD);
                    }
                    cp_commit();
                    if (gi >= WFLY) {
                        cp_wait<WFLY>();
                        named_bar(8 + wg, 128);
#pragma unroll
                        for (int u = 0; u < 5; u++) {
                            const int j = (gi - WFLY) * 5 + u;
                            if (j) { const uint4 v = ldsm4t(la + j * 2048); wa[j][0] = v.x; wa[j][1] = v.y; wa[j][2] = v.z; wa[j][3] = v.w; }
                        }
                    }
                }
                GT(tid == 0, 83);
                cluster_wait();
            }
            named_bar(10, 384);
            GT(tid == 0, 2);
            fence_async_smem();
            named_bar(8 + wg, 128);
            cluster_arrive_relaxed();
            float acc[16];
            const uint32_t ep_q = role == 2 ? sb + O_VM + warp * 512 + (lane ^ ((lane >> 3) & 1)) * 16
                                            : sb + O_QRY + wg * 10240 + ((lane >> 1) & 1) * 5120 + (4 * (lane >> 4) + 2 * ((lane >> 2) & 1) + (lane & 1)) * 128 +
                                                  (((2 * w4 + ((lane >> 3) & 1)) ^ (4 * (lane >> 4) + 2 * ((lane >> 2) & 1) + (lane & 1)) ^ ((lane & 2) << 1)) << 4);
            const uint32_t ep_t = role == 2 ? sb + O_VT + warp * 1024 + ((lane >> 3) & 1) * 512 + (lane >> 4) * 128 + (lane & 7) * 16
                                            : sb + O_QRY + wg * 10240 + (8 + 8 * (lane >> 4) + (lane & 7)) * 128 + (((2 * w4 + ((lane >> 3) & 1)) ^ (lane & 7)) << 4);
                        const int pz = role == 2 ? P1C : P1A;
            const uint32_t ab = (1024 + O_AS + wg * 2048) >> 4;
            uint32_t ok = 1;
            const uint32_t tidk = __shfl_sync(0xffffffffu, tid, lane);
            auto token_gemm = [&](auto ll, const bool pause, const uint32_t vo, const uint32_t nbar, const uint32_t npar, const int t) {
                constexpr int l = decltype(ll)::value;
                constexpr uint32_t hb = ((1024 + O_H + l * 40960) >> 4) | (1u << 16);
                const uint32_t pr = opq(p0);
                if (l) TS(15); else TS(14);
                wg_fence();
#pragma unroll
                for (int j = 0; j < 40; j++) {
                    const uint64_t db = mkdesc(hb + ((pr - j / 5) & 7) * 320 + (j % 5) * 64, 0xC0000010u);
                    if (j == 0) wg_n32_sfirst(acc, mkdesc(ab, 0x40000040u), db);
                    else if (j < TG_STEPS) wg_n32(acc, wa[j][0], wa[j][1], wa[j][2], wa[j][3], db);
                    if (l == 0 && (j + 1 == P1A || j + 1 == P1C)) {
                        if (pause && pz == j + 1) {
                            wg_commit();
                            if (role == 2) mwait(bb + B_OTE, vo >> 14);
                            wg_wait<0>();
                            named_arrive(3, 384);
                            named_bar(4, 384);
                            wg_fence();
                        }
                    }
                }
                wg_commit();
                ok = mtest(nbar, npar);
                wg_wait<0>();
                uint32_t pk[8];
#pragma unroll
                for (int i = 0; i < 8; i++) pk[i] = pack2(acc[2 * i], acc[2 * i + 1]);
                if (role == 2) {
                    stsm4(ep_t + l * 8192 + vo, pk[0], pk[1], pk[2], pk[3]);
                    stsm4(ep_t + l * 8192 + vo + 256, pk[4], pk[5], pk[6], pk[7]);
                } else {
                    stsm4t((ep_t ^ (l << 6)) + l * 5120, pk[0], pk[1], pk[2], pk[3]);
                    stsm4t((ep_t ^ (l << 6)) + l * 5120 + 2048, pk[4], pk[5], pk[6], pk[7]);
                }
                asm volatile("{\n.reg .pred p, q;\nsetp.eq.u32 p, %0, 0;\nsetp.eq.u32 q, %1, 0;\n"
                             "@p mbarrier.arrive.expect_tx.shared::cta.b64 _, [%2], %3;\n@q mbarrier.arrive.shared::cluster.b64 _, [%4];\n}"
                             ::"r"(tidk), "r"(tidk & 127), "r"(bb + B_HF + l * 8), "r"(40960), "r"(mapa(bb + B_HE, l)) : "memory");
            };
            GT(tid == 0, 86);
            mwait(bb + B_HF, 0);
            GT(tid == 0, 87);
            token_gemm(IC<0>{}, false, 0, bb + B_MEM, 1, -1);
            GT(tid == 0, 88);
            named_bar(11, 384);
            cluster_wait();
            named_arrive(13, 384);
#pragma unroll 1
            for (int t = 0; t < NT; t++) {
                GT(tid == 0 && blockIdx.x == 98, 100 + t);
                SC(tid == 0 && blockIdx.x == 98, 160 + t);
                TS(0);
                const uint32_t mp = (t & 1) ^ 1;
                const bool tg0 = t + 1 < NSEG, tg1 = t + 1 >= LAG;
                constexpr uint32_t mb = ((1024 + O_MEM) >> 4) | (16u << 16);
#pragma unroll
                for (int G = 0; G < 8; G++) {
                    if (__builtin_expect(!ok, 0)) mwait(bb + B_MEM + G * 8, mp);
                    ok = mtest(G < 7 ? bb + B_MEM + (G + 1) * 8 : bb + B_HF, mp);
                    if (G == 0) { TS(1); wg_fence(); }
                    if (G == 7) TS(2);
                    if (G == 1) TS(8); if (G == 2) TS(9); if (G == 3) TS(10); if (G == 4) TS(11); if (G == 5) TS(12); if (G == 6) TS(13);
#pragma unroll
                    for (int u = 0; u < 5; u++) {
                        const int j = G * 5 + u;
                        const uint64_t db = mkdesc(mb + j * 32, 8);
                        if (j == 0) wg_n16t_sfirst(acc, mkdesc(ab, 0x40000040u), db);
                        else wg_n16t(acc, wa[j][0], wa[j][1], wa[j][2], wa[j][3], db);
                    }
                    wg_commit();
                }
                if (role == 2 && t) named_bar(5, 384);
                wg_wait<0>();
                TS(3);
                if (role == 2) sts128(ep_q, pack2(acc[0], acc[1]), pack2(acc[2], acc[3]), pack2(acc[4], acc[5]), pack2(acc[6], acc[7]));
                else stsm4t(ep_q, pack2(acc[0], acc[1]), pack2(acc[2], acc[3]), pack2(acc[4], acc[5]), pack2(acc[6], acc[7]));
                named_arrive(1, 384);
                if (tidk < 8) mbar_expect_tx(bb + B_MEM + tidk * 8, 2560);
                if (t == NT - 1) break;
                if (tg0) {
                    if (__builtin_expect(!ok, 0)) mwait(bb + B_HF, mp);
                    if (role != 2) named_bar(2, 384);
                    token_gemm(IC<0>{}, true, mp * 16384, tg1 ? bb + B_HF + 8 : bb + B_MEM, tg1 ? (t + 1 - LAG) & 1 : mp ^ 1, t);
                } else {
                    if (role == 2) mwait(bb + B_OTE, mp); else named_bar(2, 384);
                    named_arrive(3, 384); named_bar(4, 384);
                    ok = 0;
                }
                TS(5);
                if (tg1) {
                    if (__builtin_expect(!ok, 0)) mwait(bb + B_HF + 8, (t + 1 - LAG) & 1);
                    token_gemm(IC<1>{}, false, mp * 16384, bb + B_MEM, mp ^ 1, t);
                }
                TS(6);
                named_arrive(13, 384);
            }
        } else {
            cluster_wait(); cluster_arrive_relaxed();
            const int ep = ld_relaxed(&g_epoch) + 1;
            const uint32_t cb = sb + (warp < 4 ? warp * CV_W : CV_HI + (warp - 4) * CV_W), lb = bb + B_MEM + warp * 8;
            auto fetch = [&](int k) {
                const int ps = k / 5, rg = ps ? ps - 1 : 0, ch = (sp * 5 + k - 5 * ps) * 8 + warp;
                if (k == 5 * ps) { flag_wait(FLG(F_U + ps), (ps > 1 ? 20 : (ps ? 32 : 320)) * ep, 50); fence_async_global(); }
                if (lane == 0) {
                    const uint32_t nb = ps ? ps * 1024 : 512;
                    mbar_expect_tx(lb, 2 * nb);
                    asm volatile("cp.async.bulk.shared::cluster.global.mbarrier::complete_tx::bytes [%0], [%1], %2, [%3];" ::"r"(cb + (k & 1) * 4096), "l"(g_U + ch * (S_LEN / 8)), "r"(nb), "r"(lb) : "memory");
                    asm volatile("cp.async.bulk.shared::cluster.global.mbarrier::complete_tx::bytes [%0], [%1], %2, [%3];" ::"r"(cb + 8192 + (k & 1) * CV_E + 128), "l"(A.ssmk + (size_t)ch * S_LEN), "r"(nb), "r"(lb) : "memory");
                }
                __syncwarp();
            };
            sts32(cb + 8192 + lane * 4, 0u); sts32(cb + 8192 + CV_E + lane * 4, 0u);
            if (warp == 0) sts32(sb + CV_Z + lane * 4, 0u);
            uint32_t dv = 0;
            if (lane < 5) {
                prefetch_l2(A.ssmk + (size_t)((sp * 5 + lane) * 8 + warp) * S_LEN, 1024);
                dv = *reinterpret_cast<const unsigned short*>(A.ssmD + (sp * 5 + lane) * 8 + warp) * 0x10001u;
            }
#pragma unroll
            for (int i = 1; i < 5; i++) sts32(cb + 8192 + i * 768 + lane * 4, 0u);
            named_bar(8, 256);
            flag_wait(FLG(F_U), 320 * ep, 50);
            fence_async_global();
            if (lane == 0) mbar_expect_tx(lb, 5120);
            __syncwarp();
            if (lane < 10) {
                const int j = lane >> 1, ch = (sp * 5 + j) * 8 + warp;
                asm volatile("cp.async.bulk.shared::cluster.global.mbarrier::complete_tx::bytes [%0], [%1], %2, [%3];" ::"r"((lane & 1) ? cb + j * 512 : cb + 8192 + j * 768 + 128),
                             "l"((lane & 1) ? (const void*)(g_U + ch * (S_LEN / 8)) : (const void*)(A.ssmk + (size_t)ch * S_LEN)), "r"(512), "r"(lb) : "memory");
            }
            __syncwarp();
#pragma unroll 1
            for (int k = 0; k < 25; k++) {
                const int ps = k / 5, rg = ps ? ps - 1 : 0;
                const uint32_t Dv = __shfl_sync(0xffffffffu, dv, k - 5 * ps);
                const int tb = sp == 0 && tid == 0 && k >= -1 && k < 7 ? 72 + k * 8 : -1;
                SC(tb >= 0, tb);
                if (k == 0 || ps) {
                    mwait(lb, k & 1);
                    SC(tb >= 0, tb + 1);
                    if (ps && k - 5 * ps < 4) { fence_async_smem(); fetch(k + 1); }
                    SC(tb >= 0, tb + 2);
                }
                const uint32_t tt = sb + CV_T + (k & 1) * 8192;
                conv_unit(cb + (ps ? (k & 1) * 4096 : k * 512), cb + 8192 + (ps ? (k & 1) * CV_E : k * 768), cb + 8192 + 2 * CV_E + 64, sb + CV_Z,
                          tt + warp * 1024 + (lane & 7) * 128 + (((lane >> 3) ^ (lane & 7) ^ warp) & 7) * 16, Dv, rg, ps ? 2 * ps : 1, lane, (uint32_t)A.h_target >> 8, tb);
                mwait(bb + B_OTE + (k & 1) * 16, ((k >> 1) & 1) ^ 1);
                named_bar(8, 256);
                {
                    const uint32_t la = tt + (lane & 7) * 1024 + warp * 128 + (((lane >> 3) ^ (lane & 7) ^ warp) & 7) * 16;
                    const uint4 v0 = ldsm4t(la), v1 = ldsm4t(la ^ 64);
                    const uint32_t ya = sb + CV_Y + (k & 1) * 8192 + (warp * 64 + (lane >> 3) * 8 + 7 - (lane & 7)) * 16;
                    stsm4(ya, v0.x, v0.y, v0.z, v0.w);
                    stsm4(ya + 512, v1.x, v1.y, v1.z, v1.w);
                }
                SC(tb >= 0, tb + 6);
                fence_async_smem();
                __syncwarp();
                if (lane == 0) mbar_arrive(bb + B_OTF + (k & 1) * 8);
                if (k - 5 * ps == 4 && k < 24) fetch(k + 1);
                if (k == 0 && lane < 5) prefetch_l2(A.ssmk + (size_t)((sp * 5 + lane) * 8 + warp) * S_LEN + 512, 3072);
            }
            cluster_wait();
        }
    } else if (warp < 12) {
        asm volatile("setmaxnreg.dec.sync.aligned.u32 %0;" ::"n"(REG_T));
        const int w = warp & 3, c = w >> 1, hh = w & 1;
        const uint32_t lane0 = __shfl_sync(0xffffffffu, tid & 31, tid & 31);
        if (head) {
            const int tile0 = role * 4 * WTA, ntile = role == 2 ? 4 * WTC : 4 * WTA;
            const uint32_t wo = sb + O_WO;
            uint32_t mi[5][4];
#pragma unroll
            for (int i = 0; i < 5; i++)
#pragma unroll
                for (int q = 0; q < 4; q++) {
                    const unsigned short* mp = reinterpret_cast<const unsigned short*>(A.mem0) + 2 * q * DM + i * 128 + (tid & 127);
                    mi[i][q] = mp[0] | (uint32_t)mp[DM] << 16;
                }
            cluster_wait();
            named_bar(10, 384);
#pragma unroll
            for (int i = 0; i < 5; i++) {
                const int col = i * 128 + (tid & 127), kk = col >> 4, pr = (kk * 13) >> 6;
                const uint32_t ma = sb + O_MEM + (((p0 - pr) & 7) * 5 + kk - 5 * pr) * 512 + (col & 8) * 32 + (col & 7) * 16;
                sts128(ma, mi[i][0], mi[i][0], mi[i][1], mi[i][1]);
                sts128(ma + 128, mi[i][2], mi[i][2], mi[i][3], mi[i][3]);
            }
            fence_async_smem();
            named_arrive(11, 384);
            for (int i = tid & 127; i < ntile * 256; i += 128) {
                const int ti = i >> 8, p = (i >> 1) & 127, ch = i & 1;
                const int ks = p >> 4, kh = (p >> 3) & 1, e8 = p & 7;
                const int dim = 64 * (ks >> 2) + 16 * (e8 >> 1) + 8 * (e8 & 1) + 2 * (ks & 3) + kh;
                cp_async16(wo + ti * 4096 + p * 32 + ((ch ^ ((p >> 2) & 1)) << 4), A.Wo + (size_t)(h * DH + dim) * DM + (tile0 + ti) * 16 + ch * 8);
            }
            cp_commit();
            if (lane < 8) {
                const int u = 2 * (tile0 + w + 4 * (lane >> 1)) + (lane & 1), ow = u / 5;
                const int sl = u - 5 * ow;
                sts32(sb + O_TAB + w * 32 + lane * 4, mapa(sb + O_RED + (sl >> 1) * 2560 + (sl & 1) * 256 + hi * (sl < 4 ? 512 : 256), ow & 15));
            }
            cluster_arrive_relaxed(); cluster_wait();
            cp_wait<0>();
            named_bar(7, 128);
            const uint32_t wo_a = wo + w * 4096 + ((lane >> 4) * 8 + (lane & 7)) * 32 + ((((lane >> 3) & 1) ^ ((lane >> 2) & 1)) << 4);
            const uint32_t ob_0 = sb + (role == 2 ? O_PB : O_OBA) + (lane >> 4) * 2048 + ((lane >> 3) & 1) * 128 + ((lane & 7) ^ ((lane >> 1) & 4)) * 16;
            const float cs = 0.08838834764831845f * 1.4426950408889634f;
            auto w_frag = [&](auto four, int i) {
                return ldsm4t(wo_a + (i < 16 || decltype(four)::value == 4 ? (i >> 4) * 32768 + (i & 1) * 16384 + ((i >> 1) & 7) * 512 : 32768 + (i & 1) * 2048 + ((i >> 1) & 7) * 512));
            };
            auto w_pre = [&](auto four, uint4* wf) {
#pragma unroll
                for (int i = 0; i < 8; i++) wf[i] = w_frag(four, i);
            };
            auto w_run = [&](auto four, auto rem_, uint4* wf, int t, const uint32_t ob_a) {
                constexpr int NTL = decltype(four)::value, NF = 8 * NTL, NP = NTL > 2 ? 2 : 1;
                constexpr bool REMOTE = decltype(rem_)::value;
                const uint32_t ln = opq(lane0), l8 = (ln & 2) * 64 + (ln >> 2) * 16 + (ln & 1) * 8, rb = (bb + B_RED) & 0xFFFFFFu;
                auto slot = [](int i) { return i < 8 ? i : 8 - WR + (i - 8) % WR; };
                uint4 obr[8];
#pragma unroll
                for (int k = 0; k < 4; k++) obr[k] = ldsm4(ob_a + k * 256);
#pragma unroll
                for (int p = 0; p < NP; p++) {
                    const bool split = p == 1 && NTL == 3;
                    const int nk = split ? 4 : 8;
                    float d[4][4];
                    uint4 ta;
#pragma unroll
                    for (int i = 0; i < 16; i++) (&d[0][0])[i] = 0.f;
#pragma unroll
                    for (int ks = 0; ks < 8; ks++) {
                        if (ks >= nk) continue;
                        if (p == 0 && ks == OBK) {
                            if (REMOTE) { mwait(bb + B_OB + 64, t & 1); TS(7); }
#pragma unroll
                            for (int k = 4; k < 8; k++) obr[k] = ldsm4(ob_a + k * 256);
                        }
                        if (ks == nk - 2) ta = lds128(sb + O_TAB + w * 32 + p * 16);
#pragma unroll
                        for (int u = 0; u < 2; u++) {
                            const int i = p * 16 + ks * 2 + u;
                            const uint4& o = obr[split && u ? ks + 4 : ks];
                            const uint4& f = wf[slot(i)];
                            mmav(d[2 * u], f.x, f.y, f.z, f.w, o.x, o.y); mmav(d[2 * u + 1], f.x, f.y, f.z, f.w, o.z, o.w);
                            if (i + WR >= 8 && i + WR < NF) wf[slot(i + WR)] = w_frag(four, i + WR);
                        }
                    }
                    if (p) TS(10); else TS(8);
                    if (split) {
#pragma unroll
                        for (int i = 0; i < 4; i++) { d[0][i] += d[2][i]; d[1][i] += d[3][i]; }
                    }
                    st_async_v2(ta.x + l8, pack2(d[0][0], d[0][1]), pack2(d[1][0], d[1][1]), (ta.x & 0xFF000000u) | rb);
                    st_async_v2(ta.y + l8, pack2(d[0][2], d[0][3]), pack2(d[1][2], d[1][3]), (ta.y & 0xFF000000u) | rb);
                    if (!split) {
                        st_async_v2(ta.z + l8, pack2(d[2][0], d[2][1]), pack2(d[3][0], d[3][1]), (ta.z & 0xFF000000u) | rb);
                        st_async_v2(ta.w + l8, pack2(d[2][2], d[2][3]), pack2(d[3][2], d[3][3]), (ta.w & 0xFF000000u) | rb);
                    }
                }
            };
            if (role != 2) {
#pragma unroll 1
                for (int t = 0; t < NT; t++) {
                    const uint32_t lane = opq(lane0);
                    const uint32_t dc = mapa(sb, hi * 3 + 2), dp = mapa(sb, hi * 3 + (role ^ 1));
                    const uint32_t qa = sb + O_QRY + c * 5120 + (lane & 7) * 128;
                    const uint32_t sw = (((lane >> 3) ^ (lane & 7)) << 4) ^ (c << 6);
                    {
                        const uint32_t ka = qa + 10240;
                        const uint32_t kt = sb + O_KEY + c * 5120 + (lane & 15) * 128, kx = (((lane >> 4) ^ (lane & 7)) << 4) ^ (c << 6);
                        const uint32_t sd = dc + O_SM + role * 1536 + c * 768 + lane * 4, sbar = dc + O_BAR + B_SM;
                        const uint32_t ta = sb + O_QRY + c * 5120 + (8 + 16 * hh + ((lane & 15) ^ (role * 8))) * 128;
                        uint4 a[4], f[4];
                        named_bar(13, 384);
#pragma unroll
                        for (int i = 0; i < 4; i++) f[i] = ldsm4(kt + 1024 + hh * 2048 + (kx ^ (i << 5) ^ (hh << 6)));
#pragma unroll
                        for (int i = 0; i < 4; i++) a[i] = ldsm4(ta + (kx ^ (i << 5)));
                        const uint32_t kd = ka + (1 + 2 * hh) * 1024 + sw;
                        uint4 k[5];
                        k[1] = ldsm4(kd); k[2] = ldsm4(kd + 1024);
                        {
                            const uint32_t qh = qa + (sw ^ (hh << 6)), kh = kt + (kx ^ (hh << 6));
                            named_bar(1, 384);
                            const uint4 q0 = ldsm4(qh), g0 = ldsm4(kh), g1 = ldsm4(kh ^ 32), q1 = ldsm4(qh ^ 64);
                            float s0[4] = {0.f, 0.f, 0.f, 0.f}, s1[4] = {0.f, 0.f, 0.f, 0.f}, s2[4] = {0.f, 0.f, 0.f, 0.f}, s3[4] = {0.f, 0.f, 0.f, 0.f};
                            mmav(s0, f[0].x, f[0].y, f[0].z, f[0].w, q0.x, q0.y); mmav(s1, f[1].x, f[1].y, f[1].z, f[1].w, q0.z, q0.w);
                            mmav(s2, g0.x, g0.y, g0.z, g0.w, q0.x, q0.y); mmav(s3, g1.x, g1.y, g1.z, g1.w, q0.z, q0.w);
                            mmav(s0, f[2].x, f[2].y, f[2].z, f[2].w, q1.x, q1.y); mmav(s1, f[3].x, f[3].y, f[3].z, f[3].w, q1.z, q1.w);
                            k[0] = ldsm4(ka + sw); k[3] = ldsm4(ka + 1024 + sw); k[4] = ldsm4(ka + 2048 + sw);
                            st_async_b32(sd + hh * 128, pack2(s2[0] + s3[0], s2[1] + s3[1]), sbar);
                            st_async_b32(sd + 256 + hh * 256, pack2(s0[0] + s1[0], s0[1] + s1[1]), sbar);
                            st_async_b32(sd + 384 + hh * 256, pack2(s0[2] + s1[2], s0[3] + s1[3]), sbar);
                        }
                        TS(1);
                        float u[5][4];
#pragma unroll
                        for (int i = 0; i < 20; i++) (&u[0][0])[i] = 0.f;
                        auto half = [&](auto nn, const uint4& a0, const uint4& a1, bool more) {
                            constexpr int NU = decltype(nn)::value;
                            constexpr int ord[5] = {1, 2, 0, 3, 4};
#pragma unroll
                            for (int i = 0; i < NU; i++) mmav(u[ord[i]], a0.x, a0.y, a0.z, a0.w, k[ord[i]].x, k[ord[i]].y);
#pragma unroll
                            for (int i = 0; i < NU; i++) {
                                const int n = ord[i];
                                mmav(u[n], a1.x, a1.y, a1.z, a1.w, k[n].z, k[n].w);
                                if (more) k[n] = ldsm4(((n == 0 ? ka + sw : (n < 3 ? kd + (n - 1) * 1024 : ka + (n - 2) * 1024 + sw))) ^ 64);
                            }
                        };
                        auto fu = [](float x) { return __float_as_uint(x); };
                        const uint32_t so = O_ST + c * 2048 + hh * 768, td = dp + so, tb = dp + O_BAR + B_ST, lo = sb + so + 4096;
                        if (hh) {
                            half(IC<5>{}, a[0], a[1], true); half(IC<5>{}, a[2], a[3], false);
                            st_async_v4(td + lane * 16, fu(u[0][2]), fu(u[0][3]), fu(u[1][2]), fu(u[1][3]), tb);
                            st_async_v4(td + 512 + lane * 16, fu(u[2][2]), fu(u[2][3]), fu(u[3][2]), fu(u[3][3]), tb);
                            st_async_v2(td + 1024 + lane * 8, fu(u[4][2]), fu(u[4][3]), tb);
                            sts128(lo + lane * 16, fu(u[0][0]), fu(u[0][1]), fu(u[1][0]), fu(u[1][1]));
                            sts128(lo + 512 + lane * 16, fu(u[2][0]), fu(u[2][1]), fu(u[3][0]), fu(u[3][1]));
                            sts64(lo + 1024 + lane * 8, fu(u[4][0]), fu(u[4][1]));
                        } else {
                            half(IC<3>{}, a[0], a[1], true); half(IC<3>{}, a[2], a[3], false);
                            st_async_v4(td + lane * 16, fu(u[0][2]), fu(u[0][3]), fu(u[1][2]), fu(u[1][3]), tb);
                            st_async_v2(td + 512 + lane * 8, fu(u[2][2]), fu(u[2][3]), tb);
                            sts128(lo + lane * 16, fu(u[0][0]), fu(u[0][1]), fu(u[1][0]), fu(u[1][1]));
                            sts64(lo + 512 + lane * 8, fu(u[2][0]), fu(u[2][1]));
                        }
                        if (t < NT - 1) named_arrive(2, 384);
                        __syncwarp();
                        if (lane == 0) mbar_arrive(bb + B_ST);
                        TS(2);
                    }
                    if (t == NT - 1) break;
                    uint4 wf[8];
                    w_pre(IC<WTA>{}, wf);
                    mwait(bb + B_OB, t & 1);
                    TS(3);
                    named_bar(3, 384);
                    w_run(IC<WTA>{}, IC<1>{}, wf, t, ob_0);
                    named_arrive(4, 384);
                    if (w == 0 && lane == 0) { mbar_expect_tx(bb + B_OB, 2048); mbar_expect_tx(bb + B_OB + 64, 2048); }
                    TS(5);
                }
            } else {
#pragma unroll 1
                for (int t = 0; t < NT; t++) {
                    const uint32_t lane = opq(lane0);
                    const int g = lane >> 2, tq = lane & 3;
                    const uint32_t vm_a = sb + O_VM + (g * 4 + 2 * (tq & 1) + (c ^ ((g >> 1) & 1))) * 16 + (tq >> 1) * 8;
                    const uint32_t vt_a = sb + O_VT + (t & 1) * 16384 + ((lane >> 3) & 1) * 512 + (lane >> 4) * 128 + (lane & 7) * 16;
                    named_bar(13, 384);
                    uint4 va[4][2];
#pragma unroll
                    for (int i = 0; i < 4; i++) {
                        va[i][0] = ldsm4(vt_a + c * 8192 + (4 * hh + i) * 1024);
                        va[i][1] = ldsm4(vt_a + c * 8192 + (4 * hh + i) * 1024 + 256);
                    }
                    const uint32_t sa = opq(sb + O_SM + c * 768 + 256 + lane * 16), sa2 = opq(sb + O_SM + c * 768 + (lane & 15) * 16 + (lane >> 4) * 1536), vm_b = opq(vm_a + hh * 2048);
                    named_bar(1, 384);
                    if (__builtin_expect(t < NT - 1, 1)) {
                        uint2 vm[4];
#pragma unroll
                        for (int i = 0; i < 4; i++) vm[i] = lds64(vm_b + i * 512);
                        mwait(bb + B_SM, t & 1);
                        TS(1);
                        const uint4 x0 = ldsm4t(sa), y0 = ldsm4t(sa + 1536), x1 = ldsm4t(sa2);
                        float s[10];
                        s[2] = blo(x0.x) + blo(y0.x); s[3] = bhi(x0.x) + bhi(y0.x); s[4] = blo(x0.y) + blo(y0.y); s[5] = bhi(x0.y) + bhi(y0.y);
                        s[6] = blo(x0.z) + blo(y0.z); s[7] = bhi(x0.z) + bhi(y0.z); s[8] = blo(x0.w) + blo(y0.w); s[9] = bhi(x0.w) + bhi(y0.w);
                        s[0] = (blo(x1.x) + blo(x1.y)) + (blo(x1.z) + blo(x1.w)); s[1] = (bhi(x1.x) + bhi(x1.y)) + (bhi(x1.z) + bhi(x1.w));
                        float mx = fmaxf(fmaxf(fmaxf(s[0], s[1]), fmaxf(s[2], s[3])), fmaxf(fmaxf(fmaxf(s[4], s[5]), fmaxf(s[6], s[7])), fmaxf(s[8], s[9])));
                        const float m1 = __shfl_xor_sync(0xffffffffu, mx, 1), m2 = __shfl_xor_sync(0xffffffffu, mx, 2), m3 = __shfl_xor_sync(0xffffffffu, mx, 3);
                        mx = fmaxf(fmaxf(mx, m1), fmaxf(m2, m3)) * -cs;
                        uint32_t pb[5];
#pragma unroll
                        for (int i = 0; i < 5; i++) pb[i] = pack2(ex2f(fmaf(s[2 * i], cs, mx)), ex2f(fmaf(s[2 * i + 1], cs, mx)));
                        TS(9);
                        named_bar(3, 384);
                        float o[5][4];
#pragma unroll
                        for (int i = 0; i < 20; i++) (&o[0][0])[i] = 0.f;
                        const uint32_t one2 = 0x3F803F80u;
                        float z[2][4] = {{0.f, 0.f, 0.f, 0.f}, {0.f, 0.f, 0.f, 0.f}};
                        mmav8(o[4], one2, one2, pb[0]);
                        mmav(z[0], one2, one2, one2, one2, pb[1], pb[2]);
                        mmav(z[1], one2, one2, one2, one2, pb[3], pb[4]);
#pragma unroll
                        for (int i = 0; i < 4; i++) mmav8(o[i], vm[i].x, vm[i].y, pb[0]);
#pragma unroll
                        for (int i = 0; i < 4; i++) mmav(o[i], va[i][0].x, va[i][0].y, va[i][0].z, va[i][0].w, pb[1], pb[2]);
#pragma unroll
                        for (int i = 0; i < 4; i++) mmav(o[i], va[i][1].x, va[i][1].y, va[i][1].z, va[i][1].w, pb[3], pb[4]);
                        o[4][0] += z[0][0] + z[1][0]; o[4][1] += z[0][1] + z[1][1];
                        uint4 wf[8];
                        w_pre(IC<WTC>{}, wf);
                        const float r0 = rcpf(o[4][0]), r1 = rcpf(o[4][1]);
                        const uint32_t oo = c * 2048 + hh * 1024 + g * 128 + tq * 16 + (g & 1) * 64;
                        uint32_t e0[4], e1[4];
#pragma unroll
                        for (int i = 0; i < 4; i++) { e0[i] = pack2(o[i][0] * r0, o[i][2] * r0); e1[i] = pack2(o[i][1] * r1, o[i][3] * r1); }
                        sts128(sb + O_PB + (~t & 1) * 5120 + oo, e0[0], e0[1], e0[2], e0[3]);
                        sts128(sb + O_PB + (~t & 1) * 5120 + (oo ^ 64), e1[0], e1[1], e1[2], e1[3]);
                        {
                            const uint32_t da = mapa(sb + O_OBA, r - 2) + oo, ba = mapa(bb + B_OB + hh * 64, r - 2);
                            st_async_v4(da, e0[0], e0[1], e0[2], e0[3], ba);
                            st_async_v4(da + 0x01000000u, e0[0], e0[1], e0[2], e0[3], ba + 0x01000000u);
                            st_async_v4(da ^ 64, e1[0], e1[1], e1[2], e1[3], ba);
                            st_async_v4((da ^ 64) + 0x01000000u, e1[0], e1[1], e1[2], e1[3], ba + 0x01000000u);
                        }
                        TS(3);
                        named_bar(7, 128);
                        w_run(IC<WTC>{}, IC<0>{}, wf, t, ob_0 + (~t & 1) * 5120);
                        named_arrive(4, 384);
                        mwait(bb + B_ST, t & 1);
                        TS(4);
                    } else { mwait(bb + B_SM, t & 1); mwait(bb + B_ST, t & 1); }
                    TS(5);
                    fence_async_smem();
#pragma unroll 1
                    for (int l = t < NSEG ? 0 : 1; l < (t >= LAG ? 2 : 1); l++) {
                        const uint32_t pb_ = ((1024 + O_PB) >> 4) + (t & 1) * 320 + l * 160, va_ = (((1024 + O_VT) >> 4) + (t & 1) * 1024 + l * 512) | (8u << 16);
                        const uint32_t oa = sb + O_VT + (t & 1) * 16384 + l * 8192 + w * 1024 + g * 64 + ((tq ^ (g >> 1)) & 3) * 16;
                        const uint32_t vl = (vm_a ^ ((l ^ c) << 4)) + w * 512;
                        const uint2 a0 = lds64(vl), a1 = lds64(vl + 2048);
                        float d[2][16];
                        wg_fence();
                        wg_n32_first(d[0], a0.x, a0.y, 0u, 0u, mkdesc(pb_, 8));
                        wg_n32_first(d[1], a1.x, a1.y, 0u, 0u, mkdesc(pb_, 8));
#pragma unroll
                        for (int i = 0; i < 4; i++) wg_n32_kk(d[i & 1], mkdesc(va_ + (i & 1) * 256 + (i >> 1) * 16, 32), mkdesc(pb_ + 32 + (i >> 1) * 64 + (32u << 16), 8));
                        wg_commit();
                        if (l) TS(13); else TS(11);
                        wg_wait<0>();
                        if (l) TS(14); else TS(12);
#pragma unroll
                        for (int mt = 0; mt < 2; mt++) {
                            sts128(oa + mt * 4096, pack2(d[mt][0], d[mt][1]), pack2(d[mt][4], d[mt][5]), pack2(d[mt][8], d[mt][9]), pack2(d[mt][12], d[mt][13]));
                            sts128(oa + mt * 4096 + 512, pack2(d[mt][2], d[mt][3]), pack2(d[mt][6], d[mt][7]), pack2(d[mt][10], d[mt][11]), pack2(d[mt][14], d[mt][15]));
                        }
                        if (l == 0) {
                            fence_async_smem();
                            __syncwarp();
                            if (lane == 0) mbar_arrive(bb + B_OTF + 8);
                        }
                    }
                    TS(6);
                    if (w == 0 && lane == 0) { mbar_expect_tx(bb + B_ST, 5120); mbar_expect_tx(bb + B_SM, 3072); }
                    fence_async_smem();
                    __syncwarp();
                    if (lane == 0) mbar_arrive(bb + B_OTF);
                    if (t < NT - 1) named_arrive(5, 384);
                }
            }
        } else {
            cluster_wait(); cluster_arrive_relaxed();
            const int wi = sp * 4 + w, half = wi >> 5, tok = wi & 31, ep = ld_relaxed(&g_epoch) + 1;
            GT(lane == 0, 89);
            if (lane < LN0_AHEAD / 2) prefetch_l2(A.x + (size_t)((half + 2 * lane) * SEG + tok) * DM, 1280);
#pragma unroll 1
            for (int k = -LN0_AHEAD / 2; k < NT; k++) {
                const int s0 = k < 0 ? 2 * k + LN0_AHEAD + half : (half ? k + LN0_AHEAD : NSEG);
                if (s0 < NSEG) { ln0_row(A.x, s0, tok, lane); GT(lane == 0 && k < 0, 30 + s0); }
                if (k == -1 && half) {
#pragma unroll 1
                    for (int u = 320 + tok; u < 640; u += 32) u_half(A.Bk, A.Bv, A.shiftk, u, lane);
                    __syncwarp();
                    if (lane == 0) red_release(FLG(F_U + 1), 1);
                }
                const int n = k - half * LAG;
                if (n >= 0 && n < NSEG && k >= 0) {
                    post_row(half, n, tok, lane, A.x, A.out, ep);
                    GT(lane == 0 && (n & 3) == 0 && k >= 0, 460 + half * 16 + (n >> 2)); GT(lane == 0 && n == 63 && half, 40);
                }
            }
            cluster_wait();
        }
    } else {
        asm volatile("setmaxnreg.dec.sync.aligned.u32 %0;" ::"n"(REG_X));
        cluster_wait();
        const int s = warp - 12;
        const uint32_t lane0 = __shfl_sync(0xffffffffu, tid & 31, tid & 31);
        if (s < 3) {
            cluster_arrive_relaxed();
            GT(lane == 0, 84);
            if (blockIdx.x * 3 + s < 320) {
                u_half(A.Bk, A.Bv, A.shiftk, blockIdx.x * 3 + s, lane);
                GT(lane == 0, 85);
                __syncwarp();
                if (lane == 0) red_release(FLG(F_U), 1);
                GT(lane == 0, 4);
            }
            const int ztgt = 3 * 16 * NCL * (ld_relaxed(&g_epoch) + 1);
#pragma unroll
            for (int i = 0; i < XRS; i++) st_relaxed_v4(g_xc + ((i * 16 + r) * 3 + s) * 256 + cq * 32 + lane, 0, 0, 0, 0);
            __syncwarp();
            if (lane == 0) red_release(FLG(F_Z), 1);
            cluster_wait();
            constexpr uint32_t XSLOT = 16 * 3 * 4096;
            uint32_t xo_ = (r * 3 + s) * 4096;
            if (s == 0) {
                const uint32_t G = lane >> 1, d = ((r + 2 * G) & 15) ^ (lane & 1);
                if (lane < 16) { sts32(sb + O_BT + lane * 8, (d << 24) + G * 2560); sts32(sb + O_BT + lane * 8 + 4, d < 3 * nh ? mapa(bb + B_MEM + G * 8, d) : 0u); }
            }
            while (ld_acquire(FLG(F_Z)) < ztgt) __nanosleep(100);
            named_bar(14, 96);
#pragma unroll 1
            for (int t = 0; t < NT; t++) {
                const uint32_t lane = opq(lane0);
                if (head && role != 2) {
                    auto soft = [&](auto uu, auto vv, int c0, int hh) {
                        constexpr int U = decltype(uu)::value, NV = decltype(vv)::value;
                        const uint32_t dc = mapa(sb, hi * 3 + 2), sa = sb + O_ST + c0 * 2048 + hh * 768;
                        const uint32_t pd = dc + O_PB + (t & 1) * 5120 + c0 * 2560 + (2 * hh + role) * 128 + lane * 4, pbar = dc + O_BAR + B_ST;
                        const int lim = 8 * role + (int)(lane >> 2) - 2 * (int)(lane & 3);
                        auto uf = [](uint32_t x) { return __uint_as_float(x); };
                        mwait(bb + B_ST, t & 1);
                        if (r == 1 && U == 2 && t >= LAG - 1 && t < NT - 1) named_arrive(12, 64);
                        uint32_t z[U][NV];
                        auto zz = [](float x, float y) { const uint32_t w = pack2(x, y); return pack2(blo(w) * 0.08838834764831845f, bhi(w) * 0.08838834764831845f); };
#pragma unroll
                        for (int i = 0; i < U; i++) {
                            const uint4 v = lds128(sa + i * 2048 + lane * 16), w = lds128(sa + i * 2048 + 4096 + lane * 16);
                            z[i][0] = zz(uf(v.x) + uf(w.x), uf(v.y) + uf(w.y));
                            z[i][1] = zz(lim < 0 ? -INFINITY : uf(v.z) + uf(w.z), lim < 1 ? -INFINITY : uf(v.w) + uf(w.w));
                            if (NV == 3) {
                                const uint2 x = lds64(sa + i * 2048 + 512 + lane * 8), y = lds64(sa + i * 2048 + 4608 + lane * 8);
                                z[i][2] = zz(lim < 8 ? -INFINITY : uf(x.x) + uf(y.x), lim < 9 ? -INFINITY : uf(x.y) + uf(y.y));
                            } else {
                                const uint4 x = lds128(sa + 512 + lane * 16), y = lds128(sa + 4608 + lane * 16);
                                const uint2 p = lds64(sa + 1024 + lane * 8), q = lds64(sa + 5120 + lane * 8);
                                z[i][2] = zz(lim < 8 ? -INFINITY : uf(x.x) + uf(y.x), lim < 9 ? -INFINITY : uf(x.y) + uf(y.y));
                                z[i][NV - 2] = zz(uf(x.z) + uf(y.z), uf(x.w) + uf(y.w));
                                z[i][NV - 1] = zz(uf(p.x) + uf(q.x), uf(p.y) + uf(q.y));
                            }
                        }
                        const float l2e = 1.4426950408889634f;
                        float e[U][2 * NV], sum[U];
#pragma unroll
                        for (int i = 0; i < U; i++) {
                            uint32_t zm = bmax2(bmax2(z[i][0], z[i][1]), z[i][2]);
                            if (NV == 5) zm = bmax2(zm, bmax2(z[i][NV - 2], z[i][NV - 1]));
                            zm = bmax2(zm, __shfl_xor_sync(0xffffffffu, zm, 1));
                            zm = bmax2(zm, __shfl_xor_sync(0xffffffffu, zm, 2));
                            const float mx = fmaxf(blo(zm), bhi(zm)) * -l2e;
                            sum[i] = 0.f;
#pragma unroll
                            for (int n = 0; n < NV; n++) { e[i][2 * n] = ex2f(fmaf(blo(z[i][n]), l2e, mx)); e[i][2 * n + 1] = ex2f(fmaf(bhi(z[i][n]), l2e, mx)); }
                            sum[i] = ((e[i][0] + e[i][1]) + (e[i][2] + e[i][3])) + (e[i][4] + e[i][5]);
                            if (NV == 5) sum[i] += (e[i][2 * NV - 4] + e[i][2 * NV - 3]) + (e[i][2 * NV - 2] + e[i][2 * NV - 1]);
                            sum[i] += __shfl_xor_sync(0xffffffffu, sum[i], 1);
                            sum[i] += __shfl_xor_sync(0xffffffffu, sum[i], 2);
                            sum[i] = rcpf(sum[i]);
                        }
#pragma unroll
                        for (int i = 0; i < U; i++)
#pragma unroll
                            for (int n = 0; n < 5; n++)
                                st_async_b32(pd + i * 2560 + (n == 0 ? 0 : (NV == 3 ? n : (n < 3 ? n + 2 : n - 2)) * 512), n < NV ? pack2(e[i][2 * n] * sum[i], e[i][2 * n + 1] * sum[i]) : 0u, pbar);
                    };
                    if (s < 2) soft(IC<1>{}, IC<5>{}, s, 1); else soft(IC<2>{}, IC<3>{}, 0, 0);
                    TS(12);
                    named_bar(14, 96);
                    if (s == 0 && lane == 0) mbar_expect_tx(bb + B_ST, 4096);
                }
                if (t == NT - 1) break;
                uint32_t m0 = 0x80008000u, m1 = 0x80008000u;
                if (t < LAG && cq == 0) {
                    const uint32_t ch = s < 2 ? lane : lane >> 1;
                    const unsigned short* mp = reinterpret_cast<const unsigned short*>(A.mem0) + (((ch >> 3) & 1) * 4 + (s < 2 ? 0 : (lane & 1) * 2)) * DM + (5 * r + 2 * s + (ch >> 4)) * 8 + (ch & 7);
                    m0 = max(mp[0] | (uint32_t)mp[DM] << 16, 1u);
                    if (s < 2) m1 = max(mp[2 * DM] | (uint32_t)mp[3 * DM] << 16, 1u);
                }
                const bool late = t >= LAG;
                auto sum5 = [](uint32_t a, uint32_t b, uint32_t c, uint32_t d, uint32_t e) { return nz(badd(badd(badd(a, b), e), badd(c, d))); };
                auto sum7 = [](uint32_t a, uint32_t b, uint32_t c, uint32_t d, uint32_t e, uint32_t f, uint32_t h_) {
                    return badd(badd(badd(a, b), badd(c, d)), badd(badd(e, f), h_));
                };
                auto min3 = [](uint32_t a, uint32_t b, uint32_t c) { return min(min(a, b), c); };
                auto bcast = [&](auto two, const uint32_t aa, uint32_t x0, uint32_t x1, uint32_t x2, uint32_t x3) {
                    auto send = [&](uint32_t o, uint32_t bar) { if (decltype(two)::value) st_async_v4p(aa + o, x0, x1, x2, x3, bar); else st_async_v2p(aa + o, x0, x1, bar); };
                    uint4 e[5];
                    e[0] = lds128(sb + O_BT);
                    TS(8);
                    send(e[0].x, e[0].y); send(e[0].z, e[0].w);
                    TS(9);
#pragma unroll
                    for (int i = 1; i < 5; i++) e[i] = lds128(sb + O_BT + i * 16);
#pragma unroll
                    for (int i = 1; i < 8; i++) {
                        send(e[(i - 1) % 4 + 1].x, e[(i - 1) % 4 + 1].y); send(e[(i - 1) % 4 + 1].z, e[(i - 1) % 4 + 1].w);
                        if (i < 4) e[i] = lds128(sb + O_BT + (i + 4) * 16);
                    }
                };
                const uint32_t ma = (sb + O_MEM + (5 * (r & 1) + 2 * s) * 256) & 0xFFFFFFu;
                int guard = 0;
                if (s < 2) {
                    const uint32_t ra = sb + O_RED + s * 2560 + lane * 16;
                    uint4* xb = reinterpret_cast<uint4*>(reinterpret_cast<char*>(g_xc) + xo_ + lane * 16);
                    uint4* xo = xb + cq * 32;
                    touch(xo); touch(xb);
                    mwait(bb + B_RED, t & 1);
                    TS(0);
                    uint4 p[5];
#pragma unroll
                    for (int i = 0; i < 5; i++) p[i] = i < 4 || nh == 5 ? lds128(ra + i * 512) : make_uint4(0, 0, 0, 0);
                    const uint32_t u1 = sum5(p[0].y, p[1].y, p[2].y, p[3].y, p[4].y), u3 = sum5(p[0].w, p[1].w, p[2].w, p[3].w, p[4].w);
                    st_relaxed_v4(xo, sum5(p[0].x, p[1].x, p[2].x, p[3].x, p[4].x), late ? u1 : m0, sum5(p[0].z, p[1].z, p[2].z, p[3].z, p[4].z), late ? u3 : m1);
                    TS(1);
                    delay(XD);
                    uint4 x[NCL];
                    while (true) {
                        ld7_relaxed(x, xb);
                        const uint32_t mn = min3(min3(min3(x[0].x, x[0].y, x[0].z), min3(x[0].w, x[1].x, x[1].y), min3(x[1].z, x[1].w, x[2].x)),
                                                 min3(min3(x[2].y, x[2].z, x[2].w), min3(x[3].x, x[3].y, x[3].z), min3(x[3].w, x[4].x, x[4].y)),
                                                 min3(min3(x[4].z, x[4].w, x[5].x), min3(x[5].y, x[5].z, x[5].w), min(min3(x[6].x, x[6].y, x[6].z), x[6].w)));
                        if (NO_X || __all_sync(0xffffffffu, mn != 0)) break;
                        if (++guard > 2000000) __trap();
                    }
                    TS(2);
                    TV(4, guard);
                    bcast(IC<1>{}, ma + lane * 16, sum7(x[0].x, x[1].x, x[2].x, x[3].x, x[4].x, x[5].x, x[6].x), sum7(x[0].y, x[1].y, x[2].y, x[3].y, x[4].y, x[5].y, x[6].y),
                          sum7(x[0].z, x[1].z, x[2].z, x[3].z, x[4].z, x[5].z, x[6].z), sum7(x[0].w, x[1].w, x[2].w, x[3].w, x[4].w, x[5].w, x[6].w));
                } else {
                    const uint32_t ra = sb + O_RED + 5120 + lane * 8;
                    uint2* xb = reinterpret_cast<uint2*>(reinterpret_cast<char*>(g_xc) + xo_ + lane * 8);
                    uint2* xo = xb + cq * 64;
                    touch(xo); touch(xb);
                    mwait(bb + B_RED, t & 1);
                    TS(0);
                    uint2 p[5];
#pragma unroll
                    for (int i = 0; i < 5; i++) p[i] = i < 4 || nh == 5 ? lds64(ra + i * 256) : make_uint2(0, 0);
                    const uint32_t u1 = sum5(p[0].y, p[1].y, p[2].y, p[3].y, p[4].y);
                    st_relaxed_v2(xo, sum5(p[0].x, p[1].x, p[2].x, p[3].x, p[4].x), late ? u1 : m0);
                    if (lane == 0) mbar_expect_tx(bb + B_RED, nh * 1280);
                    TS(1);
                    delay(XD);
                    uint32_t y0, y1;
                    while (true) {
                        uint2 x[NCL];
                        ld7_relaxed(x, xb);
                        const uint32_t mn = min3(min3(min3(x[0].x, x[0].y, x[1].x), min3(x[1].y, x[2].x, x[2].y), min3(x[3].x, x[3].y, x[4].x)), min3(x[4].y, x[5].x, x[5].y), min(x[6].x, x[6].y));
                        y0 = sum7(x[0].x, x[1].x, x[2].x, x[3].x, x[4].x, x[5].x, x[6].x); y1 = sum7(x[0].y, x[1].y, x[2].y, x[3].y, x[4].y, x[5].y, x[6].y);
                        if (NO_X || __all_sync(0xffffffffu, mn != 0)) break;
                        if (++guard > 2000000) __trap();
                    }
                    TS(2);
                    TV(4, guard);
                    bcast(IC<0>{}, ma + lane * 8, y0, y1, 0u, 0u);
                }
                TS(3);
                if (head && role == 2) named_arrive(6, 128);
                xo_ += XSLOT; if (xo_ >= XRS * XSLOT) xo_ -= XRS * XSLOT;
                {
                    const uint32_t zo = xo_ + XSLOT >= XRS * XSLOT ? xo_ + XSLOT - XRS * XSLOT : xo_ + XSLOT;
                    char* zp = reinterpret_cast<char*>(g_xc) + zo + cq * 512 + lane * 16;
                    st_relaxed_v4(zp, 0, 0, 0, 0);
                    if (ld_relaxed_v4(zp).x) __trap();
                }
            }
        } else if (r < 2) {
            const uint16_t mask = (uint16_t)((1u << (3 * nh)) - 1u);
            const int htgt = A.h_target * (ld_relaxed(&g_epoch) + 1);
#pragma unroll 1
            for (int n = 0; n < NSEG; n++) {
                if (n == (r == 0 ? 1 : 0)) { cluster_arrive(); cluster_wait(); }
                int guard = 0;
                while (ld_acquire(FLG(F_H + r * 64 + n)) < htgt) { if (++guard > 2000000) __trap(); __nanosleep(H_NS); }
                fence_async_global();
                if (r == 1) named_bar(12, 64);
                if (n) mwait(bb + B_HE, (n - 1) & 1);
                if (lane < 8)
                    asm volatile("cp.async.bulk.shared::cluster.global.mbarrier::complete_tx::bytes.multicast::cluster [%0], [%1], %2, [%3], %4;" ::"r"(sb + O_H + r * 40960 + lane * 5120),
                                 "l"(g_ht + rslot(r, n) * 2560 + lane * 320), "r"(5120), "r"(bb + B_HF + r * 8), "h"(mask) : "memory");
                __syncwarp();
            }
        } else {
            cluster_arrive(); cluster_wait();
            if (head && role == 2) {
#pragma unroll 1
                for (int t = 0; t < NT; t++) {
                    auto put = [&](int l, int n) {
                        asm volatile("cp.async.bulk.global.shared::cta.bulk_group [%0], [%1], %2;" ::"l"(g_ot + (rslot(l, n) * 256 + h * 8) * 64), "r"(sb + O_VT + (t & 1) * 16384 + l * 8192), "r"(8192) : "memory");
                        asm volatile("cp.async.bulk.commit_group;" ::: "memory");
                    };
                    auto publish = [&](int l, int n) {
                        asm volatile("cp.async.bulk.wait_group 0;" ::: "memory");
                        fence_async_global();
                        red_release(FLG(F_O + l * 64 + n) + (h >> 3), 1);
                        GT(true, 200 + l * 64 + n);
                    };
                    if (t < NSEG) {
                        mwait(bb + B_OTF + 8, t & 1);
                        if (lane == 0) { put(0, t); publish(0, t); }
                        __syncwarp();
                    }
                    mwait(bb + B_OTF, t & 1);
                    if (t < NT - 1) named_bar(6, 128);
                    if (lane == 0) {
                        if (t >= LAG) {
                            put(1, t - LAG);
                            asm volatile("cp.async.bulk.wait_group.read 0;" ::: "memory");
                        }
                        mbar_arrive(bb + B_OTE);
                        if (t >= LAG) publish(1, t - LAG);
                    }
                    __syncwarp();
                }
            }
            if (!head && lane == 0) {
#pragma unroll 1
                for (int k = 0; k < 25; k++) {
                    const int rg = k / 5, r0 = rg == 1 ? 256 : 0;
                    mwait(bb + B_OTF + (k & 1) * 8, (k >> 1) & 1);
                    asm volatile("cp.async.bulk.global.shared::cta.bulk_group [%0], [%1], %2;" ::"l"(g_Y + (sp * 5 + k - 5 * rg) * S_LEN + (rg ? rg - 1 : 0) * 512 + r0),
                                 "r"(sb + CV_Y + (k & 1) * 8192 + r0 * 16), "r"(rg < 2 ? 4096 : 8192) : "memory");
                    asm volatile("cp.async.bulk.commit_group;" ::: "memory");
                    asm volatile("cp.async.bulk.wait_group 0;" ::: "memory");
                    mbar_arrive(bb + B_OTE + (k & 1) * 16);
                    fence_async_global();
                    red_release(FLG(F_CV + rg), 1);
                    GT(true, 50 + k);
                }
            }
            __syncwarp();
        }
    }
    cluster_arrive(); cluster_wait();
    if (blockIdx.x == 0 && tid == 0) atomicAdd(&g_epoch, 1);
}
}

namespace ws {
constexpr int OP_SS = 17;
constexpr int P_RING = 0, P_AS = 131072, P_STG = P_AS + 2 * OP_SS * 2048, P_BAR = P_STG + 16384, OP_SMEM = P_BAR + 256;
constexpr int PB_FULL = 0, PB_EMPTY = 128, PB_SF = 144, PB_SE = 176;
static_assert(OP_SMEM <= 232448, "smem");

__global__ void __launch_bounds__(384, 1) op_kernel(const bf16* __restrict__ Wo, const bf16* __restrict__ Bk, const bf16* __restrict__ Bv, const bf16* __restrict__ shiftk) {
    extern __shared__ __align__(1024) unsigned char smem_raw[];
    const int tid = threadIdx.x, warp = __shfl_sync(0xffffffffu, tid >> 5, 0), lane = tid & 31;
    const int nb = blockIdx.x % 5, ks = blockIdx.x / 5;
    const uint32_t sb = smem_u32(smem_raw), bb = sb + P_BAR;
    if (tid == 0) {
        if ((sb & 0xFFFFFFu) != 1024) __trap();
        for (int i = 0; i < 16; i++) mbar_init(bb + PB_FULL + i * 8, 1);
        for (int i = 0; i < 2; i++) mbar_init(bb + PB_EMPTY + i * 8, 2);
        for (int i = 0; i < 4; i++) { mbar_init(bb + PB_SF + i * 8, 4); mbar_init(bb + PB_SE + i * 8, 1); }
        asm volatile("fence.mbarrier_init.release.cluster;" ::: "memory");
    }
    GT(tid == 0, 8);
    __syncthreads();
    if (warp < 4) {
        asm volatile("setmaxnreg.dec.sync.aligned.u32 40;");
        if (warp == 0) {
            named_bar(3, 288);
            GT(lane == 0, 3);
            uint32_t it = 0;
            const int otgt = 8 * (ld_relaxed(&g_epoch) + 1);
#pragma unroll 1
            for (int q = 0; q < 2 * NT; q++) {
                const int l = q & 1, n = (q >> 1) - l * LAG;
                if (n < 0 || n >= NSEG) continue;
                int guard = 0;
                while (ld_acquire(FLG(F_O + l * 64 + n) + ks) < otgt) { if (++guard > 4000000) __trap(); __nanosleep(OP_NS); }
                fence_async_global();
                mwait(bb + PB_EMPTY + (it & 1) * 8, ((it >> 1) & 1) ^ 1);
                if (lane < 8) {
                    const uint32_t fb = bb + PB_FULL + ((it & 1) * 8 + lane) * 8;
                    mbar_expect_tx(fb, 8192);
                    asm volatile("cp.async.bulk.shared::cluster.global.mbarrier::complete_tx::bytes [%0], [%1], %2, [%3];" ::"r"(sb + P_RING + (it & 1) * 65536 + lane * 8192),
                                 "l"(g_ot + (rslot(l, n) * 256 + (ks * 8 + lane) * 8) * 64), "r"(8192), "r"(fb) : "memory");
                }
                __syncwarp();
                it++;
            }
        } else if (warp == 3) {
#pragma unroll 1
            for (int rg = 1; rg < 4; rg++) {
#pragma unroll 1
                for (int u = rg * 640 + blockIdx.x; u < rg * 640 + 640; u += 20) u_half(Bk, Bv, shiftk, u, lane);
                __syncwarp();
                if (lane == 0) red_release(FLG(F_U + rg + 1), 1);
                GT(lane == 0 && rg, 4 + rg);
            }
        } else if (lane == 0) {
            const int cw = warp - 1;
            uint32_t it = 0;
#pragma unroll 1
            for (int q = 0; q < 2 * NT; q++) {
                const int l = q & 1, n = (q >> 1) - l * LAG;
                if (n < 0 || n >= NSEG) continue;
                mwait(bb + PB_SF + cw * 8, it & 1);
                asm volatile("cp.reduce.async.bulk.global.shared::cta.bulk_group.add.f32 [%0], [%1], %2;" ::"l"(g_pt + (rslot(l, n) * 10 + nb * 2 + cw) * 512), "r"(sb + P_STG + cw * 8192), "r"(8192) : "memory");
                asm volatile("cp.async.bulk.commit_group;" ::: "memory");
                asm volatile("cp.async.bulk.wait_group.read 0;" ::: "memory");
                mbar_arrive(bb + PB_SE + cw * 8);
                asm volatile("cp.async.bulk.wait_group 0;" ::: "memory");
                fence_async_global();
                red_release(FLG(F_P + l * 64 + n), 1);
                GT(true, 330 + l * 64 + n);
                it++;
            }
        }
    } else {
        asm volatile("setmaxnreg.inc.sync.aligned.u32 232;");
        const int cw = (warp >> 2) - 1, w4 = warp & 3, t7 = tid & 127;
        uint32_t wa[64 - OP_SS][4];
        {
            const bf16* W = Wo + (size_t)ks * 1024 * DM + nb * 128 + cw * 64 + (t7 & 7) * 8;
            const uint32_t so = (t7 >> 3) * 128 + (((t7 & 7) ^ ((t7 >> 3) & 7)) << 4);
            const uint32_t stg = sb + P_RING + cw * 65536;
            const uint32_t la = stg + ((lane & 7) + (lane >> 4) * 8) * 128 + (((w4 * 2 + ((lane >> 3) & 1)) ^ (lane & 7)) << 4);
#pragma unroll 4
            for (int i = 0; i < 32; i++) cp_async16(stg + i * 2048 + so, W + (size_t)((OP_SS + i) * 16 + (t7 >> 3)) * DM);
            cp_commit();
#pragma unroll 1
            for (int i = 0; i < OP_SS; i++) cp_async16(sb + P_AS + cw * OP_SS * 2048 + i * 2048 + so, W + (size_t)(i * 16 + (t7 >> 3)) * DM);
            cp_commit();
            cp_wait<1>();
            named_bar(1 + cw, 128);
#pragma unroll
            for (int j = 0; j < 32; j++) { const uint4 v = ldsm4t(la + j * 2048); wa[j][0] = v.x; wa[j][1] = v.y; wa[j][2] = v.z; wa[j][3] = v.w; }
            named_bar(1 + cw, 128);
#pragma unroll 1
            for (int i = 0; i < 32 - OP_SS; i++) cp_async16(stg + i * 2048 + so, W + (size_t)((OP_SS + 32 + i) * 16 + (t7 >> 3)) * DM);
            cp_commit();
            cp_wait<0>();
            named_bar(1 + cw, 128);
#pragma unroll
            for (int j = 0; j < 32 - OP_SS; j++) { const uint4 v = ldsm4t(la + j * 2048); wa[32 + j][0] = v.x; wa[32 + j][1] = v.y; wa[32 + j][2] = v.z; wa[32 + j][3] = v.w; }
            fence_async_smem();
            named_bar(3, 288);
        }
        const uint32_t ab = (1024 + P_AS + cw * OP_SS * 2048) >> 4;
        const uint32_t ea = sb + P_STG + cw * 8192 + (lane & 3) * 2048 + (((2 * w4) ^ (lane & 3)) << 5) + (lane >> 2) * 4;
#pragma unroll 1
        for (uint32_t it = 0; it < 2 * NSEG; it++) {
            float acc[16];
            const uint32_t fb = bb + PB_FULL + (it & 1) * 64, par = (it >> 1) & 1;
            const uint32_t ob = opq(((1024 + P_RING) >> 4) + (it & 1) * 4096);
            uint32_t ok = 0;
#pragma unroll
            for (int j = 0; j < 64; j++) {
                if ((j & 7) == 0) {
                    if (j) wg_commit();
                    if (!ok) mslow(fb + j, par);
                    ok = j < 56 ? mtest(fb + j + 8, par) : mtest(bb + PB_SE + cw * 8, (it & 1) ^ 1);
                    if (j == 0) wg_fence();
                }
                const uint64_t db = mkdesc(ob + j * 64, 0x80000020u);
                if (j == 0) wg_n32t_sfirst(acc, mkdesc(ab, 0x40000040u), db);
                else if (j < OP_SS) wg_n32t_s(acc, mkdesc(ab + j * 128, 0x40000040u), db);
                else wg_n32t(acc, wa[j - OP_SS][0], wa[j - OP_SS][1], wa[j - OP_SS][2], wa[j - OP_SS][3], db);
            }
            wg_commit();
            if (!ok) mslow(bb + PB_SE + cw * 8, (it & 1) ^ 1);
            wg_wait<0>();
            if (t7 == 0) mbar_arrive(bb + PB_EMPTY + (it & 1) * 8);
#pragma unroll
            for (int i = 0; i < 16; i++) sts32((ea ^ ((i & 2) << 4)) + ((i >> 2) * 2 + (i & 1)) * 256, __float_as_uint(acc[i]));
            fence_async_smem();
            __syncwarp();
            if (lane == 0) mbar_arrive(bb + PB_SF + cw * 8);
        }
    }
}
}

namespace ws {
static bool usable() {
    static int ok = -1;
    if (ok < 0) {
        cudaFuncSetAttribute(head_kernel, cudaFuncAttributeMaxDynamicSharedMemorySize, HEAD_SMEM);
        cudaFuncSetAttribute(head_kernel, cudaFuncAttributeNonPortableClusterSizeAllowed, 1);
        cudaFuncSetAttribute(op_kernel, cudaFuncAttributeMaxDynamicSharedMemorySize, OP_SMEM);
        cudaLaunchConfig_t cfg = {};
        cfg.gridDim = dim3(NCL * 16); cfg.blockDim = dim3(512); cfg.dynamicSmemBytes = HEAD_SMEM;
        cudaLaunchAttribute at[1];
        at[0].id = cudaLaunchAttributeClusterDimension;
        at[0].val.clusterDim.x = 16; at[0].val.clusterDim.y = 1; at[0].val.clusterDim.z = 1;
        cfg.attrs = at; cfg.numAttrs = 1;
        int n = 0, nsm = 0;
        cudaDeviceGetAttribute(&nsm, cudaDevAttrMultiProcessorCount, 0);
        ok = cudaOccupancyMaxActiveClusters(&n, head_kernel, &cfg) == cudaSuccess && n >= NCL && nsm >= NCL * 16 + 20;
        (void)cudaGetLastError();
    }
    return ok > 0;
}
static void launch_all(void* const* d_in, void* d_out) {
    HeadArgs A;
    A.x = (const bf16*)d_in[0]; A.mem0 = (const bf16*)d_in[1]; A.Wq = (const bf16*)d_in[2]; A.Wk = (const bf16*)d_in[3]; A.Wv = (const bf16*)d_in[4]; A.Wo = (const bf16*)d_in[5];
    A.Bk = (const bf16*)d_in[8]; A.Bv = (const bf16*)d_in[9]; A.shiftk = (const bf16*)d_in[10]; A.ssmk = (const bf16*)d_in[11]; A.ssmD = (const bf16*)d_in[12];
    A.out = (bf16*)d_out; A.h_target = 32;
    cudaStream_t s = cudaStreamPerThread;
    {
        cudaLaunchConfig_t cfg = {};
        cfg.gridDim = dim3(NCL * 16); cfg.blockDim = dim3(512); cfg.dynamicSmemBytes = HEAD_SMEM; cfg.stream = s;
        cudaLaunchAttribute at[2];
        at[0].id = cudaLaunchAttributeClusterDimension;
        at[0].val.clusterDim.x = 16; at[0].val.clusterDim.y = 1; at[0].val.clusterDim.z = 1;
        at[1].id = cudaLaunchAttributeProgrammaticStreamSerialization;
        at[1].val.programmaticStreamSerializationAllowed = 1;
        cfg.attrs = at; cfg.numAttrs = 1;
        cudaLaunchKernelEx(&cfg, head_kernel, A);
    }
    {
        cudaLaunchConfig_t cfg = {};
        cfg.gridDim = dim3(20); cfg.blockDim = dim3(384); cfg.dynamicSmemBytes = OP_SMEM; cfg.stream = s;
        cudaLaunchAttribute at[1];
        at[0].id = cudaLaunchAttributeProgrammaticStreamSerialization;
        at[0].val.programmaticStreamSerializationAllowed = 1;
        cfg.attrs = at; cfg.numAttrs = 1;
        cudaLaunchKernelEx(&cfg, op_kernel, A.Wo, A.Bk, A.Bv, A.shiftk);
    }
}
}

#undef FLG
#undef GT
#undef H_NS
#undef LAGT
#undef LN0_AHEAD
#undef NO_X
#undef OBK
#undef OP_NS
#undef P1A
#undef P1C
#undef POST_NS
#undef REG_G
#undef REG_T
#undef REG_X
#undef RING
#undef SC
#undef SD
#undef TG_STEPS
#undef TS
#undef TV
#undef UNI
#undef WFLY
#undef WR
#undef WTA
#undef XD
namespace ni {

constexpr int S_LEN = 2048;
constexpr int DM = 640;
constexpr int NH = 32;
constexpr int DH = 128;
constexpr int HD = NH * DH;
constexpr int MEMR = 8;
constexpr int SEG = 32;
constexpr int NSEG = S_LEN / SEG;

__device__ __forceinline__ float bf2f(bf16 v) { return __bfloat162float(v); }
__device__ __forceinline__ bf16 f2bf(float v) { return __float2bfloat16_rn(v); }
__device__ __forceinline__ float rbf(float v) { return __bfloat162float(__float2bfloat16_rn(v)); }
__device__ __forceinline__ uint32_t pack2(float a, float b) {
    __nv_bfloat162 t = __floats2bfloat162_rn(a, b);
    return *reinterpret_cast<uint32_t*>(&t);
}
__device__ __forceinline__ uint32_t smem_u32(const void* p) { return (uint32_t)__cvta_generic_to_shared(p); }
__device__ __forceinline__ void ldsm_x4(uint32_t& r0, uint32_t& r1, uint32_t& r2, uint32_t& r3, uint32_t addr) {
    asm volatile("ldmatrix.sync.aligned.m8n8.x4.shared.b16 {%0,%1,%2,%3}, [%4];"
                 : "=r"(r0), "=r"(r1), "=r"(r2), "=r"(r3) : "r"(addr));
}
__device__ __forceinline__ void ldsm_x2(uint32_t& r0, uint32_t& r1, uint32_t addr) {
    asm volatile("ldmatrix.sync.aligned.m8n8.x2.shared.b16 {%0,%1}, [%2];" : "=r"(r0), "=r"(r1) : "r"(addr));
}
__device__ __forceinline__ void ldsm_x4_t(uint32_t& r0, uint32_t& r1, uint32_t& r2, uint32_t& r3, uint32_t addr) {
    asm volatile("ldmatrix.sync.aligned.m8n8.x4.trans.shared.b16 {%0,%1,%2,%3}, [%4];"
                 : "=r"(r0), "=r"(r1), "=r"(r2), "=r"(r3) : "r"(addr));
}
__device__ __forceinline__ void mma16816(float* c, uint32_t a0, uint32_t a1, uint32_t a2, uint32_t a3,
                                         uint32_t b0, uint32_t b1) {
    asm("mma.sync.aligned.m16n8k16.row.col.f32.bf16.bf16.f32 {%0,%1,%2,%3}, {%4,%5,%6,%7}, {%8,%9}, {%0,%1,%2,%3};"
        : "+f"(c[0]), "+f"(c[1]), "+f"(c[2]), "+f"(c[3])
        : "r"(a0), "r"(a1), "r"(a2), "r"(a3), "r"(b0), "r"(b1));
}
__device__ __forceinline__ void cp_async16(uint32_t dst, const void* src) {
    asm volatile("cp.async.cg.shared.global [%0], [%1], 16;" ::"r"(dst), "l"(src));
}
__device__ __forceinline__ void cp_commit() { asm volatile("cp.async.commit_group;"); }
template <int N> __device__ __forceinline__ void cp_wait() { asm volatile("cp.async.wait_group %0;" ::"n"(N)); }
__device__ __forceinline__ uint4 ld_relaxed_v4(const void* p) {
    uint4 v;
    asm volatile("ld.relaxed.gpu.global.v4.u32 {%0,%1,%2,%3}, [%4];"
                 : "=r"(v.x), "=r"(v.y), "=r"(v.z), "=r"(v.w) : "l"(p) : "memory");
    return v;
}
__device__ __forceinline__ void st_relaxed_v4(void* p, uint32_t a, uint32_t b, uint32_t c, uint32_t d) {
    asm volatile("st.relaxed.gpu.global.v4.u32 [%0], {%1,%2,%3,%4};" ::"l"(p), "r"(a), "r"(b), "r"(c), "r"(d) : "memory");
}
__device__ __forceinline__ int ld_acquire(const int* p) {
    int v;
    asm volatile("ld.acquire.gpu.global.u32 %0, [%1];" : "=r"(v) : "l"(p) : "memory");
    return v;
}
__device__ __forceinline__ void mbar_init(uint32_t bar, int count) {
    asm volatile("mbarrier.init.shared::cta.b64 [%0], %1;" ::"r"(bar), "r"(count));
}
__device__ __forceinline__ void mbar_expect_tx(uint32_t bar, uint32_t bytes) {
    asm volatile("mbarrier.arrive.expect_tx.shared::cta.b64 _, [%0], %1;" ::"r"(bar), "r"(bytes) : "memory");
}
__device__ __forceinline__ void mbar_arrive(uint32_t bar) {
    asm volatile("mbarrier.arrive.shared::cta.b64 _, [%0];" ::"r"(bar) : "memory");
}
constexpr int SPIN_LIMIT = 4000000;
__device__ __forceinline__ void mbar_wait_spin(uint32_t bar, uint32_t parity) {
    uint32_t ok = 0;
    int guard = 0;
    while (!ok && ++guard < SPIN_LIMIT) {
        asm volatile(
            "{\n.reg .pred P1;\n"
            "mbarrier.try_wait.parity.shared::cta.b64 P1, [%1], %2;\n"
            "selp.u32 %0, 1, 0, P1;\n}\n"
            : "=r"(ok) : "r"(bar), "r"(parity) : "memory");
    }
}
__device__ __forceinline__ uint32_t mapa(uint32_t addr, uint32_t rank) {
    uint32_t r;
    asm volatile("mapa.shared::cluster.u32 %0, %1, %2;" : "=r"(r) : "r"(addr), "r"(rank));
    return r;
}
__device__ __forceinline__ void st_async_u32(uint32_t addr, uint32_t v, uint32_t bar) {
    asm volatile("st.async.weak.shared::cluster.mbarrier::complete_tx::bytes.b32 [%0], %1, [%2];" ::"r"(addr), "r"(v), "r"(bar) : "memory");
}
__device__ __forceinline__ void st_async_v2(uint32_t addr, uint32_t a, uint32_t b, uint32_t bar) {
    asm volatile("st.async.weak.shared::cluster.mbarrier::complete_tx::bytes.v2.b32 [%0], {%1,%2}, [%3];" ::"r"(addr), "r"(a), "r"(b), "r"(bar) : "memory");
}
__device__ __forceinline__ void cluster_sync_all() {
    asm volatile("barrier.cluster.arrive.release.aligned;\nbarrier.cluster.wait.acquire.aligned;" ::: "memory");
}
__device__ __forceinline__ void named_bar(int id, int n) { asm volatile("bar.sync %0, %1;" ::"r"(id), "r"(n) : "memory"); }

}

namespace ni {
#define CHAIN_LAG 16
constexpr int CL = 16;
constexpr int OWN = DM / CL;
constexpr int NSRC = CL / 2;
constexpr int NCLU = 64 / CL;
constexpr int CSEG = 4;
constexpr int NCHK = NSEG / CSEG;
constexpr int LAG = CHAIN_LAG;
constexpr int NTICK = NSEG + LAG;

constexpr int F_KV = 0, F_MEM = 32, F_H = 64, F_OP = 96, F_CONV = 128, F_U = 130, F_PROG = 132, F_ZERO = 133, F_CNT = 136;
constexpr int NFLAG = 192;
__device__ int g_flags[NFLAG * 32];
#define FLG(i) (g_flags + (i) * 32)
constexpr int CHAIN_THREADS = 384;
__device__ bf16 g_Y[S_LEN * DM];
__device__ bf16 g_U[DM * S_LEN];
__device__ bf16 g_h[2][S_LEN * DM];
__device__ bf16 g_x[S_LEN * DM];
__device__ bf16 g_kv[2][S_LEN * HD];
#define PRING 4
constexpr int PROWS = PRING * 128, PG = 4;
__device__ bf16 g_part[2 * PROWS * PG * DM];
__device__ uint4 g_kvf[2 * NSEG * NH * 256];
__device__ uint32_t g_xc[2 * 2 * CL * NCLU * 8 * OWN];

#define TVAL(i, v)
#define TSTAMP(i)

#define NRQ 36
#define NRW 8
#define PDQ 4
#define PDW1 0
#define PROBE 2
#define PDW 6
constexpr int NSQ = 60 - NRQ, NSW = 20 - NRW;
__host__ __device__ constexpr bool q_smem(int i) { return ((i + 1) * NSQ) / 60 != (i * NSQ) / 60; }
__host__ __device__ constexpr int q_slot(int i) { return q_smem(i) ? (i * NSQ) / 60 : i - (i * NSQ) / 60; }
__host__ __device__ constexpr int w_tile(int i) { return i < 8 ? ((i & 1) ? 0 : 2) : (i < 16 ? (i & 1) : 1); }
__host__ __device__ constexpr int w_k(int i) { return i < 8 ? i / 2 : (i < 16 ? ((i & 1) ? (i - 8) / 2 : 4 + (i - 8) / 2) : i - 12); }
__host__ __device__ constexpr int w_acc(int i) { return (i >= 16 && (i & 1)) ? 3 : w_tile(i); }
__host__ __device__ constexpr bool w_smem(int i) { return i < PDW || NRW == 0 || ((i - PDW + 1) * NRW) / (20 - PDW) == ((i - PDW) * NRW) / (20 - PDW); }
__host__ __device__ constexpr int w_slot(int i) { return i < PDW ? i : (w_smem(i) ? i - ((i - PDW) * NRW) / (20 - PDW) : ((i - PDW) * NRW) / (20 - PDW)); }
constexpr int O_WQ = 0, O_WW = NSQ * 4096, O_REST = (NSQ + NSW) * 4096;
constexpr int C_TOK = 0, C_MEM = 12288, C_RED = C_MEM + 10240, C_Q = C_RED + 6144, C_K = C_Q + 2048, C_V = C_K + 2048, C_S = C_V + 4096,
              C_BAR = C_S + 3072, C_SIZE = 40960;
constexpr int S_BYTES = 3072 + 4096;
constexpr int B_S = 64, B_R = 72, B_T = 96, B_F = 104;
static_assert(C_BAR + 112 <= C_SIZE, "chain block");
constexpr int O_STB = O_REST - 61440;
static_assert((45 * NSQ) / 60 * 4096 <= O_STB && NSQ <= 32, "staging");
struct ChainSmem { unsigned char b[O_REST + 81920 + 1536]; };
static_assert(sizeof(ChainSmem) <= 232448, "smem");

struct ChainArgs {
    CUtensorMap tk[2], tv[2];
    const bf16 *x, *mem0, *Wq, *Wk, *Wv, *Wo;
    int kv_target;
};
__device__ __forceinline__ uint32_t movmat(uint32_t v) {
    uint32_t r;
    asm volatile("movmatrix.sync.aligned.m8n8.trans.b16 %0, %1;" : "=r"(r) : "r"(v));
    return r;
}
__device__ __forceinline__ void named_arrive(int id, int n) { asm volatile("bar.arrive %0, %1;" ::"r"(id), "r"(n) : "memory"); }
__device__ __forceinline__ void red_release(int* p, int v) { asm volatile("red.release.gpu.global.add.u32 [%0], %1;" ::"l"(p), "r"(v) : "memory"); }

#define CVT(i)
__device__ __forceinline__ uint4 lds128(uint32_t a) {
    uint4 v;
    asm volatile("ld.shared.v4.u32 {%0,%1,%2,%3}, [%4];" : "=r"(v.x), "=r"(v.y), "=r"(v.z), "=r"(v.w) : "r"(a));
    return v;
}
__device__ __forceinline__ uint2 lds64(uint32_t a) {
    uint2 v;
    asm volatile("ld.shared.v2.u32 {%0,%1}, [%2];" : "=r"(v.x), "=r"(v.y) : "r"(a));
    return v;
}
__device__ __forceinline__ uint32_t lds32(uint32_t a) {
    uint32_t v;
    asm volatile("ld.shared.u32 %0, [%1];" : "=r"(v) : "r"(a));
    return v;
}
__device__ __forceinline__ void sts64(uint32_t a, uint32_t x, uint32_t y) { asm volatile("st.shared.v2.u32 [%0], {%1,%2};" ::"r"(a), "r"(x), "r"(y) : "memory"); }
__device__ __forceinline__ void sts128(uint32_t a, uint32_t x, uint32_t y, uint32_t z, uint32_t w) {
    asm volatile("st.shared.v4.u32 [%0], {%1,%2,%3,%4};" ::"r"(a), "r"(x), "r"(y), "r"(z), "r"(w) : "memory");
}
__device__ __forceinline__ void st_async_v4(uint32_t addr, uint32_t a, uint32_t b, uint32_t c, uint32_t d, uint32_t bar) {
    asm volatile("st.async.weak.shared::cluster.mbarrier::complete_tx::bytes.v4.b32 [%0], {%1,%2,%3,%4}, [%5];" ::"r"(addr), "r"(a), "r"(b), "r"(c), "r"(d), "r"(bar) : "memory");
}
__device__ __forceinline__ uint2 ld_relaxed_v2(const void* p) {
    uint2 v;
    asm volatile("ld.relaxed.gpu.global.v2.u32 {%0,%1}, [%2];" : "=r"(v.x), "=r"(v.y) : "l"(p) : "memory");
    return v;
}
__device__ __forceinline__ void st_relaxed_v2(void* p, uint32_t a, uint32_t b) {
    asm volatile("st.relaxed.gpu.global.v2.u32 [%0], {%1,%2};" ::"l"(p), "r"(a), "r"(b) : "memory");
}
__device__ __forceinline__ float blo(uint32_t v) { return __uint_as_float(v << 16); }
__device__ __forceinline__ float bhi(uint32_t v) { return __uint_as_float(v & 0xffff0000u); }
__device__ __forceinline__ uint32_t badd2(uint32_t a, uint32_t b) {
    __nv_bfloat162 r = __hadd2(*reinterpret_cast<__nv_bfloat162*>(&a), *reinterpret_cast<__nv_bfloat162*>(&b));
    return *reinterpret_cast<uint32_t*>(&r);
}
__device__ __forceinline__ void mmau(float* c, const uint4& a, uint32_t b0, uint32_t b1) { mma16816(c, a.x, a.y, a.z, a.w, b0, b1); }

__device__ __forceinline__ void stsm_x4_t(uint32_t a, uint32_t r0, uint32_t r1, uint32_t r2, uint32_t r3) {
    asm volatile("stmatrix.sync.aligned.m8n8.x4.trans.shared.b16 [%0], {%1,%2,%3,%4};" ::"r"(a), "r"(r0), "r"(r1), "r"(r2), "r"(r3) : "memory");
}
__device__ __forceinline__ uint4 ldsm4(uint32_t a) { uint4 v; ldsm_x4(v.x, v.y, v.z, v.w, a); return v; }
__device__ __forceinline__ float ex2f(float x) { float y; asm("ex2.approx.ftz.f32 %0, %1;" : "=f"(y) : "f"(x)); return y; }
__device__ __forceinline__ float rcpf(float x) { float y; asm("rcp.approx.ftz.f32 %0, %1;" : "=f"(y) : "f"(x)); return y; }
#define XD 300
__device__ __forceinline__ void xdelay() {
    uint32_t t0, t1;
    asm volatile("mov.u32 %0, %clock;" : "=r"(t0));
    do { asm volatile("mov.u32 %0, %clock;" : "=r"(t1)); } while (t1 - t0 < XD);
}
template <int V> struct IC { static constexpr int value = V; };
__device__ __forceinline__ uint32_t opq(uint32_t x) { uint32_t y; asm volatile("mov.u32 %0, %1;" : "=r"(y) : "r"(x)); return y; }
#define UNI(x) __shfl_sync(0xffffffffu, (uint32_t)(x), 0)
__device__ __forceinline__ uint32_t mtest(uint32_t bar, uint32_t parity) {
    uint32_t ok;
    asm volatile("{\n.reg .pred P1;\nmbarrier.test_wait.parity.shared::cta.b64 P1, [%1], %2;\nselp.u32 %0, 1, 0, P1;\n}\n" : "=r"(ok) : "r"(bar), "r"(parity) : "memory");
    return ok;
}
__device__ __forceinline__ void mwait(uint32_t bar, uint32_t parity) {
    asm volatile(
        "{\n.reg .pred P1;\n.reg .u32 cnt;\n"
        "mbarrier.try_wait.parity.shared::cta.b64 P1, [%0], %1;\n"
        "@P1 bra DONE;\n"
        "mov.u32 cnt, 0;\n"
        "LAB_WAIT:\n"
        "mbarrier.try_wait.parity.shared::cta.b64 P1, [%0], %1;\n"
        "@P1 bra DONE;\n"
        "add.u32 cnt, cnt, 1;\n"
        "setp.lt.u32 P1, cnt, 4000000;\n"
        "@P1 bra LAB_WAIT;\n"
        "DONE:\n}\n" ::"r"(bar), "r"(parity) : "memory");
}

__global__ void __launch_bounds__(CHAIN_THREADS, 1) chain_kernel(const __grid_constant__ ChainArgs A) {
    extern __shared__ __align__(1024) unsigned char smem_raw[];
    const int tid = threadIdx.x, warp = __shfl_sync(0xffffffffu, tid >> 5, 0), lane = tid & 31;
    const int cq = blockIdx.x / CL, r = blockIdx.x % CL;
    const int h = cq * NSRC + (r >> 1), hf = r & 1;
    const uint32_t sb = smem_u32(smem_raw);
    asm volatile("griddepcontrol.launch_dependents;");
    CVT(0);
    if (warp == 8) {
        if (lane < 8) asm volatile("cp.async.bulk.prefetch.L2.global [%0], %1;" ::"l"(A.x + (size_t)(blockIdx.x * 8 + lane) * 2560), "r"(5120) : "memory");
        asm volatile("cp.async.bulk.prefetch.L2.global [%0], %1;" ::"l"((lane < 16 ? A.Wk : A.Wv) + (size_t)(blockIdx.x * 16 + (lane & 15)) * 2560), "r"(5120) : "memory");
        asm volatile("cp.async.bulk.prefetch.L2.global [%0], %1;" ::"l"((lane < 16 ? A.Wq : A.Wo) + (size_t)(blockIdx.x * 16 + (lane & 15)) * 2560), "r"(5120) : "memory");
    }
    CVT(1);
    if (warp < 8) {
        asm volatile("setmaxnreg.inc.sync.aligned.u32 232;");
        const int j = warp & 3, kh = warp >> 2;
        uint4 wr[NRQ + NRW];
        {
            auto load_round = [&](int gi) {
                const uint32_t buf = sb + ((gi & 1) ? O_STB : O_REST);
#pragma unroll
                for (int it = 0; it < 15; it++) {
                    const int i = tid + it * 256;
                    const int pc = i / 1920, rem = i % 1920, row = rem / 24, ch = rem % 24;
                    const int mat = ch >> 3, pi = ((r >> 1) - (2 * gi + pc)) & 7;
                    const bf16* W = mat == 0 ? A.Wq : (mat == 1 ? A.Wk : A.Wv);
                    cp_async16(buf + pc * 30720 + row * 384 + ((ch ^ (row & 7)) << 4), W + (size_t)(pi * 80 + row) * HD + h * DH + hf * 64 + (ch & 7) * 8);
                }
                cp_commit();
            };
            load_round(0);
            load_round(1);
#pragma unroll
            for (int gi = 0; gi < 4; gi++) {
                cp_wait<1>();
                named_bar(1, 256);
                const uint32_t pb = sb + ((gi & 1) ? O_STB : O_REST) + kh * 30720;
                uint4 tmp[8];
#pragma unroll
                for (int u = 0; u < 5; u++)
#pragma unroll
                    for (int tt = 0; tt < 3; tt++) {
                        const int row = u * 16 + (lane & 7) + (lane >> 4) * 8;
                        const int ch = tt * 8 + j * 2 + ((lane >> 3) & 1);
                        uint4 v;
                        ldsm_x4_t(v.x, v.y, v.z, v.w, pb + row * 384 + ((ch ^ (row & 7)) << 4));
                        const int i = (gi * 5 + u) * 3 + tt;
                        if (q_smem(i)) {
                            if (gi == 3) tmp[q_slot(i) & 7] = v;
                            else sts128(sb + O_WQ + q_slot(i) * 4096 + tid * 16, v.x, v.y, v.z, v.w);
                        } else wr[q_slot(i)] = v;
                    }
                named_bar(1, 256);
                if (gi == 3) {
#pragma unroll
                    for (int i = 45; i < 60; i++)
                        if (q_smem(i)) { const uint4 v = tmp[q_slot(i) & 7]; sts128(sb + O_WQ + q_slot(i) * 4096 + tid * 16, v.x, v.y, v.z, v.w); }
                }
                if (gi < 2) load_round(gi + 2);
                else if (gi == 2) {
                    for (int i = tid; i < 128 * 40; i += 256) {
                        const int row = i / 40, ch = i % 40;
                        cp_async16(sb + O_REST + row * 640 + ((ch ^ (row & 7)) << 4), A.Wo + ((size_t)h * DH + row) * DM + hf * 320 + ch * 8);
                    }
                    cp_commit();
                }
            }
            cp_wait<0>();
            named_bar(1, 256);
#pragma unroll
            for (int i = 0; i < 20; i++) {
                const int tl = w_tile(i), et = (w_k(i) + 4 * (warp & 1)) & 7;
                const int row = et * 16 + (lane & 7) + (lane >> 4) * 8;
                const int ch = (warp >> 1) * 10 + (tl == 2 ? 8 : (warp & 1) * 4 + tl * 2) + ((lane >> 3) & 1);
                uint4 v;
                ldsm_x4_t(v.x, v.y, v.z, v.w, sb + O_REST + row * 640 + ((ch ^ (row & 7)) << 4));
                if (w_smem(i)) sts128(sb + O_WW + w_slot(i) * 4096 + tid * 16, v.x, v.y, v.z, v.w);
                else wr[NRQ + w_slot(i)] = v;
            }
            named_bar(1, 256);
            for (int i = tid; i < 2560; i += 256) {
                const int ks = i >> 6, ln = (i >> 1) & 31, wd = i & 1;
                const int pi = ((r >> 1) - ks / 5) & 7;
                const uint32_t v = *reinterpret_cast<const uint32_t*>(A.mem0 + (ln >> 2) * DM + pi * 80 + (ks % 5) * 16 + wd * 8 + (ln & 3) * 2);
                const int o = ks % 5 == 4 ? ks * 256 + wd * 128 + ln * 4 : i * 4;
                asm volatile("st.shared.u32 [%0], %1;" ::"r"(sb + O_REST + C_MEM + o), "r"(v) : "memory");
                asm volatile("st.shared.u32 [%0], %1;" ::"r"(sb + O_REST + C_SIZE + C_MEM + o), "r"(v) : "memory");
            }
            if (tid < 2) {
                const uint32_t bb = sb + O_REST + tid * C_SIZE + C_BAR;
                for (int i = 0; i < 13; i++) mbar_init(bb + i * 8, 1);
                mbar_init(bb + B_F, 4);
                asm volatile("fence.mbarrier_init.release.cluster;" ::: "memory");
                mbar_expect_tx(bb + B_S, S_BYTES);
                for (int i = 0; i < 3; i++) mbar_expect_tx(bb + B_R + i * 8, 2048);
            }
            asm volatile("fence.proxy.async;" ::: "memory");
        }
        CVT(2);
        cluster_sync_all();
        const uint32_t wq_a = sb + O_WQ + tid * 16;
        const uint32_t cb0 = sb + O_REST;
        const uint32_t qk_a = cb0 + j * 512 + (lane & 7) * 16 + (lane < 16 ? C_Q + (lane >> 3) * 256 + kh * 128 : C_K + kh * 256 + ((lane >> 3) & 1) * 128);
        const uint32_t pd = UNI(mapa(sb, (uint32_t)(r ^ 1)) - sb), sd = UNI(mapa(sb, (uint32_t)r) - sb);
        const uint32_t od = UNI(mapa(sb, (uint32_t)(hf * 8 + warp)) - sb);
        const uint32_t oe = UNI(mapa(sb, (uint32_t)(hf * 8 + (warp & 6))) - sb), oo = UNI(mapa(sb, (uint32_t)(hf * 8 + (warp | 1))) - sb);
        const uint32_t u_mem = UNI(cb0 + C_MEM + kh * 1280), u_bm = UNI(cb0 + C_BAR + kh * 8);
        const uint32_t u_v = UNI(cb0 + C_V + hf * 2048 + j * 512 + kh * 256);
        const uint32_t u_ra = UNI(cb0 + C_RED + (r >> 1) * 256);
        const uint32_t u_ob0 = UNI(cb0 + C_Q + (warp & 1) * 1024), u_ob1 = UNI(cb0 + C_Q + ((warp & 1) ^ 1) * 1024);
        const uint32_t u_role = UNI(warp < 3 ? cb0 + C_S + hf * 1536 + warp * 512 : cb0 + C_V + j * 1024);
        const uint32_t t_tok = cb0 + C_TOK + ((lane & 7) + (lane >> 4) * 8) * 128 +
                               (warp < 3 ? warp * 2048 + ((((lane >> 3) & 1) ^ (lane & 7)) << 4) : 4096 + (j >> 1) * 4096 + ((((j & 1) * 4 + ((lane >> 3) & 1)) ^ (lane & 7)) << 4));
        uint4 qb[PDQ];
#pragma unroll
        for (int s = 0; s < PDQ; s++) qb[s] = lds128(wq_a + s * 4096);
        auto tick = [&](auto cc, const int n) {
            constexpr int c = decltype(cc)::value;
            constexpr uint32_t CO = c * C_SIZE;
            const uint32_t cb = cb0 + CO;
            const uint32_t par = (uint32_t)(n & 1);
            const uint32_t l4 = opq(lane * 4), l8 = l4 * 2, l16 = l4 * 4;
            float acc[3][4];
#pragma unroll
            for (int a = 0; a < 3; a++)
#pragma unroll
                for (int i = 0; i < 4; i++) acc[a][i] = 0.f;
            {
                const uint32_t mb = u_mem + CO + l8;
                uint2 bf[3];
                uint32_t ok = 1;
                auto ldb = [&](int ks) {
                    if (ks == 0) mwait(u_bm + CO, par ^ 1);
                    else if (ks % 5 == 0) { if (!ok) mwait(u_bm + CO + (ks / 5) * 16, par ^ 1); }
                    if (ks % 5 == PROBE && ks < 15) ok = mtest(u_bm + CO + (ks / 5 + 1) * 16, par ^ 1);
                    if (ks % 5 == 4) {
                        bf[ks % 3].x = lds32(u_mem + CO + l4 + (ks / 5) * 2560 + 1024);
                        bf[ks % 3].y = lds32(u_mem + CO + l4 + (ks / 5) * 2560 + 1152);
                    } else bf[ks % 3] = lds64(mb + (ks / 5) * 2560 + (ks % 5) * 256);
                };
                ldb(0);
                TSTAMP(c * 12 + 0);
                ldb(1);
#pragma unroll
                for (int ks = 0; ks < 20; ks++) {
                    if (ks + 2 < 20) ldb(ks + 2);
#pragma unroll
                    for (int tt = 0; tt < 3; tt++) {
                        const int i = ks * 3 + tt;
                        if (q_smem(i)) {
                            const int s = q_slot(i);
                            mmau(acc[tt], qb[s % PDQ], bf[ks % 3].x, bf[ks % 3].y);
                            if (s + PDQ < NSQ) qb[s % PDQ] = lds128(wq_a + (s + PDQ) * 4096);
                        } else mmau(acc[tt], wr[q_slot(i)], bf[ks % 3].x, bf[ks % 3].y);
                    }
                }
            }
            TSTAMP(c * 12 + 1);
            stsm_x4_t(opq(qk_a) + CO, pack2(acc[0][0], acc[0][1]), pack2(acc[0][2], acc[0][3]), pack2(acc[1][0], acc[1][1]), pack2(acc[1][2], acc[1][3]));
            const uint32_t v0 = pack2(acc[2][0], acc[2][1]), v1 = pack2(acc[2][2], acc[2][3]);
            if (n == NSEG - 1) {
                sts64(u_v + CO + l8, v0, v1);
                named_bar(1, 256);
                if (kh == 1 && lane == 0) mbar_arrive(cb + C_BAR + B_F);
#pragma unroll
                for (int s = 0; s < PDQ; s++) qb[s] = lds128(wq_a + s * 4096);
                return;
            }
            named_arrive(1, 384);
            st_async_v2(u_v + CO + l8 + pd, v0, v1, cb + C_BAR + B_S + pd);
            st_async_v2(u_v + CO + l8 + sd, v0, v1, cb + C_BAR + B_S + sd);
            uint4 wb[PDW];
            const uint32_t ww_a = wq_a + (O_WW - O_WQ);
            if (warp < 3) {
                uint4 kb[4];
                const uint32_t t_tk = opq(t_tok);
                mwait(cb + C_BAR + B_T, par);
#pragma unroll
                for (int i = 0; i < 4; i++) kb[i] = ldsm4((t_tk ^ (i << 5)) + CO);
                named_bar(1, 384);
                uint4 qa[4];
#pragma unroll
                for (int i = 0; i < 4; i++) qa[i] = ldsm4(cb + l16 + C_Q + i * 512);
                if (warp == 2) {
#pragma unroll
                    for (int i = 0; i < 4; i++) kb[i] = ldsm4(cb + l16 + C_K + i * 512);
                }
                float s0[4][4], s1[4][4];
#pragma unroll
                for (int i = 0; i < 4; i++) {
#pragma unroll
                    for (int q = 0; q < 4; q++) s0[i][q] = s1[i][q] = 0.f;
                    mmau(s0[i], qa[i], kb[i].x, kb[i].y);
                    mmau(s1[i], qa[i], kb[i].z, kb[i].w);
                }
                const float a0 = ((s0[0][0] + s0[0][2]) + (s0[1][0] + s0[1][2])) + ((s0[2][0] + s0[2][2]) + (s0[3][0] + s0[3][2]));
                const float a1 = ((s0[0][1] + s0[0][3]) + (s0[1][1] + s0[1][3])) + ((s0[2][1] + s0[2][3]) + (s0[3][1] + s0[3][3]));
                const float b0 = ((s1[0][0] + s1[0][2]) + (s1[1][0] + s1[1][2])) + ((s1[2][0] + s1[2][2]) + (s1[3][0] + s1[3][2]));
                const float b1 = ((s1[0][1] + s1[0][3]) + (s1[1][1] + s1[1][3])) + ((s1[2][1] + s1[2][3]) + (s1[3][1] + s1[3][3]));
                const uint32_t so = u_role + CO + l16, bs = cb + C_BAR + B_S;
                const float c0 = warp == 2 ? a0 + b0 : a0, c1 = warp == 2 ? a1 + b1 : a1;
                st_async_v4(so + pd, __float_as_uint(c0), __float_as_uint(c1), __float_as_uint(b0), __float_as_uint(b1), bs + pd);
                st_async_v4(so + sd, __float_as_uint(c0), __float_as_uint(c1), __float_as_uint(b0), __float_as_uint(b1), bs + sd);
                TSTAMP(c * 12 + 2);
#pragma unroll
                for (int s = 0; s < PDW; s++) wb[s] = lds128(ww_a + s * 4096);
            } else if (warp == 3) {
                named_bar(1, 384);
                if (lane < 8) mbar_expect_tx(cb + C_BAR + l8, 1280);
#pragma unroll
                for (int s = 0; s < PDW; s++) wb[s] = lds128(ww_a + s * 4096);
            } else {
                mwait(cb + C_BAR + B_T, par);
                uint4 va[2][2];
                const uint32_t t_tk = opq(t_tok);
#pragma unroll
                for (int e = 0; e < 2; e++)
#pragma unroll
                    for (int k = 0; k < 2; k++)
                        ldsm_x4_t(va[e][k].x, va[e][k].y, va[e][k].z, va[e][k].w, (t_tk ^ (e << 5)) + CO + k * 2048);
#pragma unroll
                for (int s2 = 0; s2 < PDW1; s2++) wb[s2] = lds128(ww_a + s2 * 4096);
                mwait(cb + C_BAR + B_S, par);
                TSTAMP(c * 12 + 3);
                const uint32_t xa = cb + l16 + C_S;
                const uint4 x0 = lds128(xa), y0 = lds128(xa + 1536), x1 = lds128(xa + 512), y1 = lds128(xa + 512 + 1536);
                const uint2 x2 = lds64(xa + 1024), y2 = lds64(xa + 1024 + 1536);
                const uint32_t fv = u_role + CO + l8;
                const float cs = 0.08838834764831845f * 1.4426950408889634f;
                float s[10];
                s[8] = __uint_as_float(x2.x) + __uint_as_float(y2.x); s[9] = __uint_as_float(x2.y) + __uint_as_float(y2.y);
                s[0] = __uint_as_float(x0.x) + __uint_as_float(y0.x); s[1] = __uint_as_float(x0.y) + __uint_as_float(y0.y);
                s[2] = __uint_as_float(x0.z) + __uint_as_float(y0.z); s[3] = __uint_as_float(x0.w) + __uint_as_float(y0.w);
                s[4] = __uint_as_float(x1.x) + __uint_as_float(y1.x); s[5] = __uint_as_float(x1.y) + __uint_as_float(y1.y);
                s[6] = __uint_as_float(x1.z) + __uint_as_float(y1.z); s[7] = __uint_as_float(x1.w) + __uint_as_float(y1.w);
                float mx = fmaxf(fmaxf(fmaxf(s[0], s[1]), fmaxf(s[2], s[3])), fmaxf(fmaxf(fmaxf(s[4], s[5]), fmaxf(s[6], s[7])), fmaxf(s[8], s[9])));
                const float m1 = __shfl_xor_sync(0xffffffffu, mx, 1), m2 = __shfl_xor_sync(0xffffffffu, mx, 2), m3 = __shfl_xor_sync(0xffffffffu, mx, 3);
                const uint2 vm00 = lds64(fv), vm01 = lds64(fv + 256), vm10 = lds64(fv + 512), vm11 = lds64(fv + 768);
                const uint4 vm0 = make_uint4(vm00.x, vm00.y, vm01.x, vm01.y), vm1 = make_uint4(vm10.x, vm10.y, vm11.x, vm11.y);
                mx = fmaxf(fmaxf(mx, m1), fmaxf(m2, m3)) * -cs;
                uint32_t pb[5];
                pb[4] = pack2(ex2f(fmaf(s[8], cs, mx)), ex2f(fmaf(s[9], cs, mx)));
#pragma unroll
                for (int i = 0; i < 4; i++) pb[i] = pack2(ex2f(fmaf(s[2 * i], cs, mx)), ex2f(fmaf(s[2 * i + 1], cs, mx)));
                float o[3][4];
#pragma unroll
                for (int i = 0; i < 4; i++) { o[0][i] = o[1][i] = o[2][i] = 0.f; }
                const uint32_t one2 = 0x3F803F80u;
                mma16816(o[2], one2, one2, one2, one2, pb[4], 0u);
                mmau(o[0], vm0, pb[4], pb[4]);
                mmau(o[1], vm1, pb[4], pb[4]);
                mma16816(o[2], one2, one2, one2, one2, pb[0], pb[1]);
                mmau(o[0], va[0][0], pb[0], pb[1]);
                mmau(o[1], va[1][0], pb[0], pb[1]);
                mma16816(o[2], one2, one2, one2, one2, pb[2], pb[3]);
                mmau(o[0], va[0][1], pb[2], pb[3]);
                mmau(o[1], va[1][1], pb[2], pb[3]);
                const float r0 = rcpf(o[2][0]), r1 = rcpf(o[2][1]);
                stsm_x4_t(cb + l16 + C_Q + j * 512, pack2(o[0][0] * r0, o[0][1] * r1), pack2(o[0][2] * r0, o[0][3] * r1), pack2(o[1][0] * r0, o[1][1] * r1), pack2(o[1][2] * r0, o[1][3] * r1));
                named_arrive(2, 384);
                TSTAMP(c * 12 + 4);
#pragma unroll
                for (int s2 = PDW1; s2 < PDW; s2++) wb[s2] = lds128(ww_a + s2 * 4096);
                if (lane == 0) mbar_arrive(cb + C_BAR + B_F);
                if (warp == 4 && lane == 0) mbar_expect_tx(cb + C_BAR + B_S, S_BYTES);
            }
            named_bar(2, 384);
            TSTAMP(c * 12 + 5);
            {
                uint4 ob[4];
                ob[0] = ldsm4(u_ob0 + CO + l16); ob[1] = ldsm4(u_ob0 + CO + l16 + 512);
                ob[2] = ldsm4(u_ob1 + CO + l16); ob[3] = ldsm4(u_ob1 + CO + l16 + 512);
                float d[4][4];
#pragma unroll
                for (int a = 0; a < 4; a++)
#pragma unroll
                    for (int i = 0; i < 4; i++) d[a][i] = 0.f;
                const uint32_t ra = u_ra + CO + l8, rb = cb + C_BAR + B_R;
#pragma unroll
                for (int i = 0; i < 20; i++) {
                    const int k = w_k(i), ac = w_acc(i);
                    const uint32_t b0 = (k & 1) ? ob[k >> 1].z : ob[k >> 1].x, b1 = (k & 1) ? ob[k >> 1].w : ob[k >> 1].y;
                    if (w_smem(i)) {
                        const int s = w_slot(i);
                        mmau(d[ac], wb[s % PDW], b0, b1);
                        if (s + PDW < NSW) wb[s % PDW] = lds128(ww_a + (s + PDW) * 4096);
                    } else mmau(d[ac], wr[NRQ + w_slot(i)], b0, b1);
                    if (i == 9) {
                        const uint32_t rs = u_ra + CO + l4 + 4096 + (warp & 1) * 128;
                        st_async_u32(rs + oe, pack2(d[2][0], d[2][1]), rb + 16 + oe);
                        st_async_u32(rs + oo, pack2(d[2][2], d[2][3]), rb + 16 + oo);
                    }
                    if (i == 17) st_async_v2(ra + od, pack2(d[0][0], d[0][1]), pack2(d[0][2], d[0][3]), rb + od);
                }
                st_async_v2(ra + 2048 + od, pack2(d[1][0] + d[3][0], d[1][1] + d[3][1]), pack2(d[1][2] + d[3][2], d[1][3] + d[3][3]), rb + 8 + od);
                TSTAMP(c * 12 + 6);
#pragma unroll
                for (int s = 0; s < PDQ; s++) qb[s] = lds128(wq_a + s * 4096);
            }
        };
#pragma unroll 1
        for (int t = 0; t < NTICK; t++) {
            if (t < NSEG) tick(IC<0>{}, t);
            if (t >= LAG) tick(IC<1>{}, t - LAG);
        }
    } else {
        asm volatile("setmaxnreg.dec.sync.aligned.u32 40;");
        const int s = warp - 8;
        cluster_sync_all();
        if (s < 3) {
#pragma unroll 1
            for (int hs = 0; hs < 2 * NTICK; hs++) {
                const int c = hs & 1, t = hs >> 1;
                const int n = t - c * LAG;
                if (n < 0 || n >= NSEG - 1) continue;
                const uint32_t cb = sb + O_REST + c * C_SIZE;
                const uint32_t par = (uint32_t)(n & 1);
                const uint32_t tag = (uint32_t)(n % 13) + 1u;
                uint32_t* xb = g_xc + (size_t)((c * 2 + par) * CL + r) * (NCLU * 320) + s * 128;
                const uint32_t ra = cb + C_RED + s * 2048 + lane * (s < 2 ? 8 : 4);
                mwait(cb + C_BAR + B_R + s * 8, par);
                TSTAMP(c * 12 + 7);
                uint4 p[4];
                if (s < 2) {
#pragma unroll
                    for (int i = 0; i < 4; i++) {
                        const uint2 a = lds64(ra + i * 512), b = lds64(ra + i * 512 + 256);
                        p[i] = make_uint4(a.x, a.y, b.x, b.y);
                    }
                } else {
#pragma unroll
                    for (int i = 0; i < 4; i++) p[i] = make_uint4(lds32(ra + i * 512), lds32(ra + i * 512 + 128), lds32(ra + i * 512 + 256), lds32(ra + i * 512 + 384));
                }
                if (lane == 0) mbar_expect_tx(cb + C_BAR + B_R + s * 8, 2048);
                uint32_t m0, m1;
                if (s < 2) {
                    float f0 = 0.f, f1 = 0.f, f2 = 0.f, f3 = 0.f;
#pragma unroll
                    for (int i = 0; i < 4; i++) {
                        f0 += blo(p[i].x) + blo(p[i].z); f1 += bhi(p[i].x) + bhi(p[i].z);
                        f2 += blo(p[i].y) + blo(p[i].w); f3 += bhi(p[i].y) + bhi(p[i].w);
                    }
                    xb += lane * 4;
                    const uint32_t u0 = (__float_as_uint(f0) & ~0xFu) | tag, u1 = (__float_as_uint(f1) & ~0xFu) | tag;
                    const uint32_t u2 = (__float_as_uint(f2) & ~0xFu) | tag, u3 = (__float_as_uint(f3) & ~0xFu) | tag;
                    st_relaxed_v4(xb + cq * 320, u0, u1, u2, u3);
                    TSTAMP(c * 12 + 8);
                    xdelay();
                    uint4 x[NCLU];
#pragma unroll
                    for (int k = 0; k < NCLU; k++) x[k] = make_uint4(u0, u1, u2, u3);
                    int guard = 0;
                    bool first = true;
                    while (true) {
                        bool ok = true;
#pragma unroll
                        for (int k = 0; k < NCLU; k++) {
                            const bool okk = k == cq || (!first && ((x[k].x ^ tag) | (x[k].y ^ tag) | (x[k].z ^ tag) | (x[k].w ^ tag)) << 28 == 0);
                            if (!okk) { x[k] = ld_relaxed_v4(xb + k * 320); ok = false; }
                        }
                        first = false;
                        if (__all_sync(0xffffffffu, ok) || ++guard > SPIN_LIMIT) break;
                    }
                    TVAL(c * 12 + 11, guard);
                    f0 = f1 = f2 = f3 = 0.f;
#pragma unroll
                    for (int k = 0; k < NCLU; k++) {
                        f0 += __uint_as_float(x[k].x & ~0xFu); f1 += __uint_as_float(x[k].y & ~0xFu);
                        f2 += __uint_as_float(x[k].z & ~0xFu); f3 += __uint_as_float(x[k].w & ~0xFu);
                    }
                    m0 = movmat(pack2(f0, f1)); m1 = movmat(pack2(f2, f3));
                } else {
                    float f0 = 0.f, f1 = 0.f;
#pragma unroll
                    for (int i = 0; i < 4; i++) {
                        f0 += (blo(p[i].x) + blo(p[i].y)) + (blo(p[i].z) + blo(p[i].w));
                        f1 += (bhi(p[i].x) + bhi(p[i].y)) + (bhi(p[i].z) + bhi(p[i].w));
                    }
                    xb += lane * 2;
                    const uint32_t u0 = (__float_as_uint(f0) & ~0xFu) | tag, u1 = (__float_as_uint(f1) & ~0xFu) | tag;
                    st_relaxed_v2(xb + cq * 320, u0, u1);
                    TSTAMP(c * 12 + 8);
                    xdelay();
                    uint2 x[NCLU];
#pragma unroll
                    for (int k = 0; k < NCLU; k++) x[k] = make_uint2(u0, u1);
                    int guard = 0;
                    bool first = true;
                    while (true) {
                        bool ok = true;
#pragma unroll
                        for (int k = 0; k < NCLU; k++) {
                            const bool okk = k == cq || (!first && ((x[k].x ^ tag) | (x[k].y ^ tag)) << 28 == 0);
                            if (!okk) { x[k] = ld_relaxed_v2(xb + k * 320); ok = false; }
                        }
                        first = false;
                        if (__all_sync(0xffffffffu, ok) || ++guard > SPIN_LIMIT) break;
                    }
                    TVAL(c * 12 + 11, guard);
                    f0 = f1 = 0.f;
#pragma unroll
                    for (int k = 0; k < NCLU; k++) { f0 += __uint_as_float(x[k].x & ~0xFu); f1 += __uint_as_float(x[k].y & ~0xFu); }
                    m0 = movmat(pack2(f0, f1)); m1 = 0;
                }
                TSTAMP(c * 12 + 9);
                const uint32_t ma = cb + C_MEM + (s < 2 ? lane * 8 + (hf * 2 + s) * 256 : 1024 + hf * 128 + lane * 4), bm = cb + C_BAR;
                if (s < 2) {
#pragma unroll
                    for (int G = 0; G < 8; G++)
#pragma unroll
                        for (int b = 0; b < 2; b++) {
                            const uint32_t dd = mapa(sb, (uint32_t)(((r + 2 * G) & 15) ^ b)) - sb;
                            st_async_v2(ma + G * 1280 + dd, m0, m1, bm + G * 8 + dd);
                        }
                } else {
#pragma unroll
                    for (int G = 0; G < 8; G++)
#pragma unroll
                        for (int b = 0; b < 2; b++) {
                            const uint32_t dd = mapa(sb, (uint32_t)(((r + 2 * G) & 15) ^ b)) - sb;
                            st_async_u32(ma + G * 1280 + dd, m0, bm + G * 8 + dd);
                        }
                }
                TSTAMP(c * 12 + 10);
            }
        } else {
            auto fetch = [&](int c, int seg) {
                if (lane == 0) {
                    if (seg % CSEG == 0) {
                        int guard = 0;
                        while (ld_acquire(FLG(F_KV + c * NCHK + seg / CSEG)) < A.kv_target && ++guard < SPIN_LIMIT) __nanosleep(64);
                    }
                    asm volatile("fence.proxy.async;" ::: "memory");
                    const uint32_t cb = sb + O_REST + c * C_SIZE;
                    const uint32_t bt = cb + C_BAR + B_T, d = cb + C_TOK;
                    mbar_expect_tx(bt, 12288);
                    const CUtensorMap* mk = &A.tk[c];
                    const CUtensorMap* mv = &A.tv[c];
                    asm volatile("cp.async.bulk.tensor.2d.shared::cluster.global.mbarrier::complete_tx::bytes [%0], [%1, {%3, %4}], [%2];" ::"r"(d),
                                 "l"(mk), "r"(bt), "r"(h * DH + hf * 64), "r"(seg * SEG) : "memory");
#pragma unroll
                    for (int i = 0; i < 2; i++)
                        asm volatile("cp.async.bulk.tensor.2d.shared::cluster.global.mbarrier::complete_tx::bytes [%0], [%1, {%3, %4}], [%2];" ::"r"(d + 4096 + i * 4096),
                                     "l"(mv), "r"(bt), "r"(h * DH + i * 64), "r"(seg * SEG) : "memory");
                }
                __syncwarp();
            };
            fetch(0, 0);
#pragma unroll 1
            for (int hs = 0; hs < 2 * NTICK; hs++) {
                const int c = hs & 1, t = hs >> 1;
                const int n = t - c * LAG;
                if (n < -1 || n >= NSEG) continue;
                if (n >= 0) {
                    const uint32_t cb = sb + O_REST + c * C_SIZE;
                    mwait(cb + C_BAR + B_F, (uint32_t)(n & 1));
                    uint4* fd = g_kvf + (size_t)((c * NSEG + n) * NH + h) * 256 + hf * 64 + lane;
#pragma unroll
                    for (int i = 0; i < 2; i++) {
                        const uint4 k0 = ldsm4(cb + C_K + i * 1024 + lane * 16), k1 = ldsm4(cb + C_K + i * 1024 + 512 + lane * 16);
                        fd[i * 32] = make_uint4(badd2(k0.x, k0.z), badd2(k0.y, k0.w), badd2(k1.x, k1.z), badd2(k1.y, k1.w));
                        const uint32_t va = cb + C_V + hf * 2048 + i * 1024 + lane * 8;
                        const uint2 v0 = lds64(va), v1 = lds64(va + 256), v2 = lds64(va + 512), v3 = lds64(va + 768);
                        fd[128 + i * 32] = make_uint4(badd2(v0.x, v1.x), badd2(v0.y, v1.y), badd2(v2.x, v3.x), badd2(v2.y, v3.y));
                    }
                    if (blockIdx.x == 0 && lane == 0 && (c == 0 || t >= NSEG)) asm volatile("st.relaxed.gpu.global.u32 [%0], %1;" ::"l"(FLG(F_PROG)), "r"(t + 1) : "memory");
                    if ((n % CSEG) == CSEG - 1) {
                        asm volatile("fence.proxy.async;" ::: "memory");
                        __syncwarp();
                        if (lane == 0) { red_release(FLG(F_MEM + c * NCHK + n / CSEG), 1); }
                    }
                }
                if (n + 1 < NSEG - 1) fetch(c, n + 1);
            }
        }
    }
    cluster_sync_all();
}
}

namespace ni {
constexpr int KV_TGT = 32, MEM_TGT = 64, OP_TGT = 16, CONV_TGT = 80, H_TGT = 128;
constexpr int PDIST = (LAG + 3) / 4;
#define QA_PRE 3
#define KV1_W 5
#define KV1_N 16
static_assert(QA_PRE < 4, "inputs of the chunk must be complete");
#define SPLAN 0x102030
#define URGENT 1
#define POST_NS 40

#define ELECT "{\n.reg .pred p;\nelect.sync _|p, 0xffffffff;\n@p "
__device__ __forceinline__ void tma_load_2d(uint32_t dst, const CUtensorMap* map, uint32_t bar, int c0, int c1) {
    asm volatile(ELECT "cp.async.bulk.tensor.2d.shared::cluster.global.mbarrier::complete_tx::bytes [%0], [%1, {%3, %4}], [%2];\n}" ::"r"(dst),
                 "l"(map), "r"(bar), "r"(c0), "r"(c1) : "memory");
}
__device__ __forceinline__ void tma_load_2d_mc(uint32_t dst, const CUtensorMap* map, uint32_t bar, int c0, int c1) {
    asm volatile(ELECT "cp.async.bulk.tensor.2d.shared::cluster.global.mbarrier::complete_tx::bytes.multicast::cluster [%0], [%1, {%3, %4}], [%2], %5;\n}" ::"r"(dst),
                 "l"(map), "r"(bar), "r"(c0), "r"(c1), "h"((unsigned short)3) : "memory");
}
__device__ __forceinline__ void tma_load_3d(uint32_t dst, const CUtensorMap* map, uint32_t bar, int c1, int c2) {
    asm volatile(ELECT "cp.async.bulk.tensor.3d.shared::cluster.global.mbarrier::complete_tx::bytes [%0], [%1, {%5, %3, %4}], [%2];\n}" ::"r"(dst),
                 "l"(map), "r"(bar), "r"(c1), "r"(c2), "r"(0) : "memory");
}
__device__ __forceinline__ void tma_load_3d_mc(uint32_t dst, const CUtensorMap* map, uint32_t bar, int c1, int c2) {
    asm volatile(ELECT "cp.async.bulk.tensor.3d.shared::cluster.global.mbarrier::complete_tx::bytes.multicast::cluster [%0], [%1, {%6, %3, %4}], [%2], %5;\n}" ::"r"(dst),
                 "l"(map), "r"(bar), "r"(c1), "r"(c2), "h"((unsigned short)3), "r"(0) : "memory");
}
__device__ __forceinline__ void bulk_load(uint32_t dst, const void* src, uint32_t bytes, uint32_t bar) {
    asm volatile(ELECT "cp.async.bulk.shared::cluster.global.mbarrier::complete_tx::bytes [%0], [%1], %2, [%3];\n}" ::"r"(dst), "l"(src), "r"(bytes), "r"(bar) : "memory");
}
__device__ __forceinline__ void expect_tx1(uint32_t bar, uint32_t bytes) {
    asm volatile(ELECT "mbarrier.arrive.expect_tx.shared::cta.b64 _, [%0], %1;\n}" ::"r"(bar), "r"(bytes) : "memory");
}
__device__ __forceinline__ void wg_fence() { asm volatile("wgmma.fence.sync.aligned;" ::: "memory"); }
__device__ __forceinline__ void wg_commit() { asm volatile("wgmma.commit_group.sync.aligned;" ::: "memory"); }
template <int N> __device__ __forceinline__ void wg_wait() { asm volatile("wgmma.wait_group.sync.aligned %0;" ::"n"(N) : "memory"); }
__device__ __forceinline__ uint64_t make_desc(uint32_t addr, uint32_t lbo, uint32_t sbo) {
    return (uint64_t)((addr & 0x3FFFF) >> 4) | ((uint64_t)((lbo & 0x3FFFF) >> 4) << 16) |
           ((uint64_t)((sbo & 0x3FFFF) >> 4) << 32) | (1ull << 62);
}
__device__ __forceinline__ void wgmma_m64n256k16(float* d, uint64_t da, uint64_t db) {
    asm volatile("{\n.reg .pred p;\nsetp.ne.b32 p, 1, 0;\n"
                 "wgmma.mma_async.sync.aligned.m64n256k16.f32.bf16.bf16 {%0, %1, %2, %3, %4, %5, %6, %7, %8, %9, %10, %11, %12, %13, %14, %15, %16, %17, %18, %19, %20, %21, %22, %23, %24, %25, %26, %27, %28, %29, %30, %31, %32, %33, %34, %35, %36, %37, %38, %39, %40, %41, %42, %43, %44, %45, %46, %47, %48, %49, %50, %51, %52, %53, %54, %55, %56, %57, %58, %59, %60, %61, %62, %63, %64, %65, %66, %67, %68, %69, %70, %71, %72, %73, %74, %75, %76, %77, %78, %79, %80, %81, %82, %83, %84, %85, %86, %87, %88, %89, %90, %91, %92, %93, %94, %95, %96, %97, %98, %99, %100, %101, %102, %103, %104, %105, %106, %107, %108, %109, %110, %111, %112, %113, %114, %115, %116, %117, %118, %119, %120, %121, %122, %123, %124, %125, %126, %127}, %128, %129, p, 1, 1, 0, 1;\n}\n"
                 : "+f"(d[0]), "+f"(d[1]), "+f"(d[2]), "+f"(d[3]), "+f"(d[4]), "+f"(d[5]), "+f"(d[6]), "+f"(d[7]), "+f"(d[8]), "+f"(d[9]), "+f"(d[10]), "+f"(d[11]), "+f"(d[12]), "+f"(d[13]), "+f"(d[14]), "+f"(d[15]), "+f"(d[16]), "+f"(d[17]), "+f"(d[18]), "+f"(d[19]), "+f"(d[20]), "+f"(d[21]), "+f"(d[22]), "+f"(d[23]), "+f"(d[24]), "+f"(d[25]), "+f"(d[26]), "+f"(d[27]), "+f"(d[28]), "+f"(d[29]), "+f"(d[30]), "+f"(d[31]), "+f"(d[32]), "+f"(d[33]), "+f"(d[34]), "+f"(d[35]), "+f"(d[36]), "+f"(d[37]), "+f"(d[38]), "+f"(d[39]), "+f"(d[40]), "+f"(d[41]), "+f"(d[42]), "+f"(d[43]), "+f"(d[44]), "+f"(d[45]), "+f"(d[46]), "+f"(d[47]), "+f"(d[48]), "+f"(d[49]), "+f"(d[50]), "+f"(d[51]), "+f"(d[52]), "+f"(d[53]), "+f"(d[54]), "+f"(d[55]), "+f"(d[56]), "+f"(d[57]), "+f"(d[58]), "+f"(d[59]), "+f"(d[60]), "+f"(d[61]), "+f"(d[62]), "+f"(d[63]), "+f"(d[64]), "+f"(d[65]), "+f"(d[66]), "+f"(d[67]), "+f"(d[68]), "+f"(d[69]), "+f"(d[70]), "+f"(d[71]), "+f"(d[72]), "+f"(d[73]), "+f"(d[74]), "+f"(d[75]), "+f"(d[76]), "+f"(d[77]), "+f"(d[78]), "+f"(d[79]), "+f"(d[80]), "+f"(d[81]), "+f"(d[82]), "+f"(d[83]), "+f"(d[84]), "+f"(d[85]), "+f"(d[86]), "+f"(d[87]), "+f"(d[88]), "+f"(d[89]), "+f"(d[90]), "+f"(d[91]), "+f"(d[92]), "+f"(d[93]), "+f"(d[94]), "+f"(d[95]), "+f"(d[96]), "+f"(d[97]), "+f"(d[98]), "+f"(d[99]), "+f"(d[100]), "+f"(d[101]), "+f"(d[102]), "+f"(d[103]), "+f"(d[104]), "+f"(d[105]), "+f"(d[106]), "+f"(d[107]), "+f"(d[108]), "+f"(d[109]), "+f"(d[110]), "+f"(d[111]), "+f"(d[112]), "+f"(d[113]), "+f"(d[114]), "+f"(d[115]), "+f"(d[116]), "+f"(d[117]), "+f"(d[118]), "+f"(d[119]), "+f"(d[120]), "+f"(d[121]), "+f"(d[122]), "+f"(d[123]), "+f"(d[124]), "+f"(d[125]), "+f"(d[126]), "+f"(d[127])
                 : "l"(da), "l"(db));
}
__device__ __forceinline__ void wgmma_m64n256k16_first(float* d, uint64_t da, uint64_t db) {
    asm volatile("{\n.reg .pred p;\nsetp.ne.b32 p, 0, 0;\n"
                 "wgmma.mma_async.sync.aligned.m64n256k16.f32.bf16.bf16 {%0, %1, %2, %3, %4, %5, %6, %7, %8, %9, %10, %11, %12, %13, %14, %15, %16, %17, %18, %19, %20, %21, %22, %23, %24, %25, %26, %27, %28, %29, %30, %31, %32, %33, %34, %35, %36, %37, %38, %39, %40, %41, %42, %43, %44, %45, %46, %47, %48, %49, %50, %51, %52, %53, %54, %55, %56, %57, %58, %59, %60, %61, %62, %63, %64, %65, %66, %67, %68, %69, %70, %71, %72, %73, %74, %75, %76, %77, %78, %79, %80, %81, %82, %83, %84, %85, %86, %87, %88, %89, %90, %91, %92, %93, %94, %95, %96, %97, %98, %99, %100, %101, %102, %103, %104, %105, %106, %107, %108, %109, %110, %111, %112, %113, %114, %115, %116, %117, %118, %119, %120, %121, %122, %123, %124, %125, %126, %127}, %128, %129, p, 1, 1, 0, 1;\n}\n"
                 : "=f"(d[0]), "=f"(d[1]), "=f"(d[2]), "=f"(d[3]), "=f"(d[4]), "=f"(d[5]), "=f"(d[6]), "=f"(d[7]), "=f"(d[8]), "=f"(d[9]), "=f"(d[10]), "=f"(d[11]), "=f"(d[12]), "=f"(d[13]), "=f"(d[14]), "=f"(d[15]), "=f"(d[16]), "=f"(d[17]), "=f"(d[18]), "=f"(d[19]), "=f"(d[20]), "=f"(d[21]), "=f"(d[22]), "=f"(d[23]), "=f"(d[24]), "=f"(d[25]), "=f"(d[26]), "=f"(d[27]), "=f"(d[28]), "=f"(d[29]), "=f"(d[30]), "=f"(d[31]), "=f"(d[32]), "=f"(d[33]), "=f"(d[34]), "=f"(d[35]), "=f"(d[36]), "=f"(d[37]), "=f"(d[38]), "=f"(d[39]), "=f"(d[40]), "=f"(d[41]), "=f"(d[42]), "=f"(d[43]), "=f"(d[44]), "=f"(d[45]), "=f"(d[46]), "=f"(d[47]), "=f"(d[48]), "=f"(d[49]), "=f"(d[50]), "=f"(d[51]), "=f"(d[52]), "=f"(d[53]), "=f"(d[54]), "=f"(d[55]), "=f"(d[56]), "=f"(d[57]), "=f"(d[58]), "=f"(d[59]), "=f"(d[60]), "=f"(d[61]), "=f"(d[62]), "=f"(d[63]), "=f"(d[64]), "=f"(d[65]), "=f"(d[66]), "=f"(d[67]), "=f"(d[68]), "=f"(d[69]), "=f"(d[70]), "=f"(d[71]), "=f"(d[72]), "=f"(d[73]), "=f"(d[74]), "=f"(d[75]), "=f"(d[76]), "=f"(d[77]), "=f"(d[78]), "=f"(d[79]), "=f"(d[80]), "=f"(d[81]), "=f"(d[82]), "=f"(d[83]), "=f"(d[84]), "=f"(d[85]), "=f"(d[86]), "=f"(d[87]), "=f"(d[88]), "=f"(d[89]), "=f"(d[90]), "=f"(d[91]), "=f"(d[92]), "=f"(d[93]), "=f"(d[94]), "=f"(d[95]), "=f"(d[96]), "=f"(d[97]), "=f"(d[98]), "=f"(d[99]), "=f"(d[100]), "=f"(d[101]), "=f"(d[102]), "=f"(d[103]), "=f"(d[104]), "=f"(d[105]), "=f"(d[106]), "=f"(d[107]), "=f"(d[108]), "=f"(d[109]), "=f"(d[110]), "=f"(d[111]), "=f"(d[112]), "=f"(d[113]), "=f"(d[114]), "=f"(d[115]), "=f"(d[116]), "=f"(d[117]), "=f"(d[118]), "=f"(d[119]), "=f"(d[120]), "=f"(d[121]), "=f"(d[122]), "=f"(d[123]), "=f"(d[124]), "=f"(d[125]), "=f"(d[126]), "=f"(d[127])
                 : "l"(da), "l"(db));
}
__device__ __forceinline__ void wgmma_rs_m64n128k16(float* d, const uint32_t* a, uint64_t db) {
    asm volatile("{\n.reg .pred p;\nsetp.ne.b32 p, 1, 0;\n"
                 "wgmma.mma_async.sync.aligned.m64n128k16.f32.bf16.bf16 {%0, %1, %2, %3, %4, %5, %6, %7, %8, %9, %10, %11, %12, %13, %14, %15, %16, %17, %18, %19, %20, %21, %22, %23, %24, %25, %26, %27, %28, %29, %30, %31, %32, %33, %34, %35, %36, %37, %38, %39, %40, %41, %42, %43, %44, %45, %46, %47, %48, %49, %50, %51, %52, %53, %54, %55, %56, %57, %58, %59, %60, %61, %62, %63}, {%64, %65, %66, %67}, %68, p, 1, 1, 1;\n}\n"
                 : "+f"(d[0]), "+f"(d[1]), "+f"(d[2]), "+f"(d[3]), "+f"(d[4]), "+f"(d[5]), "+f"(d[6]), "+f"(d[7]), "+f"(d[8]), "+f"(d[9]), "+f"(d[10]), "+f"(d[11]), "+f"(d[12]), "+f"(d[13]), "+f"(d[14]), "+f"(d[15]), "+f"(d[16]), "+f"(d[17]), "+f"(d[18]), "+f"(d[19]), "+f"(d[20]), "+f"(d[21]), "+f"(d[22]), "+f"(d[23]), "+f"(d[24]), "+f"(d[25]), "+f"(d[26]), "+f"(d[27]), "+f"(d[28]), "+f"(d[29]), "+f"(d[30]), "+f"(d[31]), "+f"(d[32]), "+f"(d[33]), "+f"(d[34]), "+f"(d[35]), "+f"(d[36]), "+f"(d[37]), "+f"(d[38]), "+f"(d[39]), "+f"(d[40]), "+f"(d[41]), "+f"(d[42]), "+f"(d[43]), "+f"(d[44]), "+f"(d[45]), "+f"(d[46]), "+f"(d[47]), "+f"(d[48]), "+f"(d[49]), "+f"(d[50]), "+f"(d[51]), "+f"(d[52]), "+f"(d[53]), "+f"(d[54]), "+f"(d[55]), "+f"(d[56]), "+f"(d[57]), "+f"(d[58]), "+f"(d[59]), "+f"(d[60]), "+f"(d[61]), "+f"(d[62]), "+f"(d[63])
                 : "r"(a[0]), "r"(a[1]), "r"(a[2]), "r"(a[3]), "l"(db));
}
__device__ __forceinline__ void wgmma_rs_m64n128k16_first(float* d, const uint32_t* a, uint64_t db) {
    asm volatile("{\n.reg .pred p;\nsetp.ne.b32 p, 0, 0;\n"
                 "wgmma.mma_async.sync.aligned.m64n128k16.f32.bf16.bf16 {%0, %1, %2, %3, %4, %5, %6, %7, %8, %9, %10, %11, %12, %13, %14, %15, %16, %17, %18, %19, %20, %21, %22, %23, %24, %25, %26, %27, %28, %29, %30, %31, %32, %33, %34, %35, %36, %37, %38, %39, %40, %41, %42, %43, %44, %45, %46, %47, %48, %49, %50, %51, %52, %53, %54, %55, %56, %57, %58, %59, %60, %61, %62, %63}, {%64, %65, %66, %67}, %68, p, 1, 1, 1;\n}\n"
                 : "=f"(d[0]), "=f"(d[1]), "=f"(d[2]), "=f"(d[3]), "=f"(d[4]), "=f"(d[5]), "=f"(d[6]), "=f"(d[7]), "=f"(d[8]), "=f"(d[9]), "=f"(d[10]), "=f"(d[11]), "=f"(d[12]), "=f"(d[13]), "=f"(d[14]), "=f"(d[15]), "=f"(d[16]), "=f"(d[17]), "=f"(d[18]), "=f"(d[19]), "=f"(d[20]), "=f"(d[21]), "=f"(d[22]), "=f"(d[23]), "=f"(d[24]), "=f"(d[25]), "=f"(d[26]), "=f"(d[27]), "=f"(d[28]), "=f"(d[29]), "=f"(d[30]), "=f"(d[31]), "=f"(d[32]), "=f"(d[33]), "=f"(d[34]), "=f"(d[35]), "=f"(d[36]), "=f"(d[37]), "=f"(d[38]), "=f"(d[39]), "=f"(d[40]), "=f"(d[41]), "=f"(d[42]), "=f"(d[43]), "=f"(d[44]), "=f"(d[45]), "=f"(d[46]), "=f"(d[47]), "=f"(d[48]), "=f"(d[49]), "=f"(d[50]), "=f"(d[51]), "=f"(d[52]), "=f"(d[53]), "=f"(d[54]), "=f"(d[55]), "=f"(d[56]), "=f"(d[57]), "=f"(d[58]), "=f"(d[59]), "=f"(d[60]), "=f"(d[61]), "=f"(d[62]), "=f"(d[63])
                 : "r"(a[0]), "r"(a[1]), "r"(a[2]), "r"(a[3]), "l"(db));
}

struct BulkMaps { CUtensorMap h, h2, wq, wk, wv, wo, kv, lu; };
struct BulkArgs {
    const bf16 *x, *ssmk, *ssmD, *Bk, *Bv, *shiftk;
    bf16* out;
};
enum { T_KV = 0, T_QA, T_CONV, T_ATT, T_POST, T_LN0 };
constexpr int MAXG = 52, SENT = MAXG - 1;
struct Sched { uint32_t chk[MAXG * 4]; uint32_t info[MAXG]; int sbeg[8]; };

constexpr int BK_STAGES = 4, BK_STAGE_BYTES = 49152, TSLOTS = 4;
struct BulkSmemTail {
    unsigned long long full[BK_STAGES], empty[BK_STAGES], tfull[TSLOTS], tempty[TSLOTS], sfull[4], sempty[4];
    int task[TSLOTS];
    uint32_t tab[MAXG * 5];
};
constexpr int BULK_STG = BK_STAGES * BK_STAGE_BYTES;
constexpr int BULK_TAIL = BULK_STG + 32768;
constexpr int BULK_SMEM = BULK_TAIL + (int)sizeof(BulkSmemTail);
static_assert(BULK_SMEM <= 232448, "bulk smem");
#define PACE 0
#define REG_C 224
#define REG_P 56

#define BT(lead, type, l, c, k)
#define TT(k)
#define FT(k)
#define TTV(k, v)
__device__ __forceinline__ void tma_store_2d(const CUtensorMap* map, uint32_t src, int c0, int c1) {
    asm volatile("cp.async.bulk.tensor.2d.global.shared::cta.bulk_group [%0, {%2, %3}], [%1];" ::"l"(map), "r"(src), "r"(c0), "r"(c1) : "memory");
}
__device__ __forceinline__ void bulk_commit() { asm volatile("cp.async.bulk.commit_group;" ::: "memory"); }
template <int N> __device__ __forceinline__ void bulk_wait_read() { asm volatile("cp.async.bulk.wait_group.read %0;" ::"n"(N) : "memory"); }
template <int N> __device__ __forceinline__ void bulk_wait() { asm volatile("cp.async.bulk.wait_group %0;" ::"n"(N) : "memory"); }
__device__ __forceinline__ void mbar_arrive_cluster(uint32_t bar) {
    asm volatile("mbarrier.arrive.shared::cluster.b64 _, [%0];" ::"r"(bar) : "memory");
}
__device__ __forceinline__ void stsm_x4(uint32_t addr, uint32_t r0, uint32_t r1, uint32_t r2, uint32_t r3) {
    asm volatile("stmatrix.sync.aligned.m8n8.x4.shared.b16 [%0], {%1,%2,%3,%4};" ::"r"(addr), "r"(r0), "r"(r1), "r"(r2), "r"(r3) : "memory");
}
__device__ __forceinline__ void mma1688(float* c, uint32_t a0, uint32_t a1, uint32_t b0) {
    asm("mma.sync.aligned.m16n8k8.row.col.f32.bf16.bf16.f32 {%0,%1,%2,%3}, {%4,%5}, {%6}, {%0,%1,%2,%3};"
        : "+f"(c[0]), "+f"(c[1]), "+f"(c[2]), "+f"(c[3]) : "r"(a0), "r"(a1), "r"(b0));
}
__device__ __forceinline__ int ld_relaxed(const int* p) {
    int v;
    asm volatile("ld.relaxed.gpu.global.u32 %0, [%1];" : "=r"(v) : "l"(p) : "memory");
    return v;
}
__device__ __forceinline__ void flag_wait(const int* f, int tgt, int ns) {
    int guard = 0;
    while (ld_relaxed(f) < tgt && ++guard < 4000000) __nanosleep(ns);
}
__device__ __forceinline__ void fence_async() { asm volatile("fence.proxy.async.global;" ::: "memory"); }
__device__ __forceinline__ uint32_t bmul2(uint32_t a, uint32_t b) { uint32_t r; asm("mul.rn.bf16x2 %0, %1, %2;" : "=r"(r) : "r"(a), "r"(b)); return r; }
__device__ __forceinline__ uint32_t bsum2(uint32_t a, uint32_t b) { uint32_t r; asm("add.rn.bf16x2 %0, %1, %2;" : "=r"(r) : "r"(a), "r"(b)); return r; }
__device__ __forceinline__ uint32_t bmax2(uint32_t a, uint32_t b) { uint32_t r; asm("max.bf16x2 %0, %1, %2;" : "=r"(r) : "r"(a), "r"(b)); return r; }
__device__ __forceinline__ uint32_t rscore(float a, float b) {
    const uint32_t u = pack2(a, b);
    return pack2(blo(u) * 0.08838834764831845f, bhi(u) * 0.08838834764831845f);
}
template <int STRIDE> __device__ __forceinline__ void ld5(uint32_t* w, const bf16* p) {
#pragma unroll
    for (int r = 0; r < 5; r++) { const uint2 v = __ldcg(reinterpret_cast<const uint2*>(p + r * STRIDE)); w[2 * r] = v.x; w[2 * r + 1] = v.y; }
}
__device__ __forceinline__ void st5(bf16* p, const uint32_t* w) {
#pragma unroll
    for (int r = 0; r < 5; r++) *reinterpret_cast<uint2*>(p + r * 128) = make_uint2(w[2 * r], w[2 * r + 1]);
}
__device__ __forceinline__ void ln_row(const uint32_t* x, uint32_t* y) {
    float s = 0.f;
#pragma unroll
    for (int i = 0; i < 10; i++) s += blo(x[i]) + bhi(x[i]);
#pragma unroll
    for (int o = 16; o > 0; o >>= 1) s += __shfl_xor_sync(0xffffffffu, s, o);
    const float mean = s * (1.0f / DM);
    float q = 0.f;
#pragma unroll
    for (int i = 0; i < 10; i++) { const float d0 = blo(x[i]) - mean, d1 = bhi(x[i]) - mean; q = fmaf(d0, d0, q); q = fmaf(d1, d1, q); }
#pragma unroll
    for (int o = 16; o > 0; o >>= 1) q += __shfl_xor_sync(0xffffffffu, q, o);
    const uint32_t nm = pack2(-mean, -mean);
    float sq;
    asm("sqrt.approx.ftz.f32 %0, %1;" : "=f"(sq) : "f"(rbf(rbf(q * (1.0f / DM)) + 1e-5f)));
    const float rd = rcpf(rbf(sq));
#pragma unroll
    for (int i = 0; i < 10; i++) { const uint32_t d = bsum2(x[i], nm); y[i] = pack2(blo(d) * rd, bhi(d) * rd); }
}
__device__ __forceinline__ void red_add8(uint4* p, uint32_t a, uint32_t b, uint32_t c, uint32_t d) {
    asm volatile("red.relaxed.gpu.global.add.noftz.v4.bf16x2 [%0], {%1,%2,%3,%4};" ::"l"(p), "r"(a), "r"(b), "r"(c), "r"(d) : "memory");
}
__device__ __forceinline__ void part_sum(const uint4& v, const uint4& w, int lane, uint32_t& x0, uint32_t& x1) {
    float t[8];
    t[0] = blo(v.x) + blo(w.x); t[1] = bhi(v.x) + bhi(w.x); t[2] = blo(v.y) + blo(w.y); t[3] = bhi(v.y) + bhi(w.y);
    t[4] = blo(v.z) + blo(w.z); t[5] = bhi(v.z) + bhi(w.z); t[6] = blo(v.w) + blo(w.w); t[7] = bhi(v.w) + bhi(w.w);
#pragma unroll
    for (int i = 0; i < 4; i++) t[i] = (lane < 16 ? t[i] : t[4 + i]) + __shfl_xor_sync(0xffffffffu, lane < 16 ? t[4 + i] : t[i], 16);
    const uint32_t r0 = pack2(t[0], t[1]), r1 = pack2(t[2], t[3]);
    const uint32_t ex = __shfl_xor_sync(0xffffffffu, (lane & 1) ? r0 : r1, 1);
    x0 = (lane & 1) ? ex : r0; x1 = (lane & 1) ? r1 : ex;
}
__device__ __forceinline__ void post_row(int l, int row, int lane, const bf16* xin, bf16* xout) {
    uint32_t x[10], y[10], n[10];
    const int cl = (lane & 12) * 8 + (lane >> 4) * 16 + (lane & 1) * 8 + (lane & 2) * 2;
    uint4* pp = reinterpret_cast<uint4*>(g_part + (size_t)(l * PROWS + (row & (PROWS - 1))) * (PG * DM)) + (lane & 15) + (lane >> 4) * 80;
    int* f = FLG(F_OP + l * NCHK + (row >> 7));
    flag_wait(FLG(F_CONV + (row >> 10)), CONV_TGT, 200);
    ld5<128>(x, xin + (size_t)row * DM + cl);
    flag_wait(f + 4, OP_TGT, POST_NS);
    {
        uint4 v[10];
#pragma unroll
        for (int i = 0; i < 10; i++) v[i] = __ldcg(pp + (i >> 1) * 16 + (i & 1) * 160);
#pragma unroll
        for (int r = 0; r < 5; r++) {
            uint32_t s0, s1;
            part_sum(v[2 * r], v[2 * r + 1], lane, s0, s1);
            if (r == 1) ld5<16 * S_LEN * 8>(y, g_Y + ((size_t)(cl >> 3) * S_LEN + (row ^ ((row >> 6) & 7))) * 8 + (cl & 4));
            x[2 * r] = bsum2(x[2 * r], s0); x[2 * r + 1] = bsum2(x[2 * r + 1], s1);
        }
    }
    ln_row(x, n);
#pragma unroll
    for (int i = 0; i < 10; i++) x[i] = bsum2(x[i], bmul2(n[i], y[i]));
    if (l == 0) {
        ln_row(x, n);
        st5(g_h[1] + (size_t)row * DM + cl, n);
        __syncwarp();
        if (lane == 0) red_release(FLG(F_H + NCHK + (row >> 7)), 1);
    }
#pragma unroll
    for (int i = 0; i < 10; i++) pp[(i >> 1) * 16 + (i & 1) * 160] = make_uint4(0, 0, 0, 0);
    st5(xout + (size_t)row * DM + cl, x);
    __syncwarp();
    if (l && lane == 0) red_release(f + 5, 1);
}
__device__ __forceinline__ void u_unit(const bf16* Bk, const bf16* Bv, const bf16* shiftk, int unit, int lane) {
    const int t0 = (unit / 10) * 16, cp = (unit % 10) * 32 + lane;
    uint32_t kk[19], vv[16];
    const uint32_t* pk = reinterpret_cast<const uint32_t*>(Bk + (size_t)t0 * DM) + cp;
    const uint32_t* pv = reinterpret_cast<const uint32_t*>(Bv + (size_t)t0 * DM) + cp;
#pragma unroll
    for (int i = 0; i < 19; i++) kk[i] = (i >= 3 || t0 > 0) ? __ldg(pk + (i - 3) * (DM / 2)) : 0u;
#pragma unroll
    for (int i = 0; i < 16; i++) vv[i] = __ldg(pv + i * (DM / 2));
    const uint4 sh0 = __ldg(reinterpret_cast<const uint4*>(shiftk + cp * 8));
    const uint32_t s0 = __byte_perm(sh0.x, sh0.z, 0x5410), s1 = __byte_perm(sh0.x, sh0.z, 0x7632), s2 = __byte_perm(sh0.y, sh0.w, 0x5410), s3 = __byte_perm(sh0.y, sh0.w, 0x7632);
#pragma unroll
    for (int t = 0; t < 16; t++)
        vv[t] = bmul2(bsum2(bsum2(bsum2(bmul2(kk[t], s3), bmul2(kk[t + 1], s2)), bmul2(kk[t + 2], s1)), bmul2(kk[t + 3], s0)), vv[t]);
    uint4* d = reinterpret_cast<uint4*>(g_U + (size_t)(cp * 2) * S_LEN + (t0 ^ 48));
#pragma unroll
    for (int c = 0; c < 2; c++) {
        const uint32_t sel = c ? 0x7632 : 0x5410;
#pragma unroll
        for (int hh = 0; hh < 2; hh++)
            d[c * (S_LEN / 8) + hh] = make_uint4(__byte_perm(vv[15 - hh * 8], vv[14 - hh * 8], sel), __byte_perm(vv[13 - hh * 8], vv[12 - hh * 8], sel),
                                                 __byte_perm(vv[11 - hh * 8], vv[10 - hh * 8], sel), __byte_perm(vv[9 - hh * 8], vv[8 - hh * 8], sel));
    }
}
constexpr int CV_EP = 4224;
template <class F> __device__ __forceinline__ void conv_unit(uint32_t ub, uint32_t e0, uint32_t e1, uint32_t zrow, uint32_t yt, float Dv, int m, int lane, F&& nearly_done) {
    const int g = lane >> 2, tq = lane & 3;
    asm volatile("st.shared.u32 [%0], %1;" ::"r"(e0 + lane * 4), "r"(0) : "memory");
    asm volatile("st.shared.u32 [%0], %1;" ::"r"(zrow + lane * 4), "r"(0) : "memory");
    __syncwarp();
    for (int i = lane; i < CV_EP / 16; i += 32) {
        const uint4 v = lds128(e0 + i * 16);
        const uint32_t nx = i + 1 < CV_EP / 16 ? lds32(e0 + i * 16 + 16) : 0u;
        sts128(e1 + i * 16, __byte_perm(v.x, v.y, 0x5432), __byte_perm(v.y, v.z, 0x5432), __byte_perm(v.z, v.w, 0x5432), __byte_perm(v.w, nx, 0x5432));
    }
    __syncwarp();
    float acc[8][4];
#pragma unroll
    for (int n = 0; n < 8; n++)
#pragma unroll
        for (int i = 0; i < 4; i++) acc[n][i] = 0.f;
    uint32_t wb = (g & 1) ? e0 + (1 + g + 2 * tq) * 2 : e1 + (g + 2 * tq) * 2;
    uint32_t W[16], a[4][4], an[4][4];
    int row = m * 16 + (lane & 15);
    auto lda = [&](uint32_t (*d)[4]) {
        const uint32_t x = row < 0 ? zrow : ub + row * 128 + (((lane >> 4) ^ (row & 7)) << 4);
#pragma unroll
        for (int ks = 0; ks < 4; ks++) ldsm_x4(d[ks][0], d[ks][1], d[ks][2], d[ks][3], x ^ (ks << 5));
        row--;
    };
#pragma unroll
    for (int i = 0; i < 16; i++) W[i] = lds32(wb + i * 16);
    lda(a);
    const int nD = m == 0 ? 16 : 32;
#pragma unroll 2
    for (int D = 0; D < nD; D++) {
        uint32_t Wn[8];
        wb += 128;
        if (D == nD - 6) nearly_done();
        lda(an);
#pragma unroll
        for (int i = 0; i < 8; i++) Wn[i] = lds32(wb + 128 + i * 16);
#pragma unroll
        for (int ks = 0; ks < 4; ks++)
#pragma unroll
            for (int n = 0; n < 8; n++) mma16816(acc[n], a[ks][0], a[ks][1], a[ks][2], a[ks][3], W[2 * ks + n], W[2 * ks + n + 1]);
#pragma unroll
        for (int i = 0; i < 8; i++) { W[i] = W[i + 8]; W[i + 8] = Wn[i]; }
#pragma unroll
        for (int ks = 0; ks < 4; ks++)
#pragma unroll
            for (int i = 0; i < 4; i++) a[ks][i] = an[ks][i];
    }
#pragma unroll
    for (int n = 0; n < 8; n++)
#pragma unroll
        for (int r = 0; r < 2; r++) {
            const int a_ = g + r * 8, b_ = n * 8 + tq * 2;
            const int ar = m * 16 + a_, p = 62 - b_;
            const uint32_t kv = lds32(ub + ar * 128 + (((p >> 3) ^ (ar & 7)) << 4) + (p & 7) * 2);
            const float y0 = rbf(acc[n][2 * r]) + rbf(bhi(kv) * Dv), y1 = rbf(acc[n][2 * r + 1]) + rbf(blo(kv) * Dv);
            const uint32_t pk = pack2(y0, y1);
            asm volatile("st.shared.u16 [%0], %1;" ::"r"(yt + ((a_ * 64 + b_) ^ g) * 16), "h"((unsigned short)(pk & 0xffff)) : "memory");
            asm volatile("st.shared.u16 [%0], %1;" ::"r"(yt + ((a_ * 64 + b_ + 1) ^ g) * 16), "h"((unsigned short)(pk >> 16)) : "memory");
        }
}

__global__ void __launch_bounds__(384, 1) bulk_kernel(const __grid_constant__ BulkMaps M, const __grid_constant__ BulkArgs A,
                                                      const __grid_constant__ Sched SC) {
    extern __shared__ __align__(1024) unsigned char smem_raw[];
    const uint32_t sb0 = smem_u32(smem_raw);
    const uint32_t full0 = sb0 + BULK_TAIL, empty0 = full0 + 32, tfull0 = full0 + 64, tempty0 = full0 + 96, sfull = full0 + 128, sempty = full0 + 160,
                   task0 = full0 + 192, tab0 = full0 + 208;
    const int tid = threadIdx.x, wid = __shfl_sync(0xffffffffu, tid >> 5, 0), lane = tid & 31;
    const int rank = blockIdx.x & 1;
    if (tid == 0) {
        for (int i = 0; i < BK_STAGES; i++) { mbar_init(full0 + 8 * i, 1); mbar_init(empty0 + 8 * i, 4); }
        for (int i = 0; i < TSLOTS; i++) { mbar_init(tfull0 + 8 * i, 1); mbar_init(tempty0 + 8 * i, 19); }
        for (int i = 0; i < 4; i++) { mbar_init(sfull + 8 * i, 8); mbar_init(sempty + 8 * i, 1); }
        asm volatile("fence.mbarrier_init.release.cluster;" ::: "memory");
        if (rank == 1) for (int i = 0; i < TSLOTS; i++) mbar_expect_tx(tfull0 + 8 * i, 4);
        BT(true, T_LN0, 0, 0, 0);
    }
    if (tid < MAXG * 5) asm volatile("st.shared.u32 [%0], %1;" ::"r"(tab0 + tid * 4), "r"(SC.chk[tid]) : "memory");
    cluster_sync_all();
    uint32_t tc = 0, it = 0;
    if (wid < 4) {
        asm volatile("setmaxnreg.dec.sync.aligned.u32 %0;" ::"n"(REG_P));
        if (wid == 0) {
            int head = SC.sbeg[lane >> 3];
            const int hend = SC.sbeg[(lane >> 3) + 1];
            uint32_t chk = 0; int pv = (blockIdx.x >> 1) & 31, grp = (SC.sbeg[3] + (blockIdx.x >> 6)) << 2 | 3, ncode = 0, code = 3 << 6 | 2, guard = 0;
            auto acquire = [&](uint32_t bytes) -> uint32_t {
                const uint32_t s = it & 3;
                mwait(empty0 + 8 * s, ((it >> 2) & 1) ^ 1);
                it++;
                expect_tx1(full0 + 8 * s, bytes);
                return s;
            };
            auto uwait = [&](const int* f, int tgt) {
                int g2 = 0;
                while ((int)UNI(ld_relaxed(f)) < tgt && ++g2 < 4000000) __nanosleep(32);
                fence_async();
            };
#pragma unroll 1
            while (true) {
                const int type = (code >> 6) & 3;
                const int iend = type == T_KV ? 10 : (type == T_QA ? 24 : 31);
                const int jj = code & 63, g0 = (jj & 15) * 4, lc = (code >> 9) & 31;
                const bool lm = (code >> 8) & 1;
                const CUtensorMap* mb = type == T_QA ? &M.wq : (jj < 16 ? &M.wk : &M.wv);
                bool have = false, ok = (code >> 14) & 1;
                int imem = 16;
#pragma unroll 1
                for (int i = type < T_CONV ? 0 : (type == T_CONV ? 24 : 28 + jj); i < iend; i++) {
                    const int sd = (type < T_CONV ? SPLAN : 0x1230) >> 4 * min(iend - i, 7) & 15;
                    if (rank == 0 && sd) {
                        if (sd == 1) {
                            if (type == T_CONV) mwait(empty0 + 8 * (it & 3), ((it >> 2) & 1) ^ 1);
                            const int gi = head + ((lane >> 2) & 1);
                            chk = lds32(tab0 + ((gi < hend ? gi : SENT) * 4 + (lane & 3)) * 4);
                            pv = ld_relaxed(g_flags + (chk & 0xffff));
                        } else if (sd == 2) {
                            const int tgt = (int)(chk >> 16);
                            const uint32_t b = (__ballot_sync(0xffffffffu, (lane & 3) == 0 ? pv < tgt : pv >= tgt) >> (lane & 24)) & 0xff;
                            const uint32_t cand = (b & 1) ? b & 15 : b >> 4;
                            head += (b & 1) ? 0 : ((b & 16) ? 1 : 2);
                            if (head > hend || guard > 4000000) head = hend;
                            const uint32_t req = lane >= 24 ? 1 : 15;
                            grp = (int)__reduce_min_sync(0xffffffffu, (cand & req) == req ? ((uint32_t)head << 2 | (cand ^ req) >> 2 | ((cand ^ req) & 2 ? 0 : 256)) : (head < hend ? 1000u : 1004u));
                            if (grp < 1000) grp &= 255;
                            if (grp < 1000) asm volatile("{\n.reg .pred p;\nsetp.eq.u32 p, %2, 0;\n@p atom.relaxed.gpu.global.inc.u32 %0, [%1], 0x7fffffff;\n}" : "+r"(pv) : "l"(FLG(F_CNT + (grp >> 2))), "r"(lane) : "memory");
                        } else {
                            if (grp < 1000) {
                                const int tk = (int)UNI(pv);
                                have = tk < (int)(UNI(lds32(tab0 + (grp >> 2) * 16)) >> 16);
                                ncode = (int)UNI(lds32(tab0 + MAXG * 16 + (grp & ~3))) | (grp & 3) << 19 | tk;
                            } else if (grp == 1004) { have = true; ncode = -1; }
                            if (have) {
                                const uint32_t o = (tc & 3) * 4;
                                mwait(tempty0 + 2 * o, ((tc >> 2) & 1) ^ 1);
                                asm volatile(ELECT "st.shared.u32 [%0], %1;\n@p mbarrier.arrive.shared::cta.b64 _, [%2];\n"
                                             "@p st.async.weak.shared::cluster.mbarrier::complete_tx::bytes.b32 [%3], %1, [%4];\n}"
                                             ::"r"(task0 + o), "r"(ncode), "r"(tfull0 + 2 * o), "r"(mapa(task0 + o, 1)), "r"(mapa(tfull0 + 2 * o, 1)) : "memory");
                            }
                        }
                    }
                    if (i >= 28) continue;
                    if (i == 8 && type == T_QA) pv = ld_relaxed(FLG((lane & 1 ? F_MEM : F_KV) + lc));
                    if (i == 10) {
                        const uint32_t b = __ballot_sync(0xffffffffu, pv >= (lane & 1 ? MEM_TGT : KV_TGT));
                        if (b & 2) imem = 13;
                        if (!(b & 1)) uwait(FLG(F_KV + lc), KV_TGT);
                        fence_async();
                    }
                    const uint32_t s = acquire(i < 12 ? 49152 : (i == 24 || i == 27 ? 0 : 32768));
                    const uint32_t sa = sb0 + s * BK_STAGE_BYTES, fb = full0 + 8 * s;
                    if (i == 0) TT(3);
                    if (i < 10) {
                        if (lm) {
                            tma_load_3d(sa + 16384, mb, fb, i * 64, g0);
                            tma_load_3d(sa + 32768, mb, fb, i * 64, g0 + 2);
                        } else tma_load_3d_mc(sa + 16384 + rank * 16384, mb, fb, i * 64, g0 + rank * 2);
                        int d = 0;
                        if (!ok) {
                            d = 1;
                            if (i == 3) {
                                uwait(FLG(F_H + lc), H_TGT);
                                ok = true;
                                d = -3;
                                TT(4);
                            }
                        }
#pragma unroll 1
                        for (; d <= 0; d++) {
                            const uint32_t s2 = (s + d) & 3;
                            if (lm) tma_load_2d_mc(sb0 + s2 * BK_STAGE_BYTES + rank * 8192, &M.h, full0 + 8 * s2, (i + d) * 64, lc * 128 + rank * 64);
                            else tma_load_2d(sb0 + s2 * BK_STAGE_BYTES, &M.h2, full0 + 8 * s2, (i + d) * 64, lc * 128);
                        }
                    } else if (i < 13) {
#pragma unroll 1
                        for (int k = 0, bx = (i - 10) * 3; k < 3 && bx < 8; k++, bx++)
                            tma_load_2d(sa + k * 16384, &M.kv, fb, (g0 + (bx & 3)) * 64, (bx >> 2) * S_LEN + (lc & 15) * 128);
                    } else if (i < 24) {
                        const int cn = ((i - 14) >> 1) * 128, ck = g0 * 64 + (i & 1) * 128;
                        if (i > 13) {
                            if (lm) { tma_load_2d(sa, &M.wo, fb, cn, ck); tma_load_2d(sa + 16384, &M.wo, fb, cn + 64, ck); }
                            else tma_load_2d_mc(sa + rank * 16384, &M.wo, fb, cn + rank * 64, ck);
                        }
                        if (i == imem) {
                            TT(5);
                            if (i == 16) uwait(FLG(F_MEM + lc), MEM_TGT);
                            const uint32_t s2 = (s + (i >> 4)) & 3;
#pragma unroll 1
                            for (int k = 0; k < 4; k++)
                                bulk_load(sb0 + s2 * BK_STAGE_BYTES + k * 8192, g_kvf + (size_t)((lc * CSEG + k) * NH + jj * 2) * 256, 8192, full0 + 8 * s2);
                            TT(6);
                        }
                    } else if (i == 25) {
                        tma_load_2d(sa, &M.lu, fb, 0, (2 * jj + rank) * 256);
                    } else if (i == 26) {
#pragma unroll 1
                        for (int k = 0; k < 8; k++)
                            bulk_load(sa + k * CV_EP + 128, A.ssmk + (size_t)((2 * jj + rank) * 8 + k) * S_LEN, 4096, fb);
                    }
                }
                if (type != 3) TT(7);
                if (rank == 0) {
                    if (!have) {
                        if (type == 3) { guard++; __nanosleep(64); }
                        code = 3 << 6;
                        continue;
                    }
                } else {
                    const uint32_t o = (tc & 3) * 4;
                    mwait(tfull0 + 2 * o, (tc >> 2) & 1);
                    ncode = (int)UNI(lds32(task0 + o));
                    asm volatile(ELECT "mbarrier.arrive.expect_tx.shared::cta.b64 _, [%0], 4;\n@p mbarrier.arrive.shared::cluster.b64 _, [%1];\n}" ::"r"(tfull0 + 2 * o), "r"(mapa(tempty0 + 2 * o, 0)) : "memory");
                    __syncwarp();
                }
                tc++;
                if (ncode < 0) break;
                TT(0); TTV(15, ncode);
                code = ((ncode & 256) ? (2 * ncode + rank) & 63 : ncode & 63) | (ncode & 0x1c0) | ((ncode >> (rank ? 14 : 9)) & 31) << 9 | ((ncode >> (19 + rank)) & 1) << 14;
                fence_async();
            }
        } else if (wid == 1) {
            if (lane < 8) asm volatile("prefetch.tensormap [%0];" ::"l"(&M.h + lane) : "memory");
            __syncwarp();
            if (lane == 0) {
                uint32_t rc = 0;
                while (true) {
                    mwait(tfull0 + 8 * (tc & 3), (tc >> 2) & 1);
                    const int code = (int)lds32(task0 + 4 * (tc & 3));
                    mbar_arrive_cluster(mapa(tempty0 + 8 * (tc & 3), 0));
                    tc++;
                    if (code < 0) break;
                    const int type = (code >> 6) & 3;
                    const int lc = (code >> (rank ? 14 : 9)) & 31;
                    mwait(sfull + 8 * (rc & 3), (rc >> 2) & 1);
                    if (type == T_CONV) {
                        asm volatile("cp.async.bulk.global.shared::cta.bulk_group [%0], [%1], %2;" ::"l"(g_Y + (size_t)((2 * (code & 63) + rank) * S_LEN + lc * 1024) * 8), "r"(sb0 + BULK_STG), "r"(16384) : "memory");
                        bulk_commit();
                        bulk_wait<0>();
                    }
                    mbar_arrive(sempty + 8 * (rc & 3));
                    rc++;
                    FT(0);
                    red_release(type == T_QA ? FLG(F_OP + lc) + 4 : FLG((type == T_KV ? F_KV : F_CONV) + lc), 1);
                    FT(1);
                    BT(true, type, lc >> 4, lc & 15, 2);
                }
            }
        } else {
            const int nw = 2 * gridDim.x, idx = (wid - 2) * gridDim.x + blockIdx.x;
#pragma unroll 1
            for (int hh = 0; hh < 2; hh++) {
#pragma unroll 1
                for (int u = hh * 640 + idx; u < hh * 640 + 640; u += nw) u_unit(A.Bk, A.Bv, A.shiftk, u, lane);
                __syncwarp();
                if (lane == 0) red_release(FLG(F_U + hh), 1);
                BT(lane == 0, T_LN0, hh, 0, 2);
            }
#pragma unroll 1
            for (int q = 0; q < 2 * (NCHK + PDIST); q++) {
                const int l = q & 1, c = (q >> 1) - l * PDIST;
                if (c < 0 || c >= NCHK) continue;
#pragma unroll 1
                for (int rr = idx; rr < 128; rr += nw) post_row(l, c * 128 + rr, lane, l ? g_x : A.x, l ? A.out : g_x);
                BT(lane == 0, T_POST, l, c, 2);
            }
        }
    } else {
        asm volatile("setmaxnreg.inc.sync.aligned.u32 %0;" ::"n"(REG_C));
        const int cw = (wid >> 2) - 1, warp = wid & 3;
        const uint32_t wst = sb0 + BULK_STG + (cw * 4 + warp) * 4096;
        uint32_t rc = 0;
        int npend = 0;
        bool urgent = false;
        uint32_t oofs = 0;
        uint32_t qf[16][4];
        auto release = [&](int s) { if ((tid & 127) == 0) { mbar_arrive(empty0 + 8 * s); mbar_arrive_cluster(mapa(empty0 + 8 * s, rank ^ 1)); } };
        auto next = [&]() -> int { const int s = it & 3; mwait(full0 + 8 * s, (it >> 2) & 1); it++; return s; };
        auto wgbar = [&]() { if (cw == 0) named_bar(2, 128); else named_bar(3, 128); };
        auto handoff = [&]() {
            mwait(sempty + 8 * (rc & 3), ((rc >> 2) & 1) ^ 1);
            asm volatile(ELECT "mbarrier.arrive.shared::cta.b64 _, [%0];\n}" ::"r"(sfull + 8 * (rc & 3)) : "memory");
            rc++;
        };
        auto stg_free = [&]() { mwait(sempty + 8 * ((rc - 1) & 3), ((rc - 1) >> 2) & 1); };
        auto round_q = [&]() {
            if (npend > 4) {
                uint4* d = reinterpret_cast<uint4*>(g_part) + oofs;
                if (npend == 6) {
#pragma unroll
                    for (int i = 0; i < 4; i++) red_add8(d + (i >> 1) * 4 + (i & 1) * (8 * PG * DM / 8), qf[i][0], qf[i][1], qf[i][2], qf[i][3]);
                    npend = 5;
                } else {
#pragma unroll
                    for (int i = 4; i < 8; i++) red_add8(d + (i >> 1) * 4 + (i & 1) * (8 * PG * DM / 8), qf[i][0], qf[i][1], qf[i][2], qf[i][3]);
                    npend = 0;
                    handoff();
                }
                return;
            }
            const uint32_t sst = wst + (lane & 15) * 128 + (((lane >> 4) ^ (lane & 7)) << 4) + (npend & 1) * 2048;
#pragma unroll
            for (int q = 0; q < 4; q++)
                if (npend == 4 - q) {
#pragma unroll
                    for (int i = 0; i < 4; i++) stsm_x4(sst ^ (i << 5), qf[q * 4 + i][0], qf[q * 4 + i][1], qf[q * 4 + i][2], qf[q * 4 + i][3]);
                }
            __syncwarp();
            uint4* d = reinterpret_cast<uint4*>(&g_kv[0][0]) + oofs;
            const uint32_t src = wst + (lane >> 3) * 128 + (((lane & 7) ^ (lane >> 3)) << 4) + (npend & 1) * 2048;
#pragma unroll
            for (int i = 0; i < 4; i++) d[i * (4 * HD / 8)] = lds128((src + i * 512) ^ ((i & 1) << 6));
            oofs += 8;
            if (--npend == 0) handoff();
        };
        auto round_a = [&](const float* a, int hh) {
            uint4* d = reinterpret_cast<uint4*>(g_part) + oofs;
#pragma unroll
            for (int i = hh * 4; i < hh * 4 + 4; i++) {
                const float* b = a + (i >> 1) * 16 + (i & 1) * 2;
                red_add8(d + (i >> 1) * 4 + (i & 1) * (8 * PG * DM / 8), pack2(b[0], b[1]), pack2(b[4], b[5]), pack2(b[8], b[9]), pack2(b[12], b[13]));
            }
            if (hh) oofs += 16;
        };
        while (true) {
            tc++; TT(0); tc--;
            int code;
            while (true) {
                if (npend == 0) mwait(tfull0 + 8 * (tc & 3), (tc >> 2) & 1);
                if (npend == 0 || UNI(mtest(tfull0 + 8 * (tc & 3), (tc >> 2) & 1))) {
                    code = (int)UNI(lds32(task0 + 4 * (tc & 3)));
                    if (npend == 0 || ((code & 0x80) == 0 && !urgent && UNI(mtest(full0 + 8 * (it & 3), (it >> 2) & 1)))) break;
                }
                round_q();
            }
            if (lane == 0) mbar_arrive_cluster(mapa(tempty0 + 8 * (tc & 3), 0));
            tc++;
            TT(2);
            if (code < 0) break;
            const int type = (code >> 6) & 3;
            TTV(15, code);
#define BTC(type, k)
            if (type == T_CONV) {
                const int m = (code >> 9) & 1;
                BT((tid & 127) == 0, T_CONV, 0, m, 0);
                const int u = 2 * (code & 63) + rank, ch = cw * 4 + warp;
                int lane = tid & 31;
                asm volatile("" : "+r"(lane));
                const float Dv = bf2f(A.ssmD[u * 8 + ch]);
                const int sd = next(), s0 = next(), s1 = next(), s2 = next();
                TT(3);
                const uint32_t e1 = sb0 + s2 * BK_STAGE_BYTES;
                conv_unit(sb0 + s0 * BK_STAGE_BYTES + ch * 4096, sb0 + s1 * BK_STAGE_BYTES + ch * CV_EP, e1 + 64 + ch * CV_EP, e1 + 40960 + ch * 128, sb0 + BULK_STG + ch * 2, Dv, m, lane,
                          [&]() { release(sd); stg_free(); });
                asm volatile("fence.proxy.async.shared::cta;" ::: "memory");
                __syncwarp();
                handoff();
                TT(5);
                wgbar();
                release(s0); release(s1); release(s2);
                __syncwarp();
#pragma unroll
                for (int i = 0; i < 64; i++) qf[i >> 2][i & 3] = 0;
                continue;
            }
            float acc[128];
            {
                int s = next();
                TT(3); BTC(type, 0); BTC(type, 1);
                uint32_t sa = sb0 + s * BK_STAGE_BYTES + cw * 8192, sb = sb0 + s * BK_STAGE_BYTES + 16384;
                wg_fence();
                wgmma_m64n256k16_first(acc, make_desc(sa, 16, 1024), make_desc(sb, 8192, 1024));
#pragma unroll 1
                for (int kb = 0;;) {
#pragma unroll
                    for (int k = 1; k < 4; k++) wgmma_m64n256k16(acc, make_desc(sa + k * 32, 16, 1024), make_desc(sb + k * 2048, 8192, 1024));
                    wg_commit();
                    if (npend) round_q();
                    if (kb) { wg_wait<1>(); release((s - 1) & 3); }
                    if (++kb == 10) break;
                    s = next();
                    sa = sb0 + s * BK_STAGE_BYTES + cw * 8192; sb = sb0 + s * BK_STAGE_BYTES + 16384;
                    wg_fence();
                    wgmma_m64n256k16(acc, make_desc(sa, 16, 1024), make_desc(sb, 8192, 1024));
                }
            }
            wg_wait<0>();
            TT(4);
            release((it - 1) & 3);
            stg_free();
#pragma unroll
            for (int i = 0; i < 16; i++)
#pragma unroll
                for (int e = 0; e < 4; e++) qf[i][e] = pack2(acc[i * 8 + e * 2], acc[i * 8 + e * 2 + 1]);
            {
                const int cd = (int)lds32(task0 + 4 * ((tc - 1) & 3)), lc = (cd >> (rank ? 14 : 9)) & 31, jj = (cd & 256) ? (2 * cd + rank) & 63 : cd & 63;
                const int r0 = cw * 64 + warp * 16;
                if (type == T_KV) {
                    oofs = ((jj >> 4) * S_LEN + (lc & 15) * 128 + r0 + (lane >> 3)) * (HD / 8) + (jj & 15) * 32 + (lane & 7);
                    npend = 4;
                    urgent = URGENT && (lc < 2 || lc >= 16);
                    continue;
                }
                oofs = (((lc >> 4) * PRING + (lc & (PRING - 1))) * 128 + r0 + (lane >> 2)) * (PG * DM / 8) + (jj & (PG - 1)) * (DM / 8) + (lane & 3);
            }
            const float cs = 1.4426950408889634f;
            int lane = tid & 31;
            asm volatile("" : "+r"(lane));
            const int g = lane >> 2, tq = lane & 3;
            const int sg = cw * 2 + (warp >> 1), hs = warp & 1;
            float mt[2][2], sum[2][2];
            {
                const int x0 = next(), x1 = next();
                TT(5);
                float s[2][4][4];
#pragma unroll
                for (int hd = 0; hd < 2; hd++)
#pragma unroll
                    for (int n = 0; n < 4; n++)
#pragma unroll
                        for (int e = 0; e < 4; e++) s[hd][n][e] = 0.f;
                const uint32_t krow = (sg * 32 + (lane & 7) + (lane >> 4) * 8) * 128 + ((((lane >> 3) & 1) ^ (lane & 7)) << 4);
#pragma unroll
                for (int ii = 0; ii < 16; ii++) {
                    const int i = (ii >> 1) + (ii & 1) * 8;
                    const uint32_t kb = sb0 + (i < 12 ? x0 * BK_STAGE_BYTES + (i >> 2) * 16384 : x1 * BK_STAGE_BYTES) + (krow ^ ((i & 3) << 5));
                    const uint4 k0 = ldsm4(kb), k1 = ldsm4(kb + 2048);
                    mma16816(s[i >> 3][0], qf[i][0], qf[i][1], qf[i][2], qf[i][3], k0.x, k0.y);
                    mma16816(s[i >> 3][1], qf[i][0], qf[i][1], qf[i][2], qf[i][3], k0.z, k0.w);
                    mma16816(s[i >> 3][2], qf[i][0], qf[i][1], qf[i][2], qf[i][3], k1.x, k1.y);
                    mma16816(s[i >> 3][3], qf[i][0], qf[i][1], qf[i][2], qf[i][3], k1.z, k1.w);
                }
#pragma unroll
                for (int i = 0; i < 8; i++) sts128(wst + i * 512 + lane * 16, qf[8 + i][0], qf[8 + i][1], qf[8 + i][2], qf[8 + i][3]);
                wgbar();
                release(x0);
                TT(6);
                uint32_t pa[2][4][2];
#pragma unroll
                for (int hd = 0; hd < 2; hd++) {
                    uint32_t mx[2] = {0xff80ff80u, 0xff80ff80u};
#pragma unroll
                    for (int n = 0; n < 4; n++)
#pragma unroll
                        for (int r = 0; r < 2; r++) {
                            const int d = hs * 16 + g + r * 8 - n * 8 - tq * 2;
                            pa[hd][n][r] = rscore(d < 0 ? -INFINITY : s[hd][n][2 * r], d < 1 ? -INFINITY : s[hd][n][2 * r + 1]);
                            mx[r] = bmax2(mx[r], pa[hd][n][r]);
                        }
#pragma unroll
                    for (int r = 0; r < 2; r++) {
                        mx[r] = bmax2(mx[r], __shfl_xor_sync(0xffffffffu, mx[r], 1));
                        mx[r] = bmax2(mx[r], __shfl_xor_sync(0xffffffffu, mx[r], 2));
                        mt[hd][r] = fmaxf(blo(mx[r]), bhi(mx[r])) * cs;
                        sum[hd][r] = 0.f;
                    }
#pragma unroll
                    for (int n = 0; n < 4; n++)
#pragma unroll
                        for (int r = 0; r < 2; r++) {
                            const float p0 = ex2f(fmaf(blo(pa[hd][n][r]), cs, -mt[hd][r])), p1 = ex2f(fmaf(bhi(pa[hd][n][r]), cs, -mt[hd][r]));
                            sum[hd][r] += p0 + p1;
                            pa[hd][n][r] = pack2(p0, p1);
                        }
                }
                const uint32_t vrow = (sg * 32 + (lane & 15)) * 128 + (((lane >> 4) ^ (lane & 7)) << 4);
                int xv = x1;
#pragma unroll
                for (int hd = 0; hd < 2; hd++) {
                    if (hd == 1) xv = next();
#pragma unroll
                    for (int i = 0; i < 8; i++) {
                        const uint32_t vb = sb0 + xv * BK_STAGE_BYTES + (hd == 0 ? 16384 : 0) + (i >> 2) * 16384 + (vrow ^ ((i & 3) << 5));
                        uint4 v0, v1;
                        ldsm_x4_t(v0.x, v0.y, v0.z, v0.w, vb);
                        ldsm_x4_t(v1.x, v1.y, v1.z, v1.w, vb + 2048);
                        float* o = acc + hd * 64 + i * 8;
#pragma unroll
                        for (int e = 0; e < 8; e++) o[e] = 0.f;
                        mma16816(o, pa[hd][0][0], pa[hd][0][1], pa[hd][1][0], pa[hd][1][1], v0.x, v0.y);
                        mma16816(o + 4, pa[hd][0][0], pa[hd][0][1], pa[hd][1][0], pa[hd][1][1], v0.z, v0.w);
                        mma16816(o, pa[hd][2][0], pa[hd][2][1], pa[hd][3][0], pa[hd][3][1], v1.x, v1.y);
                        mma16816(o + 4, pa[hd][2][0], pa[hd][2][1], pa[hd][3][0], pa[hd][3][1], v1.z, v1.w);
                    }
                    wgbar();
                    release(xv);
                }
            }
            TT(7);
            BTC(T_ATT, 0);
            {
                const int xm = next();
                TT(8);
                BTC(T_ATT, 1);
                const uint32_t mb = sb0 + xm * BK_STAGE_BYTES + sg * 8192 + lane * 16;
                float sm[2][2][4];
#pragma unroll
                for (int i = 0; i < 16; i++) (&sm[0][0][0])[i] = 0.f;
#pragma unroll
                for (int q = 0; q < 4; q++) {
                    const uint4 k0 = lds128(mb + q * 512), k1 = lds128(mb + 4096 + q * 512);
                    const uint4 qa = lds128(wst + q * 1024 + lane * 16), qb = lds128(wst + q * 1024 + 512 + lane * 16);
                    mma16816(sm[0][0], qf[2 * q][0], qf[2 * q][1], qf[2 * q][2], qf[2 * q][3], k0.x, k0.y);
                    mma16816(sm[0][1], qf[2 * q + 1][0], qf[2 * q + 1][1], qf[2 * q + 1][2], qf[2 * q + 1][3], k0.z, k0.w);
                    mmau(sm[1][0], qa, k1.x, k1.y);
                    mmau(sm[1][1], qb, k1.z, k1.w);
                }
                float f[2][2];
                uint32_t pm[2][2];
#pragma unroll
                for (int hd = 0; hd < 2; hd++)
#pragma unroll
                    for (int r = 0; r < 2; r++) {
                        const uint32_t w = rscore(sm[hd][0][2 * r] + sm[hd][1][2 * r], sm[hd][0][2 * r + 1] + sm[hd][1][2 * r + 1]);
                        const float s0 = blo(w) * cs, s1 = bhi(w) * cs;
                        float m = fmaxf(s0, s1);
                        m = fmaxf(m, __shfl_xor_sync(0xffffffffu, m, 1));
                        m = fmaxf(fmaxf(m, __shfl_xor_sync(0xffffffffu, m, 2)), mt[hd][r]);
                        const float a = ex2f(mt[hd][r] - m), p0 = ex2f(s0 - m), p1 = ex2f(s1 - m);
                        float t = fmaf(sum[hd][r], a, p0 + p1);
                        t += __shfl_xor_sync(0xffffffffu, t, 1);
                        t += __shfl_xor_sync(0xffffffffu, t, 2);
                        t = rcpf(t);
                        f[hd][r] = a * t;
                        pm[hd][r] = pack2(p0 * t, p1 * t);
                    }
#pragma unroll
                for (int q = 0; q < 8; q++) {
                    const int hd = q >> 2;
                    const uint4 vm = lds128(mb + hd * 4096 + 2048 + (q & 3) * 512);
                    float* o = acc + q * 16;
#pragma unroll
                    for (int e = 0; e < 16; e++) o[e] *= f[hd][(e >> 1) & 1];
                    mma1688(o, pm[hd][0], pm[hd][1], vm.x);
                    mma1688(o + 4, pm[hd][0], pm[hd][1], vm.y);
                    mma1688(o + 8, pm[hd][0], pm[hd][1], vm.z);
                    mma1688(o + 12, pm[hd][0], pm[hd][1], vm.w);
#pragma unroll
                    for (int e = 0; e < 8; e++) qf[q * 2 + (e >> 2)][e & 3] = pack2(o[2 * e], o[2 * e + 1]);
                }
                wgbar();
                release(xm);
            }
            TT(9);
#pragma unroll
            for (int t = 0; t < 10; t++) {
                const int s = next();
                const uint32_t sb = sb0 + s * BK_STAGE_BYTES;
                float* d = acc + ((t >> 1) & 1) * 64;
                wg_fence();
#pragma unroll
                for (int k = 0; k < 8; k++) {
                    const uint64_t db = make_desc(sb + k * 2048, 16384, 1024);
                    if (k == 0 && !(t & 1)) wgmma_rs_m64n128k16_first(d, qf[k], db);
                    else wgmma_rs_m64n128k16(d, qf[(t & 1) * 8 + k], db);
                }
                wg_commit();
                if (t) {
                    wg_wait<1>();
                    release((s - 1) & 3);
                    if (t > 1) round_a(acc + (((t >> 1) & 1) ^ 1) * 64, t & 1);
                }
            }
            wg_wait<0>();
            release((it - 1) & 3);
            TT(10);
#pragma unroll
            for (int i = 0; i < 32; i++) qf[i >> 2][i & 3] = pack2(acc[(i >> 3) * 16 + (i & 4) / 2 + (i & 3) * 4], acc[(i >> 3) * 16 + (i & 4) / 2 + (i & 3) * 4 + 1]);
            npend = 6;
            urgent = URGENT > 1;
        }
    }
    cluster_sync_all();
}

__global__ void __launch_bounds__(256) reset_kernel(const bf16* x, int g0, int ncl) {
    const int lane = threadIdx.x & 31, row = blockIdx.x * 8 + (threadIdx.x >> 5);
    uint32_t r[10];
    ld5<128>(r, x + (size_t)row * DM + lane * 4);
    if (blockIdx.x == 0)
        for (int i = threadIdx.x; i < NFLAG * 2; i += blockDim.x) reinterpret_cast<uint4*>(FLG(i >> 1))[i & 1] = make_uint4(i == g0 ? min(ncl, 32) : (i == g0 + 2 ? max(ncl - 32, 0) : 0), 0, 0, 0);
    for (int i = blockIdx.x * 256 + threadIdx.x; i < 2 * PROWS * PG * DM / 8; i += S_LEN * 32) reinterpret_cast<uint4*>(g_part)[i] = make_uint4(0, 0, 0, 0);
    ln_row(r, r);
    st5(g_h[0] + (size_t)row * DM + lane * 4, r);
    if (blockIdx.x) return;
}

typedef CUresult (*PFN_encodeTiled)(CUtensorMap*, CUtensorMapDataType, cuuint32_t, void*, const cuuint64_t*, const cuuint64_t*,
                                    const cuuint32_t*, const cuuint32_t*, CUtensorMapInterleave, CUtensorMapSwizzle,
                                    CUtensorMapL2promotion, CUtensorMapFloatOOBfill);
static PFN_encodeTiled get_encode() {
    static PFN_encodeTiled fn = nullptr;
    if (!fn) {
        void* p = nullptr;
        cudaDriverEntryPointQueryResult qr;
        cudaGetDriverEntryPoint("cuTensorMapEncodeTiled", &p, cudaEnableDefault, &qr);
        fn = (PFN_encodeTiled)p;
    }
    return fn;
}
static void make_map(CUtensorMap* m, const void* ptr, uint64_t rows, uint64_t cols, uint32_t box_rows) {
    cuuint64_t dims[2] = {cols, rows};
    cuuint64_t strides[1] = {cols * 2};
    cuuint32_t box[2] = {64u, box_rows};
    cuuint32_t es[2] = {1, 1};
    get_encode()(m, CU_TENSOR_MAP_DATA_TYPE_BFLOAT16, 2, const_cast<void*>(ptr), dims, strides, box, es,
                 CU_TENSOR_MAP_INTERLEAVE_NONE, CU_TENSOR_MAP_SWIZZLE_128B, CU_TENSOR_MAP_L2_PROMOTION_L2_128B,
                 CU_TENSOR_MAP_FLOAT_OOB_FILL_NONE);
}
static void make_map3(CUtensorMap* m, const void* ptr) {
    cuuint64_t dims[3] = {64, DM, HD / 64};
    cuuint64_t strides[2] = {HD * 2, 128};
    cuuint32_t box[3] = {64u, 64u, 2u};
    cuuint32_t es[3] = {1, 1, 1};
    get_encode()(m, CU_TENSOR_MAP_DATA_TYPE_BFLOAT16, 3, const_cast<void*>(ptr), dims, strides, box, es,
                 CU_TENSOR_MAP_INTERLEAVE_NONE, CU_TENSOR_MAP_SWIZZLE_128B, CU_TENSOR_MAP_L2_PROMOTION_L2_128B,
                 CU_TENSOR_MAP_FLOAT_OOB_FILL_NONE);
}
#define QA_PRE0 4
#define KV1_E 1
#define KV1_L 16
#define KV0_X 6
#define CONV0_AT 1
#define CONV1_AT 9
static void build_sched(Sched& S, int naux) {
    int n = 0;
    auto ck = [](int f, int t) { return (uint32_t)(f * 32) | (uint32_t)t << 16; };
    auto add = [&](int lm, int type, int la, int ca, int lb, int cb, int ntask, uint32_t soft) {
        S.info[n] = (uint32_t)(type << 6 | lm << 8 | (la * 16 + ca) << 9 | (lb * 16 + cb) << 14);
        S.chk[n * 4] = ck(F_CNT + n, ntask); S.chk[n * 4 + 1] = soft;
        S.chk[n * 4 + 2] = ck(F_H + la * NCHK + ca, H_TGT); S.chk[n * 4 + 3] = ck(F_H + lb * NCHK + cb, H_TGT);
        n++;
    };
    for (int i = 0; i < MAXG * 4; i++) S.chk[i] = ck(F_ZERO, 0);
    for (int i = 0; i < MAXG; i++) S.info[i] = 0;
    S.sbeg[0] = n;
    for (int i = 0; i < NCHK; i++) {
        add(1, T_KV, 1, i, 1, i, 16, i < KV1_E || i >= KV1_L ? ck(F_OP + i, 14) + 4 : ck(F_H + NCHK + i, KV1_N));
        S.chk[n * 4 - 2] = S.chk[n * 4 - 1] = ck(F_CONV + i / 8, CONV_TGT);
    }
    S.sbeg[1] = n;
    auto addqa = [&]() {
    for (int p = 0; p < NCHK + PDIST; p++) {
        const bool h0 = p < NCHK, h1 = p >= PDIST;
        const int la = h0 ? 0 : 1, ca = h0 ? p : p - PDIST, lb = h1 ? 1 : 0, cb = h1 ? p - PDIST : p;
        const int ta = ca * CSEG + CSEG + la * LAG;
        add(!(h0 && h1), T_QA, la, ca, lb, cb, h0 && h1 ? 16 : 8,
            ck(F_PROG, h1 ? ta - QA_PRE : (ta > QA_PRE0 ? ta - QA_PRE0 : 0)));
        S.info[n - 1] |= 3u << 19;
        S.chk[n * 4 - 2] = h0 && ca >= PRING ? ck(F_H + NCHK + ca - PRING + 1, H_TGT) : ck(F_ZERO, 0);
        S.chk[n * 4 - 1] = !h1 ? ck(F_KV + ca, KV_TGT) : (cb >= PRING ? ck(F_OP + NCHK + cb - PRING, 128) + 5 : ck(F_ZERO, 0));
    }
    };
    auto addkv = [&]() {
    for (int i = 0; i < NCHK; i += 2) add(0, T_KV, 0, i, 0, i + 1, 32, ck(F_PROG, 4 * i > KV0_X + 1 ? 4 * i - KV0_X : 1)), S.chk[n * 4 - 2] = S.chk[n * 4 - 1] = ck(F_ZERO, 0);
    };
    addqa();
    S.sbeg[2] = n;
    for (int m = 0; m < 2; m++) {
        add(0, T_CONV, 0, m, 0, m, 40, ck(F_U + m, naux));
        S.chk[n * 4 - 2] = S.chk[n * 4 - 1] = ck(F_CNT + S.sbeg[2] + 2 + (m ? CONV1_AT : CONV0_AT) / 2, 32);
    }
    S.sbeg[3] = n;
    addkv();
    S.sbeg[4] = n;
}

static void launch_all(void* const* d_in, void* d_out) {
    const bf16* x = (const bf16*)d_in[0];
    const bf16* mem0 = (const bf16*)d_in[1];
    const bf16* Wq = (const bf16*)d_in[2];
    const bf16* Wk = (const bf16*)d_in[3];
    const bf16* Wv = (const bf16*)d_in[4];
    const bf16* Wo = (const bf16*)d_in[5];
    static bool inited = false;
    static int nsm = 132;
    static Sched SC;
    bf16 *p_h, *p_kv, *p_u;
    cudaGetSymbolAddress((void**)&p_h, g_h);
    cudaGetSymbolAddress((void**)&p_kv, g_kv);
    cudaGetSymbolAddress((void**)&p_u, g_U);
    if (!inited) {
        inited = true;
        cudaDeviceGetAttribute(&nsm, cudaDevAttrMultiProcessorCount, 0);
        cudaFuncSetAttribute(chain_kernel, cudaFuncAttributeMaxDynamicSharedMemorySize, (int)sizeof(ChainSmem));
        cudaFuncSetAttribute(chain_kernel, cudaFuncAttributeNonPortableClusterSizeAllowed, 1);
        cudaFuncSetAttribute(bulk_kernel, cudaFuncAttributeMaxDynamicSharedMemorySize, BULK_SMEM);
        build_sched(SC, 2 * ((nsm - 64) & ~1));
    }
    const size_t QS = (size_t)S_LEN * HD;
    BulkMaps M;
    make_map(&M.h, p_h, 2 * S_LEN, DM, 64);
    make_map(&M.h2, p_h, 2 * S_LEN, DM, 128);
    make_map3(&M.wq, Wq);
    make_map3(&M.wk, Wk);
    make_map3(&M.wv, Wv);
    make_map(&M.wo, Wo, HD, DM, 128);
    make_map(&M.kv, p_kv, 2 * S_LEN, HD, 128);
    make_map(&M.lu, p_u, DM * 32, 64, 256);
    BulkArgs BA;
    BA.x = x; BA.out = (bf16*)d_out;
    BA.Bk = (const bf16*)d_in[8]; BA.Bv = (const bf16*)d_in[9]; BA.shiftk = (const bf16*)d_in[10];
    BA.ssmk = (const bf16*)d_in[11]; BA.ssmD = (const bf16*)d_in[12];
    ChainArgs ca;
    for (int l = 0; l < 2; l++) {
        make_map(&ca.tk[l], p_kv, S_LEN, HD, 32);
        make_map(&ca.tv[l], p_kv + QS, S_LEN, HD, 32);
    }
    ca.x = x; ca.mem0 = mem0; ca.Wq = Wq; ca.Wk = Wk; ca.Wv = Wv; ca.Wo = Wo; ca.kv_target = KV_TGT;
    cudaStream_t s = cudaStreamPerThread;
    reset_kernel<<<S_LEN / 8, 256, 0, s>>>(x, 2 * (F_CNT + SC.sbeg[3]), (nsm - 64) / 2);
    {
        cudaLaunchConfig_t cfg = {};
        cfg.gridDim = dim3(64); cfg.blockDim = dim3(CHAIN_THREADS); cfg.dynamicSmemBytes = sizeof(ChainSmem); cfg.stream = s;
        cudaLaunchAttribute at[1];
        at[0].id = cudaLaunchAttributeClusterDimension;
        at[0].val.clusterDim.x = CL; at[0].val.clusterDim.y = 1; at[0].val.clusterDim.z = 1;
        cfg.attrs = at; cfg.numAttrs = 1;
        cudaLaunchKernelEx(&cfg, chain_kernel, ca);
    }
    {
        cudaLaunchConfig_t cfg = {};
        cfg.gridDim = dim3((nsm - 64) & ~1); cfg.blockDim = dim3(384); cfg.dynamicSmemBytes = BULK_SMEM; cfg.stream = s;
        cudaLaunchAttribute at[2];
        at[0].id = cudaLaunchAttributeProgrammaticStreamSerialization;
        at[0].val.programmaticStreamSerializationAllowed = 1;
        at[1].id = cudaLaunchAttributeClusterDimension;
        at[1].val.clusterDim.x = 2; at[1].val.clusterDim.y = 1; at[1].val.clusterDim.z = 1;
        cfg.attrs = at; cfg.numAttrs = 2;
        cudaLaunchKernelEx(&cfg, bulk_kernel, M, BA, SC);
    }
}
}

extern "C" void kernel_launch(void* const* d_in, const int* in_sizes, int n_in, void* d_out, int out_size) {
    (void)in_sizes; (void)n_in; (void)out_size;
    if (ws::usable()) ws::launch_all(d_in, d_out);
    else ni::launch_all(d_in, d_out);
}
```

```cpp
#include <cuda_runtime.h>
#include <cuda_bf16.h>
#include <stdint.h>
#include <cuda.h>

typedef __nv_bfloat16 bf16;
namespace ws {
constexpr int S_LEN = 2048, DM = 640, NH = 32, DH = 128, HD = NH * DH, SEG = 32, NSEG = S_LEN / SEG;

__device__ __forceinline__ float bf2f(bf16 v) { return __bfloat162float(v); }
__device__ __forceinline__ float rbf(float v) { return __bfloat162float(__float2bfloat16_rn(v)); }
__device__ __forceinline__ uint32_t pack2(float a, float b) {
    __nv_bfloat162 t = __floats2bfloat162_rn(a, b);
    return *reinterpret_cast<uint32_t*>(&t);
}
__device__ __forceinline__ float blo(uint32_t v) { return __uint_as_float(v << 16); }
__device__ __forceinline__ float bhi(uint32_t v) { return __uint_as_float(v & 0xffff0000u); }
__device__ __forceinline__ uint32_t badd(uint32_t a, uint32_t b) { uint32_t r; asm("add.rn.bf16x2 %0, %1, %2;" : "=r"(r) : "r"(a), "r"(b)); return r; }
__device__ __forceinline__ uint32_t smem_u32(const void* p) { return (uint32_t)__cvta_generic_to_shared(p); }
__device__ __forceinline__ uint4 ldsm4(uint32_t a) {
    uint4 v;
    asm volatile("ldmatrix.sync.aligned.m8n8.x4.shared.b16 {%0,%1,%2,%3}, [%4];" : "=r"(v.x), "=r"(v.y), "=r"(v.z), "=r"(v.w) : "r"(a));
    return v;
}
__device__ __forceinline__ uint4 ldsm4t(uint32_t a) {
    uint4 v;
    asm volatile("ldmatrix.sync.aligned.m8n8.x4.trans.shared.b16 {%0,%1,%2,%3}, [%4];" : "=r"(v.x), "=r"(v.y), "=r"(v.z), "=r"(v.w) : "r"(a));
    return v;
}
__device__ __forceinline__ void stsm4(uint32_t a, uint32_t r0, uint32_t r1, uint32_t r2, uint32_t r3) {
    asm volatile("stmatrix.sync.aligned.m8n8.x4.shared.b16 [%0], {%1,%2,%3,%4};" ::"r"(a), "r"(r0), "r"(r1), "r"(r2), "r"(r3) : "memory");
}
__device__ __forceinline__ void stsm4t(uint32_t a, uint32_t r0, uint32_t r1, uint32_t r2, uint32_t r3) {
    asm volatile("stmatrix.sync.aligned.m8n8.x4.trans.shared.b16 [%0], {%1,%2,%3,%4};" ::"r"(a), "r"(r0), "r"(r1), "r"(r2), "r"(r3) : "memory");
}
__device__ __forceinline__ void mma16816(float* c, uint32_t a0, uint32_t a1, uint32_t a2, uint32_t a3, uint32_t b0, uint32_t b1) {
    asm("mma.sync.aligned.m16n8k16.row.col.f32.bf16.bf16.f32 {%0,%1,%2,%3}, {%4,%5,%6,%7}, {%8,%9}, {%0,%1,%2,%3};"
        : "+f"(c[0]), "+f"(c[1]), "+f"(c[2]), "+f"(c[3]) : "r"(a0), "r"(a1), "r"(a2), "r"(a3), "r"(b0), "r"(b1));
}
__device__ __forceinline__ void mmav(float* c, uint32_t a0, uint32_t a1, uint32_t a2, uint32_t a3, uint32_t b0, uint32_t b1) {
    asm volatile("mma.sync.aligned.m16n8k16.row.col.f32.bf16.bf16.f32 {%0,%1,%2,%3}, {%4,%5,%6,%7}, {%8,%9}, {%0,%1,%2,%3};"
        : "+f"(c[0]), "+f"(c[1]), "+f"(c[2]), "+f"(c[3]) : "r"(a0), "r"(a1), "r"(a2), "r"(a3), "r"(b0), "r"(b1));
}
__device__ __forceinline__ void mmau(float* c, const uint4& a, uint32_t b0, uint32_t b1) { mma16816(c, a.x, a.y, a.z, a.w, b0, b1); }
__device__ __forceinline__ void mma1688(float* c, uint32_t a0, uint32_t a1, uint32_t b0) {
    asm("mma.sync.aligned.m16n8k8.row.col.f32.bf16.bf16.f32 {%0,%1,%2,%3}, {%4,%5}, {%6}, {%0,%1,%2,%3};"
        : "+f"(c[0]), "+f"(c[1]), "+f"(c[2]), "+f"(c[3]) : "r"(a0), "r"(a1), "r"(b0));
}
__device__ __forceinline__ void mmav8(float* c, uint32_t a0, uint32_t a1, uint32_t b0) {
    asm volatile("mma.sync.aligned.m16n8k8.row.col.f32.bf16.bf16.f32 {%0,%1,%2,%3}, {%4,%5}, {%6}, {%0,%1,%2,%3};"
        : "+f"(c[0]), "+f"(c[1]), "+f"(c[2]), "+f"(c[3]) : "r"(a0), "r"(a1), "r"(b0));
}
__device__ __forceinline__ void cp_async16(uint32_t dst, const void* src) { asm volatile("cp.async.cg.shared.global [%0], [%1], 16;" ::"r"(dst), "l"(src)); }
__device__ __forceinline__ void cp_commit() { asm volatile("cp.async.commit_group;"); }
template <int N> __device__ __forceinline__ void cp_wait() { asm volatile("cp.async.wait_group %0;" ::"n"(N)); }
__device__ __forceinline__ uint4 lds128(uint32_t a) {
    uint4 v;
    asm volatile("ld.shared.v4.u32 {%0,%1,%2,%3}, [%4];" : "=r"(v.x), "=r"(v.y), "=r"(v.z), "=r"(v.w) : "r"(a));
    return v;
}
__device__ __forceinline__ uint2 lds64(uint32_t a) {
    uint2 v;
    asm volatile("ld.shared.v2.u32 {%0,%1}, [%2];" : "=r"(v.x), "=r"(v.y) : "r"(a));
    return v;
}
__device__ __forceinline__ uint32_t lds32(uint32_t a) { uint32_t v; asm volatile("ld.shared.u32 %0, [%1];" : "=r"(v) : "r"(a)); return v; }
__device__ __forceinline__ void sts32(uint32_t a, uint32_t x) { asm volatile("st.shared.u32 [%0], %1;" ::"r"(a), "r"(x) : "memory"); }
__device__ __forceinline__ void sts64(uint32_t a, uint32_t x, uint32_t y) { asm volatile("st.shared.v2.u32 [%0], {%1,%2};" ::"r"(a), "r"(x), "r"(y) : "memory"); }
__device__ __forceinline__ void sts128(uint32_t a, uint32_t x, uint32_t y, uint32_t z, uint32_t w) {
    asm volatile("st.shared.v4.u32 [%0], {%1,%2,%3,%4};" ::"r"(a), "r"(x), "r"(y), "r"(z), "r"(w) : "memory");
}
__device__ __forceinline__ uint4 ld_relaxed_v4(const void* p) {
    uint4 v;
    asm volatile("ld.relaxed.gpu.global.v4.u32 {%0,%1,%2,%3}, [%4];" : "=r"(v.x), "=r"(v.y), "=r"(v.z), "=r"(v.w) : "l"(p) : "memory");
    return v;
}
__device__ __forceinline__ uint2 ld_relaxed_v2(const void* p) {
    uint2 v;
    asm volatile("ld.relaxed.gpu.global.v2.u32 {%0,%1}, [%2];" : "=r"(v.x), "=r"(v.y) : "l"(p) : "memory");
    return v;
}
__device__ __forceinline__ void ld7_relaxed(uint4* x, const void* p) {
    asm volatile("ld.relaxed.gpu.global.v4.u32 {%0,%1,%2,%3}, [%28 + 0];\nld.relaxed.gpu.global.v4.u32 {%4,%5,%6,%7}, [%28 + 512];\nld.relaxed.gpu.global.v4.u32 {%8,%9,%10,%11}, [%28 + 1024];\nld.relaxed.gpu.global.v4.u32 {%12,%13,%14,%15}, [%28 + 1536];\nld.relaxed.gpu.global.v4.u32 {%16,%17,%18,%19}, [%28 + 2048];\nld.relaxed.gpu.global.v4.u32 {%20,%21,%22,%23}, [%28 + 2560];\nld.relaxed.gpu.global.v4.u32 {%24,%25,%26,%27}, [%28 + 3072];\n" : "=r"(x[0].x), "=r"(x[0].y), "=r"(x[0].z), "=r"(x[0].w), "=r"(x[1].x), "=r"(x[1].y), "=r"(x[1].z), "=r"(x[1].w), "=r"(x[2].x), "=r"(x[2].y), "=r"(x[2].z), "=r"(x[2].w), "=r"(x[3].x), "=r"(x[3].y), "=r"(x[3].z), "=r"(x[3].w), "=r"(x[4].x), "=r"(x[4].y), "=r"(x[4].z), "=r"(x[4].w), "=r"(x[5].x), "=r"(x[5].y), "=r"(x[5].z), "=r"(x[5].w), "=r"(x[6].x), "=r"(x[6].y), "=r"(x[6].z), "=r"(x[6].w) : "l"(p) : "memory");
}
__device__ __forceinline__ void ld7_relaxed(uint2* x, const void* p) {
    asm volatile("ld.relaxed.gpu.global.v2.u32 {%0,%1}, [%14 + 0];\nld.relaxed.gpu.global.v2.u32 {%2,%3}, [%14 + 512];\nld.relaxed.gpu.global.v2.u32 {%4,%5}, [%14 + 1024];\nld.relaxed.gpu.global.v2.u32 {%6,%7}, [%14 + 1536];\nld.relaxed.gpu.global.v2.u32 {%8,%9}, [%14 + 2048];\nld.relaxed.gpu.global.v2.u32 {%10,%11}, [%14 + 2560];\nld.relaxed.gpu.global.v2.u32 {%12,%13}, [%14 + 3072];\n" : "=r"(x[0].x), "=r"(x[0].y), "=r"(x[1].x), "=r"(x[1].y), "=r"(x[2].x), "=r"(x[2].y), "=r"(x[3].x), "=r"(x[3].y), "=r"(x[4].x), "=r"(x[4].y), "=r"(x[5].x), "=r"(x[5].y), "=r"(x[6].x), "=r"(x[6].y) : "l"(p) : "memory");
}
__device__ __forceinline__ void st_relaxed_v4(void* p, uint32_t a, uint32_t b, uint32_t c, uint32_t d) {
    asm volatile("st.relaxed.gpu.global.v4.u32 [%0], {%1,%2,%3,%4};" ::"l"(p), "r"(a), "r"(b), "r"(c), "r"(d) : "memory");
}
__device__ __forceinline__ void st_relaxed_v2(void* p, uint32_t a, uint32_t b) {
    asm volatile("st.relaxed.gpu.global.v2.u32 [%0], {%1,%2};" ::"l"(p), "r"(a), "r"(b) : "memory");
}
__device__ __forceinline__ uint32_t nz(uint32_t v) { uint32_t r; asm("max.u32 %0, %1, 1;" : "=r"(r) : "r"(v)); return r; }
__device__ __forceinline__ void touch(const void* p) { asm volatile("prefetch.global.L2 [%0];" ::"l"(p) : "memory"); }
__device__ __forceinline__ int ld_relaxed(const int* p) {
    int v;
    asm volatile("ld.relaxed.gpu.global.u32 %0, [%1];" : "=r"(v) : "l"(p) : "memory");
    return v;
}
__device__ __forceinline__ int ld_acquire(const int* p) {
    int v;
    asm volatile("ld.acquire.gpu.global.u32 %0, [%1];" : "=r"(v) : "l"(p) : "memory");
    return v;
}
__device__ __forceinline__ void red_release(int* p, int v) { asm volatile("red.release.gpu.global.add.u32 [%0], %1;" ::"l"(p), "r"(v) : "memory"); }
__device__ __forceinline__ void mbar_init(uint32_t bar, int count) { asm volatile("mbarrier.init.shared::cta.b64 [%0], %1;" ::"r"(bar), "r"(count)); }
__device__ __forceinline__ void mbar_expect_tx(uint32_t bar, uint32_t bytes) {
    asm volatile("mbarrier.arrive.expect_tx.shared::cta.b64 _, [%0], %1;" ::"r"(bar), "r"(bytes) : "memory");
}
__device__ __forceinline__ void mbar_arrive(uint32_t bar) { asm volatile("mbarrier.arrive.shared::cta.b64 _, [%0];" ::"r"(bar) : "memory"); }
__device__ __forceinline__ void mbar_arrive_cluster(uint32_t bar) { asm volatile("mbarrier.arrive.shared::cluster.b64 _, [%0];" ::"r"(bar) : "memory"); }
__device__ __forceinline__ void mslow(uint32_t bar, uint32_t parity) {
    asm volatile(
        "{\n.reg .pred P1;\n.reg .u32 cnt;\n"
        "mov.u32 cnt, 0;\n"
        "LAB_WAIT:\n"
        "mbarrier.try_wait.parity.shared::cta.b64 P1, [%0], %1;\n"
        "@P1 bra DONE;\n"
        "add.u32 cnt, cnt, 1;\n"
        "setp.lt.u32 P1, cnt, 1000000;\n"
        "@P1 bra LAB_WAIT;\n"
        "trap;\n"
        "DONE:\n}\n" ::"r"(bar), "r"(parity) : "memory");
}
__device__ __forceinline__ void mwait(uint32_t bar, uint32_t parity) {
    asm volatile(
        "{\n.reg .pred P1, P2;\n.reg .u32 cnt;\n"
        "mov.u32 cnt, 0;\n"
        "LAB_WAIT:\n"
        "mbarrier.try_wait.parity.shared::cta.b64 P1, [%0], %1;\n"
        "add.u32 cnt, cnt, 1;\n"
        "setp.gt.u32 P2, cnt, 1000000;\n"
        "@P2 trap;\n"
        "@!P1 bra LAB_WAIT;\n"
        "}\n" ::"r"(bar), "r"(parity) : "memory");
}
__device__ __forceinline__ uint32_t mtest(uint32_t bar, uint32_t parity) {
    uint32_t ok;
    asm volatile("{\n.reg .pred P1;\nmbarrier.test_wait.parity.shared::cta.b64 P1, [%1], %2;\nselp.u32 %0, 1, 0, P1;\n}\n" : "=r"(ok) : "r"(bar), "r"(parity) : "memory");
    return ok;
}
__device__ __forceinline__ uint32_t mapa(uint32_t addr, uint32_t rank) {
    uint32_t r;
    asm("mapa.shared::cluster.u32 %0, %1, %2;" : "=r"(r) : "r"(addr), "r"(rank));
    return r;
}
__device__ __forceinline__ void st_async_b32(uint32_t addr, uint32_t a, uint32_t bar) {
    asm volatile("st.async.weak.shared::cluster.mbarrier::complete_tx::bytes.b32 [%0], %1, [%2];" ::"r"(addr), "r"(a), "r"(bar) : "memory");
}
__device__ __forceinline__ void st_async_v2(uint32_t addr, uint32_t a, uint32_t b, uint32_t bar) {
    asm volatile("st.async.weak.shared::cluster.mbarrier::complete_tx::bytes.v2.b32 [%0], {%1,%2}, [%3];" ::"r"(addr), "r"(a), "r"(b), "r"(bar) : "memory");
}
__device__ __forceinline__ void st_async_v4(uint32_t addr, uint32_t a, uint32_t b, uint32_t c, uint32_t d, uint32_t bar) {
    asm volatile("st.async.weak.shared::cluster.mbarrier::complete_tx::bytes.v4.b32 [%0], {%1,%2,%3,%4}, [%5];" ::"r"(addr), "r"(a), "r"(b), "r"(c), "r"(d), "r"(bar) : "memory");
}
__device__ __forceinline__ void st_async_v4p(uint32_t addr, uint32_t a, uint32_t b, uint32_t c, uint32_t d, uint32_t bar) {
    asm volatile("{\n.reg .pred p;\nsetp.ne.u32 p, %5, 0;\n@p st.async.weak.shared::cluster.mbarrier::complete_tx::bytes.v4.b32 [%0], {%1,%2,%3,%4}, [%5];\n}"
                 ::"r"(addr), "r"(a), "r"(b), "r"(c), "r"(d), "r"(bar) : "memory");
}
__device__ __forceinline__ void st_async_v2p(uint32_t addr, uint32_t a, uint32_t b, uint32_t bar) {
    asm volatile("{\n.reg .pred p;\nsetp.ne.u32 p, %3, 0;\n@p st.async.weak.shared::cluster.mbarrier::complete_tx::bytes.v2.b32 [%0], {%1,%2}, [%3];\n}"
                 ::"r"(addr), "r"(a), "r"(b), "r"(bar) : "memory");
}
__device__ __forceinline__ void cluster_arrive() { asm volatile("barrier.cluster.arrive.release.aligned;" ::: "memory"); }
__device__ __forceinline__ void cluster_arrive_relaxed() { asm volatile("barrier.cluster.arrive.relaxed.aligned;" ::: "memory"); }
__device__ __forceinline__ void prefetch_l2(const void* p, uint32_t bytes) { asm volatile("cp.async.bulk.prefetch.L2.global [%0], %1;" ::"l"(p), "r"(bytes) : "memory"); }
__device__ __forceinline__ void cluster_wait() { asm volatile("barrier.cluster.wait.acquire.aligned;" ::: "memory"); }
__device__ __forceinline__ void named_bar(int id, int n) { asm volatile("bar.sync %0, %1;" ::"r"(id), "r"(n) : "memory"); }
__device__ __forceinline__ void named_arrive(int id, int n) { asm volatile("bar.arrive %0, %1;" ::"r"(id), "r"(n) : "memory"); }
__device__ __forceinline__ void fence_async_smem() { asm volatile("fence.proxy.async.shared::cta;" ::: "memory"); }
__device__ __forceinline__ void fence_async_global() { asm volatile("fence.proxy.async.global;" ::: "memory"); }
__device__ __forceinline__ void wg_fence() { asm volatile("wgmma.fence.sync.aligned;" ::: "memory"); }
__device__ __forceinline__ void wg_commit() { asm volatile("wgmma.commit_group.sync.aligned;" ::: "memory"); }
template <int N> __device__ __forceinline__ void wg_wait() { asm volatile("wgmma.wait_group.sync.aligned %0;" ::"n"(N) : "memory"); }
__device__ __forceinline__ float ex2f(float x) { float y; asm("ex2.approx.ftz.f32 %0, %1;" : "=f"(y) : "f"(x)); return y; }
__device__ __forceinline__ float rcpf(float x) { float y; asm("rcp.approx.ftz.f32 %0, %1;" : "=f"(y) : "f"(x)); return y; }
__device__ __forceinline__ uint32_t clk32() { uint32_t c; asm volatile("mov.u32 %0, %clock;" : "=r"(c)); return c; }
__device__ __forceinline__ uint32_t opq(uint32_t x) { uint32_t y; asm volatile("mov.u32 %0, %1;" : "=r"(y) : "r"(x)); return y; }
__device__ __forceinline__ uint64_t mkdesc(uint32_t lo, uint32_t hi) { uint64_t d; asm("mov.b64 %0, {%1,%2};" : "=l"(d) : "r"(lo), "r"(hi)); return d; }
__device__ __forceinline__ void delay(uint32_t n) {
    asm volatile("{\n.reg .pred P;\n.reg .u32 a, b;\nmov.u32 a, %clock;\nadd.u32 a, a, %0;\nDL:\nmov.u32 b, %clock;\nsub.u32 b, b, a;\nsetp.lt.s32 P, b, 0;\n@P bra.uni DL;\n}" ::"r"(n) : "memory");
}
#define UNI(x) __shfl_sync(0xffffffffu, (uint32_t)(x), 0)
__device__ __forceinline__ void wg_n16t(float* d, uint32_t a0, uint32_t a1, uint32_t a2, uint32_t a3, uint64_t db) {
    asm volatile("wgmma.mma_async.sync.aligned.m64n16k16.f32.bf16.bf16 {%0, %1, %2, %3, %4, %5, %6, %7}, {%8, %9, %10, %11}, %12, 1, 1, 1, 1;"
                 : "+f"(d[0]), "+f"(d[1]), "+f"(d[2]), "+f"(d[3]), "+f"(d[4]), "+f"(d[5]), "+f"(d[6]), "+f"(d[7]) : "r"(a0), "r"(a1), "r"(a2), "r"(a3), "l"(db));
}
__device__ __forceinline__ void wg_n16t_first(float* d, uint32_t a0, uint32_t a1, uint32_t a2, uint32_t a3, uint64_t db) {
    asm volatile("wgmma.mma_async.sync.aligned.m64n16k16.f32.bf16.bf16 {%0, %1, %2, %3, %4, %5, %6, %7}, {%8, %9, %10, %11}, %12, 0, 1, 1, 1;"
                 : "=f"(d[0]), "=f"(d[1]), "=f"(d[2]), "=f"(d[3]), "=f"(d[4]), "=f"(d[5]), "=f"(d[6]), "=f"(d[7]) : "r"(a0), "r"(a1), "r"(a2), "r"(a3), "l"(db));
}
__device__ __forceinline__ void wg_n32(float* d, uint32_t a0, uint32_t a1, uint32_t a2, uint32_t a3, uint64_t db) {
    asm volatile("wgmma.mma_async.sync.aligned.m64n32k16.f32.bf16.bf16 {%0, %1, %2, %3, %4, %5, %6, %7, %8, %9, %10, %11, %12, %13, %14, %15}, {%16, %17, %18, %19}, %20, 1, 1, 1, 0;"
                 : "+f"(d[0]), "+f"(d[1]), "+f"(d[2]), "+f"(d[3]), "+f"(d[4]), "+f"(d[5]), "+f"(d[6]), "+f"(d[7]), "+f"(d[8]), "+f"(d[9]), "+f"(d[10]), "+f"(d[11]), "+f"(d[12]), "+f"(d[13]), "+f"(d[14]), "+f"(d[15]) : "r"(a0), "r"(a1), "r"(a2), "r"(a3), "l"(db));
}
__device__ __forceinline__ void wg_n32_first(float* d, uint32_t a0, uint32_t a1, uint32_t a2, uint32_t a3, uint64_t db) {
    asm volatile("wgmma.mma_async.sync.aligned.m64n32k16.f32.bf16.bf16 {%0, %1, %2, %3, %4, %5, %6, %7, %8, %9, %10, %11, %12, %13, %14, %15}, {%16, %17, %18, %19}, %20, 0, 1, 1, 0;"
                 : "=f"(d[0]), "=f"(d[1]), "=f"(d[2]), "=f"(d[3]), "=f"(d[4]), "=f"(d[5]), "=f"(d[6]), "=f"(d[7]), "=f"(d[8]), "=f"(d[9]), "=f"(d[10]), "=f"(d[11]), "=f"(d[12]), "=f"(d[13]), "=f"(d[14]), "=f"(d[15]) : "r"(a0), "r"(a1), "r"(a2), "r"(a3), "l"(db));
}

__device__ __forceinline__ void wg_n16t_sfirst(float* d, uint64_t da, uint64_t db) {
    asm volatile("wgmma.mma_async.sync.aligned.m64n16k16.f32.bf16.bf16 {%0, %1, %2, %3, %4, %5, %6, %7}, %8, %9, 0, 1, 1, 1, 1;"
                 : "=f"(d[0]), "=f"(d[1]), "=f"(d[2]), "=f"(d[3]), "=f"(d[4]), "=f"(d[5]), "=f"(d[6]), "=f"(d[7]) : "l"(da), "l"(db));
}
__device__ __forceinline__ void wg_n32_sfirst(float* d, uint64_t da, uint64_t db) {
    asm volatile("wgmma.mma_async.sync.aligned.m64n32k16.f32.bf16.bf16 {%0, %1, %2, %3, %4, %5, %6, %7, %8, %9, %10, %11, %12, %13, %14, %15}, %16, %17, 0, 1, 1, 1, 0;"
                 : "=f"(d[0]), "=f"(d[1]), "=f"(d[2]), "=f"(d[3]), "=f"(d[4]), "=f"(d[5]), "=f"(d[6]), "=f"(d[7]), "=f"(d[8]), "=f"(d[9]), "=f"(d[10]), "=f"(d[11]), "=f"(d[12]), "=f"(d[13]), "=f"(d[14]), "=f"(d[15]) : "l"(da), "l"(db));
}

__device__ __forceinline__ void wg_n16t_s(float* d, uint64_t da, uint64_t db) {
    asm volatile("wgmma.mma_async.sync.aligned.m64n16k16.f32.bf16.bf16 {%0, %1, %2, %3, %4, %5, %6, %7}, %8, %9, 1, 1, 1, 1, 1;"
                 : "+f"(d[0]), "+f"(d[1]), "+f"(d[2]), "+f"(d[3]), "+f"(d[4]), "+f"(d[5]), "+f"(d[6]), "+f"(d[7]) : "l"(da), "l"(db));
}
__device__ __forceinline__ void wg_n64_sfirst(float* d, uint64_t da, uint64_t db) {
    asm volatile("wgmma.mma_async.sync.aligned.m64n64k16.f32.bf16.bf16 {%0, %1, %2, %3, %4, %5, %6, %7, %8, %9, %10, %11, %12, %13, %14, %15, %16, %17, %18, %19, %20, %21, %22, %23, %24, %25, %26, %27, %28, %29, %30, %31}, %32, %33, 0, 1, 1, 1, 0;"
                 : "=f"(d[0]), "=f"(d[1]), "=f"(d[2]), "=f"(d[3]), "=f"(d[4]), "=f"(d[5]), "=f"(d[6]), "=f"(d[7]), "=f"(d[8]), "=f"(d[9]), "=f"(d[10]), "=f"(d[11]), "=f"(d[12]), "=f"(d[13]), "=f"(d[14]), "=f"(d[15]), "=f"(d[16]), "=f"(d[17]), "=f"(d[18]), "=f"(d[19]), "=f"(d[20]), "=f"(d[21]), "=f"(d[22]), "=f"(d[23]), "=f"(d[24]), "=f"(d[25]), "=f"(d[26]), "=f"(d[27]), "=f"(d[28]), "=f"(d[29]), "=f"(d[30]), "=f"(d[31]) : "l"(da), "l"(db));
}
__device__ __forceinline__ void wg_n64_s(float* d, uint64_t da, uint64_t db) {
    asm volatile("wgmma.mma_async.sync.aligned.m64n64k16.f32.bf16.bf16 {%0, %1, %2, %3, %4, %5, %6, %7, %8, %9, %10, %11, %12, %13, %14, %15, %16, %17, %18, %19, %20, %21, %22, %23, %24, %25, %26, %27, %28, %29, %30, %31}, %32, %33, 1, 1, 1, 1, 0;"
                 : "+f"(d[0]), "+f"(d[1]), "+f"(d[2]), "+f"(d[3]), "+f"(d[4]), "+f"(d[5]), "+f"(d[6]), "+f"(d[7]), "+f"(d[8]), "+f"(d[9]), "+f"(d[10]), "+f"(d[11]), "+f"(d[12]), "+f"(d[13]), "+f"(d[14]), "+f"(d[15]), "+f"(d[16]), "+f"(d[17]), "+f"(d[18]), "+f"(d[19]), "+f"(d[20]), "+f"(d[21]), "+f"(d[22]), "+f"(d[23]), "+f"(d[24]), "+f"(d[25]), "+f"(d[26]), "+f"(d[27]), "+f"(d[28]), "+f"(d[29]), "+f"(d[30]), "+f"(d[31]) : "l"(da), "l"(db));
}
__device__ __forceinline__ void wg_n64(float* d, uint32_t a0, uint32_t a1, uint32_t a2, uint32_t a3, uint64_t db) {
    asm volatile("wgmma.mma_async.sync.aligned.m64n64k16.f32.bf16.bf16 {%0, %1, %2, %3, %4, %5, %6, %7, %8, %9, %10, %11, %12, %13, %14, %15, %16, %17, %18, %19, %20, %21, %22, %23, %24, %25, %26, %27, %28, %29, %30, %31}, {%32, %33, %34, %35}, %36, 1, 1, 1, 0;"
                 : "+f"(d[0]), "+f"(d[1]), "+f"(d[2]), "+f"(d[3]), "+f"(d[4]), "+f"(d[5]), "+f"(d[6]), "+f"(d[7]), "+f"(d[8]), "+f"(d[9]), "+f"(d[10]), "+f"(d[11]), "+f"(d[12]), "+f"(d[13]), "+f"(d[14]), "+f"(d[15]), "+f"(d[16]), "+f"(d[17]), "+f"(d[18]), "+f"(d[19]), "+f"(d[20]), "+f"(d[21]), "+f"(d[22]), "+f"(d[23]), "+f"(d[24]), "+f"(d[25]), "+f"(d[26]), "+f"(d[27]), "+f"(d[28]), "+f"(d[29]), "+f"(d[30]), "+f"(d[31]) : "r"(a0), "r"(a1), "r"(a2), "r"(a3), "l"(db));
}
__device__ __forceinline__ void wg_n64_first(float* d, uint32_t a0, uint32_t a1, uint32_t a2, uint32_t a3, uint64_t db) {
    asm volatile("wgmma.mma_async.sync.aligned.m64n64k16.f32.bf16.bf16 {%0, %1, %2, %3, %4, %5, %6, %7, %8, %9, %10, %11, %12, %13, %14, %15, %16, %17, %18, %19, %20, %21, %22, %23, %24, %25, %26, %27, %28, %29, %30, %31}, {%32, %33, %34, %35}, %36, 0, 1, 1, 0;"
                 : "=f"(d[0]), "=f"(d[1]), "=f"(d[2]), "=f"(d[3]), "=f"(d[4]), "=f"(d[5]), "=f"(d[6]), "=f"(d[7]), "=f"(d[8]), "=f"(d[9]), "=f"(d[10]), "=f"(d[11]), "=f"(d[12]), "=f"(d[13]), "=f"(d[14]), "=f"(d[15]), "=f"(d[16]), "=f"(d[17]), "=f"(d[18]), "=f"(d[19]), "=f"(d[20]), "=f"(d[21]), "=f"(d[22]), "=f"(d[23]), "=f"(d[24]), "=f"(d[25]), "=f"(d[26]), "=f"(d[27]), "=f"(d[28]), "=f"(d[29]), "=f"(d[30]), "=f"(d[31]) : "r"(a0), "r"(a1), "r"(a2), "r"(a3), "l"(db));
}

__device__ __forceinline__ void wg_n32t(float* d, uint32_t a0, uint32_t a1, uint32_t a2, uint32_t a3, uint64_t db) {
    asm volatile("wgmma.mma_async.sync.aligned.m64n32k16.f32.bf16.bf16 {%0, %1, %2, %3, %4, %5, %6, %7, %8, %9, %10, %11, %12, %13, %14, %15}, {%16, %17, %18, %19}, %20, 1, 1, 1, 1;"
                 : "+f"(d[0]), "+f"(d[1]), "+f"(d[2]), "+f"(d[3]), "+f"(d[4]), "+f"(d[5]), "+f"(d[6]), "+f"(d[7]), "+f"(d[8]), "+f"(d[9]), "+f"(d[10]), "+f"(d[11]), "+f"(d[12]), "+f"(d[13]), "+f"(d[14]), "+f"(d[15]) : "r"(a0), "r"(a1), "r"(a2), "r"(a3), "l"(db));
}
__device__ __forceinline__ void wg_n32t_first(float* d, uint32_t a0, uint32_t a1, uint32_t a2, uint32_t a3, uint64_t db) {
    asm volatile("wgmma.mma_async.sync.aligned.m64n32k16.f32.bf16.bf16 {%0, %1, %2, %3, %4, %5, %6, %7, %8, %9, %10, %11, %12, %13, %14, %15}, {%16, %17, %18, %19}, %20, 0, 1, 1, 1;"
                 : "=f"(d[0]), "=f"(d[1]), "=f"(d[2]), "=f"(d[3]), "=f"(d[4]), "=f"(d[5]), "=f"(d[6]), "=f"(d[7]), "=f"(d[8]), "=f"(d[9]), "=f"(d[10]), "=f"(d[11]), "=f"(d[12]), "=f"(d[13]), "=f"(d[14]), "=f"(d[15]) : "r"(a0), "r"(a1), "r"(a2), "r"(a3), "l"(db));
}
__device__ __forceinline__ void wg_n32t_sfirst(float* d, uint64_t da, uint64_t db) {
    asm volatile("wgmma.mma_async.sync.aligned.m64n32k16.f32.bf16.bf16 {%0, %1, %2, %3, %4, %5, %6, %7, %8, %9, %10, %11, %12, %13, %14, %15}, %16, %17, 0, 1, 1, 1, 1;"
                 : "=f"(d[0]), "=f"(d[1]), "=f"(d[2]), "=f"(d[3]), "=f"(d[4]), "=f"(d[5]), "=f"(d[6]), "=f"(d[7]), "=f"(d[8]), "=f"(d[9]), "=f"(d[10]), "=f"(d[11]), "=f"(d[12]), "=f"(d[13]), "=f"(d[14]), "=f"(d[15]) : "l"(da), "l"(db));
}
__device__ __forceinline__ void wg_n32t_s(float* d, uint64_t da, uint64_t db) {
    asm volatile("wgmma.mma_async.sync.aligned.m64n32k16.f32.bf16.bf16 {%0, %1, %2, %3, %4, %5, %6, %7, %8, %9, %10, %11, %12, %13, %14, %15}, %16, %17, 1, 1, 1, 1, 1;"
                 : "+f"(d[0]), "+f"(d[1]), "+f"(d[2]), "+f"(d[3]), "+f"(d[4]), "+f"(d[5]), "+f"(d[6]), "+f"(d[7]), "+f"(d[8]), "+f"(d[9]), "+f"(d[10]), "+f"(d[11]), "+f"(d[12]), "+f"(d[13]), "+f"(d[14]), "+f"(d[15]) : "l"(da), "l"(db));
}

__device__ __forceinline__ void wg_n32_kk(float* d, uint64_t da, uint64_t db) {
    asm volatile("wgmma.mma_async.sync.aligned.m64n32k16.f32.bf16.bf16 {%0, %1, %2, %3, %4, %5, %6, %7, %8, %9, %10, %11, %12, %13, %14, %15}, %16, %17, 1, 1, 1, 0, 0;"
                 : "+f"(d[0]), "+f"(d[1]), "+f"(d[2]), "+f"(d[3]), "+f"(d[4]), "+f"(d[5]), "+f"(d[6]), "+f"(d[7]), "+f"(d[8]), "+f"(d[9]), "+f"(d[10]), "+f"(d[11]), "+f"(d[12]), "+f"(d[13]), "+f"(d[14]), "+f"(d[15]) : "l"(da), "l"(db));
}

}

namespace ws {
#define LAGT 4
constexpr int LAG = LAGT, NT = NSEG + LAG, NCL = 7;
#define P1A 24
#define P1C 10
#define XD 350
#define REG_G 200
#define REG_T 72
#define REG_X 40
template <int V> struct IC { static constexpr int value = V; };
#define POST_NS 20
#define OP_NS 20
#define LN0_AHEAD 8
#define TG_STEPS 40
#define NO_X 0
#define WTA 3
constexpr int WTC = 10 - 2 * WTA;
#define WR 3
#define OBK 2
#define WFLY 2
#define H_NS 20
#define C_REV 1
#define ONE_FENCE 0
#define LN0_BATCH 1
static_assert(LN0_AHEAD + LN0_BATCH + LAG + 1 <= 16 && (NSEG - LN0_AHEAD) % LN0_BATCH == 0, "ring of the scratch buffers");
constexpr int XRS = 3;
constexpr int O_H = 0, O_MEM = 81920, O_RED = 102400, O_BAR = 110080, O_TAB = O_BAR + 192, O_BT = O_TAB + 128, O_TR = O_BAR + 512, O_X = O_TR + 1024;
constexpr int O_QRY = O_X, O_KEY = O_X + 10240, O_OBA = O_KEY + 10240, O_ST = O_OBA + 4096;
constexpr int O_VT = O_X, O_VM = O_VT + 32768, O_SM = O_VM + 4096, O_PB = O_SM + 3072;
constexpr int O_AS = 228352, O_WO = O_AS - 65536, HEAD_SMEM = O_AS + 4096, O_STG = 40960;
static_assert(O_ST + 8192 <= O_WO && O_PB + 10240 <= O_WO && O_AS % 1024 == 0 && O_STG + 163840 <= O_AS && HEAD_SMEM <= 232448, "smem");
constexpr int B_MEM = 0, B_RED = 64, B_SM = 88, B_ST = 96, B_OB = 104, B_HF = 112, B_HE = 128, B_OTF = 144, B_OTE = 160;

constexpr int F_H = 0, F_O = 128, F_P = 256, F_U = 384, F_CV = 392, F_XL = 398, F_Z = 399, NFLAG = 400;
__device__ int g_flags[NFLAG * 8];
#define FLG(i) (g_flags + (i) * 8)
#define RING 16
__device__ __forceinline__ int rslot(int l, int seg) { return l * RING + (seg & (RING - 1)); }
__device__ uint4 g_ht[2 * RING * 2560];
__device__ uint4 g_ot[2 * RING * 256 * 64];
__device__ uint4 g_pt[2 * RING * 5120];
__device__ uint4 g_Y[80 * S_LEN];
__device__ uint4 g_U[DM * S_LEN / 8];
__device__ bf16 g_x[RING * SEG * DM];
__device__ int g_epoch;
__device__ uint4 g_xc[XRS * 16 * 3 * 8 * 32];
#define GT(cond, i)
#define SC(cond, i)
#define SD(x)
#define TS(i)
#define TV(i, v)

}

namespace ws {
__device__ __forceinline__ uint32_t bmul2(uint32_t a, uint32_t b) { uint32_t r; asm("mul.rn.bf16x2 %0, %1, %2;" : "=r"(r) : "r"(a), "r"(b)); return r; }
__device__ __forceinline__ uint32_t bmax2(uint32_t a, uint32_t b) { uint32_t r; asm("max.bf16x2 %0, %1, %2;" : "=r"(r) : "r"(a), "r"(b)); return r; }
__device__ __forceinline__ void flag_wait(const int* f, int tgt, int ns) {
    int guard = 0;
    while (ld_relaxed(f) < tgt) { if (++guard > 4000000) __trap(); __nanosleep(ns); }
}
template <int STRIDE> __device__ __forceinline__ void ld5(uint32_t* w, const void* p) {
#pragma unroll
    for (int r = 0; r < 5; r++) { const uint2 v = __ldcg(reinterpret_cast<const uint2*>(reinterpret_cast<const char*>(p) + r * STRIDE)); w[2 * r] = v.x; w[2 * r + 1] = v.y; }
}
template <int STRIDE> __device__ __forceinline__ void st5(void* p, const uint32_t* w) {
#pragma unroll
    for (int r = 0; r < 5; r++) *reinterpret_cast<uint2*>(reinterpret_cast<char*>(p) + r * STRIDE) = make_uint2(w[2 * r], w[2 * r + 1]);
}
__device__ __forceinline__ void ln_row(const uint32_t* x, uint32_t* y) {
    const float c = blo(__shfl_sync(0xffffffffu, x[0], 0));
    float s0 = 0.f, s1 = 0.f, q0 = 0.f, q1 = 0.f;
#pragma unroll
    for (int i = 0; i < 10; i++) { const float d0 = blo(x[i]) - c, d1 = bhi(x[i]) - c; s0 += d0; s1 += d1; q0 = fmaf(d0, d0, q0); q1 = fmaf(d1, d1, q1); }
    float s = s0 + s1, q = q0 + q1;
#pragma unroll
    for (int o = 16; o > 0; o >>= 1) { s += __shfl_xor_sync(0xffffffffu, s, o); q += __shfl_xor_sync(0xffffffffu, q, o); }
    s *= 1.0f / DM;
    const float mean = c + s;
    q = fmaxf(fmaf(q, 1.0f / DM, -s * s), 0.f);
    const uint32_t nm = pack2(-mean, -mean);
    float sq;
    asm("sqrt.approx.ftz.f32 %0, %1;" : "=f"(sq) : "f"(rbf(rbf(q) + 1e-5f)));
    const float rd = rcpf(rbf(sq));
#pragma unroll
    for (int i = 0; i < 10; i++) { const uint32_t d = badd(x[i], nm); y[i] = pack2(blo(d) * rd, bhi(d) * rd); }
}
__device__ __forceinline__ void clear_acc(int l, int seg, int tok, int lane) {
    uint4* pz = g_pt + rslot(l, seg) * 5120 + (lane >> 4) * 512 + tok * 16 + (lane & 15);
#pragma unroll
    for (int i = 0; i < 5; i++) pz[i * 1024] = make_uint4(0, 0, 0, 0);
}
__device__ __forceinline__ void put_h(int l, int seg, int tok, int lane, const uint32_t* n) {
    st5<8192>(reinterpret_cast<char*>(g_ht + rslot(l, seg) * 2560) + (lane >> 2) * 1024 + tok * 32 + (((lane & 3) * 8) ^ ((tok & 4) << 2)), n);
}
__device__ __forceinline__ void ln0_rows(const bf16* x, int seg, int cnt, int tok, int lane) {
#pragma unroll 1
    for (int i = 0; i < cnt; i++) {
        uint32_t v[10];
        ld5<256>(v, x + (size_t)((seg + i) * SEG + tok) * DM + lane * 4);
        clear_acc(0, seg + i, tok, lane);
        ln_row(v, v);
        put_h(0, seg + i, tok, lane, v);
    }
    __syncwarp();
    if (lane == 0) {
        red_release(FLG(F_H + seg), 1);
        for (int i = 1; i < cnt; i++) asm volatile("red.relaxed.gpu.global.add.u32 [%0], 1;" ::"l"(FLG(F_H + seg + i)) : "memory");
    }
}
__device__ __forceinline__ void post_row(int l, int seg, int tok, int lane, const bf16* xin, bf16* xout, int ep) {
    uint32_t x[10], y[10], n[10];
    const int row = seg * SEG + tok;
    SC(tr, tb);
    const bool first = seg == 0;
    if (seg == 8 || ((seg & 15) == 0 && seg)) flag_wait(FLG(F_CV + (seg >> 4) + 1), 80 * ep, 50);
    const char* yp = reinterpret_cast<const char*>(g_Y) + ((size_t)(lane >> 1) * S_LEN + row) * 16 + (lane & 1) * 8;
    SC(tr, tb + 1);
    if (!first) ld5<16 * S_LEN * 16>(y, yp);
    bf16* xm = g_x + ((seg & (RING - 1)) * SEG + tok) * DM + lane * 4;
    if (l == 0) {
        ld5<256>(x, xin + (size_t)row * DM + lane * 4);
        clear_acc(1, seg, tok, lane);
    } else {
        flag_wait(seg + 1 < NSEG ? FLG(F_H + 65 + seg) : FLG(F_XL), 32 * ep, 50);
        ld5<256>(x, xm);
    }
    flag_wait(FLG(F_P + l * 64 + seg), 40 * ep, POST_NS);
    SC(tr, tb + 2);
    const uint4* pp = g_pt + rslot(l, seg) * 5120 + (lane >> 4) * 512 + tok * 16 + ((lane & 15) ^ ((tok >> 3) << 1));
    {
        uint4 a[5];
#pragma unroll
        for (int i = 0; i < 5; i++) a[i] = __ldcg(pp + i * 1024);
#pragma unroll
        for (int i = 0; i < 5; i++) {
            x[2 * i] = badd(x[2 * i], pack2(__uint_as_float(a[i].x), __uint_as_float(a[i].y)));
            x[2 * i + 1] = badd(x[2 * i + 1], pack2(__uint_as_float(a[i].z), __uint_as_float(a[i].w)));
        }
    }
    SC(tr && x[0] != 0x12345, tb + 3);
    if (first) { flag_wait(FLG(F_CV), 80 * ep, 50); ld5<16 * S_LEN * 16>(y, yp); }
    ln_row(x, n);
#pragma unroll
    for (int i = 0; i < 10; i++) x[i] = badd(x[i], bmul2(n[i], y[i]));
    SC(tr && x[0] != 0x12345, tb + 4);
    if (l) st5<256>(xout + (size_t)row * DM + lane * 4, x);
    else {
        ln_row(x, n);
        SC(tr && n[0] != 0x12345, tb + 5);
        put_h(1, seg, tok, lane, n);
        __syncwarp();
        if (lane == 0) red_release(FLG(F_H + 64 + seg), 1);
        SC(tr, tb + 6);
        st5<256>(xm, x);
        if (seg == NSEG - 1) { __syncwarp(); if (lane == 0) red_release(FLG(F_XL), 1); }
    }
}
__device__ __forceinline__ void u_piece(const bf16* Bk, const bf16* Bv, const bf16* shiftk, int t0, int cp, uint4* o) {
    uint32_t kk[11], vv[8];
    const uint32_t* pk = reinterpret_cast<const uint32_t*>(Bk + (size_t)t0 * DM) + cp;
    const uint32_t* pv = reinterpret_cast<const uint32_t*>(Bv + (size_t)t0 * DM) + cp;
#pragma unroll
    for (int i = 0; i < 11; i++) kk[i] = (i >= 3 || t0 > 0) ? __ldg(pk + (i - 3) * (DM / 2)) : 0u;
#pragma unroll
    for (int i = 0; i < 8; i++) vv[i] = __ldg(pv + i * (DM / 2));
    const uint4 sh0 = __ldg(reinterpret_cast<const uint4*>(shiftk + cp * 8));
    const uint32_t s0 = __byte_perm(sh0.x, sh0.z, 0x5410), s1 = __byte_perm(sh0.x, sh0.z, 0x7632), s2 = __byte_perm(sh0.y, sh0.w, 0x5410), s3 = __byte_perm(sh0.y, sh0.w, 0x7632);
#pragma unroll
    for (int t = 0; t < 8; t++)
        vv[t] = bmul2(badd(badd(badd(bmul2(kk[t], s3), bmul2(kk[t + 1], s2)), bmul2(kk[t + 2], s1)), bmul2(kk[t + 3], s0)), vv[t]);
#pragma unroll
    for (int c = 0; c < 2; c++) {
        const uint32_t sel = c ? 0x7632 : 0x5410;
        o[c] = make_uint4(__byte_perm(vv[7], vv[6], sel), __byte_perm(vv[5], vv[4], sel), __byte_perm(vv[3], vv[2], sel), __byte_perm(vv[1], vv[0], sel));
    }
}
__device__ __forceinline__ int u_pos(int t0) { return (t0 >> 6) * 8 + ((((t0 ^ 56) & 63) >> 3) ^ ((t0 >> 6) & 7)); }
__device__ __forceinline__ void u_half(const bf16* Bk, const bf16* Bv, const bf16* shiftk, int unit, int lane) {
    const int t0 = (unit / 20) * 16 + (lane & 1) * 8, cp = (unit % 20) * 16 + (lane >> 1);
    uint4 o[2];
    u_piece(Bk, Bv, shiftk, t0, cp, o);
    uint4* d = g_U + (size_t)(cp * 2) * (S_LEN / 8) + u_pos(t0);
    d[0] = o[0]; d[S_LEN / 8] = o[1];
}
constexpr int CV_E = 4224, CV_W = 2 * 4096 + 3 * CV_E + 128, CV_HI = O_X, CV_Y = CV_HI + 4 * CV_W, CV_T = CV_Y + 16384, CV_Z = CV_T + 16384;
static_assert(4 * CV_W <= O_RED && CV_W % 128 == 0 && CV_Z + 128 <= HEAD_SMEM, "conv buffers");
__device__ __forceinline__ void conv_unit(uint32_t ub, uint32_t e0, uint32_t e1, uint32_t zrow, uint32_t tt, uint32_t Dv, int rg, int nq, int lane, uint32_t zero, int tb) {
    const int g7 = 7 - (lane >> 2), tq = lane & 3;
    SC(tb >= 0, tb + 3);
    for (int i = lane; i < 32 * nq + 8; i += 32) {
        const uint4 v = lds128(e0 + i * 16);
        const uint32_t nx = lds32(e0 + i * 16 + 16);
        sts128(e1 + i * 16, __byte_perm(v.x, v.y, 0x5432), __byte_perm(v.y, v.z, 0x5432), __byte_perm(v.z, v.w, 0x5432), __byte_perm(v.w, nx, 0x5432));
    }
    __syncwarp();
    SC(tb >= 0, tb + 4);
    float acc[4][4];
#pragma unroll
    for (int i = 0; i < 16; i++) (&acc[0][0])[i] = 0.f;
    uint32_t wb = (g7 & 1) ? e0 + (1 + g7 + 2 * tq) * 2 : e1 + (g7 + 2 * tq) * 2;
    int row = 8 * rg + (lane & 7);
    auto ldb = [&](uint4* b) {
        const uint32_t x = row < 0 ? zrow : ub + row * 128 + (((lane >> 3) ^ (row & 7)) << 4);
        b[0] = ldsm4(x); b[1] = ldsm4(x ^ 64);
        row--;
    };
    uint4 Q[16], b[2][2];
    Q[15].w = lds32(wb);
    auto ldq = [&](int q, int o) { Q[q].y = lds32(wb + o * 32 + 16); Q[q].w = lds32(wb + o * 32 + 32); };
    auto cpq = [&](int q) { Q[q].x = Q[(q + 15) & 15].w + zero; Q[q].z = Q[q].y + zero; };
#pragma unroll
    for (int q = 0; q < 11; q++) ldq(q, q);
#pragma unroll
    for (int q = 0; q < 7; q++) cpq(q);
    ldb(b[0]);
#pragma unroll 1
    for (int D0 = nq; D0 > 0; D0--) {
#pragma unroll
        for (int d = 0; d < 4; d++) {
            ldb(b[(d + 1) & 1]);
#pragma unroll
            for (int q = 11; q < 15; q++) ldq((4 * d + q) & 15, 4 * d + q);
#pragma unroll
            for (int ks = 0; ks < 4; ks++) {
                const uint4& bb_ = b[d & 1][ks >> 1];
#pragma unroll
                for (int m = 0; m < 4; m++) {
                    const uint4& a = Q[(4 * d + m + ks) & 15];
                    mmav(acc[m], a.x, a.y, a.z, a.w, (ks & 1) ? bb_.z : bb_.x, (ks & 1) ? bb_.w : bb_.y);
                }
                cpq((4 * d + 7 + ks) & 15);
            }
        }
        wb += 512;
    }
    SC(tb >= 0 && acc[0][0] != 1.2345f, tb + 5);
    const uint32_t ua = ub + (8 * rg + (lane & 7)) * 128 + (((lane >> 3) ^ (lane & 7)) << 4);
    const uint4 u0 = ldsm4t(ua), u1 = ldsm4t(ua ^ 64);
    auto y = [&](int m, int hf, uint32_t u) { return badd(pack2(acc[m][2 * hf], acc[m][2 * hf + 1]), bmul2(u, Dv)); };
    stsm4t(tt, y(0, 0, u1.w), y(0, 1, u1.z), y(1, 0, u1.y), y(1, 1, u1.x));
    stsm4t(tt ^ 64, y(2, 0, u0.w), y(2, 1, u0.z), y(3, 0, u0.y), y(3, 1, u0.x));
}
}

namespace ws {
struct HeadArgs { const bf16 *x, *mem0, *Wq, *Wk, *Wv, *Wo, *Bk, *Bv, *shiftk, *ssmk, *ssmD; bf16* out; int h_target; };

__global__ void __launch_bounds__(512, 1) head_kernel(const __grid_constant__ HeadArgs A) {
    extern __shared__ __align__(1024) unsigned char smem_raw[];
    const int tid = threadIdx.x, warp = __shfl_sync(0xffffffffu, tid >> 5, 0), lane = tid & 31;
    const int cq = blockIdx.x >> 4, r = blockIdx.x & 15;
    const int nh = cq < 4 ? 5 : 4, hi = r / 3, role = r - hi * 3;
    const bool head = r < 3 * nh;
    const int p0 = r >> 1;
    const int h = (cq < 4 ? 5 * cq : 4 * cq + 4) + hi;
    const uint32_t sb = smem_u32(smem_raw), bb = sb + O_BAR;
    GT(tid == 0, 1);
    const int sp = cq < 4 ? cq : 4 * cq + r - 24;
    if (tid == 0) {
        if ((sb & 0xFFFFFFu) != 1024) __trap();
        for (int i = 0; i < 12; i++) mbar_init(bb + i * 8, 1);
        mbar_init(bb + B_ST, role == 2 ? 1 : 5);
        mbar_init(bb + B_OB, 1); mbar_init(bb + B_OB + 64, 1);
        mbar_init(bb + B_HF, 1); mbar_init(bb + B_HF + 8, 1);
        mbar_init(bb + B_HE, 6 * nh);
        mbar_init(bb + B_OTF, head ? 4 : 8); mbar_init(bb + B_OTE, 1); mbar_init(bb + B_OTF + 8, head ? 4 : 8); mbar_init(bb + B_OTE + 16, 1);
        asm volatile("fence.mbarrier_init.release.cluster;" ::: "memory");
        mbar_expect_tx(bb + B_RED, nh * 1280);
        mbar_expect_tx(bb + B_SM, 3072); mbar_expect_tx(bb + B_ST, role == 2 ? 5120 : 4096);
        if (role != 2) { mbar_expect_tx(bb + B_OB, 2048); mbar_expect_tx(bb + B_OB + 64, 2048); }
        mbar_expect_tx(bb + B_HF, 40960); mbar_expect_tx(bb + B_HF + 8, 40960);
    }
    asm volatile("griddepcontrol.launch_dependents;");
    __syncwarp();
    cluster_arrive_relaxed();
    if (warp < 8) {
        asm volatile("setmaxnreg.inc.sync.aligned.u32 %0;" ::"n"(REG_G));
        const int wg = warp >> 2, w4 = warp & 3;
        if (head) {
            uint32_t wa[40][4];
            {
                const int t7 = tid & 127;
                const bf16* W = (role == 2 ? A.Wv + wg * 64 : (wg ? A.Wk : A.Wq) + role * 64) + h * DH + (size_t)(t7 >> 3) * HD + (t7 & 7) * 8;
                const uint32_t so = (t7 >> 3) * 128 + (((t7 & 7) ^ ((t7 >> 3) & 7)) << 4), stg = sb + O_STG + wg * 81920;
                const uint32_t la = stg + ((lane & 7) + (lane >> 4) * 8) * 128 + (((w4 * 2 + ((lane >> 3) & 1)) ^ (lane & 7)) << 4);
                GT(tid == 0, 80);
#pragma unroll
                for (int gi = 0; gi < 8 + WFLY; gi++) {
                    if (gi < 8) {
                        const bf16* Wg = W + (size_t)(((p0 - gi) & 7) * 80) * HD;
#pragma unroll
                        for (int u = 0; u < 5; u++) cp_async16((gi == 0 && u == 0 ? sb + O_AS + wg * 2048 : stg + (gi * 5 + u) * 2048) + so, Wg + (size_t)u * 16 * HD);
                    }
                    cp_commit();
                    if (gi >= WFLY) {
                        cp_wait<WFLY>();
                        named_bar(8 + wg, 128);
#pragma unroll
                        for (int u = 0; u < 5; u++) {
                            const int j = (gi - WFLY) * 5 + u;
                            if (j) { const uint4 v = ldsm4t(la + j * 2048); wa[j][0] = v.x; wa[j][1] = v.y; wa[j][2] = v.z; wa[j][3] = v.w; }
                        }
                    }
                }
                GT(tid == 0, 83);
                cluster_wait();
            }
            named_bar(10, 384);
            GT(tid == 0, 2);
            fence_async_smem();
            named_bar(8 + wg, 128);
            cluster_arrive_relaxed();
            float acc[16];
            const uint32_t ep_q = role == 2 ? sb + O_VM + warp * 512 + (lane ^ ((lane >> 3) & 1)) * 16
                                            : sb + O_QRY + wg * 10240 + ((lane >> 1) & 1) * 5120 + (4 * (lane >> 4) + 2 * ((lane >> 2) & 1) + (lane & 1)) * 128 +
                                                  (((2 * w4 + ((lane >> 3) & 1)) ^ (4 * (lane >> 4) + 2 * ((lane >> 2) & 1) + (lane & 1)) ^ ((lane & 2) << 1)) << 4);
            const uint32_t ep_t = role == 2 ? sb + O_VT + warp * 1024 + ((lane >> 3) & 1) * 512 + (lane >> 4) * 128 + (lane & 7) * 16
                                            : sb + O_QRY + wg * 10240 + (8 + 8 * (lane >> 4) + (lane & 7)) * 128 + (((2 * w4 + ((lane >> 3) & 1)) ^ (lane & 7)) << 4);
                        const int pz = role == 2 ? P1C : P1A;
            const uint32_t ab = (1024 + O_AS + wg * 2048) >> 4;
            uint32_t ok = 1;
            const uint32_t tidk = __shfl_sync(0xffffffffu, tid, lane);
            auto token_gemm = [&](auto ll, const bool pause, const uint32_t vo, const uint32_t nbar, const uint32_t npar, const int t) {
                constexpr int l = decltype(ll)::value;
                constexpr uint32_t hb = ((1024 + O_H + l * 40960) >> 4) | (1u << 16);
                const uint32_t pr = opq(p0);
                if (l) TS(15); else TS(14);
                wg_fence();
#pragma unroll
                for (int j = 0; j < 40; j++) {
                    const uint64_t db = mkdesc(hb + ((pr - j / 5) & 7) * 320 + (j % 5) * 64, 0xC0000010u);
                    if (j == 0) wg_n32_sfirst(acc, mkdesc(ab, 0x40000040u), db);
                    else if (j < TG_STEPS) wg_n32(acc, wa[j][0], wa[j][1], wa[j][2], wa[j][3], db);
                    if (l == 0 && (j + 1 == P1A || j + 1 == P1C)) {
                        if (pause && pz == j + 1) {
                            wg_commit();
                            if (role == 2) mwait(bb + B_OTE, vo >> 14);
                            wg_wait<0>();
                            named_arrive(3, 384);
                            named_bar(4, 384);
                            wg_fence();
                        }
                    }
                }
                wg_commit();
                ok = mtest(nbar, npar);
                wg_wait<0>();
                uint32_t pk[8];
#pragma unroll
                for (int i = 0; i < 8; i++) pk[i] = pack2(acc[2 * i], acc[2 * i + 1]);
                if (role == 2) {
                    stsm4(ep_t + l * 8192 + vo, pk[0], pk[1], pk[2], pk[3]);
                    stsm4(ep_t + l * 8192 + vo + 256, pk[4], pk[5], pk[6], pk[7]);
                } else {
                    stsm4t((ep_t ^ (l << 6)) + l * 5120, pk[0], pk[1], pk[2], pk[3]);
                    stsm4t((ep_t ^ (l << 6)) + l * 5120 + 2048, pk[4], pk[5], pk[6], pk[7]);
                }
                asm volatile("{\n.reg .pred p, q;\nsetp.eq.u32 p, %0, 0;\nsetp.eq.u32 q, %1, 0;\n"
                             "@p mbarrier.arrive.expect_tx.shared::cta.b64 _, [%2], %3;\n@q mbarrier.arrive.shared::cluster.b64 _, [%4];\n}"
                             ::"r"(tidk), "r"(tidk & 127), "r"(bb + B_HF + l * 8), "r"(40960), "r"(mapa(bb + B_HE, l)) : "memory");
            };
            GT(tid == 0, 86);
            mwait(bb + B_HF, 0);
            GT(tid == 0, 87);
            token_gemm(IC<0>{}, false, 0, bb + B_MEM, 1, -1);
            GT(tid == 0, 88);
            named_bar(11, 384);
            cluster_wait();
            named_arrive(13, 384);
#pragma unroll 1
            for (int t = 0; t < NT; t++) {
                GT(tid == 0 && blockIdx.x == 98, 100 + t);
                SC(tid == 0 && blockIdx.x == 98, 160 + t);
                TS(0);
                const uint32_t mp = (t & 1) ^ 1;
                const bool tg0 = t + 1 < NSEG, tg1 = t + 1 >= LAG;
                constexpr uint32_t mb = ((1024 + O_MEM) >> 4) | (16u << 16);
#pragma unroll
                for (int G = 0; G < 8; G++) {
                    if (__builtin_expect(!ok, 0)) mwait(bb + B_MEM + G * 8, mp);
                    ok = mtest(G < 7 ? bb + B_MEM + (G + 1) * 8 : bb + B_HF, mp);
                    if (G == 0) { TS(1); wg_fence(); }
                    if (G == 7) TS(2);
                    if (G == 1) TS(8); if (G == 2) TS(9); if (G == 3) TS(10); if (G == 4) TS(11); if (G == 5) TS(12); if (G == 6) TS(13);
#pragma unroll
                    for (int u = 0; u < 5; u++) {
                        const int j = G * 5 + u;
                        const uint64_t db = mkdesc(mb + j * 32, 8);
                        if (j == 0) wg_n16t_sfirst(acc, mkdesc(ab, 0x40000040u), db);
                        else wg_n16t(acc, wa[j][0], wa[j][1], wa[j][2], wa[j][3], db);
                    }
                    wg_commit();
                }
                if (role == 2 && t) named_bar(5, 384);
                wg_wait<0>();
                TS(3);
                if (role == 2) sts128(ep_q, pack2(acc[0], acc[1]), pack2(acc[2], acc[3]), pack2(acc[4], acc[5]), pack2(acc[6], acc[7]));
                else stsm4t(ep_q, pack2(acc[0], acc[1]), pack2(acc[2], acc[3]), pack2(acc[4], acc[5]), pack2(acc[6], acc[7]));
                named_arrive(1, 384);
                if (tidk < 8) mbar_expect_tx(bb + B_MEM + tidk * 8, 2560);
                if (t == NT - 1) break;
                if (tg0) {
                    if (__builtin_expect(!ok, 0)) mwait(bb + B_HF, mp);
                    if (role != 2) named_bar(2, 384);
                    token_gemm(IC<0>{}, true, mp * 16384, tg1 ? bb + B_HF + 8 : bb + B_MEM, tg1 ? (t + 1 - LAG) & 1 : mp ^ 1, t);
                } else {
                    if (role == 2) mwait(bb + B_OTE, mp); else named_bar(2, 384);
                    named_arrive(3, 384); named_bar(4, 384);
                    ok = 0;
                }
                TS(5);
                if (tg1) {
                    if (__builtin_expect(!ok, 0)) mwait(bb + B_HF + 8, (t + 1 - LAG) & 1);
                    token_gemm(IC<1>{}, false, mp * 16384, bb + B_MEM, mp ^ 1, t);
                }
                TS(6);
                named_arrive(13, 384);
            }
        } else {
            cluster_wait(); cluster_arrive_relaxed();
            const int ep = ld_relaxed(&g_epoch) + 1;
            const uint32_t cb = sb + (warp < 4 ? warp * CV_W : CV_HI + (warp - 4) * CV_W), lb = bb + B_MEM + warp * 8;
            auto fetch = [&](int k) {
                const int ps = k / 5, rg = ps ? ps - 1 : 0, ch = (sp * 5 + k - 5 * ps) * 8 + warp;
                if (k == 5 * ps) { flag_wait(FLG(F_U + ps), (ps > 1 ? 20 : (ps ? 32 : 320)) * ep, 50); fence_async_global(); }
                if (lane == 0) {
                    const uint32_t nb = ps ? ps * 1024 : 512;
                    mbar_expect_tx(lb, 2 * nb);
                    asm volatile("cp.async.bulk.shared::cluster.global.mbarrier::complete_tx::bytes [%0], [%1], %2, [%3];" ::"r"(cb + (k & 1) * 4096), "l"(g_U + ch * (S_LEN / 8)), "r"(nb), "r"(lb) : "memory");
                    asm volatile("cp.async.bulk.shared::cluster.global.mbarrier::complete_tx::bytes [%0], [%1], %2, [%3];" ::"r"(cb + 8192 + (k & 1) * CV_E + 128), "l"(A.ssmk + (size_t)ch * S_LEN), "r"(nb), "r"(lb) : "memory");
                }
                __syncwarp();
            };
            sts32(cb + 8192 + lane * 4, 0u); sts32(cb + 8192 + CV_E + lane * 4, 0u);
            if (warp == 0) sts32(sb + CV_Z + lane * 4, 0u);
            uint32_t dv = 0;
            if (lane < 5) {
                prefetch_l2(A.ssmk + (size_t)((sp * 5 + lane) * 8 + warp) * S_LEN, 1024);
                dv = *reinterpret_cast<const unsigned short*>(A.ssmD + (sp * 5 + lane) * 8 + warp) * 0x10001u;
            }
#pragma unroll
            for (int i = 1; i < 5; i++) sts32(cb + 8192 + i * 768 + lane * 4, 0u);
            named_bar(8, 256);
            flag_wait(FLG(F_U), 320 * ep, 50);
            fence_async_global();
            if (lane == 0) mbar_expect_tx(lb, 5120);
            __syncwarp();
            if (lane < 10) {
                const int j = lane >> 1, ch = (sp * 5 + j) * 8 + warp;
                asm volatile("cp.async.bulk.shared::cluster.global.mbarrier::complete_tx::bytes [%0], [%1], %2, [%3];" ::"r"((lane & 1) ? cb + j * 512 : cb + 8192 + j * 768 + 128),
                             "l"((lane & 1) ? (const void*)(g_U + ch * (S_LEN / 8)) : (const void*)(A.ssmk + (size_t)ch * S_LEN)), "r"(512), "r"(lb) : "memory");
            }
            __syncwarp();
#pragma unroll 1
            for (int k = 0; k < 25; k++) {
                const int ps = k / 5, rg = ps ? ps - 1 : 0;
                const uint32_t Dv = __shfl_sync(0xffffffffu, dv, k - 5 * ps);
                const int tb = sp == 0 && tid == 0 && k >= -1 && k < 7 ? 72 + k * 8 : -1;
                SC(tb >= 0, tb);
                if (k == 0 || ps) {
                    mwait(lb, k & 1);
                    SC(tb >= 0, tb + 1);
                    if (ps && k - 5 * ps < 4) { fence_async_smem(); fetch(k + 1); }
                    SC(tb >= 0, tb + 2);
                }
                const uint32_t tt = sb + CV_T + (k & 1) * 8192;
                conv_unit(cb + (ps ? (k & 1) * 4096 : k * 512), cb + 8192 + (ps ? (k & 1) * CV_E : k * 768), cb + 8192 + 2 * CV_E + 64, sb + CV_Z,
                          tt + warp * 1024 + (lane & 7) * 128 + (((lane >> 3) ^ (lane & 7) ^ warp) & 7) * 16, Dv, rg, ps ? 2 * ps : 1, lane, (uint32_t)A.h_target >> 8, tb);
                mwait(bb + B_OTE + (k & 1) * 16, ((k >> 1) & 1) ^ 1);
                named_bar(8, 256);
                {
                    const uint32_t la = tt + (lane & 7) * 1024 + warp * 128 + (((lane >> 3) ^ (lane & 7) ^ warp) & 7) * 16;
                    const uint4 v0 = ldsm4t(la), v1 = ldsm4t(la ^ 64);
                    const uint32_t ya = sb + CV_Y + (k & 1) * 8192 + (warp * 64 + (lane >> 3) * 8 + 7 - (lane & 7)) * 16;
                    stsm4(ya, v0.x, v0.y, v0.z, v0.w);
                    stsm4(ya + 512, v1.x, v1.y, v1.z, v1.w);
                }
                SC(tb >= 0, tb + 6);
                fence_async_smem();
                __syncwarp();
                if (lane == 0) mbar_arrive(bb + B_OTF + (k & 1) * 8);
                if (k - 5 * ps == 4 && k < 24) fetch(k + 1);
                if (k == 0 && lane < 5) prefetch_l2(A.ssmk + (size_t)((sp * 5 + lane) * 8 + warp) * S_LEN + 512, 3072);
            }
            cluster_wait();
        }
    } else if (warp < 12) {
        asm volatile("setmaxnreg.dec.sync.aligned.u32 %0;" ::"n"(REG_T));
        const int w = warp & 3, c = w >> 1, hh = w & 1;
        const uint32_t lane0 = __shfl_sync(0xffffffffu, tid & 31, tid & 31);
        if (head) {
            const int ntile = role == 2 ? 4 * WTC : 4 * WTA;
            auto tile = [&](int i) { return role == 2 && C_REV ? 39 - i : role * 4 * WTA + i; };
            const uint32_t wo = sb + O_WO;
            uint32_t mi[5][4];
#pragma unroll
            for (int i = 0; i < 5; i++)
#pragma unroll
                for (int q = 0; q < 4; q++) {
                    const unsigned short* mp = reinterpret_cast<const unsigned short*>(A.mem0) + 2 * q * DM + i * 128 + (tid & 127);
                    mi[i][q] = mp[0] | (uint32_t)mp[DM] << 16;
                }
            cluster_wait();
            named_bar(10, 384);
#pragma unroll
            for (int i = 0; i < 5; i++) {
                const int col = i * 128 + (tid & 127), kk = col >> 4, pr = (kk * 13) >> 6;
                const uint32_t ma = sb + O_MEM + (((p0 - pr) & 7) * 5 + kk - 5 * pr) * 512 + (col & 8) * 32 + (col & 7) * 16;
                sts128(ma, mi[i][0], mi[i][0], mi[i][1], mi[i][1]);
                sts128(ma + 128, mi[i][2], mi[i][2], mi[i][3], mi[i][3]);
            }
            fence_async_smem();
            named_arrive(11, 384);
            for (int i = tid & 127; i < ntile * 256; i += 128) {
                const int ti = i >> 8, p = (i >> 1) & 127, ch = i & 1;
                const int ks = p >> 4, kh = (p >> 3) & 1, e8 = p & 7;
                const int dim = 64 * (ks >> 2) + 16 * (e8 >> 1) + 8 * (e8 & 1) + 2 * (ks & 3) + kh;
                cp_async16(wo + ti * 4096 + p * 32 + ((ch ^ ((p >> 2) & 1)) << 4), A.Wo + (size_t)(h * DH + dim) * DM + tile(ti) * 16 + ch * 8);
            }
            cp_commit();
            if (lane < 8) {
                const int u = 2 * tile(w + 4 * (lane >> 1)) + (lane & 1), ow = u / 5;
                const int sl = u - 5 * ow;
                sts32(sb + O_TAB + w * 32 + lane * 4, mapa(sb + O_RED + (sl >> 1) * 2560 + (sl & 1) * 256 + hi * (sl < 4 ? 512 : 256), ow & 15));
            }
            cluster_arrive_relaxed(); cluster_wait();
            cp_wait<0>();
            named_bar(7, 128);
            const uint32_t wo_a = wo + w * 4096 + ((lane >> 4) * 8 + (lane & 7)) * 32 + ((((lane >> 3) & 1) ^ ((lane >> 2) & 1)) << 4);
            const uint32_t ob_0 = sb + (role == 2 ? O_PB : O_OBA) + (lane >> 4) * 2048 + ((lane >> 3) & 1) * 128 + ((lane & 7) ^ ((lane >> 1) & 4)) * 16;
            const float cs = 0.08838834764831845f * 1.4426950408889634f;
            auto w_frag = [&](auto four, int i) {
                return ldsm4t(wo_a + (i < 16 || decltype(four)::value == 4 ? (i >> 4) * 32768 + (i & 1) * 16384 + ((i >> 1) & 7) * 512 : 32768 + (i & 1) * 2048 + ((i >> 1) & 7) * 512));
            };
            auto w_pre = [&](auto four, uint4* wf) {
#pragma unroll
                for (int i = 0; i < 8; i++) wf[i] = w_frag(four, i);
            };
            auto w_run = [&](auto four, auto rem_, uint4* wf, int t, const uint32_t ob_a) {
                constexpr int NTL = decltype(four)::value, NF = 8 * NTL, NP = NTL > 2 ? 2 : 1;
                constexpr bool REMOTE = decltype(rem_)::value;
                const uint32_t ln = opq(lane0), l8 = (ln & 2) * 64 + (ln >> 2) * 16 + (ln & 1) * 8, rb = (bb + B_RED) & 0xFFFFFFu;
                auto slot = [](int i) { return i < 8 ? i : 8 - WR + (i - 8) % WR; };
                uint4 obr[8];
#pragma unroll
                for (int k = 0; k < 4; k++) obr[k] = ldsm4(ob_a + k * 256);
#pragma unroll
                for (int p = 0; p < NP; p++) {
                    const bool split = p == 1 && NTL == 3;
                    const int nk = split ? 4 : 8;
                    float d[4][4];
                    uint4 ta;
#pragma unroll
                    for (int i = 0; i < 16; i++) (&d[0][0])[i] = 0.f;
#pragma unroll
                    for (int ks = 0; ks < 8; ks++) {
                        if (ks >= nk) continue;
                        if (p == 0 && ks == OBK) {
                            if (REMOTE) { mwait(bb + B_OB + 64, t & 1); TS(7); }
#pragma unroll
                            for (int k = 4; k < 8; k++) obr[k] = ldsm4(ob_a + k * 256);
                        }
                        if (ks == nk - 2) ta = lds128(sb + O_TAB + w * 32 + p * 16);
#pragma unroll
                        for (int u = 0; u < 2; u++) {
                            const int i = p * 16 + ks * 2 + u;
                            const uint4& o = obr[split && u ? ks + 4 : ks];
                            const uint4& f = wf[slot(i)];
                            mmav(d[2 * u], f.x, f.y, f.z, f.w, o.x, o.y); mmav(d[2 * u + 1], f.x, f.y, f.z, f.w, o.z, o.w);
                            if (i + WR >= 8 && i + WR < NF) wf[slot(i + WR)] = w_frag(four, i + WR);
                        }
                    }
                    if (p) TS(10); else TS(8);
                    if (split) {
#pragma unroll
                        for (int i = 0; i < 4; i++) { d[0][i] += d[2][i]; d[1][i] += d[3][i]; }
                    }
                    st_async_v2(ta.x + l8, pack2(d[0][0], d[0][1]), pack2(d[1][0], d[1][1]), (ta.x & 0xFF000000u) | rb);
                    st_async_v2(ta.y + l8, pack2(d[0][2], d[0][3]), pack2(d[1][2], d[1][3]), (ta.y & 0xFF000000u) | rb);
                    if (!split) {
                        st_async_v2(ta.z + l8, pack2(d[2][0], d[2][1]), pack2(d[3][0], d[3][1]), (ta.z & 0xFF000000u) | rb);
                        st_async_v2(ta.w + l8, pack2(d[2][2], d[2][3]), pack2(d[3][2], d[3][3]), (ta.w & 0xFF000000u) | rb);
                    }
                }
            };
            if (role != 2) {
#pragma unroll 1
                for (int t = 0; t < NT; t++) {
                    const uint32_t lane = opq(lane0);
                    const uint32_t dc = mapa(sb, hi * 3 + 2), dp = mapa(sb, hi * 3 + (role ^ 1));
                    const uint32_t qa = sb + O_QRY + c * 5120 + (lane & 7) * 128;
                    const uint32_t sw = (((lane >> 3) ^ (lane & 7)) << 4) ^ (c << 6);
                    {
                        const uint32_t ka = qa + 10240;
                        const uint32_t kt = sb + O_KEY + c * 5120 + (lane & 15) * 128, kx = (((lane >> 4) ^ (lane & 7)) << 4) ^ (c << 6);
                        const uint32_t sd = dc + O_SM + role * 1536 + c * 768 + lane * 4, sbar = dc + O_BAR + B_SM;
                        const uint32_t ta = sb + O_QRY + c * 5120 + (8 + 16 * hh + ((lane & 15) ^ (role * 8))) * 128;
                        uint4 a[4], f[4];
                        named_bar(13, 384);
#pragma unroll
                        for (int i = 0; i < 4; i++) f[i] = ldsm4(kt + 1024 + hh * 2048 + (kx ^ (i << 5) ^ (hh << 6)));
#pragma unroll
                        for (int i = 0; i < 4; i++) a[i] = ldsm4(ta + (kx ^ (i << 5)));
                        const uint32_t kd = ka + (1 + 2 * hh) * 1024 + sw;
                        uint4 k[5];
                        k[1] = ldsm4(kd); k[2] = ldsm4(kd + 1024);
                        {
                            const uint32_t qh = qa + (sw ^ (hh << 6)), kh = kt + (kx ^ (hh << 6));
                            named_bar(1, 384);
                            const uint4 q0 = ldsm4(qh), g0 = ldsm4(kh), g1 = ldsm4(kh ^ 32), q1 = ldsm4(qh ^ 64);
                            float s0[4] = {0.f, 0.f, 0.f, 0.f}, s1[4] = {0.f, 0.f, 0.f, 0.f}, s2[4] = {0.f, 0.f, 0.f, 0.f}, s3[4] = {0.f, 0.f, 0.f, 0.f};
                            mmav(s0, f[0].x, f[0].y, f[0].z, f[0].w, q0.x, q0.y); mmav(s1, f[1].x, f[1].y, f[1].z, f[1].w, q0.z, q0.w);
                            mmav(s2, g0.x, g0.y, g0.z, g0.w, q0.x, q0.y); mmav(s3, g1.x, g1.y, g1.z, g1.w, q0.z, q0.w);
                            mmav(s0, f[2].x, f[2].y, f[2].z, f[2].w, q1.x, q1.y); mmav(s1, f[3].x, f[3].y, f[3].z, f[3].w, q1.z, q1.w);
                            k[0] = ldsm4(ka + sw); k[3] = ldsm4(ka + 1024 + sw); k[4] = ldsm4(ka + 2048 + sw);
                            st_async_b32(sd + hh * 128, pack2(s2[0] + s3[0], s2[1] + s3[1]), sbar);
                            st_async_b32(sd + 256 + hh * 256, pack2(s0[0] + s1[0], s0[1] + s1[1]), sbar);
                            st_async_b32(sd + 384 + hh * 256, pack2(s0[2] + s1[2], s0[3] + s1[3]), sbar);
                        }
                        TS(1);
                        float u[5][4];
#pragma unroll
                        for (int i = 0; i < 20; i++) (&u[0][0])[i] = 0.f;
                        auto half = [&](auto nn, const uint4& a0, const uint4& a1, bool more) {
                            constexpr int NU = decltype(nn)::value;
                            constexpr int ord[5] = {1, 2, 0, 3, 4};
#pragma unroll
                            for (int i = 0; i < NU; i++) mmav(u[ord[i]], a0.x, a0.y, a0.z, a0.w, k[ord[i]].x, k[ord[i]].y);
#pragma unroll
                            for (int i = 0; i < NU; i++) {
                                const int n = ord[i];
                                mmav(u[n], a1.x, a1.y, a1.z, a1.w, k[n].z, k[n].w);
                                if (more) k[n] = ldsm4(((n == 0 ? ka + sw : (n < 3 ? kd + (n - 1) * 1024 : ka + (n - 2) * 1024 + sw))) ^ 64);
                            }
                        };
                        auto fu = [](float x) { return __float_as_uint(x); };
                        const uint32_t so = O_ST + c * 2048 + hh * 768, td = dp + so, tb = dp + O_BAR + B_ST, lo = sb + so + 4096;
                        if (hh) {
                            half(IC<5>{}, a[0], a[1], true); half(IC<5>{}, a[2], a[3], false);
                            st_async_v4(td + lane * 16, fu(u[0][2]), fu(u[0][3]), fu(u[1][2]), fu(u[1][3]), tb);
                            st_async_v4(td + 512 + lane * 16, fu(u[2][2]), fu(u[2][3]), fu(u[3][2]), fu(u[3][3]), tb);
                            st_async_v2(td + 1024 + lane * 8, fu(u[4][2]), fu(u[4][3]), tb);
                            sts128(lo + lane * 16, fu(u[0][0]), fu(u[0][1]), fu(u[1][0]), fu(u[1][1]));
                            sts128(lo + 512 + lane * 16, fu(u[2][0]), fu(u[2][1]), fu(u[3][0]), fu(u[3][1]));
                            sts64(lo + 1024 + lane * 8, fu(u[4][0]), fu(u[4][1]));
                        } else {
                            half(IC<3>{}, a[0], a[1], true); half(IC<3>{}, a[2], a[3], false);
                            st_async_v4(td + lane * 16, fu(u[0][2]), fu(u[0][3]), fu(u[1][2]), fu(u[1][3]), tb);
                            st_async_v2(td + 512 + lane * 8, fu(u[2][2]), fu(u[2][3]), tb);
                            sts128(lo + lane * 16, fu(u[0][0]), fu(u[0][1]), fu(u[1][0]), fu(u[1][1]));
                            sts64(lo + 512 + lane * 8, fu(u[2][0]), fu(u[2][1]));
                        }
                        if (t < NT - 1) named_arrive(2, 384);
                        __syncwarp();
                        if (lane == 0) mbar_arrive(bb + B_ST);
                        TS(2);
                    }
                    if (t == NT - 1) break;
                    uint4 wf[8];
                    w_pre(IC<WTA>{}, wf);
                    mwait(bb + B_OB, t & 1);
                    TS(3);
                    named_bar(3, 384);
                    w_run(IC<WTA>{}, IC<1>{}, wf, t, ob_0);
                    named_arrive(4, 384);
                    if (w == 0 && lane == 0) { mbar_expect_tx(bb + B_OB, 2048); mbar_expect_tx(bb + B_OB + 64, 2048); }
                    TS(5);
                }
            } else {
#pragma unroll 1
                for (int t = 0; t < NT; t++) {
                    const uint32_t lane = opq(lane0);
                    const int g = lane >> 2, tq = lane & 3;
                    const uint32_t vm_a = sb + O_VM + (g * 4 + 2 * (tq & 1) + (c ^ ((g >> 1) & 1))) * 16 + (tq >> 1) * 8;
                    const uint32_t vt_a = sb + O_VT + (t & 1) * 16384 + ((lane >> 3) & 1) * 512 + (lane >> 4) * 128 + (lane & 7) * 16;
                    named_bar(13, 384);
                    uint4 va[4][2];
#pragma unroll
                    for (int i = 0; i < 4; i++) {
                        va[i][0] = ldsm4(vt_a + c * 8192 + (4 * hh + i) * 1024);
                        va[i][1] = ldsm4(vt_a + c * 8192 + (4 * hh + i) * 1024 + 256);
                    }
                    const uint32_t sa = opq(sb + O_SM + c * 768 + 256 + lane * 16), sa2 = opq(sb + O_SM + c * 768 + (lane & 15) * 16 + (lane >> 4) * 1536), vm_b = opq(vm_a + hh * 2048);
                    named_bar(1, 384);
                    if (__builtin_expect(t < NT - 1, 1)) {
                        uint2 vm[4];
#pragma unroll
                        for (int i = 0; i < 4; i++) vm[i] = lds64(vm_b + i * 512);
                        mwait(bb + B_SM, t & 1);
                        TS(1);
                        const uint4 x0 = ldsm4t(sa), y0 = ldsm4t(sa + 1536), x1 = ldsm4t(sa2);
                        float s[10];
                        s[2] = blo(x0.x) + blo(y0.x); s[3] = bhi(x0.x) + bhi(y0.x); s[4] = blo(x0.y) + blo(y0.y); s[5] = bhi(x0.y) + bhi(y0.y);
                        s[6] = blo(x0.z) + blo(y0.z); s[7] = bhi(x0.z) + bhi(y0.z); s[8] = blo(x0.w) + blo(y0.w); s[9] = bhi(x0.w) + bhi(y0.w);
                        s[0] = (blo(x1.x) + blo(x1.y)) + (blo(x1.z) + blo(x1.w)); s[1] = (bhi(x1.x) + bhi(x1.y)) + (bhi(x1.z) + bhi(x1.w));
                        float mx = fmaxf(fmaxf(fmaxf(s[0], s[1]), fmaxf(s[2], s[3])), fmaxf(fmaxf(fmaxf(s[4], s[5]), fmaxf(s[6], s[7])), fmaxf(s[8], s[9])));
                        const float m1 = __shfl_xor_sync(0xffffffffu, mx, 1), m2 = __shfl_xor_sync(0xffffffffu, mx, 2), m3 = __shfl_xor_sync(0xffffffffu, mx, 3);
                        mx = fmaxf(fmaxf(mx, m1), fmaxf(m2, m3)) * -cs;
                        uint32_t pb[5];
#pragma unroll
                        for (int i = 0; i < 5; i++) pb[i] = pack2(ex2f(fmaf(s[2 * i], cs, mx)), ex2f(fmaf(s[2 * i + 1], cs, mx)));
                        TS(9);
                        named_bar(3, 384);
                        float o[5][4];
#pragma unroll
                        for (int i = 0; i < 20; i++) (&o[0][0])[i] = 0.f;
                        const uint32_t one2 = 0x3F803F80u;
                        float z[2][4] = {{0.f, 0.f, 0.f, 0.f}, {0.f, 0.f, 0.f, 0.f}};
                        mmav8(o[4], one2, one2, pb[0]);
                        mmav(z[0], one2, one2, one2, one2, pb[1], pb[2]);
                        mmav(z[1], one2, one2, one2, one2, pb[3], pb[4]);
#pragma unroll
                        for (int i = 0; i < 4; i++) mmav8(o[i], vm[i].x, vm[i].y, pb[0]);
#pragma unroll
                        for (int i = 0; i < 4; i++) mmav(o[i], va[i][0].x, va[i][0].y, va[i][0].z, va[i][0].w, pb[1], pb[2]);
#pragma unroll
                        for (int i = 0; i < 4; i++) mmav(o[i], va[i][1].x, va[i][1].y, va[i][1].z, va[i][1].w, pb[3], pb[4]);
                        o[4][0] += z[0][0] + z[1][0]; o[4][1] += z[0][1] + z[1][1];
                        uint4 wf[8];
                        w_pre(IC<WTC>{}, wf);
                        const float r0 = rcpf(o[4][0]), r1 = rcpf(o[4][1]);
                        const uint32_t oo = c * 2048 + hh * 1024 + g * 128 + tq * 16 + (g & 1) * 64;
                        uint32_t e0[4], e1[4];
#pragma unroll
                        for (int i = 0; i < 4; i++) { e0[i] = pack2(o[i][0] * r0, o[i][2] * r0); e1[i] = pack2(o[i][1] * r1, o[i][3] * r1); }
                        sts128(sb + O_PB + (~t & 1) * 5120 + oo, e0[0], e0[1], e0[2], e0[3]);
                        sts128(sb + O_PB + (~t & 1) * 5120 + (oo ^ 64), e1[0], e1[1], e1[2], e1[3]);
                        {
                            const uint32_t da = mapa(sb + O_OBA, r - 2) + oo, ba = mapa(bb + B_OB + hh * 64, r - 2);
                            st_async_v4(da, e0[0], e0[1], e0[2], e0[3], ba);
                            st_async_v4(da + 0x01000000u, e0[0], e0[1], e0[2], e0[3], ba + 0x01000000u);
                            st_async_v4(da ^ 64, e1[0], e1[1], e1[2], e1[3], ba);
                            st_async_v4((da ^ 64) + 0x01000000u, e1[0], e1[1], e1[2], e1[3], ba + 0x01000000u);
                        }
                        TS(3);
                        named_bar(7, 128);
                        w_run(IC<WTC>{}, IC<0>{}, wf, t, ob_0 + (~t & 1) * 5120);
                        named_arrive(4, 384);
                        mwait(bb + B_ST, t & 1);
                        TS(4);
                    } else { mwait(bb + B_SM, t & 1); mwait(bb + B_ST, t & 1); }
                    TS(5);
                    fence_async_smem();
#pragma unroll 1
                    for (int l = t < NSEG ? 0 : 1; l < (t >= LAG ? 2 : 1); l++) {
                        const uint32_t pb_ = ((1024 + O_PB) >> 4) + (t & 1) * 320 + l * 160, va_ = (((1024 + O_VT) >> 4) + (t & 1) * 1024 + l * 512) | (8u << 16);
                        const uint32_t oa = sb + O_VT + (t & 1) * 16384 + l * 8192 + w * 1024 + g * 64 + ((tq ^ (g >> 1)) & 3) * 16;
                        const uint32_t vl = (vm_a ^ ((l ^ c) << 4)) + w * 512;
                        const uint2 a0 = lds64(vl), a1 = lds64(vl + 2048);
                        float d[2][16];
                        wg_fence();
                        wg_n32_first(d[0], a0.x, a0.y, 0u, 0u, mkdesc(pb_, 8));
                        wg_n32_first(d[1], a1.x, a1.y, 0u, 0u, mkdesc(pb_, 8));
#pragma unroll
                        for (int i = 0; i < 4; i++) wg_n32_kk(d[i & 1], mkdesc(va_ + (i & 1) * 256 + (i >> 1) * 16, 32), mkdesc(pb_ + 32 + (i >> 1) * 64 + (32u << 16), 8));
                        wg_commit();
                        if (l) TS(13); else TS(11);
                        wg_wait<0>();
                        if (l) TS(14); else TS(12);
#pragma unroll
                        for (int mt = 0; mt < 2; mt++) {
                            sts128(oa + mt * 4096, pack2(d[mt][0], d[mt][1]), pack2(d[mt][4], d[mt][5]), pack2(d[mt][8], d[mt][9]), pack2(d[mt][12], d[mt][13]));
                            sts128(oa + mt * 4096 + 512, pack2(d[mt][2], d[mt][3]), pack2(d[mt][6], d[mt][7]), pack2(d[mt][10], d[mt][11]), pack2(d[mt][14], d[mt][15]));
                        }
                        if (l == 0) {
                            fence_async_smem();
                            __syncwarp();
                            if (lane == 0) mbar_arrive(bb + B_OTF + 8);
                        }
                    }
                    TS(6);
                    if (w == 0 && lane == 0) { mbar_expect_tx(bb + B_ST, 5120); mbar_expect_tx(bb + B_SM, 3072); }
                    fence_async_smem();
                    __syncwarp();
                    if (lane == 0) mbar_arrive(bb + B_OTF);
                    if (t < NT - 1) named_arrive(5, 384);
                }
            }
        } else {
            cluster_wait(); cluster_arrive_relaxed();
            const int wi = sp * 4 + w, half = wi >> 5, tok = wi & 31, ep = ld_relaxed(&g_epoch) + 1;
            GT(lane == 0, 89);
            if (lane < LN0_AHEAD / 2) prefetch_l2(A.x + (size_t)((half + 2 * lane) * SEG + tok) * DM, 1280);
#pragma unroll 1
            for (int k = -LN0_AHEAD / 2; k < NT; k++) {
                const int s0 = k < 0 ? 2 * k + LN0_AHEAD + half : (half && k % LN0_BATCH == 0 ? k + LN0_AHEAD : NSEG);
                if (s0 < NSEG) { ln0_rows(A.x, s0, k < 0 ? 1 : LN0_BATCH, tok, lane); GT(lane == 0 && k < 0, 30 + s0); }
                if (k == -1 && half) {
#pragma unroll 1
                    for (int u = 320 + tok; u < 640; u += 32) u_half(A.Bk, A.Bv, A.shiftk, u, lane);
                    __syncwarp();
                    if (lane == 0) red_release(FLG(F_U + 1), 1);
                }
                const int n = k - half * LAG;
                if (n >= 0 && n < NSEG && k >= 0) {
                    post_row(half, n, tok, lane, A.x, A.out, ep);
                    GT(lane == 0 && (n & 3) == 0 && k >= 0, 460 + half * 16 + (n >> 2)); GT(lane == 0 && n == 63 && half, 40);
                }
            }
            cluster_wait();
        }
    } else {
        asm volatile("setmaxnreg.dec.sync.aligned.u32 %0;" ::"n"(REG_X));
        cluster_wait();
        const int s = warp - 12;
        const uint32_t lane0 = __shfl_sync(0xffffffffu, tid & 31, tid & 31);
        if (s < 3) {
            cluster_arrive_relaxed();
            GT(lane == 0, 84);
            if (blockIdx.x * 3 + s < 320) {
                u_half(A.Bk, A.Bv, A.shiftk, blockIdx.x * 3 + s, lane);
                GT(lane == 0, 85);
                __syncwarp();
                if (lane == 0) red_release(FLG(F_U), 1);
                GT(lane == 0, 4);
            }
            const int ztgt = 3 * 16 * NCL * (ld_relaxed(&g_epoch) + 1);
#pragma unroll
            for (int i = 0; i < XRS; i++) st_relaxed_v4(g_xc + ((i * 16 + r) * 3 + s) * 256 + cq * 32 + lane, 0, 0, 0, 0);
            __syncwarp();
            if (lane == 0) red_release(FLG(F_Z), 1);
            cluster_wait();
            constexpr uint32_t XSLOT = 16 * 3 * 4096;
            uint32_t xo_ = (r * 3 + s) * 4096;
            if (s == 0) {
                const uint32_t G = lane >> 1, d = ((r + 2 * G) & 15) ^ (lane & 1);
                if (lane < 16) { sts32(sb + O_BT + lane * 8, (d << 24) + G * 2560); sts32(sb + O_BT + lane * 8 + 4, d < 3 * nh ? mapa(bb + B_MEM + G * 8, d) : 0u); }
            }
            while (ld_acquire(FLG(F_Z)) < ztgt) __nanosleep(100);
            named_bar(14, 96);
#pragma unroll 1
            for (int t = 0; t < NT; t++) {
                const uint32_t lane = opq(lane0);
                if (head && role != 2) {
                    auto soft = [&](auto uu, auto vv, int c0, int hh) {
                        constexpr int U = decltype(uu)::value, NV = decltype(vv)::value;
                        const uint32_t dc = mapa(sb, hi * 3 + 2), sa = sb + O_ST + c0 * 2048 + hh * 768;
                        const uint32_t pd = dc + O_PB + (t & 1) * 5120 + c0 * 2560 + (2 * hh + role) * 128 + lane * 4, pbar = dc + O_BAR + B_ST;
                        const int lim = 8 * role + (int)(lane >> 2) - 2 * (int)(lane & 3);
                        auto uf = [](uint32_t x) { return __uint_as_float(x); };
                        mwait(bb + B_ST, t & 1);
                        if (r == 1 && U == 2 && t >= LAG - 1 && t < NT - 1) named_arrive(12, 64);
                        uint32_t z[U][NV];
                        auto zz = [](float x, float y) { const uint32_t w = pack2(x, y); return pack2(blo(w) * 0.08838834764831845f, bhi(w) * 0.08838834764831845f); };
#pragma unroll
                        for (int i = 0; i < U; i++) {
                            const uint4 v = lds128(sa + i * 2048 + lane * 16), w = lds128(sa + i * 2048 + 4096 + lane * 16);
                            z[i][0] = zz(uf(v.x) + uf(w.x), uf(v.y) + uf(w.y));
                            z[i][1] = zz(lim < 0 ? -INFINITY : uf(v.z) + uf(w.z), lim < 1 ? -INFINITY : uf(v.w) + uf(w.w));
                            if (NV == 3) {
                                const uint2 x = lds64(sa + i * 2048 + 512 + lane * 8), y = lds64(sa + i * 2048 + 4608 + lane * 8);
                                z[i][2] = zz(lim < 8 ? -INFINITY : uf(x.x) + uf(y.x), lim < 9 ? -INFINITY : uf(x.y) + uf(y.y));
                            } else {
                                const uint4 x = lds128(sa + 512 + lane * 16), y = lds128(sa + 4608 + lane * 16);
                                const uint2 p = lds64(sa + 1024 + lane * 8), q = lds64(sa + 5120 + lane * 8);
                                z[i][2] = zz(lim < 8 ? -INFINITY : uf(x.x) + uf(y.x), lim < 9 ? -INFINITY : uf(x.y) + uf(y.y));
                                z[i][NV - 2] = zz(uf(x.z) + uf(y.z), uf(x.w) + uf(y.w));
                                z[i][NV - 1] = zz(uf(p.x) + uf(q.x), uf(p.y) + uf(q.y));
                            }
                        }
                        const float l2e = 1.4426950408889634f;
                        float e[U][2 * NV], sum[U];
#pragma unroll
                        for (int i = 0; i < U; i++) {
                            uint32_t zm = bmax2(bmax2(z[i][0], z[i][1]), z[i][2]);
                            if (NV == 5) zm = bmax2(zm, bmax2(z[i][NV - 2], z[i][NV - 1]));
                            zm = bmax2(zm, __shfl_xor_sync(0xffffffffu, zm, 1));
                            zm = bmax2(zm, __shfl_xor_sync(0xffffffffu, zm, 2));
                            const float mx = fmaxf(blo(zm), bhi(zm)) * -l2e;
                            sum[i] = 0.f;
#pragma unroll
                            for (int n = 0; n < NV; n++) { e[i][2 * n] = ex2f(fmaf(blo(z[i][n]), l2e, mx)); e[i][2 * n + 1] = ex2f(fmaf(bhi(z[i][n]), l2e, mx)); }
                            sum[i] = ((e[i][0] + e[i][1]) + (e[i][2] + e[i][3])) + (e[i][4] + e[i][5]);
                            if (NV == 5) sum[i] += (e[i][2 * NV - 4] + e[i][2 * NV - 3]) + (e[i][2 * NV - 2] + e[i][2 * NV - 1]);
                            sum[i] += __shfl_xor_sync(0xffffffffu, sum[i], 1);
                            sum[i] += __shfl_xor_sync(0xffffffffu, sum[i], 2);
                            sum[i] = rcpf(sum[i]);
                        }
#pragma unroll
                        for (int i = 0; i < U; i++)
#pragma unroll
                            for (int n = 0; n < 5; n++)
                                st_async_b32(pd + i * 2560 + (n == 0 ? 0 : (NV == 3 ? n : (n < 3 ? n + 2 : n - 2)) * 512), n < NV ? pack2(e[i][2 * n] * sum[i], e[i][2 * n + 1] * sum[i]) : 0u, pbar);
                    };
                    if (s < 2) soft(IC<1>{}, IC<5>{}, s, 1); else soft(IC<2>{}, IC<3>{}, 0, 0);
                    TS(12);
                    named_bar(14, 96);
                    if (s == 0 && lane == 0) mbar_expect_tx(bb + B_ST, 4096);
                }
                if (t == NT - 1) break;
                uint32_t m0 = 0x80008000u, m1 = 0x80008000u;
                if (t < LAG && cq == 0) {
                    const uint32_t ch = s < 2 ? lane : lane >> 1;
                    const unsigned short* mp = reinterpret_cast<const unsigned short*>(A.mem0) + (((ch >> 3) & 1) * 4 + (s < 2 ? 0 : (lane & 1) * 2)) * DM + (5 * r + 2 * s + (ch >> 4)) * 8 + (ch & 7);
                    m0 = max(mp[0] | (uint32_t)mp[DM] << 16, 1u);
                    if (s < 2) m1 = max(mp[2 * DM] | (uint32_t)mp[3 * DM] << 16, 1u);
                }
                const bool late = t >= LAG;
                auto sum5 = [](uint32_t a, uint32_t b, uint32_t c, uint32_t d, uint32_t e) { return nz(badd(badd(badd(a, b), e), badd(c, d))); };
                auto sum7 = [](uint32_t a, uint32_t b, uint32_t c, uint32_t d, uint32_t e, uint32_t f, uint32_t h_) {
                    return badd(badd(badd(a, b), badd(c, d)), badd(badd(e, f), h_));
                };
                auto min3 = [](uint32_t a, uint32_t b, uint32_t c) { return min(min(a, b), c); };
                auto bcast = [&](auto two, const uint32_t aa, uint32_t x0, uint32_t x1, uint32_t x2, uint32_t x3) {
                    auto send = [&](uint32_t o, uint32_t bar) { if (decltype(two)::value) st_async_v4p(aa + o, x0, x1, x2, x3, bar); else st_async_v2p(aa + o, x0, x1, bar); };
                    uint4 e[5];
                    e[0] = lds128(sb + O_BT);
                    TS(8);
                    send(e[0].x, e[0].y); send(e[0].z, e[0].w);
                    TS(9);
#pragma unroll
                    for (int i = 1; i < 5; i++) e[i] = lds128(sb + O_BT + i * 16);
#pragma unroll
                    for (int i = 1; i < 8; i++) {
                        send(e[(i - 1) % 4 + 1].x, e[(i - 1) % 4 + 1].y); send(e[(i - 1) % 4 + 1].z, e[(i - 1) % 4 + 1].w);
                        if (i < 4) e[i] = lds128(sb + O_BT + (i + 4) * 16);
                    }
                };
                const uint32_t ma = (sb + O_MEM + (5 * (r & 1) + 2 * s) * 256) & 0xFFFFFFu;
                int guard = 0;
                if (s < 2) {
                    const uint32_t ra = sb + O_RED + s * 2560 + lane * 16;
                    uint4* xb = reinterpret_cast<uint4*>(reinterpret_cast<char*>(g_xc) + xo_ + lane * 16);
                    uint4* xo = xb + cq * 32;
                    touch(xo); touch(xb);
                    mwait(bb + B_RED, t & 1);
                    TS(0);
                    uint4 p[5];
#pragma unroll
                    for (int i = 0; i < 5; i++) p[i] = i < 4 || nh == 5 ? lds128(ra + i * 512) : make_uint4(0, 0, 0, 0);
                    const uint32_t u1 = sum5(p[0].y, p[1].y, p[2].y, p[3].y, p[4].y), u3 = sum5(p[0].w, p[1].w, p[2].w, p[3].w, p[4].w);
                    st_relaxed_v4(xo, sum5(p[0].x, p[1].x, p[2].x, p[3].x, p[4].x), late ? u1 : m0, sum5(p[0].z, p[1].z, p[2].z, p[3].z, p[4].z), late ? u3 : m1);
                    TS(1);
                    delay(XD);
                    uint4 x[NCL];
                    while (true) {
                        ld7_relaxed(x, xb);
                        const uint32_t mn = min3(min3(min3(x[0].x, x[0].y, x[0].z), min3(x[0].w, x[1].x, x[1].y), min3(x[1].z, x[1].w, x[2].x)),
                                                 min3(min3(x[2].y, x[2].z, x[2].w), min3(x[3].x, x[3].y, x[3].z), min3(x[3].w, x[4].x, x[4].y)),
                                                 min3(min3(x[4].z, x[4].w, x[5].x), min3(x[5].y, x[5].z, x[5].w), min(min3(x[6].x, x[6].y, x[6].z), x[6].w)));
                        if (NO_X || __all_sync(0xffffffffu, mn != 0)) break;
                        if (++guard > 2000000) __trap();
                    }
                    TS(2);
                    TV(4, guard);
                    bcast(IC<1>{}, ma + lane * 16, sum7(x[0].x, x[1].x, x[2].x, x[3].x, x[4].x, x[5].x, x[6].x), sum7(x[0].y, x[1].y, x[2].y, x[3].y, x[4].y, x[5].y, x[6].y),
                          sum7(x[0].z, x[1].z, x[2].z, x[3].z, x[4].z, x[5].z, x[6].z), sum7(x[0].w, x[1].w, x[2].w, x[3].w, x[4].w, x[5].w, x[6].w));
                } else {
                    const uint32_t ra = sb + O_RED + 5120 + lane * 8;
                    uint2* xb = reinterpret_cast<uint2*>(reinterpret_cast<char*>(g_xc) + xo_ + lane * 8);
                    uint2* xo = xb + cq * 64;
                    touch(xo); touch(xb);
                    mwait(bb + B_RED, t & 1);
                    TS(0);
                    uint2 p[5];
#pragma unroll
                    for (int i = 0; i < 5; i++) p[i] = i < 4 || nh == 5 ? lds64(ra + i * 256) : make_uint2(0, 0);
                    const uint32_t u1 = sum5(p[0].y, p[1].y, p[2].y, p[3].y, p[4].y);
                    st_relaxed_v2(xo, sum5(p[0].x, p[1].x, p[2].x, p[3].x, p[4].x), late ? u1 : m0);
                    if (lane == 0) mbar_expect_tx(bb + B_RED, nh * 1280);
                    TS(1);
                    delay(XD);
                    uint32_t y0, y1;
                    while (true) {
                        uint2 x[NCL];
                        ld7_relaxed(x, xb);
                        const uint32_t mn = min3(min3(min3(x[0].x, x[0].y, x[1].x), min3(x[1].y, x[2].x, x[2].y), min3(x[3].x, x[3].y, x[4].x)), min3(x[4].y, x[5].x, x[5].y), min(x[6].x, x[6].y));
                        y0 = sum7(x[0].x, x[1].x, x[2].x, x[3].x, x[4].x, x[5].x, x[6].x); y1 = sum7(x[0].y, x[1].y, x[2].y, x[3].y, x[4].y, x[5].y, x[6].y);
                        if (NO_X || __all_sync(0xffffffffu, mn != 0)) break;
                        if (++guard > 2000000) __trap();
                    }
                    TS(2);
                    TV(4, guard);
                    bcast(IC<0>{}, ma + lane * 8, y0, y1, 0u, 0u);
                }
                TS(3);
                if (head && role == 2) named_arrive(6, 128);
                xo_ += XSLOT; if (xo_ >= XRS * XSLOT) xo_ -= XRS * XSLOT;
                {
                    const uint32_t zo = xo_ + XSLOT >= XRS * XSLOT ? xo_ + XSLOT - XRS * XSLOT : xo_ + XSLOT;
                    char* zp = reinterpret_cast<char*>(g_xc) + zo + cq * 512 + lane * 16;
                    st_relaxed_v4(zp, 0, 0, 0, 0);
                    if (ld_relaxed_v4(zp).x) __trap();
                }
            }
        } else if (r < 2) {
            const uint16_t mask = (uint16_t)((1u << (3 * nh)) - 1u);
            const int htgt = A.h_target * (ld_relaxed(&g_epoch) + 1);
#pragma unroll 1
            for (int n = 0; n < NSEG; n++) {
                if (n == (r == 0 ? 1 : 0)) { cluster_arrive(); cluster_wait(); }
                int guard = 0;
                while (ld_acquire(FLG(F_H + r * 64 + n)) < htgt) { if (++guard > 2000000) __trap(); __nanosleep(H_NS); }
                fence_async_global();
                if (r == 1) named_bar(12, 64);
                if (n) mwait(bb + B_HE, (n - 1) & 1);
                if (lane < 8)
                    asm volatile("cp.async.bulk.shared::cluster.global.mbarrier::complete_tx::bytes.multicast::cluster [%0], [%1], %2, [%3], %4;" ::"r"(sb + O_H + r * 40960 + lane * 5120),
                                 "l"(g_ht + rslot(r, n) * 2560 + lane * 320), "r"(5120), "r"(bb + B_HF + r * 8), "h"(mask) : "memory");
                __syncwarp();
            }
        } else {
            cluster_arrive(); cluster_wait();
            if (head && role == 2) {
#pragma unroll 1
                for (int t = 0; t < NT; t++) {
                    auto put = [&](int l, int n) {
                        asm volatile("cp.async.bulk.global.shared::cta.bulk_group [%0], [%1], %2;" ::"l"(g_ot + (rslot(l, n) * 256 + h * 8) * 64), "r"(sb + O_VT + (t & 1) * 16384 + l * 8192), "r"(8192) : "memory");
                        asm volatile("cp.async.bulk.commit_group;" ::: "memory");
                    };
                    auto publish = [&](int l, int n) {
                        asm volatile("cp.async.bulk.wait_group 0;" ::: "memory");
                        fence_async_global();
                        red_release(FLG(F_O + l * 64 + n) + (h >> 3), 1);
                        GT(true, 200 + l * 64 + n);
                        if (ONE_FENCE && l == 0 && n > LAG) {
                            asm volatile("red.relaxed.gpu.global.add.u32 [%0], 1;" ::"l"(FLG(F_O + 63 - LAG + n) + (h >> 3)) : "memory");
                            GT(true, 263 - LAG + n);
                        }
                    };
                    if (t < NSEG) {
                        mwait(bb + B_OTF + 8, t & 1);
                        if (lane == 0) { put(0, t); publish(0, t); }
                        __syncwarp();
                    }
                    mwait(bb + B_OTF, t & 1);
                    if (t < NT - 1) named_bar(6, 128);
                    if (lane == 0) {
                        if (t >= LAG) {
                            put(1, t - LAG);
                            asm volatile("cp.async.bulk.wait_group.read 0;" ::: "memory");
                        }
                        mbar_arrive(bb + B_OTE);
                        if (t >= (ONE_FENCE ? NSEG - 1 : LAG)) publish(1, t - LAG);
                    }
                    __syncwarp();
                }
            }
            if (!head && lane == 0) {
#pragma unroll 1
                for (int k = 0; k < 25; k++) {
                    const int rg = k / 5, r0 = rg == 1 ? 256 : 0;
                    mwait(bb + B_OTF + (k & 1) * 8, (k >> 1) & 1);
                    asm volatile("cp.async.bulk.global.shared::cta.bulk_group [%0], [%1], %2;" ::"l"(g_Y + (sp * 5 + k - 5 * rg) * S_LEN + (rg ? rg - 1 : 0) * 512 + r0),
                                 "r"(sb + CV_Y + (k & 1) * 8192 + r0 * 16), "r"(rg < 2 ? 4096 : 8192) : "memory");
                    asm volatile("cp.async.bulk.commit_group;" ::: "memory");
                    asm volatile("cp.async.bulk.wait_group 0;" ::: "memory");
                    mbar_arrive(bb + B_OTE + (k & 1) * 16);
                    fence_async_global();
                    red_release(FLG(F_CV + rg), 1);
                    GT(true, 50 + k);
                }
            }
            __syncwarp();
        }
    }
    cluster_arrive(); cluster_wait();
    if (blockIdx.x == 0 && tid == 0) atomicAdd(&g_epoch, 1);
}
}

namespace ws {
constexpr int OP_SS = 17;
constexpr int P_RING = 0, P_AS = 131072, P_STG = P_AS + 2 * OP_SS * 2048, P_BAR = P_STG + 16384, OP_SMEM = P_BAR + 256;
constexpr int PB_FULL = 0, PB_EMPTY = 128, PB_SF = 144, PB_SE = 176;
static_assert(OP_SMEM <= 232448, "smem");

__global__ void __launch_bounds__(384, 1) op_kernel(const bf16* __restrict__ Wo, const bf16* __restrict__ Bk, const bf16* __restrict__ Bv, const bf16* __restrict__ shiftk) {
    extern __shared__ __align__(1024) unsigned char smem_raw[];
    const int tid = threadIdx.x, warp = __shfl_sync(0xffffffffu, tid >> 5, 0), lane = tid & 31;
    const int nb = blockIdx.x % 5, ks = blockIdx.x / 5;
    const uint32_t sb = smem_u32(smem_raw), bb = sb + P_BAR;
    if (tid == 0) {
        if ((sb & 0xFFFFFFu) != 1024) __trap();
        for (int i = 0; i < 16; i++) mbar_init(bb + PB_FULL + i * 8, 1);
        for (int i = 0; i < 2; i++) mbar_init(bb + PB_EMPTY + i * 8, 2);
        for (int i = 0; i < 4; i++) { mbar_init(bb + PB_SF + i * 8, 4); mbar_init(bb + PB_SE + i * 8, 1); }
        asm volatile("fence.mbarrier_init.release.cluster;" ::: "memory");
    }
    GT(tid == 0, 8);
    __syncthreads();
    if (warp < 4) {
        asm volatile("setmaxnreg.dec.sync.aligned.u32 40;");
        if (warp == 0) {
            named_bar(3, 288);
            GT(lane == 0, 3);
            uint32_t it = 0;
            const int otgt = 8 * (ld_relaxed(&g_epoch) + 1);
#pragma unroll 1
            for (int q = 0; q < 2 * NT + 2; q++) {
                const int l = q & 1, n = (q >> 1) - l * (LAG + ONE_FENCE);
                if (n < 0 || n >= NSEG) continue;
                int guard = 0;
                while (ld_acquire(FLG(F_O + l * 64 + n) + ks) < otgt) { if (++guard > 4000000) __trap(); __nanosleep(OP_NS); }
                fence_async_global();
                mwait(bb + PB_EMPTY + (it & 1) * 8, ((it >> 1) & 1) ^ 1);
                if (lane < 8) {
                    const uint32_t fb = bb + PB_FULL + ((it & 1) * 8 + lane) * 8;
                    mbar_expect_tx(fb, 8192);
                    asm volatile("cp.async.bulk.shared::cluster.global.mbarrier::complete_tx::bytes [%0], [%1], %2, [%3];" ::"r"(sb + P_RING + (it & 1) * 65536 + lane * 8192),
                                 "l"(g_ot + (rslot(l, n) * 256 + (ks * 8 + lane) * 8) * 64), "r"(8192), "r"(fb) : "memory");
                }
                __syncwarp();
                it++;
            }
        } else if (warp == 3) {
#pragma unroll 1
            for (int rg = 1; rg < 4; rg++) {
#pragma unroll 1
                for (int u = rg * 640 + blockIdx.x; u < rg * 640 + 640; u += 20) u_half(Bk, Bv, shiftk, u, lane);
                __syncwarp();
                if (lane == 0) red_release(FLG(F_U + rg + 1), 1);
                GT(lane == 0 && rg, 4 + rg);
            }
        } else if (lane == 0) {
            const int cw = warp - 1;
            uint32_t it = 0;
#pragma unroll 1
            for (int q = 0; q < 2 * NT + 2; q++) {
                const int l = q & 1, n = (q >> 1) - l * (LAG + ONE_FENCE);
                if (n < 0 || n >= NSEG) continue;
                mwait(bb + PB_SF + cw * 8, it & 1);
                asm volatile("cp.reduce.async.bulk.global.shared::cta.bulk_group.add.f32 [%0], [%1], %2;" ::"l"(g_pt + (rslot(l, n) * 10 + nb * 2 + cw) * 512), "r"(sb + P_STG + cw * 8192), "r"(8192) : "memory");
                asm volatile("cp.async.bulk.commit_group;" ::: "memory");
                asm volatile("cp.async.bulk.wait_group.read 0;" ::: "memory");
                mbar_arrive(bb + PB_SE + cw * 8);
                asm volatile("cp.async.bulk.wait_group 0;" ::: "memory");
                fence_async_global();
                red_release(FLG(F_P + l * 64 + n), 1);
                GT(true, 330 + l * 64 + n);
                it++;
            }
        }
    } else {
        asm volatile("setmaxnreg.inc.sync.aligned.u32 232;");
        const int cw = (warp >> 2) - 1, w4 = warp & 3, t7 = tid & 127;
        uint32_t wa[64 - OP_SS][4];
        {
            const bf16* W = Wo + (size_t)ks * 1024 * DM + nb * 128 + cw * 64 + (t7 & 7) * 8;
            const uint32_t so = (t7 >> 3) * 128 + (((t7 & 7) ^ ((t7 >> 3) & 7)) << 4);
            const uint32_t stg = sb + P_RING + cw * 65536;
            const uint32_t la = stg + ((lane & 7) + (lane >> 4) * 8) * 128 + (((w4 * 2 + ((lane >> 3) & 1)) ^ (lane & 7)) << 4);
#pragma unroll 4
            for (int i = 0; i < 32; i++) cp_async16(stg + i * 2048 + so, W + (size_t)((OP_SS + i) * 16 + (t7 >> 3)) * DM);
            cp_commit();
#pragma unroll 1
            for (int i = 0; i < OP_SS; i++) cp_async16(sb + P_AS + cw * OP_SS * 2048 + i * 2048 + so, W + (size_t)(i * 16 + (t7 >> 3)) * DM);
            cp_commit();
            cp_wait<1>();
            named_bar(1 + cw, 128);
#pragma unroll
            for (int j = 0; j < 32; j++) { const uint4 v = ldsm4t(la + j * 2048); wa[j][0] = v.x; wa[j][1] = v.y; wa[j][2] = v.z; wa[j][3] = v.w; }
            named_bar(1 + cw, 128);
#pragma unroll 1
            for (int i = 0; i < 32 - OP_SS; i++) cp_async16(stg + i * 2048 + so, W + (size_t)((OP_SS + 32 + i) * 16 + (t7 >> 3)) * DM);
            cp_commit();
            cp_wait<0>();
            named_bar(1 + cw, 128);
#pragma unroll
            for (int j = 0; j < 32 - OP_SS; j++) { const uint4 v = ldsm4t(la + j * 2048); wa[32 + j][0] = v.x; wa[32 + j][1] = v.y; wa[32 + j][2] = v.z; wa[32 + j][3] = v.w; }
            fence_async_smem();
            named_bar(3, 288);
        }
        const uint32_t ab = (1024 + P_AS + cw * OP_SS * 2048) >> 4;
        const uint32_t ea = sb + P_STG + cw * 8192 + (lane & 3) * 2048 + (((2 * w4) ^ (lane & 3)) << 5) + (lane >> 2) * 4;
#pragma unroll 1
        for (uint32_t it = 0; it < 2 * NSEG; it++) {
            float acc[16];
            const uint32_t fb = bb + PB_FULL + (it & 1) * 64, par = (it >> 1) & 1;
            const uint32_t ob = opq(((1024 + P_RING) >> 4) + (it & 1) * 4096);
            uint32_t ok = 0;
#pragma unroll
            for (int j = 0; j < 64; j++) {
                if ((j & 7) == 0) {
                    if (j) wg_commit();
                    if (!ok) mslow(fb + j, par);
                    ok = j < 56 ? mtest(fb + j + 8, par) : mtest(bb + PB_SE + cw * 8, (it & 1) ^ 1);
                    if (j == 0) wg_fence();
                }
                const uint64_t db = mkdesc(ob + j * 64, 0x80000020u);
                if (j == 0) wg_n32t_sfirst(acc, mkdesc(ab, 0x40000040u), db);
                else if (j < OP_SS) wg_n32t_s(acc, mkdesc(ab + j * 128, 0x40000040u), db);
                else wg_n32t(acc, wa[j - OP_SS][0], wa[j - OP_SS][1], wa[j - OP_SS][2], wa[j - OP_SS][3], db);
            }
            wg_commit();
            if (!ok) mslow(bb + PB_SE + cw * 8, (it & 1) ^ 1);
            wg_wait<0>();
            if (t7 == 0) mbar_arrive(bb + PB_EMPTY + (it & 1) * 8);
#pragma unroll
            for (int i = 0; i < 16; i++) sts32((ea ^ ((i & 2) << 4)) + ((i >> 2) * 2 + (i & 1)) * 256, __float_as_uint(acc[i]));
            fence_async_smem();
            __syncwarp();
            if (lane == 0) mbar_arrive(bb + PB_SF + cw * 8);
        }
    }
}
}

namespace ws {
static bool usable() {
    static int ok = -1;
    if (ok < 0) {
        cudaFuncSetAttribute(head_kernel, cudaFuncAttributeMaxDynamicSharedMemorySize, HEAD_SMEM);
        cudaFuncSetAttribute(head_kernel, cudaFuncAttributeNonPortableClusterSizeAllowed, 1);
        cudaFuncSetAttribute(op_kernel, cudaFuncAttributeMaxDynamicSharedMemorySize, OP_SMEM);
        cudaLaunchConfig_t cfg = {};
        cfg.gridDim = dim3(NCL * 16); cfg.blockDim = dim3(512); cfg.dynamicSmemBytes = HEAD_SMEM;
        cudaLaunchAttribute at[1];
        at[0].id = cudaLaunchAttributeClusterDimension;
        at[0].val.clusterDim.x = 16; at[0].val.clusterDim.y = 1; at[0].val.clusterDim.z = 1;
        cfg.attrs = at; cfg.numAttrs = 1;
        int n = 0, nsm = 0;
        cudaDeviceGetAttribute(&nsm, cudaDevAttrMultiProcessorCount, 0);
        ok = cudaOccupancyMaxActiveClusters(&n, head_kernel, &cfg) == cudaSuccess && n >= NCL && nsm >= NCL * 16 + 20;
        (void)cudaGetLastError();
    }
    return ok > 0;
}
static void launch_all(void* const* d_in, void* d_out) {
    HeadArgs A;
    A.x = (const bf16*)d_in[0]; A.mem0 = (const bf16*)d_in[1]; A.Wq = (const bf16*)d_in[2]; A.Wk = (const bf16*)d_in[3]; A.Wv = (const bf16*)d_in[4]; A.Wo = (const bf16*)d_in[5];
    A.Bk = (const bf16*)d_in[8]; A.Bv = (const bf16*)d_in[9]; A.shiftk = (const bf16*)d_in[10]; A.ssmk = (const bf16*)d_in[11]; A.ssmD = (const bf16*)d_in[12];
    A.out = (bf16*)d_out; A.h_target = 32;
    cudaStream_t s = cudaStreamPerThread;
    {
        cudaLaunchConfig_t cfg = {};
        cfg.gridDim = dim3(NCL * 16); cfg.blockDim = dim3(512); cfg.dynamicSmemBytes = HEAD_SMEM; cfg.stream = s;
        cudaLaunchAttribute at[2];
        at[0].id = cudaLaunchAttributeClusterDimension;
        at[0].val.clusterDim.x = 16; at[0].val.clusterDim.y = 1; at[0].val.clusterDim.z = 1;
        at[1].id = cudaLaunchAttributeProgrammaticStreamSerialization;
        at[1].val.programmaticStreamSerializationAllowed = 1;
        cfg.attrs = at; cfg.numAttrs = 1;
        cudaLaunchKernelEx(&cfg, head_kernel, A);
    }
    {
        cudaLaunchConfig_t cfg = {};
        cfg.gridDim = dim3(20); cfg.blockDim = dim3(384); cfg.dynamicSmemBytes = OP_SMEM; cfg.stream = s;
        cudaLaunchAttribute at[1];
        at[0].id = cudaLaunchAttributeProgrammaticStreamSerialization;
        at[0].val.programmaticStreamSerializationAllowed = 1;
        cfg.attrs = at; cfg.numAttrs = 1;
        cudaLaunchKernelEx(&cfg, op_kernel, A.Wo, A.Bk, A.Bv, A.shiftk);
    }
}
}

#undef C_REV
#undef FLG
#undef GT
#undef H_NS
#undef LAGT
#undef LN0_AHEAD
#undef LN0_BATCH
#undef NO_X
#undef OBK
#undef ONE_FENCE
#undef OP_NS
#undef P1A
#undef P1C
#undef POST_NS
#undef REG_G
#undef REG_T
#undef REG_X
#undef RING
#undef SC
#undef SD
#undef TG_STEPS
#undef TS
#undef TV
#undef UNI
#undef WFLY
#undef WR
#undef WTA
#undef XD
namespace ni {

constexpr int S_LEN = 2048;
constexpr int DM = 640;
constexpr int NH = 32;
constexpr int DH = 128;
constexpr int HD = NH * DH;
constexpr int MEMR = 8;
constexpr int SEG = 32;
constexpr int NSEG = S_LEN / SEG;

__device__ __forceinline__ float bf2f(bf16 v) { return __bfloat162float(v); }
__device__ __forceinline__ bf16 f2bf(float v) { return __float2bfloat16_rn(v); }
__device__ __forceinline__ float rbf(float v) { return __bfloat162float(__float2bfloat16_rn(v)); }
__device__ __forceinline__ uint32_t pack2(float a, float b) {
    __nv_bfloat162 t = __floats2bfloat162_rn(a, b);
    return *reinterpret_cast<uint32_t*>(&t);
}
__device__ __forceinline__ uint32_t smem_u32(const void* p) { return (uint32_t)__cvta_generic_to_shared(p); }
__device__ __forceinline__ void ldsm_x4(uint32_t& r0, uint32_t& r1, uint32_t& r2, uint32_t& r3, uint32_t addr) {
    asm volatile("ldmatrix.sync.aligned.m8n8.x4.shared.b16 {%0,%1,%2,%3}, [%4];"
                 : "=r"(r0), "=r"(r1), "=r"(r2), "=r"(r3) : "r"(addr));
}
__device__ __forceinline__ void ldsm_x2(uint32_t& r0, uint32_t& r1, uint32_t addr) {
    asm volatile("ldmatrix.sync.aligned.m8n8.x2.shared.b16 {%0,%1}, [%2];" : "=r"(r0), "=r"(r1) : "r"(addr));
}
__device__ __forceinline__ void ldsm_x4_t(uint32_t& r0, uint32_t& r1, uint32_t& r2, uint32_t& r3, uint32_t addr) {
    asm volatile("ldmatrix.sync.aligned.m8n8.x4.trans.shared.b16 {%0,%1,%2,%3}, [%4];"
                 : "=r"(r0), "=r"(r1), "=r"(r2), "=r"(r3) : "r"(addr));
}
__device__ __forceinline__ void mma16816(float* c, uint32_t a0, uint32_t a1, uint32_t a2, uint32_t a3,
                                         uint32_t b0, uint32_t b1) {
    asm("mma.sync.aligned.m16n8k16.row.col.f32.bf16.bf16.f32 {%0,%1,%2,%3}, {%4,%5,%6,%7}, {%8,%9}, {%0,%1,%2,%3};"
        : "+f"(c[0]), "+f"(c[1]), "+f"(c[2]), "+f"(c[3])
        : "r"(a0), "r"(a1), "r"(a2), "r"(a3), "r"(b0), "r"(b1));
}
__device__ __forceinline__ void cp_async16(uint32_t dst, const void* src) {
    asm volatile("cp.async.cg.shared.global [%0], [%1], 16;" ::"r"(dst), "l"(src));
}
__device__ __forceinline__ void cp_commit() { asm volatile("cp.async.commit_group;"); }
template <int N> __device__ __forceinline__ void cp_wait() { asm volatile("cp.async.wait_group %0;" ::"n"(N)); }
__device__ __forceinline__ uint4 ld_relaxed_v4(const void* p) {
    uint4 v;
    asm volatile("ld.relaxed.gpu.global.v4.u32 {%0,%1,%2,%3}, [%4];"
                 : "=r"(v.x), "=r"(v.y), "=r"(v.z), "=r"(v.w) : "l"(p) : "memory");
    return v;
}
__device__ __forceinline__ void st_relaxed_v4(void* p, uint32_t a, uint32_t b, uint32_t c, uint32_t d) {
    asm volatile("st.relaxed.gpu.global.v4.u32 [%0], {%1,%2,%3,%4};" ::"l"(p), "r"(a), "r"(b), "r"(c), "r"(d) : "memory");
}
__device__ __forceinline__ int ld_acquire(const int* p) {
    int v;
    asm volatile("ld.acquire.gpu.global.u32 %0, [%1];" : "=r"(v) : "l"(p) : "memory");
    return v;
}
__device__ __forceinline__ void mbar_init(uint32_t bar, int count) {
    asm volatile("mbarrier.init.shared::cta.b64 [%0], %1;" ::"r"(bar), "r"(count));
}
__device__ __forceinline__ void mbar_expect_tx(uint32_t bar, uint32_t bytes) {
    asm volatile("mbarrier.arrive.expect_tx.shared::cta.b64 _, [%0], %1;" ::"r"(bar), "r"(bytes) : "memory");
}
__device__ __forceinline__ void mbar_arrive(uint32_t bar) {
    asm volatile("mbarrier.arrive.shared::cta.b64 _, [%0];" ::"r"(bar) : "memory");
}
constexpr int SPIN_LIMIT = 4000000;
__device__ __forceinline__ void mbar_wait_spin(uint32_t bar, uint32_t parity) {
    uint32_t ok = 0;
    int guard = 0;
    while (!ok && ++guard < SPIN_LIMIT) {
        asm volatile(
            "{\n.reg .pred P1;\n"
            "mbarrier.try_wait.parity.shared::cta.b64 P1, [%1], %2;\n"
            "selp.u32 %0, 1, 0, P1;\n}\n"
            : "=r"(ok) : "r"(bar), "r"(parity) : "memory");
    }
}
__device__ __forceinline__ uint32_t mapa(uint32_t addr, uint32_t rank) {
    uint32_t r;
    asm volatile("mapa.shared::cluster.u32 %0, %1, %2;" : "=r"(r) : "r"(addr), "r"(rank));
    return r;
}
__device__ __forceinline__ void st_async_u32(uint32_t addr, uint32_t v, uint32_t bar) {
    asm volatile("st.async.weak.shared::cluster.mbarrier::complete_tx::bytes.b32 [%0], %1, [%2];" ::"r"(addr), "r"(v), "r"(bar) : "memory");
}
__device__ __forceinline__ void st_async_v2(uint32_t addr, uint32_t a, uint32_t b, uint32_t bar) {
    asm volatile("st.async.weak.shared::cluster.mbarrier::complete_tx::bytes.v2.b32 [%0], {%1,%2}, [%3];" ::"r"(addr), "r"(a), "r"(b), "r"(bar) : "memory");
}
__device__ __forceinline__ void cluster_sync_all() {
    asm volatile("barrier.cluster.arrive.release.aligned;\nbarrier.cluster.wait.acquire.aligned;" ::: "memory");
}
__device__ __forceinline__ void named_bar(int id, int n) { asm volatile("bar.sync %0, %1;" ::"r"(id), "r"(n) : "memory"); }

}

namespace ni {
#define CHAIN_LAG 16
constexpr int CL = 16;
constexpr int OWN = DM / CL;
constexpr int NSRC = CL / 2;
constexpr int NCLU = 64 / CL;
constexpr int CSEG = 4;
constexpr int NCHK = NSEG / CSEG;
constexpr int LAG = CHAIN_LAG;
constexpr int NTICK = NSEG + LAG;

constexpr int F_KV = 0, F_MEM = 32, F_H = 64, F_OP = 96, F_CONV = 128, F_U = 130, F_PROG = 132, F_ZERO = 133, F_CNT = 136;
constexpr int NFLAG = 192;
__device__ int g_flags[NFLAG * 32];
#define FLG(i) (g_flags + (i) * 32)
constexpr int CHAIN_THREADS = 384;
__device__ bf16 g_Y[S_LEN * DM];
__device__ bf16 g_U[DM * S_LEN];
__device__ bf16 g_h[2][S_LEN * DM];
__device__ bf16 g_x[S_LEN * DM];
__device__ bf16 g_kv[2][S_LEN * HD];
#define PRING 4
constexpr int PROWS = PRING * 128, PG = 4;
__device__ bf16 g_part[2 * PROWS * PG * DM];
__device__ uint4 g_kvf[2 * NSEG * NH * 256];
__device__ uint32_t g_xc[2 * 2 * CL * NCLU * 8 * OWN];

#define TVAL(i, v)
#define TSTAMP(i)

#define NRQ 36
#define NRW 8
#define PDQ 4
#define PDW1 0
#define PROBE 2
#define PDW 6
constexpr int NSQ = 60 - NRQ, NSW = 20 - NRW;
__host__ __device__ constexpr bool q_smem(int i) { return ((i + 1) * NSQ) / 60 != (i * NSQ) / 60; }
__host__ __device__ constexpr int q_slot(int i) { return q_smem(i) ? (i * NSQ) / 60 : i - (i * NSQ) / 60; }
__host__ __device__ constexpr int w_tile(int i) { return i < 8 ? ((i & 1) ? 0 : 2) : (i < 16 ? (i & 1) : 1); }
__host__ __device__ constexpr int w_k(int i) { return i < 8 ? i / 2 : (i < 16 ? ((i & 1) ? (i - 8) / 2 : 4 + (i - 8) / 2) : i - 12); }
__host__ __device__ constexpr int w_acc(int i) { return (i >= 16 && (i & 1)) ? 3 : w_tile(i); }
__host__ __device__ constexpr bool w_smem(int i) { return i < PDW || NRW == 0 || ((i - PDW + 1) * NRW) / (20 - PDW) == ((i - PDW) * NRW) / (20 - PDW); }
__host__ __device__ constexpr int w_slot(int i) { return i < PDW ? i : (w_smem(i) ? i - ((i - PDW) * NRW) / (20 - PDW) : ((i - PDW) * NRW) / (20 - PDW)); }
constexpr int O_WQ = 0, O_WW = NSQ * 4096, O_REST = (NSQ + NSW) * 4096;
constexpr int C_TOK = 0, C_MEM = 12288, C_RED = C_MEM + 10240, C_Q = C_RED + 6144, C_K = C_Q + 2048, C_V = C_K + 2048, C_S = C_V + 4096,
              C_BAR = C_S + 3072, C_SIZE = 40960;
constexpr int S_BYTES = 3072 + 4096;
constexpr int B_S = 64, B_R = 72, B_T = 96, B_F = 104;
static_assert(C_BAR + 112 <= C_SIZE, "chain block");
constexpr int O_STB = O_REST - 61440;
static_assert((45 * NSQ) / 60 * 4096 <= O_STB && NSQ <= 32, "staging");
struct ChainSmem { unsigned char b[O_REST + 81920 + 1536]; };
static_assert(sizeof(ChainSmem) <= 232448, "smem");

struct ChainArgs {
    CUtensorMap tk[2], tv[2];
    const bf16 *x, *mem0, *Wq, *Wk, *Wv, *Wo;
    int kv_target;
};
__device__ __forceinline__ uint32_t movmat(uint32_t v) {
    uint32_t r;
    asm volatile("movmatrix.sync.aligned.m8n8.trans.b16 %0, %1;" : "=r"(r) : "r"(v));
    return r;
}
__device__ __forceinline__ void named_arrive(int id, int n) { asm volatile("bar.arrive %0, %1;" ::"r"(id), "r"(n) : "memory"); }
__device__ __forceinline__ void red_release(int* p, int v) { asm volatile("red.release.gpu.global.add.u32 [%0], %1;" ::"l"(p), "r"(v) : "memory"); }

#define CVT(i)
__device__ __forceinline__ uint4 lds128(uint32_t a) {
    uint4 v;
    asm volatile("ld.shared.v4.u32 {%0,%1,%2,%3}, [%4];" : "=r"(v.x), "=r"(v.y), "=r"(v.z), "=r"(v.w) : "r"(a));
    return v;
}
__device__ __forceinline__ uint2 lds64(uint32_t a) {
    uint2 v;
    asm volatile("ld.shared.v2.u32 {%0,%1}, [%2];" : "=r"(v.x), "=r"(v.y) : "r"(a));
    return v;
}
__device__ __forceinline__ uint32_t lds32(uint32_t a) {
    uint32_t v;
    asm volatile("ld.shared.u32 %0, [%1];" : "=r"(v) : "r"(a));
    return v;
}
__device__ __forceinline__ void sts64(uint32_t a, uint32_t x, uint32_t y) { asm volatile("st.shared.v2.u32 [%0], {%1,%2};" ::"r"(a), "r"(x), "r"(y) : "memory"); }
__device__ __forceinline__ void sts128(uint32_t a, uint32_t x, uint32_t y, uint32_t z, uint32_t w) {
    asm volatile("st.shared.v4.u32 [%0], {%1,%2,%3,%4};" ::"r"(a), "r"(x), "r"(y), "r"(z), "r"(w) : "memory");
}
__device__ __forceinline__ void st_async_v4(uint32_t addr, uint32_t a, uint32_t b, uint32_t c, uint32_t d, uint32_t bar) {
    asm volatile("st.async.weak.shared::cluster.mbarrier::complete_tx::bytes.v4.b32 [%0], {%1,%2,%3,%4}, [%5];" ::"r"(addr), "r"(a), "r"(b), "r"(c), "r"(d), "r"(bar) : "memory");
}
__device__ __forceinline__ uint2 ld_relaxed_v2(const void* p) {
    uint2 v;
    asm volatile("ld.relaxed.gpu.global.v2.u32 {%0,%1}, [%2];" : "=r"(v.x), "=r"(v.y) : "l"(p) : "memory");
    return v;
}
__device__ __forceinline__ void st_relaxed_v2(void* p, uint32_t a, uint32_t b) {
    asm volatile("st.relaxed.gpu.global.v2.u32 [%0], {%1,%2};" ::"l"(p), "r"(a), "r"(b) : "memory");
}
__device__ __forceinline__ float blo(uint32_t v) { return __uint_as_float(v << 16); }
__device__ __forceinline__ float bhi(uint32_t v) { return __uint_as_float(v & 0xffff0000u); }
__device__ __forceinline__ uint32_t badd2(uint32_t a, uint32_t b) {
    __nv_bfloat162 r = __hadd2(*reinterpret_cast<__nv_bfloat162*>(&a), *reinterpret_cast<__nv_bfloat162*>(&b));
    return *reinterpret_cast<uint32_t*>(&r);
}
__device__ __forceinline__ void mmau(float* c, const uint4& a, uint32_t b0, uint32_t b1) { mma16816(c, a.x, a.y, a.z, a.w, b0, b1); }

__device__ __forceinline__ void stsm_x4_t(uint32_t a, uint32_t r0, uint32_t r1, uint32_t r2, uint32_t r3) {
    asm volatile("stmatrix.sync.aligned.m8n8.x4.trans.shared.b16 [%0], {%1,%2,%3,%4};" ::"r"(a), "r"(r0), "r"(r1), "r"(r2), "r"(r3) : "memory");
}
__device__ __forceinline__ uint4 ldsm4(uint32_t a) { uint4 v; ldsm_x4(v.x, v.y, v.z, v.w, a); return v; }
__device__ __forceinline__ float ex2f(float x) { float y; asm("ex2.approx.ftz.f32 %0, %1;" : "=f"(y) : "f"(x)); return y; }
__device__ __forceinline__ float rcpf(float x) { float y; asm("rcp.approx.ftz.f32 %0, %1;" : "=f"(y) : "f"(x)); return y; }
#define XD 300
__device__ __forceinline__ void xdelay() {
    uint32_t t0, t1;
    asm volatile("mov.u32 %0, %clock;" : "=r"(t0));
    do { asm volatile("mov.u32 %0, %clock;" : "=r"(t1)); } while (t1 - t0 < XD);
}
template <int V> struct IC { static constexpr int value = V; };
__device__ __forceinline__ uint32_t opq(uint32_t x) { uint32_t y; asm volatile("mov.u32 %0, %1;" : "=r"(y) : "r"(x)); return y; }
#define UNI(x) __shfl_sync(0xffffffffu, (uint32_t)(x), 0)
__device__ __forceinline__ uint32_t mtest(uint32_t bar, uint32_t parity) {
    uint32_t ok;
    asm volatile("{\n.reg .pred P1;\nmbarrier.test_wait.parity.shared::cta.b64 P1, [%1], %2;\nselp.u32 %0, 1, 0, P1;\n}\n" : "=r"(ok) : "r"(bar), "r"(parity) : "memory");
    return ok;
}
__device__ __forceinline__ void mwait(uint32_t bar, uint32_t parity) {
    asm volatile(
        "{\n.reg .pred P1;\n.reg .u32 cnt;\n"
        "mbarrier.try_wait.parity.shared::cta.b64 P1, [%0], %1;\n"
        "@P1 bra DONE;\n"
        "mov.u32 cnt, 0;\n"
        "LAB_WAIT:\n"
        "mbarrier.try_wait.parity.shared::cta.b64 P1, [%0], %1;\n"
        "@P1 bra DONE;\n"
        "add.u32 cnt, cnt, 1;\n"
        "setp.lt.u32 P1, cnt, 4000000;\n"
        "@P1 bra LAB_WAIT;\n"
        "DONE:\n}\n" ::"r"(bar), "r"(parity) : "memory");
}

__global__ void __launch_bounds__(CHAIN_THREADS, 1) chain_kernel(const __grid_constant__ ChainArgs A) {
    extern __shared__ __align__(1024) unsigned char smem_raw[];
    const int tid = threadIdx.x, warp = __shfl_sync(0xffffffffu, tid >> 5, 0), lane = tid & 31;
    const int cq = blockIdx.x / CL, r = blockIdx.x % CL;
    const int h = cq * NSRC + (r >> 1), hf = r & 1;
    const uint32_t sb = smem_u32(smem_raw);
    asm volatile("griddepcontrol.launch_dependents;");
    CVT(0);
    if (warp == 8) {
        if (lane < 8) asm volatile("cp.async.bulk.prefetch.L2.global [%0], %1;" ::"l"(A.x + (size_t)(blockIdx.x * 8 + lane) * 2560), "r"(5120) : "memory");
        asm volatile("cp.async.bulk.prefetch.L2.global [%0], %1;" ::"l"((lane < 16 ? A.Wk : A.Wv) + (size_t)(blockIdx.x * 16 + (lane & 15)) * 2560), "r"(5120) : "memory");
        asm volatile("cp.async.bulk.prefetch.L2.global [%0], %1;" ::"l"((lane < 16 ? A.Wq : A.Wo) + (size_t)(blockIdx.x * 16 + (lane & 15)) * 2560), "r"(5120) : "memory");
    }
    CVT(1);
    if (warp < 8) {
        asm volatile("setmaxnreg.inc.sync.aligned.u32 232;");
        const int j = warp & 3, kh = warp >> 2;
        uint4 wr[NRQ + NRW];
        {
            auto load_round = [&](int gi) {
                const uint32_t buf = sb + ((gi & 1) ? O_STB : O_REST);
#pragma unroll
                for (int it = 0; it < 15; it++) {
                    const int i = tid + it * 256;
                    const int pc = i / 1920, rem = i % 1920, row = rem / 24, ch = rem % 24;
                    const int mat = ch >> 3, pi = ((r >> 1) - (2 * gi + pc)) & 7;
                    const bf16* W = mat == 0 ? A.Wq : (mat == 1 ? A.Wk : A.Wv);
                    cp_async16(buf + pc * 30720 + row * 384 + ((ch ^ (row & 7)) << 4), W + (size_t)(pi * 80 + row) * HD + h * DH + hf * 64 + (ch & 7) * 8);
                }
                cp_commit();
            };
            load_round(0);
            load_round(1);
#pragma unroll
            for (int gi = 0; gi < 4; gi++) {
                cp_wait<1>();
                named_bar(1, 256);
                const uint32_t pb = sb + ((gi & 1) ? O_STB : O_REST) + kh * 30720;
                uint4 tmp[8];
#pragma unroll
                for (int u = 0; u < 5; u++)
#pragma unroll
                    for (int tt = 0; tt < 3; tt++) {
                        const int row = u * 16 + (lane & 7) + (lane >> 4) * 8;
                        const int ch = tt * 8 + j * 2 + ((lane >> 3) & 1);
                        uint4 v;
                        ldsm_x4_t(v.x, v.y, v.z, v.w, pb + row * 384 + ((ch ^ (row & 7)) << 4));
                        const int i = (gi * 5 + u) * 3 + tt;
                        if (q_smem(i)) {
                            if (gi == 3) tmp[q_slot(i) & 7] = v;
                            else sts128(sb + O_WQ + q_slot(i) * 4096 + tid * 16, v.x, v.y, v.z, v.w);
                        } else wr[q_slot(i)] = v;
                    }
                named_bar(1, 256);
                if (gi == 3) {
#pragma unroll
                    for (int i = 45; i < 60; i++)
                        if (q_smem(i)) { const uint4 v = tmp[q_slot(i) & 7]; sts128(sb + O_WQ + q_slot(i) * 4096 + tid * 16, v.x, v.y, v.z, v.w); }
                }
                if (gi < 2) load_round(gi + 2);
                else if (gi == 2) {
                    for (int i = tid; i < 128 * 40; i += 256) {
                        const int row = i / 40, ch = i % 40;
                        cp_async16(sb + O_REST + row * 640 + ((ch ^ (row & 7)) << 4), A.Wo + ((size_t)h * DH + row) * DM + hf * 320 + ch * 8);
                    }
                    cp_commit();
                }
            }
            cp_wait<0>();
            named_bar(1, 256);
#pragma unroll
            for (int i = 0; i < 20; i++) {
                const int tl = w_tile(i), et = (w_k(i) + 4 * (warp & 1)) & 7;
                const int row = et * 16 + (lane & 7) + (lane >> 4) * 8;
                const int ch = (warp >> 1) * 10 + (tl == 2 ? 8 : (warp & 1) * 4 + tl * 2) + ((lane >> 3) & 1);
                uint4 v;
                ldsm_x4_t(v.x, v.y, v.z, v.w, sb + O_REST + row * 640 + ((ch ^ (row & 7)) << 4));
                if (w_smem(i)) sts128(sb + O_WW + w_slot(i) * 4096 + tid * 16, v.x, v.y, v.z, v.w);
                else wr[NRQ + w_slot(i)] = v;
            }
            named_bar(1, 256);
            for (int i = tid; i < 2560; i += 256) {
                const int ks = i >> 6, ln = (i >> 1) & 31, wd = i & 1;
                const int pi = ((r >> 1) - ks / 5) & 7;
                const uint32_t v = *reinterpret_cast<const uint32_t*>(A.mem0 + (ln >> 2) * DM + pi * 80 + (ks % 5) * 16 + wd * 8 + (ln & 3) * 2);
                const int o = ks % 5 == 4 ? ks * 256 + wd * 128 + ln * 4 : i * 4;
                asm volatile("st.shared.u32 [%0], %1;" ::"r"(sb + O_REST + C_MEM + o), "r"(v) : "memory");
                asm volatile("st.shared.u32 [%0], %1;" ::"r"(sb + O_REST + C_SIZE + C_MEM + o), "r"(v) : "memory");
            }
            if (tid < 2) {
                const uint32_t bb = sb + O_REST + tid * C_SIZE + C_BAR;
                for (int i = 0; i < 13; i++) mbar_init(bb + i * 8, 1);
                mbar_init(bb + B_F, 4);
                asm volatile("fence.mbarrier_init.release.cluster;" ::: "memory");
                mbar_expect_tx(bb + B_S, S_BYTES);
                for (int i = 0; i < 3; i++) mbar_expect_tx(bb + B_R + i * 8, 2048);
            }
            asm volatile("fence.proxy.async;" ::: "memory");
        }
        CVT(2);
        cluster_sync_all();
        const uint32_t wq_a = sb + O_WQ + tid * 16;
        const uint32_t cb0 = sb + O_REST;
        const uint32_t qk_a = cb0 + j * 512 + (lane & 7) * 16 + (lane < 16 ? C_Q + (lane >> 3) * 256 + kh * 128 : C_K + kh * 256 + ((lane >> 3) & 1) * 128);
        const uint32_t pd = UNI(mapa(sb, (uint32_t)(r ^ 1)) - sb), sd = UNI(mapa(sb, (uint32_t)r) - sb);
        const uint32_t od = UNI(mapa(sb, (uint32_t)(hf * 8 + warp)) - sb);
        const uint32_t oe = UNI(mapa(sb, (uint32_t)(hf * 8 + (warp & 6))) - sb), oo = UNI(mapa(sb, (uint32_t)(hf * 8 + (warp | 1))) - sb);
        const uint32_t u_mem = UNI(cb0 + C_MEM + kh * 1280), u_bm = UNI(cb0 + C_BAR + kh * 8);
        const uint32_t u_v = UNI(cb0 + C_V + hf * 2048 + j * 512 + kh * 256);
        const uint32_t u_ra = UNI(cb0 + C_RED + (r >> 1) * 256);
        const uint32_t u_ob0 = UNI(cb0 + C_Q + (warp & 1) * 1024), u_ob1 = UNI(cb0 + C_Q + ((warp & 1) ^ 1) * 1024);
        const uint32_t u_role = UNI(warp < 3 ? cb0 + C_S + hf * 1536 + warp * 512 : cb0 + C_V + j * 1024);
        const uint32_t t_tok = cb0 + C_TOK + ((lane & 7) + (lane >> 4) * 8) * 128 +
                               (warp < 3 ? warp * 2048 + ((((lane >> 3) & 1) ^ (lane & 7)) << 4) : 4096 + (j >> 1) * 4096 + ((((j & 1) * 4 + ((lane >> 3) & 1)) ^ (lane & 7)) << 4));
        uint4 qb[PDQ];
#pragma unroll
        for (int s = 0; s < PDQ; s++) qb[s] = lds128(wq_a + s * 4096);
        auto tick = [&](auto cc, const int n) {
            constexpr int c = decltype(cc)::value;
            constexpr uint32_t CO = c * C_SIZE;
            const uint32_t cb = cb0 + CO;
            const uint32_t par = (uint32_t)(n & 1);
            const uint32_t l4 = opq(lane * 4), l8 = l4 * 2, l16 = l4 * 4;
            float acc[3][4];
#pragma unroll
            for (int a = 0; a < 3; a++)
#pragma unroll
                for (int i = 0; i < 4; i++) acc[a][i] = 0.f;
            {
                const uint32_t mb = u_mem + CO + l8;
                uint2 bf[3];
                uint32_t ok = 1;
                auto ldb = [&](int ks) {
                    if (ks == 0) mwait(u_bm + CO, par ^ 1);
                    else if (ks % 5 == 0) { if (!ok) mwait(u_bm + CO + (ks / 5) * 16, par ^ 1); }
                    if (ks % 5 == PROBE && ks < 15) ok = mtest(u_bm + CO + (ks / 5 + 1) * 16, par ^ 1);
                    if (ks % 5 == 4) {
                        bf[ks % 3].x = lds32(u_mem + CO + l4 + (ks / 5) * 2560 + 1024);
                        bf[ks % 3].y = lds32(u_mem + CO + l4 + (ks / 5) * 2560 + 1152);
                    } else bf[ks % 3] = lds64(mb + (ks / 5) * 2560 + (ks % 5) * 256);
                };
                ldb(0);
                TSTAMP(c * 12 + 0);
                ldb(1);
#pragma unroll
                for (int ks = 0; ks < 20; ks++) {
                    if (ks + 2 < 20) ldb(ks + 2);
#pragma unroll
                    for (int tt = 0; tt < 3; tt++) {
                        const int i = ks * 3 + tt;
                        if (q_smem(i)) {
                            const int s = q_slot(i);
                            mmau(acc[tt], qb[s % PDQ], bf[ks % 3].x, bf[ks % 3].y);
                            if (s + PDQ < NSQ) qb[s % PDQ] = lds128(wq_a + (s + PDQ) * 4096);
                        } else mmau(acc[tt], wr[q_slot(i)], bf[ks % 3].x, bf[ks % 3].y);
                    }
                }
            }
            TSTAMP(c * 12 + 1);
            stsm_x4_t(opq(qk_a) + CO, pack2(acc[0][0], acc[0][1]), pack2(acc[0][2], acc[0][3]), pack2(acc[1][0], acc[1][1]), pack2(acc[1][2], acc[1][3]));
            const uint32_t v0 = pack2(acc[2][0], acc[2][1]), v1 = pack2(acc[2][2], acc[2][3]);
            if (n == NSEG - 1) {
                sts64(u_v + CO + l8, v0, v1);
                named_bar(1, 256);
                if (kh == 1 && lane == 0) mbar_arrive(cb + C_BAR + B_F);
#pragma unroll
                for (int s = 0; s < PDQ; s++) qb[s] = lds128(wq_a + s * 4096);
                return;
            }
            named_arrive(1, 384);
            st_async_v2(u_v + CO + l8 + pd, v0, v1, cb + C_BAR + B_S + pd);
            st_async_v2(u_v + CO + l8 + sd, v0, v1, cb + C_BAR + B_S + sd);
            uint4 wb[PDW];
            const uint32_t ww_a = wq_a + (O_WW - O_WQ);
            if (warp < 3) {
                uint4 kb[4];
                const uint32_t t_tk = opq(t_tok);
                mwait(cb + C_BAR + B_T, par);
#pragma unroll
                for (int i = 0; i < 4; i++) kb[i] = ldsm4((t_tk ^ (i << 5)) + CO);
                named_bar(1, 384);
                uint4 qa[4];
#pragma unroll
                for (int i = 0; i < 4; i++) qa[i] = ldsm4(cb + l16 + C_Q + i * 512);
                if (warp == 2) {
#pragma unroll
                    for (int i = 0; i < 4; i++) kb[i] = ldsm4(cb + l16 + C_K + i * 512);
                }
                float s0[4][4], s1[4][4];
#pragma unroll
                for (int i = 0; i < 4; i++) {
#pragma unroll
                    for (int q = 0; q < 4; q++) s0[i][q] = s1[i][q] = 0.f;
                    mmau(s0[i], qa[i], kb[i].x, kb[i].y);
                    mmau(s1[i], qa[i], kb[i].z, kb[i].w);
                }
                const float a0 = ((s0[0][0] + s0[0][2]) + (s0[1][0] + s0[1][2])) + ((s0[2][0] + s0[2][2]) + (s0[3][0] + s0[3][2]));
                const float a1 = ((s0[0][1] + s0[0][3]) + (s0[1][1] + s0[1][3])) + ((s0[2][1] + s0[2][3]) + (s0[3][1] + s0[3][3]));
                const float b0 = ((s1[0][0] + s1[0][2]) + (s1[1][0] + s1[1][2])) + ((s1[2][0] + s1[2][2]) + (s1[3][0] + s1[3][2]));
                const float b1 = ((s1[0][1] + s1[0][3]) + (s1[1][1] + s1[1][3])) + ((s1[2][1] + s1[2][3]) + (s1[3][1] + s1[3][3]));
                const uint32_t so = u_role + CO + l16, bs = cb + C_BAR + B_S;
                const float c0 = warp == 2 ? a0 + b0 : a0, c1 = warp == 2 ? a1 + b1 : a1;
                st_async_v4(so + pd, __float_as_uint(c0), __float_as_uint(c1), __float_as_uint(b0), __float_as_uint(b1), bs + pd);
                st_async_v4(so + sd, __float_as_uint(c0), __float_as_uint(c1), __float_as_uint(b0), __float_as_uint(b1), bs + sd);
                TSTAMP(c * 12 + 2);
#pragma unroll
                for (int s = 0; s < PDW; s++) wb[s] = lds128(ww_a + s * 4096);
            } else if (warp == 3) {
                named_bar(1, 384);
                if (lane < 8) mbar_expect_tx(cb + C_BAR + l8, 1280);
#pragma unroll
                for (int s = 0; s < PDW; s++) wb[s] = lds128(ww_a + s * 4096);
            } else {
                mwait(cb + C_BAR + B_T, par);
                uint4 va[2][2];
                const uint32_t t_tk = opq(t_tok);
#pragma unroll
                for (int e = 0; e < 2; e++)
#pragma unroll
                    for (int k = 0; k < 2; k++)
                        ldsm_x4_t(va[e][k].x, va[e][k].y, va[e][k].z, va[e][k].w, (t_tk ^ (e << 5)) + CO + k * 2048);
#pragma unroll
                for (int s2 = 0; s2 < PDW1; s2++) wb[s2] = lds128(ww_a + s2 * 4096);
                mwait(cb + C_BAR + B_S, par);
                TSTAMP(c * 12 + 3);
                const uint32_t xa = cb + l16 + C_S;
                const uint4 x0 = lds128(xa), y0 = lds128(xa + 1536), x1 = lds128(xa + 512), y1 = lds128(xa + 512 + 1536);
                const uint2 x2 = lds64(xa + 1024), y2 = lds64(xa + 1024 + 1536);
                const uint32_t fv = u_role + CO + l8;
                const float cs = 0.08838834764831845f * 1.4426950408889634f;
                float s[10];
                s[8] = __uint_as_float(x2.x) + __uint_as_float(y2.x); s[9] = __uint_as_float(x2.y) + __uint_as_float(y2.y);
                s[0] = __uint_as_float(x0.x) + __uint_as_float(y0.x); s[1] = __uint_as_float(x0.y) + __uint_as_float(y0.y);
                s[2] = __uint_as_float(x0.z) + __uint_as_float(y0.z); s[3] = __uint_as_float(x0.w) + __uint_as_float(y0.w);
                s[4] = __uint_as_float(x1.x) + __uint_as_float(y1.x); s[5] = __uint_as_float(x1.y) + __uint_as_float(y1.y);
                s[6] = __uint_as_float(x1.z) + __uint_as_float(y1.z); s[7] = __uint_as_float(x1.w) + __uint_as_float(y1.w);
                float mx = fmaxf(fmaxf(fmaxf(s[0], s[1]), fmaxf(s[2], s[3])), fmaxf(fmaxf(fmaxf(s[4], s[5]), fmaxf(s[6], s[7])), fmaxf(s[8], s[9])));
                const float m1 = __shfl_xor_sync(0xffffffffu, mx, 1), m2 = __shfl_xor_sync(0xffffffffu, mx, 2), m3 = __shfl_xor_sync(0xffffffffu, mx, 3);
                const uint2 vm00 = lds64(fv), vm01 = lds64(fv + 256), vm10 = lds64(fv + 512), vm11 = lds64(fv + 768);
                const uint4 vm0 = make_uint4(vm00.x, vm00.y, vm01.x, vm01.y), vm1 = make_uint4(vm10.x, vm10.y, vm11.x, vm11.y);
                mx = fmaxf(fmaxf(mx, m1), fmaxf(m2, m3)) * -cs;
                uint32_t pb[5];
                pb[4] = pack2(ex2f(fmaf(s[8], cs, mx)), ex2f(fmaf(s[9], cs, mx)));
#pragma unroll
                for (int i = 0; i < 4; i++) pb[i] = pack2(ex2f(fmaf(s[2 * i], cs, mx)), ex2f(fmaf(s[2 * i + 1], cs, mx)));
                float o[3][4];
#pragma unroll
                for (int i = 0; i < 4; i++) { o[0][i] = o[1][i] = o[2][i] = 0.f; }
                const uint32_t one2 = 0x3F803F80u;
                mma16816(o[2], one2, one2, one2, one2, pb[4], 0u);
                mmau(o[0], vm0, pb[4], pb[4]);
                mmau(o[1], vm1, pb[4], pb[4]);
                mma16816(o[2], one2, one2, one2, one2, pb[0], pb[1]);
                mmau(o[0], va[0][0], pb[0], pb[1]);
                mmau(o[1], va[1][0], pb[0], pb[1]);
                mma16816(o[2], one2, one2, one2, one2, pb[2], pb[3]);
                mmau(o[0], va[0][1], pb[2], pb[3]);
                mmau(o[1], va[1][1], pb[2], pb[3]);
                const float r0 = rcpf(o[2][0]), r1 = rcpf(o[2][1]);
                stsm_x4_t(cb + l16 + C_Q + j * 512, pack2(o[0][0] * r0, o[0][1] * r1), pack2(o[0][2] * r0, o[0][3] * r1), pack2(o[1][0] * r0, o[1][1] * r1), pack2(o[1][2] * r0, o[1][3] * r1));
                named_arrive(2, 384);
                TSTAMP(c * 12 + 4);
#pragma unroll
                for (int s2 = PDW1; s2 < PDW; s2++) wb[s2] = lds128(ww_a + s2 * 4096);
                if (lane == 0) mbar_arrive(cb + C_BAR + B_F);
                if (warp == 4 && lane == 0) mbar_expect_tx(cb + C_BAR + B_S, S_BYTES);
            }
            named_bar(2, 384);
            TSTAMP(c * 12 + 5);
            {
                uint4 ob[4];
                ob[0] = ldsm4(u_ob0 + CO + l16); ob[1] = ldsm4(u_ob0 + CO + l16 + 512);
                ob[2] = ldsm4(u_ob1 + CO + l16); ob[3] = ldsm4(u_ob1 + CO + l16 + 512);
                float d[4][4];
#pragma unroll
                for (int a = 0; a < 4; a++)
#pragma unroll
                    for (int i = 0; i < 4; i++) d[a][i] = 0.f;
                const uint32_t ra = u_ra + CO + l8, rb = cb + C_BAR + B_R;
#pragma unroll
                for (int i = 0; i < 20; i++) {
                    const int k = w_k(i), ac = w_acc(i);
                    const uint32_t b0 = (k & 1) ? ob[k >> 1].z : ob[k >> 1].x, b1 = (k & 1) ? ob[k >> 1].w : ob[k >> 1].y;
                    if (w_smem(i)) {
                        const int s = w_slot(i);
                        mmau(d[ac], wb[s % PDW], b0, b1);
                        if (s + PDW < NSW) wb[s % PDW] = lds128(ww_a + (s + PDW) * 4096);
                    } else mmau(d[ac], wr[NRQ + w_slot(i)], b0, b1);
                    if (i == 9) {
                        const uint32_t rs = u_ra + CO + l4 + 4096 + (warp & 1) * 128;
                        st_async_u32(rs + oe, pack2(d[2][0], d[2][1]), rb + 16 + oe);
                        st_async_u32(rs + oo, pack2(d[2][2], d[2][3]), rb + 16 + oo);
                    }
                    if (i == 17) st_async_v2(ra + od, pack2(d[0][0], d[0][1]), pack2(d[0][2], d[0][3]), rb + od);
                }
                st_async_v2(ra + 2048 + od, pack2(d[1][0] + d[3][0], d[1][1] + d[3][1]), pack2(d[1][2] + d[3][2], d[1][3] + d[3][3]), rb + 8 + od);
                TSTAMP(c * 12 + 6);
#pragma unroll
                for (int s = 0; s < PDQ; s++) qb[s] = lds128(wq_a + s * 4096);
            }
        };
#pragma unroll 1
        for (int t = 0; t < NTICK; t++) {
            if (t < NSEG) tick(IC<0>{}, t);
            if (t >= LAG) tick(IC<1>{}, t - LAG);
        }
    } else {
        asm volatile("setmaxnreg.dec.sync.aligned.u32 40;");
        const int s = warp - 8;
        cluster_sync_all();
        if (s < 3) {
#pragma unroll 1
            for (int hs = 0; hs < 2 * NTICK; hs++) {
                const int c = hs & 1, t = hs >> 1;
                const int n = t - c * LAG;
                if (n < 0 || n >= NSEG - 1) continue;
                const uint32_t cb = sb + O_REST + c * C_SIZE;
                const uint32_t par = (uint32_t)(n & 1);
                const uint32_t tag = (uint32_t)(n % 13) + 1u;
                uint32_t* xb = g_xc + (size_t)((c * 2 + par) * CL + r) * (NCLU * 320) + s * 128;
                const uint32_t ra = cb + C_RED + s * 2048 + lane * (s < 2 ? 8 : 4);
                mwait(cb + C_BAR + B_R + s * 8, par);
                TSTAMP(c * 12 + 7);
                uint4 p[4];
                if (s < 2) {
#pragma unroll
                    for (int i = 0; i < 4; i++) {
                        const uint2 a = lds64(ra + i * 512), b = lds64(ra + i * 512 + 256);
                        p[i] = make_uint4(a.x, a.y, b.x, b.y);
                    }
                } else {
#pragma unroll
                    for (int i = 0; i < 4; i++) p[i] = make_uint4(lds32(ra + i * 512), lds32(ra + i * 512 + 128), lds32(ra + i * 512 + 256), lds32(ra + i * 512 + 384));
                }
                if (lane == 0) mbar_expect_tx(cb + C_BAR + B_R + s * 8, 2048);
                uint32_t m0, m1;
                if (s < 2) {
                    float f0 = 0.f, f1 = 0.f, f2 = 0.f, f3 = 0.f;
#pragma unroll
                    for (int i = 0; i < 4; i++) {
                        f0 += blo(p[i].x) + blo(p[i].z); f1 += bhi(p[i].x) + bhi(p[i].z);
                        f2 += blo(p[i].y) + blo(p[i].w); f3 += bhi(p[i].y) + bhi(p[i].w);
                    }
                    xb += lane * 4;
                    const uint32_t u0 = (__float_as_uint(f0) & ~0xFu) | tag, u1 = (__float_as_uint(f1) & ~0xFu) | tag;
                    const uint32_t u2 = (__float_as_uint(f2) & ~0xFu) | tag, u3 = (__float_as_uint(f3) & ~0xFu) | tag;
                    st_relaxed_v4(xb + cq * 320, u0, u1, u2, u3);
                    TSTAMP(c * 12 + 8);
                    xdelay();
                    uint4 x[NCLU];
#pragma unroll
                    for (int k = 0; k < NCLU; k++) x[k] = make_uint4(u0, u1, u2, u3);
                    int guard = 0;
                    bool first = true;
                    while (true) {
                        bool ok = true;
#pragma unroll
                        for (int k = 0; k < NCLU; k++) {
                            const bool okk = k == cq || (!first && ((x[k].x ^ tag) | (x[k].y ^ tag) | (x[k].z ^ tag) | (x[k].w ^ tag)) << 28 == 0);
                            if (!okk) { x[k] = ld_relaxed_v4(xb + k * 320); ok = false; }
                        }
                        first = false;
                        if (__all_sync(0xffffffffu, ok) || ++guard > SPIN_LIMIT) break;
                    }
                    TVAL(c * 12 + 11, guard);
                    f0 = f1 = f2 = f3 = 0.f;
#pragma unroll
                    for (int k = 0; k < NCLU; k++) {
                        f0 += __uint_as_float(x[k].x & ~0xFu); f1 += __uint_as_float(x[k].y & ~0xFu);
                        f2 += __uint_as_float(x[k].z & ~0xFu); f3 += __uint_as_float(x[k].w & ~0xFu);
                    }
                    m0 = movmat(pack2(f0, f1)); m1 = movmat(pack2(f2, f3));
                } else {
                    float f0 = 0.f, f1 = 0.f;
#pragma unroll
                    for (int i = 0; i < 4; i++) {
                        f0 += (blo(p[i].x) + blo(p[i].y)) + (blo(p[i].z) + blo(p[i].w));
                        f1 += (bhi(p[i].x) + bhi(p[i].y)) + (bhi(p[i].z) + bhi(p[i].w));
                    }
                    xb += lane * 2;
                    const uint32_t u0 = (__float_as_uint(f0) & ~0xFu) | tag, u1 = (__float_as_uint(f1) & ~0xFu) | tag;
                    st_relaxed_v2(xb + cq * 320, u0, u1);
                    TSTAMP(c * 12 + 8);
                    xdelay();
                    uint2 x[NCLU];
#pragma unroll
                    for (int k = 0; k < NCLU; k++) x[k] = make_uint2(u0, u1);
                    int guard = 0;
                    bool first = true;
                    while (true) {
                        bool ok = true;
#pragma unroll
                        for (int k = 0; k < NCLU; k++) {
                            const bool okk = k == cq || (!first && ((x[k].x ^ tag) | (x[k].y ^ tag)) << 28 == 0);
                            if (!okk) { x[k] = ld_relaxed_v2(xb + k * 320); ok = false; }
                        }
                        first = false;
                        if (__all_sync(0xffffffffu, ok) || ++guard > SPIN_LIMIT) break;
                    }
                    TVAL(c * 12 + 11, guard);
                    f0 = f1 = 0.f;
#pragma unroll
                    for (int k = 0; k < NCLU; k++) { f0 += __uint_as_float(x[k].x & ~0xFu); f1 += __uint_as_float(x[k].y & ~0xFu); }
                    m0 = movmat(pack2(f0, f1)); m1 = 0;
                }
                TSTAMP(c * 12 + 9);
                const uint32_t ma = cb + C_MEM + (s < 2 ? lane * 8 + (hf * 2 + s) * 256 : 1024 + hf * 128 + lane * 4), bm = cb + C_BAR;
                if (s < 2) {
#pragma unroll
                    for (int G = 0; G < 8; G++)
#pragma unroll
                        for (int b = 0; b < 2; b++) {
                            const uint32_t dd = mapa(sb, (uint32_t)(((r + 2 * G) & 15) ^ b)) - sb;
                            st_async_v2(ma + G * 1280 + dd, m0, m1, bm + G * 8 + dd);
                        }
                } else {
#pragma unroll
                    for (int G = 0; G < 8; G++)
#pragma unroll
                        for (int b = 0; b < 2; b++) {
                            const uint32_t dd = mapa(sb, (uint32_t)(((r + 2 * G) & 15) ^ b)) - sb;
                            st_async_u32(ma + G * 1280 + dd, m0, bm + G * 8 + dd);
                        }
                }
                TSTAMP(c * 12 + 10);
            }
        } else {
            auto fetch = [&](int c, int seg) {
                if (lane == 0) {
                    if (seg % CSEG == 0) {
                        int guard = 0;
                        while (ld_acquire(FLG(F_KV + c * NCHK + seg / CSEG)) < A.kv_target && ++guard < SPIN_LIMIT) __nanosleep(64);
                    }
                    asm volatile("fence.proxy.async;" ::: "memory");
                    const uint32_t cb = sb + O_REST + c * C_SIZE;
                    const uint32_t bt = cb + C_BAR + B_T, d = cb + C_TOK;
                    mbar_expect_tx(bt, 12288);
                    const CUtensorMap* mk = &A.tk[c];
                    const CUtensorMap* mv = &A.tv[c];
                    asm volatile("cp.async.bulk.tensor.2d.shared::cluster.global.mbarrier::complete_tx::bytes [%0], [%1, {%3, %4}], [%2];" ::"r"(d),
                                 "l"(mk), "r"(bt), "r"(h * DH + hf * 64), "r"(seg * SEG) : "memory");
#pragma unroll
                    for (int i = 0; i < 2; i++)
                        asm volatile("cp.async.bulk.tensor.2d.shared::cluster.global.mbarrier::complete_tx::bytes [%0], [%1, {%3, %4}], [%2];" ::"r"(d + 4096 + i * 4096),
                                     "l"(mv), "r"(bt), "r"(h * DH + i * 64), "r"(seg * SEG) : "memory");
                }
                __syncwarp();
            };
            fetch(0, 0);
#pragma unroll 1
            for (int hs = 0; hs < 2 * NTICK; hs++) {
                const int c = hs & 1, t = hs >> 1;
                const int n = t - c * LAG;
                if (n < -1 || n >= NSEG) continue;
                if (n >= 0) {
                    const uint32_t cb = sb + O_REST + c * C_SIZE;
                    mwait(cb + C_BAR + B_F, (uint32_t)(n & 1));
                    uint4* fd = g_kvf + (size_t)((c * NSEG + n) * NH + h) * 256 + hf * 64 + lane;
#pragma unroll
                    for (int i = 0; i < 2; i++) {
                        const uint4 k0 = ldsm4(cb + C_K + i * 1024 + lane * 16), k1 = ldsm4(cb + C_K + i * 1024 + 512 + lane * 16);
                        fd[i * 32] = make_uint4(badd2(k0.x, k0.z), badd2(k0.y, k0.w), badd2(k1.x, k1.z), badd2(k1.y, k1.w));
                        const uint32_t va = cb + C_V + hf * 2048 + i * 1024 + lane * 8;
                        const uint2 v0 = lds64(va), v1 = lds64(va + 256), v2 = lds64(va + 512), v3 = lds64(va + 768);
                        fd[128 + i * 32] = make_uint4(badd2(v0.x, v1.x), badd2(v0.y, v1.y), badd2(v2.x, v3.x), badd2(v2.y, v3.y));
                    }
                    if (blockIdx.x == 0 && lane == 0 && (c == 0 || t >= NSEG)) asm volatile("st.relaxed.gpu.global.u32 [%0], %1;" ::"l"(FLG(F_PROG)), "r"(t + 1) : "memory");
                    if ((n % CSEG) == CSEG - 1) {
                        asm volatile("fence.proxy.async;" ::: "memory");
                        __syncwarp();
                        if (lane == 0) { red_release(FLG(F_MEM + c * NCHK + n / CSEG), 1); }
                    }
                }
                if (n + 1 < NSEG - 1) fetch(c, n + 1);
            }
        }
    }
    cluster_sync_all();
}
}

namespace ni {
constexpr int KV_TGT = 32, MEM_TGT = 64, OP_TGT = 16, CONV_TGT = 80, H_TGT = 128;
constexpr int PDIST = (LAG + 3) / 4;
#define QA_PRE 3
#define KV1_W 5
#define KV1_N 16
static_assert(QA_PRE < 4, "inputs of the chunk must be complete");
#define SPLAN 0x102030
#define URGENT 1
#define POST_NS 40

#define ELECT "{\n.reg .pred p;\nelect.sync _|p, 0xffffffff;\n@p "
__device__ __forceinline__ void tma_load_2d(uint32_t dst, const CUtensorMap* map, uint32_t bar, int c0, int c1) {
    asm volatile(ELECT "cp.async.bulk.tensor.2d.shared::cluster.global.mbarrier::complete_tx::bytes [%0], [%1, {%3, %4}], [%2];\n}" ::"r"(dst),
                 "l"(map), "r"(bar), "r"(c0), "r"(c1) : "memory");
}
__device__ __forceinline__ void tma_load_2d_mc(uint32_t dst, const CUtensorMap* map, uint32_t bar, int c0, int c1) {
    asm volatile(ELECT "cp.async.bulk.tensor.2d.shared::cluster.global.mbarrier::complete_tx::bytes.multicast::cluster [%0], [%1, {%3, %4}], [%2], %5;\n}" ::"r"(dst),
                 "l"(map), "r"(bar), "r"(c0), "r"(c1), "h"((unsigned short)3) : "memory");
}
__device__ __forceinline__ void tma_load_3d(uint32_t dst, const CUtensorMap* map, uint32_t bar, int c1, int c2) {
    asm volatile(ELECT "cp.async.bulk.tensor.3d.shared::cluster.global.mbarrier::complete_tx::bytes [%0], [%1, {%5, %3, %4}], [%2];\n}" ::"r"(dst),
                 "l"(map), "r"(bar), "r"(c1), "r"(c2), "r"(0) : "memory");
}
__device__ __forceinline__ void tma_load_3d_mc(uint32_t dst, const CUtensorMap* map, uint32_t bar, int c1, int c2) {
    asm volatile(ELECT "cp.async.bulk.tensor.3d.shared::cluster.global.mbarrier::complete_tx::bytes.multicast::cluster [%0], [%1, {%6, %3, %4}], [%2], %5;\n}" ::"r"(dst),
                 "l"(map), "r"(bar), "r"(c1), "r"(c2), "h"((unsigned short)3), "r"(0) : "memory");
}
__device__ __forceinline__ void bulk_load(uint32_t dst, const void* src, uint32_t bytes, uint32_t bar) {
    asm volatile(ELECT "cp.async.bulk.shared::cluster.global.mbarrier::complete_tx::bytes [%0], [%1], %2, [%3];\n}" ::"r"(dst), "l"(src), "r"(bytes), "r"(bar) : "memory");
}
__device__ __forceinline__ void expect_tx1(uint32_t bar, uint32_t bytes) {
    asm volatile(ELECT "mbarrier.arrive.expect_tx.shared::cta.b64 _, [%0], %1;\n}" ::"r"(bar), "r"(bytes) : "memory");
}
__device__ __forceinline__ void wg_fence() { asm volatile("wgmma.fence.sync.aligned;" ::: "memory"); }
__device__ __forceinline__ void wg_commit() { asm volatile("wgmma.commit_group.sync.aligned;" ::: "memory"); }
template <int N> __device__ __forceinline__ void wg_wait() { asm volatile("wgmma.wait_group.sync.aligned %0;" ::"n"(N) : "memory"); }
__device__ __forceinline__ uint64_t make_desc(uint32_t addr, uint32_t lbo, uint32_t sbo) {
    return (uint64_t)((addr & 0x3FFFF) >> 4) | ((uint64_t)((lbo & 0x3FFFF) >> 4) << 16) |
           ((uint64_t)((sbo & 0x3FFFF) >> 4) << 32) | (1ull << 62);
}
__device__ __forceinline__ void wgmma_m64n256k16(float* d, uint64_t da, uint64_t db) {
    asm volatile("{\n.reg .pred p;\nsetp.ne.b32 p, 1, 0;\n"
                 "wgmma.mma_async.sync.aligned.m64n256k16.f32.bf16.bf16 {%0, %1, %2, %3, %4, %5, %6, %7, %8, %9, %10, %11, %12, %13, %14, %15, %16, %17, %18, %19, %20, %21, %22, %23, %24, %25, %26, %27, %28, %29, %30, %31, %32, %33, %34, %35, %36, %37, %38, %39, %40, %41, %42, %43, %44, %45, %46, %47, %48, %49, %50, %51, %52, %53, %54, %55, %56, %57, %58, %59, %60, %61, %62, %63, %64, %65, %66, %67, %68, %69, %70, %71, %72, %73, %74, %75, %76, %77, %78, %79, %80, %81, %82, %83, %84, %85, %86, %87, %88, %89, %90, %91, %92, %93, %94, %95, %96, %97, %98, %99, %100, %101, %102, %103, %104, %105, %106, %107, %108, %109, %110, %111, %112, %113, %114, %115, %116, %117, %118, %119, %120, %121, %122, %123, %124, %125, %126, %127}, %128, %129, p, 1, 1, 0, 1;\n}\n"
                 : "+f"(d[0]), "+f"(d[1]), "+f"(d[2]), "+f"(d[3]), "+f"(d[4]), "+f"(d[5]), "+f"(d[6]), "+f"(d[7]), "+f"(d[8]), "+f"(d[9]), "+f"(d[10]), "+f"(d[11]), "+f"(d[12]), "+f"(d[13]), "+f"(d[14]), "+f"(d[15]), "+f"(d[16]), "+f"(d[17]), "+f"(d[18]), "+f"(d[19]), "+f"(d[20]), "+f"(d[21]), "+f"(d[22]), "+f"(d[23]), "+f"(d[24]), "+f"(d[25]), "+f"(d[26]), "+f"(d[27]), "+f"(d[28]), "+f"(d[29]), "+f"(d[30]), "+f"(d[31]), "+f"(d[32]), "+f"(d[33]), "+f"(d[34]), "+f"(d[35]), "+f"(d[36]), "+f"(d[37]), "+f"(d[38]), "+f"(d[39]), "+f"(d[40]), "+f"(d[41]), "+f"(d[42]), "+f"(d[43]), "+f"(d[44]), "+f"(d[45]), "+f"(d[46]), "+f"(d[47]), "+f"(d[48]), "+f"(d[49]), "+f"(d[50]), "+f"(d[51]), "+f"(d[52]), "+f"(d[53]), "+f"(d[54]), "+f"(d[55]), "+f"(d[56]), "+f"(d[57]), "+f"(d[58]), "+f"(d[59]), "+f"(d[60]), "+f"(d[61]), "+f"(d[62]), "+f"(d[63]), "+f"(d[64]), "+f"(d[65]), "+f"(d[66]), "+f"(d[67]), "+f"(d[68]), "+f"(d[69]), "+f"(d[70]), "+f"(d[71]), "+f"(d[72]), "+f"(d[73]), "+f"(d[74]), "+f"(d[75]), "+f"(d[76]), "+f"(d[77]), "+f"(d[78]), "+f"(d[79]), "+f"(d[80]), "+f"(d[81]), "+f"(d[82]), "+f"(d[83]), "+f"(d[84]), "+f"(d[85]), "+f"(d[86]), "+f"(d[87]), "+f"(d[88]), "+f"(d[89]), "+f"(d[90]), "+f"(d[91]), "+f"(d[92]), "+f"(d[93]), "+f"(d[94]), "+f"(d[95]), "+f"(d[96]), "+f"(d[97]), "+f"(d[98]), "+f"(d[99]), "+f"(d[100]), "+f"(d[101]), "+f"(d[102]), "+f"(d[103]), "+f"(d[104]), "+f"(d[105]), "+f"(d[106]), "+f"(d[107]), "+f"(d[108]), "+f"(d[109]), "+f"(d[110]), "+f"(d[111]), "+f"(d[112]), "+f"(d[113]), "+f"(d[114]), "+f"(d[115]), "+f"(d[116]), "+f"(d[117]), "+f"(d[118]), "+f"(d[119]), "+f"(d[120]), "+f"(d[121]), "+f"(d[122]), "+f"(d[123]), "+f"(d[124]), "+f"(d[125]), "+f"(d[126]), "+f"(d[127])
                 : "l"(da), "l"(db));
}
__device__ __forceinline__ void wgmma_m64n256k16_first(float* d, uint64_t da, uint64_t db) {
    asm volatile("{\n.reg .pred p;\nsetp.ne.b32 p, 0, 0;\n"
                 "wgmma.mma_async.sync.aligned.m64n256k16.f32.bf16.bf16 {%0, %1, %2, %3, %4, %5, %6, %7, %8, %9, %10, %11, %12, %13, %14, %15, %16, %17, %18, %19, %20, %21, %22, %23, %24, %25, %26, %27, %28, %29, %30, %31, %32, %33, %34, %35, %36, %37, %38, %39, %40, %41, %42, %43, %44, %45, %46, %47, %48, %49, %50, %51, %52, %53, %54, %55, %56, %57, %58, %59, %60, %61, %62, %63, %64, %65, %66, %67, %68, %69, %70, %71, %72, %73, %74, %75, %76, %77, %78, %79, %80, %81, %82, %83, %84, %85, %86, %87, %88, %89, %90, %91, %92, %93, %94, %95, %96, %97, %98, %99, %100, %101, %102, %103, %104, %105, %106, %107, %108, %109, %110, %111, %112, %113, %114, %115, %116, %117, %118, %119, %120, %121, %122, %123, %124, %125, %126, %127}, %128, %129, p, 1, 1, 0, 1;\n}\n"
                 : "=f"(d[0]), "=f"(d[1]), "=f"(d[2]), "=f"(d[3]), "=f"(d[4]), "=f"(d[5]), "=f"(d[6]), "=f"(d[7]), "=f"(d[8]), "=f"(d[9]), "=f"(d[10]), "=f"(d[11]), "=f"(d[12]), "=f"(d[13]), "=f"(d[14]), "=f"(d[15]), "=f"(d[16]), "=f"(d[17]), "=f"(d[18]), "=f"(d[19]), "=f"(d[20]), "=f"(d[21]), "=f"(d[22]), "=f"(d[23]), "=f"(d[24]), "=f"(d[25]), "=f"(d[26]), "=f"(d[27]), "=f"(d[28]), "=f"(d[29]), "=f"(d[30]), "=f"(d[31]), "=f"(d[32]), "=f"(d[33]), "=f"(d[34]), "=f"(d[35]), "=f"(d[36]), "=f"(d[37]), "=f"(d[38]), "=f"(d[39]), "=f"(d[40]), "=f"(d[41]), "=f"(d[42]), "=f"(d[43]), "=f"(d[44]), "=f"(d[45]), "=f"(d[46]), "=f"(d[47]), "=f"(d[48]), "=f"(d[49]), "=f"(d[50]), "=f"(d[51]), "=f"(d[52]), "=f"(d[53]), "=f"(d[54]), "=f"(d[55]), "=f"(d[56]), "=f"(d[57]), "=f"(d[58]), "=f"(d[59]), "=f"(d[60]), "=f"(d[61]), "=f"(d[62]), "=f"(d[63]), "=f"(d[64]), "=f"(d[65]), "=f"(d[66]), "=f"(d[67]), "=f"(d[68]), "=f"(d[69]), "=f"(d[70]), "=f"(d[71]), "=f"(d[72]), "=f"(d[73]), "=f"(d[74]), "=f"(d[75]), "=f"(d[76]), "=f"(d[77]), "=f"(d[78]), "=f"(d[79]), "=f"(d[80]), "=f"(d[81]), "=f"(d[82]), "=f"(d[83]), "=f"(d[84]), "=f"(d[85]), "=f"(d[86]), "=f"(d[87]), "=f"(d[88]), "=f"(d[89]), "=f"(d[90]), "=f"(d[91]), "=f"(d[92]), "=f"(d[93]), "=f"(d[94]), "=f"(d[95]), "=f"(d[96]), "=f"(d[97]), "=f"(d[98]), "=f"(d[99]), "=f"(d[100]), "=f"(d[101]), "=f"(d[102]), "=f"(d[103]), "=f"(d[104]), "=f"(d[105]), "=f"(d[106]), "=f"(d[107]), "=f"(d[108]), "=f"(d[109]), "=f"(d[110]), "=f"(d[111]), "=f"(d[112]), "=f"(d[113]), "=f"(d[114]), "=f"(d[115]), "=f"(d[116]), "=f"(d[117]), "=f"(d[118]), "=f"(d[119]), "=f"(d[120]), "=f"(d[121]), "=f"(d[122]), "=f"(d[123]), "=f"(d[124]), "=f"(d[125]), "=f"(d[126]), "=f"(d[127])
                 : "l"(da), "l"(db));
}
__device__ __forceinline__ void wgmma_rs_m64n128k16(float* d, const uint32_t* a, uint64_t db) {
    asm volatile("{\n.reg .pred p;\nsetp.ne.b32 p, 1, 0;\n"
                 "wgmma.mma_async.sync.aligned.m64n128k16.f32.bf16.bf16 {%0, %1, %2, %3, %4, %5, %6, %7, %8, %9, %10, %11, %12, %13, %14, %15, %16, %17, %18, %19, %20, %21, %22, %23, %24, %25, %26, %27, %28, %29, %30, %31, %32, %33, %34, %35, %36, %37, %38, %39, %40, %41, %42, %43, %44, %45, %46, %47, %48, %49, %50, %51, %52, %53, %54, %55, %56, %57, %58, %59, %60, %61, %62, %63}, {%64, %65, %66, %67}, %68, p, 1, 1, 1;\n}\n"
                 : "+f"(d[0]), "+f"(d[1]), "+f"(d[2]), "+f"(d[3]), "+f"(d[4]), "+f"(d[5]), "+f"(d[6]), "+f"(d[7]), "+f"(d[8]), "+f"(d[9]), "+f"(d[10]), "+f"(d[11]), "+f"(d[12]), "+f"(d[13]), "+f"(d[14]), "+f"(d[15]), "+f"(d[16]), "+f"(d[17]), "+f"(d[18]), "+f"(d[19]), "+f"(d[20]), "+f"(d[21]), "+f"(d[22]), "+f"(d[23]), "+f"(d[24]), "+f"(d[25]), "+f"(d[26]), "+f"(d[27]), "+f"(d[28]), "+f"(d[29]), "+f"(d[30]), "+f"(d[31]), "+f"(d[32]), "+f"(d[33]), "+f"(d[34]), "+f"(d[35]), "+f"(d[36]), "+f"(d[37]), "+f"(d[38]), "+f"(d[39]), "+f"(d[40]), "+f"(d[41]), "+f"(d[42]), "+f"(d[43]), "+f"(d[44]), "+f"(d[45]), "+f"(d[46]), "+f"(d[47]), "+f"(d[48]), "+f"(d[49]), "+f"(d[50]), "+f"(d[51]), "+f"(d[52]), "+f"(d[53]), "+f"(d[54]), "+f"(d[55]), "+f"(d[56]), "+f"(d[57]), "+f"(d[58]), "+f"(d[59]), "+f"(d[60]), "+f"(d[61]), "+f"(d[62]), "+f"(d[63])
                 : "r"(a[0]), "r"(a[1]), "r"(a[2]), "r"(a[3]), "l"(db));
}
__device__ __forceinline__ void wgmma_rs_m64n128k16_first(float* d, const uint32_t* a, uint64_t db) {
    asm volatile("{\n.reg .pred p;\nsetp.ne.b32 p, 0, 0;\n"
                 "wgmma.mma_async.sync.aligned.m64n128k16.f32.bf16.bf16 {%0, %1, %2, %3, %4, %5, %6, %7, %8, %9, %10, %11, %12, %13, %14, %15, %16, %17, %18, %19, %20, %21, %22, %23, %24, %25, %26, %27, %28, %29, %30, %31, %32, %33, %34, %35, %36, %37, %38, %39, %40, %41, %42, %43, %44, %45, %46, %47, %48, %49, %50, %51, %52, %53, %54, %55, %56, %57, %58, %59, %60, %61, %62, %63}, {%64, %65, %66, %67}, %68, p, 1, 1, 1;\n}\n"
                 : "=f"(d[0]), "=f"(d[1]), "=f"(d[2]), "=f"(d[3]), "=f"(d[4]), "=f"(d[5]), "=f"(d[6]), "=f"(d[7]), "=f"(d[8]), "=f"(d[9]), "=f"(d[10]), "=f"(d[11]), "=f"(d[12]), "=f"(d[13]), "=f"(d[14]), "=f"(d[15]), "=f"(d[16]), "=f"(d[17]), "=f"(d[18]), "=f"(d[19]), "=f"(d[20]), "=f"(d[21]), "=f"(d[22]), "=f"(d[23]), "=f"(d[24]), "=f"(d[25]), "=f"(d[26]), "=f"(d[27]), "=f"(d[28]), "=f"(d[29]), "=f"(d[30]), "=f"(d[31]), "=f"(d[32]), "=f"(d[33]), "=f"(d[34]), "=f"(d[35]), "=f"(d[36]), "=f"(d[37]), "=f"(d[38]), "=f"(d[39]), "=f"(d[40]), "=f"(d[41]), "=f"(d[42]), "=f"(d[43]), "=f"(d[44]), "=f"(d[45]), "=f"(d[46]), "=f"(d[47]), "=f"(d[48]), "=f"(d[49]), "=f"(d[50]), "=f"(d[51]), "=f"(d[52]), "=f"(d[53]), "=f"(d[54]), "=f"(d[55]), "=f"(d[56]), "=f"(d[57]), "=f"(d[58]), "=f"(d[59]), "=f"(d[60]), "=f"(d[61]), "=f"(d[62]), "=f"(d[63])
                 : "r"(a[0]), "r"(a[1]), "r"(a[2]), "r"(a[3]), "l"(db));
}

struct BulkMaps { CUtensorMap h, h2, wq, wk, wv, wo, kv, lu; };
struct BulkArgs {
    const bf16 *x, *ssmk, *ssmD, *Bk, *Bv, *shiftk;
    bf16* out;
};
enum { T_KV = 0, T_QA, T_CONV, T_ATT, T_POST, T_LN0 };
constexpr int MAXG = 52, SENT = MAXG - 1;
struct Sched { uint32_t chk[MAXG * 4]; uint32_t info[MAXG]; int sbeg[8]; };

constexpr int BK_STAGES = 4, BK_STAGE_BYTES = 49152, TSLOTS = 4;
struct BulkSmemTail {
    unsigned long long full[BK_STAGES], empty[BK_STAGES], tfull[TSLOTS], tempty[TSLOTS], sfull[4], sempty[4];
    int task[TSLOTS];
    uint32_t tab[MAXG * 5];
};
constexpr int BULK_STG = BK_STAGES * BK_STAGE_BYTES;
constexpr int BULK_TAIL = BULK_STG + 32768;
constexpr int BULK_SMEM = BULK_TAIL + (int)sizeof(BulkSmemTail);
static_assert(BULK_SMEM <= 232448, "bulk smem");
#define PACE 0
#define REG_C 224
#define REG_P 56

#define BT(lead, type, l, c, k)
#define TT(k)
#define FT(k)
#define TTV(k, v)
__device__ __forceinline__ void tma_store_2d(const CUtensorMap* map, uint32_t src, int c0, int c1) {
    asm volatile("cp.async.bulk.tensor.2d.global.shared::cta.bulk_group [%0, {%2, %3}], [%1];" ::"l"(map), "r"(src), "r"(c0), "r"(c1) : "memory");
}
__device__ __forceinline__ void bulk_commit() { asm volatile("cp.async.bulk.commit_group;" ::: "memory"); }
template <int N> __device__ __forceinline__ void bulk_wait_read() { asm volatile("cp.async.bulk.wait_group.read %0;" ::"n"(N) : "memory"); }
template <int N> __device__ __forceinline__ void bulk_wait() { asm volatile("cp.async.bulk.wait_group %0;" ::"n"(N) : "memory"); }
__device__ __forceinline__ void mbar_arrive_cluster(uint32_t bar) {
    asm volatile("mbarrier.arrive.shared::cluster.b64 _, [%0];" ::"r"(bar) : "memory");
}
__device__ __forceinline__ void stsm_x4(uint32_t addr, uint32_t r0, uint32_t r1, uint32_t r2, uint32_t r3) {
    asm volatile("stmatrix.sync.aligned.m8n8.x4.shared.b16 [%0], {%1,%2,%3,%4};" ::"r"(addr), "r"(r0), "r"(r1), "r"(r2), "r"(r3) : "memory");
}
__device__ __forceinline__ void mma1688(float* c, uint32_t a0, uint32_t a1, uint32_t b0) {
    asm("mma.sync.aligned.m16n8k8.row.col.f32.bf16.bf16.f32 {%0,%1,%2,%3}, {%4,%5}, {%6}, {%0,%1,%2,%3};"
        : "+f"(c[0]), "+f"(c[1]), "+f"(c[2]), "+f"(c[3]) : "r"(a0), "r"(a1), "r"(b0));
}
__device__ __forceinline__ int ld_relaxed(const int* p) {
    int v;
    asm volatile("ld.relaxed.gpu.global.u32 %0, [%1];" : "=r"(v) : "l"(p) : "memory");
    return v;
}
__device__ __forceinline__ void flag_wait(const int* f, int tgt, int ns) {
    int guard = 0;
    while (ld_relaxed(f) < tgt && ++guard < 4000000) __nanosleep(ns);
}
__device__ __forceinline__ void fence_async() { asm volatile("fence.proxy.async.global;" ::: "memory"); }
__device__ __forceinline__ uint32_t bmul2(uint32_t a, uint32_t b) { uint32_t r; asm("mul.rn.bf16x2 %0, %1, %2;" : "=r"(r) : "r"(a), "r"(b)); return r; }
__device__ __forceinline__ uint32_t bsum2(uint32_t a, uint32_t b) { uint32_t r; asm("add.rn.bf16x2 %0, %1, %2;" : "=r"(r) : "r"(a), "r"(b)); return r; }
__device__ __forceinline__ uint32_t bmax2(uint32_t a, uint32_t b) { uint32_t r; asm("max.bf16x2 %0, %1, %2;" : "=r"(r) : "r"(a), "r"(b)); return r; }
__device__ __forceinline__ uint32_t rscore(float a, float b) {
    const uint32_t u = pack2(a, b);
    return pack2(blo(u) * 0.08838834764831845f, bhi(u) * 0.08838834764831845f);
}
template <int STRIDE> __device__ __forceinline__ void ld5(uint32_t* w, const bf16* p) {
#pragma unroll
    for (int r = 0; r < 5; r++) { const uint2 v = __ldcg(reinterpret_cast<const uint2*>(p + r * STRIDE)); w[2 * r] = v.x; w[2 * r + 1] = v.y; }
}
__device__ __forceinline__ void st5(bf16* p, const uint32_t* w) {
#pragma unroll
    for (int r = 0; r < 5; r++) *reinterpret_cast<uint2*>(p + r * 128) = make_uint2(w[2 * r], w[2 * r + 1]);
}
__device__ __forceinline__ void ln_row(const uint32_t* x, uint32_t* y) {
    float s = 0.f;
#pragma unroll
    for (int i = 0; i < 10; i++) s += blo(x[i]) + bhi(x[i]);
#pragma unroll
    for (int o = 16; o > 0; o >>= 1) s += __shfl_xor_sync(0xffffffffu, s, o);
    const float mean = s * (1.0f / DM);
    float q = 0.f;
#pragma unroll
    for (int i = 0; i < 10; i++) { const float d0 = blo(x[i]) - mean, d1 = bhi(x[i]) - mean; q = fmaf(d0, d0, q); q = fmaf(d1, d1, q); }
#pragma unroll
    for (int o = 16; o > 0; o >>= 1) q += __shfl_xor_sync(0xffffffffu, q, o);
    const uint32_t nm = pack2(-mean, -mean);
    float sq;
    asm("sqrt.approx.ftz.f32 %0, %1;" : "=f"(sq) : "f"(rbf(rbf(q * (1.0f / DM)) + 1e-5f)));
    const float rd = rcpf(rbf(sq));
#pragma unroll
    for (int i = 0; i < 10; i++) { const uint32_t d = bsum2(x[i], nm); y[i] = pack2(blo(d) * rd, bhi(d) * rd); }
}
__device__ __forceinline__ void red_add8(uint4* p, uint32_t a, uint32_t b, uint32_t c, uint32_t d) {
    asm volatile("red.relaxed.gpu.global.add.noftz.v4.bf16x2 [%0], {%1,%2,%3,%4};" ::"l"(p), "r"(a), "r"(b), "r"(c), "r"(d) : "memory");
}
__device__ __forceinline__ void part_sum(const uint4& v, const uint4& w, int lane, uint32_t& x0, uint32_t& x1) {
    float t[8];
    t[0] = blo(v.x) + blo(w.x); t[1] = bhi(v.x) + bhi(w.x); t[2] = blo(v.y) + blo(w.y); t[3] = bhi(v.y) + bhi(w.y);
    t[4] = blo(v.z) + blo(w.z); t[5] = bhi(v.z) + bhi(w.z); t[6] = blo(v.w) + blo(w.w); t[7] = bhi(v.w) + bhi(w.w);
#pragma unroll
    for (int i = 0; i < 4; i++) t[i] = (lane < 16 ? t[i] : t[4 + i]) + __shfl_xor_sync(0xffffffffu, lane < 16 ? t[4 + i] : t[i], 16);
    const uint32_t r0 = pack2(t[0], t[1]), r1 = pack2(t[2], t[3]);
    const uint32_t ex = __shfl_xor_sync(0xffffffffu, (lane & 1) ? r0 : r1, 1);
    x0 = (lane & 1) ? ex : r0; x1 = (lane & 1) ? r1 : ex;
}
__device__ __forceinline__ void post_row(int l, int row, int lane, const bf16* xin, bf16* xout) {
    uint32_t x[10], y[10], n[10];
    const int cl = (lane & 12) * 8 + (lane >> 4) * 16 + (lane & 1) * 8 + (lane & 2) * 2;
    uint4* pp = reinterpret_cast<uint4*>(g_part + (size_t)(l * PROWS + (row & (PROWS - 1))) * (PG * DM)) + (lane & 15) + (lane >> 4) * 80;
    int* f = FLG(F_OP + l * NCHK + (row >> 7));
    flag_wait(FLG(F_CONV + (row >> 10)), CONV_TGT, 200);
    ld5<128>(x, xin + (size_t)row * DM + cl);
    flag_wait(f + 4, OP_TGT, POST_NS);
    {
        uint4 v[10];
#pragma unroll
        for (int i = 0; i < 10; i++) v[i] = __ldcg(pp + (i >> 1) * 16 + (i & 1) * 160);
#pragma unroll
        for (int r = 0; r < 5; r++) {
            uint32_t s0, s1;
            part_sum(v[2 * r], v[2 * r + 1], lane, s0, s1);
            if (r == 1) ld5<16 * S_LEN * 8>(y, g_Y + ((size_t)(cl >> 3) * S_LEN + (row ^ ((row >> 6) & 7))) * 8 + (cl & 4));
            x[2 * r] = bsum2(x[2 * r], s0); x[2 * r + 1] = bsum2(x[2 * r + 1], s1);
        }
    }
    ln_row(x, n);
#pragma unroll
    for (int i = 0; i < 10; i++) x[i] = bsum2(x[i], bmul2(n[i], y[i]));
    if (l == 0) {
        ln_row(x, n);
        st5(g_h[1] + (size_t)row * DM + cl, n);
        __syncwarp();
        if (lane == 0) red_release(FLG(F_H + NCHK + (row >> 7)), 1);
    }
#pragma unroll
    for (int i = 0; i < 10; i++) pp[(i >> 1) * 16 + (i & 1) * 160] = make_uint4(0, 0, 0, 0);
    st5(xout + (size_t)row * DM + cl, x);
    __syncwarp();
    if (l && lane == 0) red_release(f + 5, 1);
}
__device__ __forceinline__ void u_unit(const bf16* Bk, const bf16* Bv, const bf16* shiftk, int unit, int lane) {
    const int t0 = (unit / 10) * 16, cp = (unit % 10) * 32 + lane;
    uint32_t kk[19], vv[16];
    const uint32_t* pk = reinterpret_cast<const uint32_t*>(Bk + (size_t)t0 * DM) + cp;
    const uint32_t* pv = reinterpret_cast<const uint32_t*>(Bv + (size_t)t0 * DM) + cp;
#pragma unroll
    for (int i = 0; i < 19; i++) kk[i] = (i >= 3 || t0 > 0) ? __ldg(pk + (i - 3) * (DM / 2)) : 0u;
#pragma unroll
    for (int i = 0; i < 16; i++) vv[i] = __ldg(pv + i * (DM / 2));
    const uint4 sh0 = __ldg(reinterpret_cast<const uint4*>(shiftk + cp * 8));
    const uint32_t s0 = __byte_perm(sh0.x, sh0.z, 0x5410), s1 = __byte_perm(sh0.x, sh0.z, 0x7632), s2 = __byte_perm(sh0.y, sh0.w, 0x5410), s3 = __byte_perm(sh0.y, sh0.w, 0x7632);
#pragma unroll
    for (int t = 0; t < 16; t++)
        vv[t] = bmul2(bsum2(bsum2(bsum2(bmul2(kk[t], s3), bmul2(kk[t + 1], s2)), bmul2(kk[t + 2], s1)), bmul2(kk[t + 3], s0)), vv[t]);
    uint4* d = reinterpret_cast<uint4*>(g_U + (size_t)(cp * 2) * S_LEN + (t0 ^ 48));
#pragma unroll
    for (int c = 0; c < 2; c++) {
        const uint32_t sel = c ? 0x7632 : 0x5410;
#pragma unroll
        for (int hh = 0; hh < 2; hh++)
            d[c * (S_LEN / 8) + hh] = make_uint4(__byte_perm(vv[15 - hh * 8], vv[14 - hh * 8], sel), __byte_perm(vv[13 - hh * 8], vv[12 - hh * 8], sel),
                                                 __byte_perm(vv[11 - hh * 8], vv[10 - hh * 8], sel), __byte_perm(vv[9 - hh * 8], vv[8 - hh * 8], sel));
    }
}
constexpr int CV_EP = 4224;
template <class F> __device__ __forceinline__ void conv_unit(uint32_t ub, uint32_t e0, uint32_t e1, uint32_t zrow, uint32_t yt, float Dv, int m, int lane, F&& nearly_done) {
    const int g = lane >> 2, tq = lane & 3;
    asm volatile("st.shared.u32 [%0], %1;" ::"r"(e0 + lane * 4), "r"(0) : "memory");
    asm volatile("st.shared.u32 [%0], %1;" ::"r"(zrow + lane * 4), "r"(0) : "memory");
    __syncwarp();
    for (int i = lane; i < CV_EP / 16; i += 32) {
        const uint4 v = lds128(e0 + i * 16);
        const uint32_t nx = i + 1 < CV_EP / 16 ? lds32(e0 + i * 16 + 16) : 0u;
        sts128(e1 + i * 16, __byte_perm(v.x, v.y, 0x5432), __byte_perm(v.y, v.z, 0x5432), __byte_perm(v.z, v.w, 0x5432), __byte_perm(v.w, nx, 0x5432));
    }
    __syncwarp();
    float acc[8][4];
#pragma unroll
    for (int n = 0; n < 8; n++)
#pragma unroll
        for (int i = 0; i < 4; i++) acc[n][i] = 0.f;
    uint32_t wb = (g & 1) ? e0 + (1 + g + 2 * tq) * 2 : e1 + (g + 2 * tq) * 2;
    uint32_t W[16], a[4][4], an[4][4];
    int row = m * 16 + (lane & 15);
    auto lda = [&](uint32_t (*d)[4]) {
        const uint32_t x = row < 0 ? zrow : ub + row * 128 + (((lane >> 4) ^ (row & 7)) << 4);
#pragma unroll
        for (int ks = 0; ks < 4; ks++) ldsm_x4(d[ks][0], d[ks][1], d[ks][2], d[ks][3], x ^ (ks << 5));
        row--;
    };
#pragma unroll
    for (int i = 0; i < 16; i++) W[i] = lds32(wb + i * 16);
    lda(a);
    const int nD = m == 0 ? 16 : 32;
#pragma unroll 2
    for (int D = 0; D < nD; D++) {
        uint32_t Wn[8];
        wb += 128;
        if (D == nD - 6) nearly_done();
        lda(an);
#pragma unroll
        for (int i = 0; i < 8; i++) Wn[i] = lds32(wb + 128 + i * 16);
#pragma unroll
        for (int ks = 0; ks < 4; ks++)
#pragma unroll
            for (int n = 0; n < 8; n++) mma16816(acc[n], a[ks][0], a[ks][1], a[ks][2], a[ks][3], W[2 * ks + n], W[2 * ks + n + 1]);
#pragma unroll
        for (int i = 0; i < 8; i++) { W[i] = W[i + 8]; W[i + 8] = Wn[i]; }
#pragma unroll
        for (int ks = 0; ks < 4; ks++)
#pragma unroll
            for (int i = 0; i < 4; i++) a[ks][i] = an[ks][i];
    }
#pragma unroll
    for (int n = 0; n < 8; n++)
#pragma unroll
        for (int r = 0; r < 2; r++) {
            const int a_ = g + r * 8, b_ = n * 8 + tq * 2;
            const int ar = m * 16 + a_, p = 62 - b_;
            const uint32_t kv = lds32(ub + ar * 128 + (((p >> 3) ^ (ar & 7)) << 4) + (p & 7) * 2);
            const float y0 = rbf(acc[n][2 * r]) + rbf(bhi(kv) * Dv), y1 = rbf(acc[n][2 * r + 1]) + rbf(blo(kv) * Dv);
            const uint32_t pk = pack2(y0, y1);
            asm volatile("st.shared.u16 [%0], %1;" ::"r"(yt + ((a_ * 64 + b_) ^ g) * 16), "h"((unsigned short)(pk & 0xffff)) : "memory");
            asm volatile("st.shared.u16 [%0], %1;" ::"r"(yt + ((a_ * 64 + b_ + 1) ^ g) * 16), "h"((unsigned short)(pk >> 16)) : "memory");
        }
}

__global__ void __launch_bounds__(384, 1) bulk_kernel(const __grid_constant__ BulkMaps M, const __grid_constant__ BulkArgs A,
                                                      const __grid_constant__ Sched SC) {
    extern __shared__ __align__(1024) unsigned char smem_raw[];
    const uint32_t sb0 = smem_u32(smem_raw);
    const uint32_t full0 = sb0 + BULK_TAIL, empty0 = full0 + 32, tfull0 = full0 + 64, tempty0 = full0 + 96, sfull = full0 + 128, sempty = full0 + 160,
                   task0 = full0 + 192, tab0 = full0 + 208;
    const int tid = threadIdx.x, wid = __shfl_sync(0xffffffffu, tid >> 5, 0), lane = tid & 31;
    const int rank = blockIdx.x & 1;
    if (tid == 0) {
        for (int i = 0; i < BK_STAGES; i++) { mbar_init(full0 + 8 * i, 1); mbar_init(empty0 + 8 * i, 4); }
        for (int i = 0; i < TSLOTS; i++) { mbar_init(tfull0 + 8 * i, 1); mbar_init(tempty0 + 8 * i, 19); }
        for (int i = 0; i < 4; i++) { mbar_init(sfull + 8 * i, 8); mbar_init(sempty + 8 * i, 1); }
        asm volatile("fence.mbarrier_init.release.cluster;" ::: "memory");
        if (rank == 1) for (int i = 0; i < TSLOTS; i++) mbar_expect_tx(tfull0 + 8 * i, 4);
        BT(true, T_LN0, 0, 0, 0);
    }
    if (tid < MAXG * 5) asm volatile("st.shared.u32 [%0], %1;" ::"r"(tab0 + tid * 4), "r"(SC.chk[tid]) : "memory");
    cluster_sync_all();
    uint32_t tc = 0, it = 0;
    if (wid < 4) {
        asm volatile("setmaxnreg.dec.sync.aligned.u32 %0;" ::"n"(REG_P));
        if (wid == 0) {
            int head = SC.sbeg[lane >> 3];
            const int hend = SC.sbeg[(lane >> 3) + 1];
            uint32_t chk = 0; int pv = (blockIdx.x >> 1) & 31, grp = (SC.sbeg[3] + (blockIdx.x >> 6)) << 2 | 3, ncode = 0, code = 3 << 6 | 2, guard = 0;
            auto acquire = [&](uint32_t bytes) -> uint32_t {
                const uint32_t s = it & 3;
                mwait(empty0 + 8 * s, ((it >> 2) & 1) ^ 1);
                it++;
                expect_tx1(full0 + 8 * s, bytes);
                return s;
            };
            auto uwait = [&](const int* f, int tgt) {
                int g2 = 0;
                while ((int)UNI(ld_relaxed(f)) < tgt && ++g2 < 4000000) __nanosleep(32);
                fence_async();
            };
#pragma unroll 1
            while (true) {
                const int type = (code >> 6) & 3;
                const int iend = type == T_KV ? 10 : (type == T_QA ? 24 : 31);
                const int jj = code & 63, g0 = (jj & 15) * 4, lc = (code >> 9) & 31;
                const bool lm = (code >> 8) & 1;
                const CUtensorMap* mb = type == T_QA ? &M.wq : (jj < 16 ? &M.wk : &M.wv);
                bool have = false, ok = (code >> 14) & 1;
                int imem = 16;
#pragma unroll 1
                for (int i = type < T_CONV ? 0 : (type == T_CONV ? 24 : 28 + jj); i < iend; i++) {
                    const int sd = (type < T_CONV ? SPLAN : 0x1230) >> 4 * min(iend - i, 7) & 15;
                    if (rank == 0 && sd) {
                        if (sd == 1) {
                            if (type == T_CONV) mwait(empty0 + 8 * (it & 3), ((it >> 2) & 1) ^ 1);
                            const int gi = head + ((lane >> 2) & 1);
                            chk = lds32(tab0 + ((gi < hend ? gi : SENT) * 4 + (lane & 3)) * 4);
                            pv = ld_relaxed(g_flags + (chk & 0xffff));
                        } else if (sd == 2) {
                            const int tgt = (int)(chk >> 16);
                            const uint32_t b = (__ballot_sync(0xffffffffu, (lane & 3) == 0 ? pv < tgt : pv >= tgt) >> (lane & 24)) & 0xff;
                            const uint32_t cand = (b & 1) ? b & 15 : b >> 4;
                            head += (b & 1) ? 0 : ((b & 16) ? 1 : 2);
                            if (head > hend || guard > 4000000) head = hend;
                            const uint32_t req = lane >= 24 ? 1 : 15;
                            grp = (int)__reduce_min_sync(0xffffffffu, (cand & req) == req ? ((uint32_t)head << 2 | (cand ^ req) >> 2 | ((cand ^ req) & 2 ? 0 : 256)) : (head < hend ? 1000u : 1004u));
                            if (grp < 1000) grp &= 255;
                            if (grp < 1000) asm volatile("{\n.reg .pred p;\nsetp.eq.u32 p, %2, 0;\n@p atom.relaxed.gpu.global.inc.u32 %0, [%1], 0x7fffffff;\n}" : "+r"(pv) : "l"(FLG(F_CNT + (grp >> 2))), "r"(lane) : "memory");
                        } else {
                            if (grp < 1000) {
                                const int tk = (int)UNI(pv);
                                have = tk < (int)(UNI(lds32(tab0 + (grp >> 2) * 16)) >> 16);
                                ncode = (int)UNI(lds32(tab0 + MAXG * 16 + (grp & ~3))) | (grp & 3) << 19 | tk;
                            } else if (grp == 1004) { have = true; ncode = -1; }
                            if (have) {
                                const uint32_t o = (tc & 3) * 4;
                                mwait(tempty0 + 2 * o, ((tc >> 2) & 1) ^ 1);
                                asm volatile(ELECT "st.shared.u32 [%0], %1;\n@p mbarrier.arrive.shared::cta.b64 _, [%2];\n"
                                             "@p st.async.weak.shared::cluster.mbarrier::complete_tx::bytes.b32 [%3], %1, [%4];\n}"
                                             ::"r"(task0 + o), "r"(ncode), "r"(tfull0 + 2 * o), "r"(mapa(task0 + o, 1)), "r"(mapa(tfull0 + 2 * o, 1)) : "memory");
                            }
                        }
                    }
                    if (i >= 28) continue;
                    if (i == 8 && type == T_QA) pv = ld_relaxed(FLG((lane & 1 ? F_MEM : F_KV) + lc));
                    if (i == 10) {
                        const uint32_t b = __ballot_sync(0xffffffffu, pv >= (lane & 1 ? MEM_TGT : KV_TGT));
                        if (b & 2) imem = 13;
                        if (!(b & 1)) uwait(FLG(F_KV + lc), KV_TGT);
                        fence_async();
                    }
                    const uint32_t s = acquire(i < 12 ? 49152 : (i == 24 || i == 27 ? 0 : 32768));
                    const uint32_t sa = sb0 + s * BK_STAGE_BYTES, fb = full0 + 8 * s;
                    if (i == 0) TT(3);
                    if (i < 10) {
                        if (lm) {
                            tma_load_3d(sa + 16384, mb, fb, i * 64, g0);
                            tma_load_3d(sa + 32768, mb, fb, i * 64, g0 + 2);
                        } else tma_load_3d_mc(sa + 16384 + rank * 16384, mb, fb, i * 64, g0 + rank * 2);
                        int d = 0;
                        if (!ok) {
                            d = 1;
                            if (i == 3) {
                                uwait(FLG(F_H + lc), H_TGT);
                                ok = true;
                                d = -3;
                                TT(4);
                            }
                        }
#pragma unroll 1
                        for (; d <= 0; d++) {
                            const uint32_t s2 = (s + d) & 3;
                            if (lm) tma_load_2d_mc(sb0 + s2 * BK_STAGE_BYTES + rank * 8192, &M.h, full0 + 8 * s2, (i + d) * 64, lc * 128 + rank * 64);
                            else tma_load_2d(sb0 + s2 * BK_STAGE_BYTES, &M.h2, full0 + 8 * s2, (i + d) * 64, lc * 128);
                        }
                    } else if (i < 13) {
#pragma unroll 1
                        for (int k = 0, bx = (i - 10) * 3; k < 3 && bx < 8; k++, bx++)
                            tma_load_2d(sa + k * 16384, &M.kv, fb, (g0 + (bx & 3)) * 64, (bx >> 2) * S_LEN + (lc & 15) * 128);
                    } else if (i < 24) {
                        const int cn = ((i - 14) >> 1) * 128, ck = g0 * 64 + (i & 1) * 128;
                        if (i > 13) {
                            if (lm) { tma_load_2d(sa, &M.wo, fb, cn, ck); tma_load_2d(sa + 16384, &M.wo, fb, cn + 64, ck); }
                            else tma_load_2d_mc(sa + rank * 16384, &M.wo, fb, cn + rank * 64, ck);
                        }
                        if (i == imem) {
                            TT(5);
                            if (i == 16) uwait(FLG(F_MEM + lc), MEM_TGT);
                            const uint32_t s2 = (s + (i >> 4)) & 3;
#pragma unroll 1
                            for (int k = 0; k < 4; k++)
                                bulk_load(sb0 + s2 * BK_STAGE_BYTES + k * 8192, g_kvf + (size_t)((lc * CSEG + k) * NH + jj * 2) * 256, 8192, full0 + 8 * s2);
                            TT(6);
                        }
                    } else if (i == 25) {
                        tma_load_2d(sa, &M.lu, fb, 0, (2 * jj + rank) * 256);
                    } else if (i == 26) {
#pragma unroll 1
                        for (int k = 0; k < 8; k++)
                            bulk_load(sa + k * CV_EP + 128, A.ssmk + (size_t)((2 * jj + rank) * 8 + k) * S_LEN, 4096, fb);
                    }
                }
                if (type != 3) TT(7);
                if (rank == 0) {
                    if (!have) {
                        if (type == 3) { guard++; __nanosleep(64); }
                        code = 3 << 6;
                        continue;
                    }
                } else {
                    const uint32_t o = (tc & 3) * 4;
                    mwait(tfull0 + 2 * o, (tc >> 2) & 1);
                    ncode = (int)UNI(lds32(task0 + o));
                    asm volatile(ELECT "mbarrier.arrive.expect_tx.shared::cta.b64 _, [%0], 4;\n@p mbarrier.arrive.shared::cluster.b64 _, [%1];\n}" ::"r"(tfull0 + 2 * o), "r"(mapa(tempty0 + 2 * o, 0)) : "memory");
                    __syncwarp();
                }
                tc++;
                if (ncode < 0) break;
                TT(0); TTV(15, ncode);
                code = ((ncode & 256) ? (2 * ncode + rank) & 63 : ncode & 63) | (ncode & 0x1c0) | ((ncode >> (rank ? 14 : 9)) & 31) << 9 | ((ncode >> (19 + rank)) & 1) << 14;
                fence_async();
            }
        } else if (wid == 1) {
            if (lane < 8) asm volatile("prefetch.tensormap [%0];" ::"l"(&M.h + lane) : "memory");
            __syncwarp();
            if (lane == 0) {
                uint32_t rc = 0;
                while (true) {
                    mwait(tfull0 + 8 * (tc & 3), (tc >> 2) & 1);
                    const int code = (int)lds32(task0 + 4 * (tc & 3));
                    mbar_arrive_cluster(mapa(tempty0 + 8 * (tc & 3), 0));
                    tc++;
                    if (code < 0) break;
                    const int type = (code >> 6) & 3;
                    const int lc = (code >> (rank ? 14 : 9)) & 31;
                    mwait(sfull + 8 * (rc & 3), (rc >> 2) & 1);
                    if (type == T_CONV) {
                        asm volatile("cp.async.bulk.global.shared::cta.bulk_group [%0], [%1], %2;" ::"l"(g_Y + (size_t)((2 * (code & 63) + rank) * S_LEN + lc * 1024) * 8), "r"(sb0 + BULK_STG), "r"(16384) : "memory");
                        bulk_commit();
                        bulk_wait<0>();
                    }
                    mbar_arrive(sempty + 8 * (rc & 3));
                    rc++;
                    FT(0);
                    red_release(type == T_QA ? FLG(F_OP + lc) + 4 : FLG((type == T_KV ? F_KV : F_CONV) + lc), 1);
                    FT(1);
                    BT(true, type, lc >> 4, lc & 15, 2);
                }
            }
        } else {
            const int nw = 2 * gridDim.x, idx = (wid - 2) * gridDim.x + blockIdx.x;
#pragma unroll 1
            for (int hh = 0; hh < 2; hh++) {
#pragma unroll 1
                for (int u = hh * 640 + idx; u < hh * 640 + 640; u += nw) u_unit(A.Bk, A.Bv, A.shiftk, u, lane);
                __syncwarp();
                if (lane == 0) red_release(FLG(F_U + hh), 1);
                BT(lane == 0, T_LN0, hh, 0, 2);
            }
#pragma unroll 1
            for (int q = 0; q < 2 * (NCHK + PDIST); q++) {
                const int l = q & 1, c = (q >> 1) - l * PDIST;
                if (c < 0 || c >= NCHK) continue;
#pragma unroll 1
                for (int rr = idx; rr < 128; rr += nw) post_row(l, c * 128 + rr, lane, l ? g_x : A.x, l ? A.out : g_x);
                BT(lane == 0, T_POST, l, c, 2);
            }
        }
    } else {
        asm volatile("setmaxnreg.inc.sync.aligned.u32 %0;" ::"n"(REG_C));
        const int cw = (wid >> 2) - 1, warp = wid & 3;
        const uint32_t wst = sb0 + BULK_STG + (cw * 4 + warp) * 4096;
        uint32_t rc = 0;
        int npend = 0;
        bool urgent = false;
        uint32_t oofs = 0;
        uint32_t qf[16][4];
        auto release = [&](int s) { if ((tid & 127) == 0) { mbar_arrive(empty0 + 8 * s); mbar_arrive_cluster(mapa(empty0 + 8 * s, rank ^ 1)); } };
        auto next = [&]() -> int { const int s = it & 3; mwait(full0 + 8 * s, (it >> 2) & 1); it++; return s; };
        auto wgbar = [&]() { if (cw == 0) named_bar(2, 128); else named_bar(3, 128); };
        auto handoff = [&]() {
            mwait(sempty + 8 * (rc & 3), ((rc >> 2) & 1) ^ 1);
            asm volatile(ELECT "mbarrier.arrive.shared::cta.b64 _, [%0];\n}" ::"r"(sfull + 8 * (rc & 3)) : "memory");
            rc++;
        };
        auto stg_free = [&]() { mwait(sempty + 8 * ((rc - 1) & 3), ((rc - 1) >> 2) & 1); };
        auto round_q = [&]() {
            if (npend > 4) {
                uint4* d = reinterpret_cast<uint4*>(g_part) + oofs;
                if (npend == 6) {
#pragma unroll
                    for (int i = 0; i < 4; i++) red_add8(d + (i >> 1) * 4 + (i & 1) * (8 * PG * DM / 8), qf[i][0], qf[i][1], qf[i][2], qf[i][3]);
                    npend = 5;
                } else {
#pragma unroll
                    for (int i = 4; i < 8; i++) red_add8(d + (i >> 1) * 4 + (i & 1) * (8 * PG * DM / 8), qf[i][0], qf[i][1], qf[i][2], qf[i][3]);
                    npend = 0;
                    handoff();
                }
                return;
            }
            const uint32_t sst = wst + (lane & 15) * 128 + (((lane >> 4) ^ (lane & 7)) << 4) + (npend & 1) * 2048;
#pragma unroll
            for (int q = 0; q < 4; q++)
                if (npend == 4 - q) {
#pragma unroll
                    for (int i = 0; i < 4; i++) stsm_x4(sst ^ (i << 5), qf[q * 4 + i][0], qf[q * 4 + i][1], qf[q * 4 + i][2], qf[q * 4 + i][3]);
                }
            __syncwarp();
            uint4* d = reinterpret_cast<uint4*>(&g_kv[0][0]) + oofs;
            const uint32_t src = wst + (lane >> 3) * 128 + (((lane & 7) ^ (lane >> 3)) << 4) + (npend & 1) * 2048;
#pragma unroll
            for (int i = 0; i < 4; i++) d[i * (4 * HD / 8)] = lds128((src + i * 512) ^ ((i & 1) << 6));
            oofs += 8;
            if (--npend == 0) handoff();
        };
        auto round_a = [&](const float* a, int hh) {
            uint4* d = reinterpret_cast<uint4*>(g_part) + oofs;
#pragma unroll
            for (int i = hh * 4; i < hh * 4 + 4; i++) {
                const float* b = a + (i >> 1) * 16 + (i & 1) * 2;
                red_add8(d + (i >> 1) * 4 + (i & 1) * (8 * PG * DM / 8), pack2(b[0], b[1]), pack2(b[4], b[5]), pack2(b[8], b[9]), pack2(b[12], b[13]));
            }
            if (hh) oofs += 16;
        };
        while (true) {
            tc++; TT(0); tc--;
            int code;
            while (true) {
                if (npend == 0) mwait(tfull0 + 8 * (tc & 3), (tc >> 2) & 1);
                if (npend == 0 || UNI(mtest(tfull0 + 8 * (tc & 3), (tc >> 2) & 1))) {
                    code = (int)UNI(lds32(task0 + 4 * (tc & 3)));
                    if (npend == 0 || ((code & 0x80) == 0 && !urgent && UNI(mtest(full0 + 8 * (it & 3), (it >> 2) & 1)))) break;
                }
                round_q();
            }
            if (lane == 0) mbar_arrive_cluster(mapa(tempty0 + 8 * (tc & 3), 0));
            tc++;
            TT(2);
            if (code < 0) break;
            const int type = (code >> 6) & 3;
            TTV(15, code);
#define BTC(type, k)
            if (type == T_CONV) {
                const int m = (code >> 9) & 1;
                BT((tid & 127) == 0, T_CONV, 0, m, 0);
                const int u = 2 * (code & 63) + rank, ch = cw * 4 + warp;
                int lane = tid & 31;
                asm volatile("" : "+r"(lane));
                const float Dv = bf2f(A.ssmD[u * 8 + ch]);
                const int sd = next(), s0 = next(), s1 = next(), s2 = next();
                TT(3);
                const uint32_t e1 = sb0 + s2 * BK_STAGE_BYTES;
                conv_unit(sb0 + s0 * BK_STAGE_BYTES + ch * 4096, sb0 + s1 * BK_STAGE_BYTES + ch * CV_EP, e1 + 64 + ch * CV_EP, e1 + 40960 + ch * 128, sb0 + BULK_STG + ch * 2, Dv, m, lane,
                          [&]() { release(sd); stg_free(); });
                asm volatile("fence.proxy.async.shared::cta;" ::: "memory");
                __syncwarp();
                handoff();
                TT(5);
                wgbar();
                release(s0); release(s1); release(s2);
                __syncwarp();
#pragma unroll
                for (int i = 0; i < 64; i++) qf[i >> 2][i & 3] = 0;
                continue;
            }
            float acc[128];
            {
                int s = next();
                TT(3); BTC(type, 0); BTC(type, 1);
                uint32_t sa = sb0 + s * BK_STAGE_BYTES + cw * 8192, sb = sb0 + s * BK_STAGE_BYTES + 16384;
                wg_fence();
                wgmma_m64n256k16_first(acc, make_desc(sa, 16, 1024), make_desc(sb, 8192, 1024));
#pragma unroll 1
                for (int kb = 0;;) {
#pragma unroll
                    for (int k = 1; k < 4; k++) wgmma_m64n256k16(acc, make_desc(sa + k * 32, 16, 1024), make_desc(sb + k * 2048, 8192, 1024));
                    wg_commit();
                    if (npend) round_q();
                    if (kb) { wg_wait<1>(); release((s - 1) & 3); }
                    if (++kb == 10) break;
                    s = next();
                    sa = sb0 + s * BK_STAGE_BYTES + cw * 8192; sb = sb0 + s * BK_STAGE_BYTES + 16384;
                    wg_fence();
                    wgmma_m64n256k16(acc, make_desc(sa, 16, 1024), make_desc(sb, 8192, 1024));
                }
            }
            wg_wait<0>();
            TT(4);
            release((it - 1) & 3);
            stg_free();
#pragma unroll
            for (int i = 0; i < 16; i++)
#pragma unroll
                for (int e = 0; e < 4; e++) qf[i][e] = pack2(acc[i * 8 + e * 2], acc[i * 8 + e * 2 + 1]);
            {
                const int cd = (int)lds32(task0 + 4 * ((tc - 1) & 3)), lc = (cd >> (rank ? 14 : 9)) & 31, jj = (cd & 256) ? (2 * cd + rank) & 63 : cd & 63;
                const int r0 = cw * 64 + warp * 16;
                if (type == T_KV) {
                    oofs = ((jj >> 4) * S_LEN + (lc & 15) * 128 + r0 + (lane >> 3)) * (HD / 8) + (jj & 15) * 32 + (lane & 7);
                    npend = 4;
                    urgent = URGENT && (lc < 2 || lc >= 16);
                    continue;
                }
                oofs = (((lc >> 4) * PRING + (lc & (PRING - 1))) * 128 + r0 + (lane >> 2)) * (PG * DM / 8) + (jj & (PG - 1)) * (DM / 8) + (lane & 3);
            }
            const float cs = 1.4426950408889634f;
            int lane = tid & 31;
            asm volatile("" : "+r"(lane));
            const int g = lane >> 2, tq = lane & 3;
            const int sg = cw * 2 + (warp >> 1), hs = warp & 1;
            float mt[2][2], sum[2][2];
            {
                const int x0 = next(), x1 = next();
                TT(5);
                float s[2][4][4];
#pragma unroll
                for (int hd = 0; hd < 2; hd++)
#pragma unroll
                    for (int n = 0; n < 4; n++)
#pragma unroll
                        for (int e = 0; e < 4; e++) s[hd][n][e] = 0.f;
                const uint32_t krow = (sg * 32 + (lane & 7) + (lane >> 4) * 8) * 128 + ((((lane >> 3) & 1) ^ (lane & 7)) << 4);
#pragma unroll
                for (int ii = 0; ii < 16; ii++) {
                    const int i = (ii >> 1) + (ii & 1) * 8;
                    const uint32_t kb = sb0 + (i < 12 ? x0 * BK_STAGE_BYTES + (i >> 2) * 16384 : x1 * BK_STAGE_BYTES) + (krow ^ ((i & 3) << 5));
                    const uint4 k0 = ldsm4(kb), k1 = ldsm4(kb + 2048);
                    mma16816(s[i >> 3][0], qf[i][0], qf[i][1], qf[i][2], qf[i][3], k0.x, k0.y);
                    mma16816(s[i >> 3][1], qf[i][0], qf[i][1], qf[i][2], qf[i][3], k0.z, k0.w);
                    mma16816(s[i >> 3][2], qf[i][0], qf[i][1], qf[i][2], qf[i][3], k1.x, k1.y);
                    mma16816(s[i >> 3][3], qf[i][0], qf[i][1], qf[i][2], qf[i][3], k1.z, k1.w);
                }
#pragma unroll
                for (int i = 0; i < 8; i++) sts128(wst + i * 512 + lane * 16, qf[8 + i][0], qf[8 + i][1], qf[8 + i][2], qf[8 + i][3]);
                wgbar();
                release(x0);
                TT(6);
                uint32_t pa[2][4][2];
#pragma unroll
                for (int hd = 0; hd < 2; hd++) {
                    uint32_t mx[2] = {0xff80ff80u, 0xff80ff80u};
#pragma unroll
                    for (int n = 0; n < 4; n++)
#pragma unroll
                        for (int r = 0; r < 2; r++) {
                            const int d = hs * 16 + g + r * 8 - n * 8 - tq * 2;
                            pa[hd][n][r] = rscore(d < 0 ? -INFINITY : s[hd][n][2 * r], d < 1 ? -INFINITY : s[hd][n][2 * r + 1]);
                            mx[r] = bmax2(mx[r], pa[hd][n][r]);
                        }
#pragma unroll
                    for (int r = 0; r < 2; r++) {
                        mx[r] = bmax2(mx[r], __shfl_xor_sync(0xffffffffu, mx[r], 1));
                        mx[r] = bmax2(mx[r], __shfl_xor_sync(0xffffffffu, mx[r], 2));
                        mt[hd][r] = fmaxf(blo(mx[r]), bhi(mx[r])) * cs;
                        sum[hd][r] = 0.f;
                    }
#pragma unroll
                    for (int n = 0; n < 4; n++)
#pragma unroll
                        for (int r = 0; r < 2; r++) {
                            const float p0 = ex2f(fmaf(blo(pa[hd][n][r]), cs, -mt[hd][r])), p1 = ex2f(fmaf(bhi(pa[hd][n][r]), cs, -mt[hd][r]));
                            sum[hd][r] += p0 + p1;
                            pa[hd][n][r] = pack2(p0, p1);
                        }
                }
                const uint32_t vrow = (sg * 32 + (lane & 15)) * 128 + (((lane >> 4) ^ (lane & 7)) << 4);
                int xv = x1;
#pragma unroll
                for (int hd = 0; hd < 2; hd++) {
                    if (hd == 1) xv = next();
#pragma unroll
                    for (int i = 0; i < 8; i++) {
                        const uint32_t vb = sb0 + xv * BK_STAGE_BYTES + (hd == 0 ? 16384 : 0) + (i >> 2) * 16384 + (vrow ^ ((i & 3) << 5));
                        uint4 v0, v1;
                        ldsm_x4_t(v0.x, v0.y, v0.z, v0.w, vb);
                        ldsm_x4_t(v1.x, v1.y, v1.z, v1.w, vb + 2048);
                        float* o = acc + hd * 64 + i * 8;
#pragma unroll
                        for (int e = 0; e < 8; e++) o[e] = 0.f;
                        mma16816(o, pa[hd][0][0], pa[hd][0][1], pa[hd][1][0], pa[hd][1][1], v0.x, v0.y);
                        mma16816(o + 4, pa[hd][0][0], pa[hd][0][1], pa[hd][1][0], pa[hd][1][1], v0.z, v0.w);
                        mma16816(o, pa[hd][2][0], pa[hd][2][1], pa[hd][3][0], pa[hd][3][1], v1.x, v1.y);
                        mma16816(o + 4, pa[hd][2][0], pa[hd][2][1], pa[hd][3][0], pa[hd][3][1], v1.z, v1.w);
                    }
                    wgbar();
                    release(xv);
                }
            }
            TT(7);
            BTC(T_ATT, 0);
            {
                const int xm = next();
                TT(8);
                BTC(T_ATT, 1);
                const uint32_t mb = sb0 + xm * BK_STAGE_BYTES + sg * 8192 + lane * 16;
                float sm[2][2][4];
#pragma unroll
                for (int i = 0; i < 16; i++) (&sm[0][0][0])[i] = 0.f;
#pragma unroll
                for (int q = 0; q < 4; q++) {
                    const uint4 k0 = lds128(mb + q * 512), k1 = lds128(mb + 4096 + q * 512);
                    const uint4 qa = lds128(wst + q * 1024 + lane * 16), qb = lds128(wst + q * 1024 + 512 + lane * 16);
                    mma16816(sm[0][0], qf[2 * q][0], qf[2 * q][1], qf[2 * q][2], qf[2 * q][3], k0.x, k0.y);
                    mma16816(sm[0][1], qf[2 * q + 1][0], qf[2 * q + 1][1], qf[2 * q + 1][2], qf[2 * q + 1][3], k0.z, k0.w);
                    mmau(sm[1][0], qa, k1.x, k1.y);
                    mmau(sm[1][1], qb, k1.z, k1.w);
                }
                float f[2][2];
                uint32_t pm[2][2];
#pragma unroll
                for (int hd = 0; hd < 2; hd++)
#pragma unroll
                    for (int r = 0; r < 2; r++) {
                        const uint32_t w = rscore(sm[hd][0][2 * r] + sm[hd][1][2 * r], sm[hd][0][2 * r + 1] + sm[hd][1][2 * r + 1]);
                        const float s0 = blo(w) * cs, s1 = bhi(w) * cs;
                        float m = fmaxf(s0, s1);
                        m = fmaxf(m, __shfl_xor_sync(0xffffffffu, m, 1));
                        m = fmaxf(fmaxf(m, __shfl_xor_sync(0xffffffffu, m, 2)), mt[hd][r]);
                        const float a = ex2f(mt[hd][r] - m), p0 = ex2f(s0 - m), p1 = ex2f(s1 - m);
                        float t = fmaf(sum[hd][r], a, p0 + p1);
                        t += __shfl_xor_sync(0xffffffffu, t, 1);
                        t += __shfl_xor_sync(0xffffffffu, t, 2);
                        t = rcpf(t);
                        f[hd][r] = a * t;
                        pm[hd][r] = pack2(p0 * t, p1 * t);
                    }
#pragma unroll
                for (int q = 0; q < 8; q++) {
                    const int hd = q >> 2;
                    const uint4 vm = lds128(mb + hd * 4096 + 2048 + (q & 3) * 512);
                    float* o = acc + q * 16;
#pragma unroll
                    for (int e = 0; e < 16; e++) o[e] *= f[hd][(e >> 1) & 1];
                    mma1688(o, pm[hd][0], pm[hd][1], vm.x);
                    mma1688(o + 4, pm[hd][0], pm[hd][1], vm.y);
                    mma1688(o + 8, pm[hd][0], pm[hd][1], vm.z);
                    mma1688(o + 12, pm[hd][0], pm[hd][1], vm.w);
#pragma unroll
                    for (int e = 0; e < 8; e++) qf[q * 2 + (e >> 2)][e & 3] = pack2(o[2 * e], o[2 * e + 1]);
                }
                wgbar();
                release(xm);
            }
            TT(9);
#pragma unroll
            for (int t = 0; t < 10; t++) {
                const int s = next();
                const uint32_t sb = sb0 + s * BK_STAGE_BYTES;
                float* d = acc + ((t >> 1) & 1) * 64;
                wg_fence();
#pragma unroll
                for (int k = 0; k < 8; k++) {
                    const uint64_t db = make_desc(sb + k * 2048, 16384, 1024);
                    if (k == 0 && !(t & 1)) wgmma_rs_m64n128k16_first(d, qf[k], db);
                    else wgmma_rs_m64n128k16(d, qf[(t & 1) * 8 + k], db);
                }
                wg_commit();
                if (t) {
                    wg_wait<1>();
                    release((s - 1) & 3);
                    if (t > 1) round_a(acc + (((t >> 1) & 1) ^ 1) * 64, t & 1);
                }
            }
            wg_wait<0>();
            release((it - 1) & 3);
            TT(10);
#pragma unroll
            for (int i = 0; i < 32; i++) qf[i >> 2][i & 3] = pack2(acc[(i >> 3) * 16 + (i & 4) / 2 + (i & 3) * 4], acc[(i >> 3) * 16 + (i & 4) / 2 + (i & 3) * 4 + 1]);
            npend = 6;
            urgent = URGENT > 1;
        }
    }
    cluster_sync_all();
}

__global__ void __launch_bounds__(256) reset_kernel(const bf16* x, int g0, int ncl) {
    const int lane = threadIdx.x & 31, row = blockIdx.x * 8 + (threadIdx.x >> 5);
    uint32_t r[10];
    ld5<128>(r, x + (size_t)row * DM + lane * 4);
    if (blockIdx.x == 0)
        for (int i = threadIdx.x; i < NFLAG * 2; i += blockDim.x) reinterpret_cast<uint4*>(FLG(i >> 1))[i & 1] = make_uint4(i == g0 ? min(ncl, 32) : (i == g0 + 2 ? max(ncl - 32, 0) : 0), 0, 0, 0);
    for (int i = blockIdx.x * 256 + threadIdx.x; i < 2 * PROWS * PG * DM / 8; i += S_LEN * 32) reinterpret_cast<uint4*>(g_part)[i] = make_uint4(0, 0, 0, 0);
    ln_row(r, r);
    st5(g_h[0] + (size_t)row * DM + lane * 4, r);
    if (blockIdx.x) return;
}

typedef CUresult (*PFN_encodeTiled)(CUtensorMap*, CUtensorMapDataType, cuuint32_t, void*, const cuuint64_t*, const cuuint64_t*,
                                    const cuuint32_t*, const cuuint32_t*, CUtensorMapInterleave, CUtensorMapSwizzle,
                                    CUtensorMapL2promotion, CUtensorMapFloatOOBfill);
static PFN_encodeTiled get_encode() {
    static PFN_encodeTiled fn = nullptr;
    if (!fn) {
        void* p = nullptr;
        cudaDriverEntryPointQueryResult qr;
        cudaGetDriverEntryPoint("cuTensorMapEncodeTiled", &p, cudaEnableDefault, &qr);
        fn = (PFN_encodeTiled)p;
    }
    return fn;
}
static void make_map(CUtensorMap* m, const void* ptr, uint64_t rows, uint64_t cols, uint32_t box_rows) {
    cuuint64_t dims[2] = {cols, rows};
    cuuint64_t strides[1] = {cols * 2};
    cuuint32_t box[2] = {64u, box_rows};
    cuuint32_t es[2] = {1, 1};
    get_encode()(m, CU_TENSOR_MAP_DATA_TYPE_BFLOAT16, 2, const_cast<void*>(ptr), dims, strides, box, es,
                 CU_TENSOR_MAP_INTERLEAVE_NONE, CU_TENSOR_MAP_SWIZZLE_128B, CU_TENSOR_MAP_L2_PROMOTION_L2_128B,
                 CU_TENSOR_MAP_FLOAT_OOB_FILL_NONE);
}
static void make_map3(CUtensorMap* m, const void* ptr) {
    cuuint64_t dims[3] = {64, DM, HD / 64};
    cuuint64_t strides[2] = {HD * 2, 128};
    cuuint32_t box[3] = {64u, 64u, 2u};
    cuuint32_t es[3] = {1, 1, 1};
    get_encode()(m, CU_TENSOR_MAP_DATA_TYPE_BFLOAT16, 3, const_cast<void*>(ptr), dims, strides, box, es,
                 CU_TENSOR_MAP_INTERLEAVE_NONE, CU_TENSOR_MAP_SWIZZLE_128B, CU_TENSOR_MAP_L2_PROMOTION_L2_128B,
                 CU_TENSOR_MAP_FLOAT_OOB_FILL_NONE);
}
#define QA_PRE0 4
#define KV1_E 1
#define KV1_L 16
#define KV0_X 6
#define CONV0_AT 1
#define CONV1_AT 9
static void build_sched(Sched& S, int naux) {
    int n = 0;
    auto ck = [](int f, int t) { return (uint32_t)(f * 32) | (uint32_t)t << 16; };
    auto add = [&](int lm, int type, int la, int ca, int lb, int cb, int ntask, uint32_t soft) {
        S.info[n] = (uint32_t)(type << 6 | lm << 8 | (la * 16 + ca) << 9 | (lb * 16 + cb) << 14);
        S.chk[n * 4] = ck(F_CNT + n, ntask); S.chk[n * 4 + 1] = soft;
        S.chk[n * 4 + 2] = ck(F_H + la * NCHK + ca, H_TGT); S.chk[n * 4 + 3] = ck(F_H + lb * NCHK + cb, H_TGT);
        n++;
    };
    for (int i = 0; i < MAXG * 4; i++) S.chk[i] = ck(F_ZERO, 0);
    for (int i = 0; i < MAXG; i++) S.info[i] = 0;
    S.sbeg[0] = n;
    for (int i = 0; i < NCHK; i++) {
        add(1, T_KV, 1, i, 1, i, 16, i < KV1_E || i >= KV1_L ? ck(F_OP + i, 14) + 4 : ck(F_H + NCHK + i, KV1_N));
        S.chk[n * 4 - 2] = S.chk[n * 4 - 1] = ck(F_CONV + i / 8, CONV_TGT);
    }
    S.sbeg[1] = n;
    auto addqa = [&]() {
    for (int p = 0; p < NCHK + PDIST; p++) {
        const bool h0 = p < NCHK, h1 = p >= PDIST;
        const int la = h0 ? 0 : 1, ca = h0 ? p : p - PDIST, lb = h1 ? 1 : 0, cb = h1 ? p - PDIST : p;
        const int ta = ca * CSEG + CSEG + la * LAG;
        add(!(h0 && h1), T_QA, la, ca, lb, cb, h0 && h1 ? 16 : 8,
            ck(F_PROG, h1 ? ta - QA_PRE : (ta > QA_PRE0 ? ta - QA_PRE0 : 0)));
        S.info[n - 1] |= 3u << 19;
        S.chk[n * 4 - 2] = h0 && ca >= PRING ? ck(F_H + NCHK + ca - PRING + 1, H_TGT) : ck(F_ZERO, 0);
        S.chk[n * 4 - 1] = !h1 ? ck(F_KV + ca, KV_TGT) : (cb >= PRING ? ck(F_OP + NCHK + cb - PRING, 128) + 5 : ck(F_ZERO, 0));
    }
    };
    auto addkv = [&]() {
    for (int i = 0; i < NCHK; i += 2) add(0, T_KV, 0, i, 0, i + 1, 32, ck(F_PROG, 4 * i > KV0_X + 1 ? 4 * i - KV0_X : 1)), S.chk[n * 4 - 2] = S.chk[n * 4 - 1] = ck(F_ZERO, 0);
    };
    addqa();
    S.sbeg[2] = n;
    for (int m = 0; m < 2; m++) {
        add(0, T_CONV, 0, m, 0, m, 40, ck(F_U + m, naux));
        S.chk[n * 4 - 2] = S.chk[n * 4 - 1] = ck(F_CNT + S.sbeg[2] + 2 + (m ? CONV1_AT : CONV0_AT) / 2, 32);
    }
    S.sbeg[3] = n;
    addkv();
    S.sbeg[4] = n;
}

static void launch_all(void* const* d_in, void* d_out) {
    const bf16* x = (const bf16*)d_in[0];
    const bf16* mem0 = (const bf16*)d_in[1];
    const bf16* Wq = (const bf16*)d_in[2];
    const bf16* Wk = (const bf16*)d_in[3];
    const bf16* Wv = (const bf16*)d_in[4];
    const bf16* Wo = (const bf16*)d_in[5];
    static bool inited = false;
    static int nsm = 132;
    static Sched SC;
    bf16 *p_h, *p_kv, *p_u;
    cudaGetSymbolAddress((void**)&p_h, g_h);
    cudaGetSymbolAddress((void**)&p_kv, g_kv);
    cudaGetSymbolAddress((void**)&p_u, g_U);
    if (!inited) {
        inited = true;
        cudaDeviceGetAttribute(&nsm, cudaDevAttrMultiProcessorCount, 0);
        cudaFuncSetAttribute(chain_kernel, cudaFuncAttributeMaxDynamicSharedMemorySize, (int)sizeof(ChainSmem));
        cudaFuncSetAttribute(chain_kernel, cudaFuncAttributeNonPortableClusterSizeAllowed, 1);
        cudaFuncSetAttribute(bulk_kernel, cudaFuncAttributeMaxDynamicSharedMemorySize, BULK_SMEM);
        build_sched(SC, 2 * ((nsm - 64) & ~1));
    }
    const size_t QS = (size_t)S_LEN * HD;
    BulkMaps M;
    make_map(&M.h, p_h, 2 * S_LEN, DM, 64);
    make_map(&M.h2, p_h, 2 * S_LEN, DM, 128);
    make_map3(&M.wq, Wq);
    make_map3(&M.wk, Wk);
    make_map3(&M.wv, Wv);
    make_map(&M.wo, Wo, HD, DM, 128);
    make_map(&M.kv, p_kv, 2 * S_LEN, HD, 128);
    make_map(&M.lu, p_u, DM * 32, 64, 256);
    BulkArgs BA;
    BA.x = x; BA.out = (bf16*)d_out;
    BA.Bk = (const bf16*)d_in[8]; BA.Bv = (const bf16*)d_in[9]; BA.shiftk = (const bf16*)d_in[10];
    BA.ssmk = (const bf16*)d_in[11]; BA.ssmD = (const bf16*)d_in[12];
    ChainArgs ca;
    for (int l = 0; l < 2; l++) {
        make_map(&ca.tk[l], p_kv, S_LEN, HD, 32);
        make_map(&ca.tv[l], p_kv + QS, S_LEN, HD, 32);
    }
    ca.x = x; ca.mem0 = mem0; ca.Wq = Wq; ca.Wk = Wk; ca.Wv = Wv; ca.Wo = Wo; ca.kv_target = KV_TGT;
    cudaStream_t s = cudaStreamPerThread;
    reset_kernel<<<S_LEN / 8, 256, 0, s>>>(x, 2 * (F_CNT + SC.sbeg[3]), (nsm - 64) / 2);
    {
        cudaLaunchConfig_t cfg = {};
        cfg.gridDim = dim3(64); cfg.blockDim = dim3(CHAIN_THREADS); cfg.dynamicSmemBytes = sizeof(ChainSmem); cfg.stream = s;
        cudaLaunchAttribute at[1];
        at[0].id = cudaLaunchAttributeClusterDimension;
        at[0].val.clusterDim.x = CL; at[0].val.clusterDim.y = 1; at[0].val.clusterDim.z = 1;
        cfg.attrs = at; cfg.numAttrs = 1;
        cudaLaunchKernelEx(&cfg, chain_kernel, ca);
    }
    {
        cudaLaunchConfig_t cfg = {};
        cfg.gridDim = dim3((nsm - 64) & ~1); cfg.blockDim = dim3(384); cfg.dynamicSmemBytes = BULK_SMEM; cfg.stream = s;
        cudaLaunchAttribute at[2];
        at[0].id = cudaLaunchAttributeProgrammaticStreamSerialization;
        at[0].val.programmaticStreamSerializationAllowed = 1;
        at[1].id = cudaLaunchAttributeClusterDimension;
        at[1].val.clusterDim.x = 2; at[1].val.clusterDim.y = 1; at[1].val.clusterDim.z = 1;
        cfg.attrs = at; cfg.numAttrs = 2;
        cudaLaunchKernelEx(&cfg, bulk_kernel, M, BA, SC);
    }
}
}

extern "C" void kernel_launch(void* const* d_in, const int* in_sizes, int n_in, void* d_out, int out_size) {
    (void)in_sizes; (void)n_in; (void)out_size;
    if (ws::usable()) ws::launch_all(d_in, d_out);
    else ni::launch_all(d_in, d_out);
}
```

```cpp
#include <cuda_runtime.h>
#include <cuda_bf16.h>
#include <stdint.h>
#include <cuda.h>

typedef __nv_bfloat16 bf16;
namespace ws {
constexpr int S_LEN = 2048, DM = 640, NH = 32, DH = 128, HD = NH * DH, SEG = 32, NSEG = S_LEN / SEG;

__device__ __forceinline__ float bf2f(bf16 v) { return __bfloat162float(v); }
__device__ __forceinline__ float rbf(float v) { return __bfloat162float(__float2bfloat16_rn(v)); }
__device__ __forceinline__ uint32_t pack2(float a, float b) {
    __nv_bfloat162 t = __floats2bfloat162_rn(a, b);
    return *reinterpret_cast<uint32_t*>(&t);
}
__device__ __forceinline__ float blo(uint32_t v) { return __uint_as_float(v << 16); }
__device__ __forceinline__ float bhi(uint32_t v) { return __uint_as_float(v & 0xffff0000u); }
__device__ __forceinline__ uint32_t badd(uint32_t a, uint32_t b) { uint32_t r; asm("add.rn.bf16x2 %0, %1, %2;" : "=r"(r) : "r"(a), "r"(b)); return r; }
__device__ __forceinline__ uint32_t smem_u32(const void* p) { return (uint32_t)__cvta_generic_to_shared(p); }
__device__ __forceinline__ uint4 ldsm4(uint32_t a) {
    uint4 v;
    asm volatile("ldmatrix.sync.aligned.m8n8.x4.shared.b16 {%0,%1,%2,%3}, [%4];" : "=r"(v.x), "=r"(v.y), "=r"(v.z), "=r"(v.w) : "r"(a));
    return v;
}
__device__ __forceinline__ uint4 ldsm4t(uint32_t a) {
    uint4 v;
    asm volatile("ldmatrix.sync.aligned.m8n8.x4.trans.shared.b16 {%0,%1,%2,%3}, [%4];" : "=r"(v.x), "=r"(v.y), "=r"(v.z), "=r"(v.w) : "r"(a));
    return v;
}
__device__ __forceinline__ void stsm4(uint32_t a, uint32_t r0, uint32_t r1, uint32_t r2, uint32_t r3) {
    asm volatile("stmatrix.sync.aligned.m8n8.x4.shared.b16 [%0], {%1,%2,%3,%4};" ::"r"(a), "r"(r0), "r"(r1), "r"(r2), "r"(r3) : "memory");
}
__device__ __forceinline__ void stsm4t(uint32_t a, uint32_t r0, uint32_t r1, uint32_t r2, uint32_t r3) {
    asm volatile("stmatrix.sync.aligned.m8n8.x4.trans.shared.b16 [%0], {%1,%2,%3,%4};" ::"r"(a), "r"(r0), "r"(r1), "r"(r2), "r"(r3) : "memory");
}
__device__ __forceinline__ void mma16816(float* c, uint32_t a0, uint32_t a1, uint32_t a2, uint32_t a3, uint32_t b0, uint32_t b1) {
    asm("mma.sync.aligned.m16n8k16.row.col.f32.bf16.bf16.f32 {%0,%1,%2,%3}, {%4,%5,%6,%7}, {%8,%9}, {%0,%1,%2,%3};"
        : "+f"(c[0]), "+f"(c[1]), "+f"(c[2]), "+f"(c[3]) : "r"(a0), "r"(a1), "r"(a2), "r"(a3), "r"(b0), "r"(b1));
}
__device__ __forceinline__ void mmav(float* c, uint32_t a0, uint32_t a1, uint32_t a2, uint32_t a3, uint32_t b0, uint32_t b1) {
    asm volatile("mma.sync.aligned.m16n8k16.row.col.f32.bf16.bf16.f32 {%0,%1,%2,%3}, {%4,%5,%6,%7}, {%8,%9}, {%0,%1,%2,%3};"
        : "+f"(c[0]), "+f"(c[1]), "+f"(c[2]), "+f"(c[3]) : "r"(a0), "r"(a1), "r"(a2), "r"(a3), "r"(b0), "r"(b1));
}
__device__ __forceinline__ void mmau(float* c, const uint4& a, uint32_t b0, uint32_t b1) { mma16816(c, a.x, a.y, a.z, a.w, b0, b1); }
__device__ __forceinline__ void mma1688(float* c, uint32_t a0, uint32_t a1, uint32_t b0) {
    asm("mma.sync.aligned.m16n8k8.row.col.f32.bf16.bf16.f32 {%0,%1,%2,%3}, {%4,%5}, {%6}, {%0,%1,%2,%3};"
        : "+f"(c[0]), "+f"(c[1]), "+f"(c[2]), "+f"(c[3]) : "r"(a0), "r"(a1), "r"(b0));
}
__device__ __forceinline__ void mmav8(float* c, uint32_t a0, uint32_t a1, uint32_t b0) {
    asm volatile("mma.sync.aligned.m16n8k8.row.col.f32.bf16.bf16.f32 {%0,%1,%2,%3}, {%4,%5}, {%6}, {%0,%1,%2,%3};"
        : "+f"(c[0]), "+f"(c[1]), "+f"(c[2]), "+f"(c[3]) : "r"(a0), "r"(a1), "r"(b0));
}
__device__ __forceinline__ void cp_async16(uint32_t dst, const void* src) { asm volatile("cp.async.cg.shared.global [%0], [%1], 16;" ::"r"(dst), "l"(src)); }
__device__ __forceinline__ void cp_commit() { asm volatile("cp.async.commit_group;"); }
template <int N> __device__ __forceinline__ void cp_wait() { asm volatile("cp.async.wait_group %0;" ::"n"(N)); }
__device__ __forceinline__ uint4 lds128(uint32_t a) {
    uint4 v;
    asm volatile("ld.shared.v4.u32 {%0,%1,%2,%3}, [%4];" : "=r"(v.x), "=r"(v.y), "=r"(v.z), "=r"(v.w) : "r"(a));
    return v;
}
__device__ __forceinline__ uint2 lds64(uint32_t a) {
    uint2 v;
    asm volatile("ld.shared.v2.u32 {%0,%1}, [%2];" : "=r"(v.x), "=r"(v.y) : "r"(a));
    return v;
}
__device__ __forceinline__ uint32_t lds32(uint32_t a) { uint32_t v; asm volatile("ld.shared.u32 %0, [%1];" : "=r"(v) : "r"(a)); return v; }
__device__ __forceinline__ void sts32(uint32_t a, uint32_t x) { asm volatile("st.shared.u32 [%0], %1;" ::"r"(a), "r"(x) : "memory"); }
__device__ __forceinline__ void sts64(uint32_t a, uint32_t x, uint32_t y) { asm volatile("st.shared.v2.u32 [%0], {%1,%2};" ::"r"(a), "r"(x), "r"(y) : "memory"); }
__device__ __forceinline__ void sts128(uint32_t a, uint32_t x, uint32_t y, uint32_t z, uint32_t w) {
    asm volatile("st.shared.v4.u32 [%0], {%1,%2,%3,%4};" ::"r"(a), "r"(x), "r"(y), "r"(z), "r"(w) : "memory");
}
__device__ __forceinline__ uint4 ld_relaxed_v4(const void* p) {
    uint4 v;
    asm volatile("ld.relaxed.gpu.global.v4.u32 {%0,%1,%2,%3}, [%4];" : "=r"(v.x), "=r"(v.y), "=r"(v.z), "=r"(v.w) : "l"(p) : "memory");
    return v;
}
__device__ __forceinline__ uint2 ld_relaxed_v2(const void* p) {
    uint2 v;
    asm volatile("ld.relaxed.gpu.global.v2.u32 {%0,%1}, [%2];" : "=r"(v.x), "=r"(v.y) : "l"(p) : "memory");
    return v;
}
__device__ __forceinline__ void ld7_relaxed(uint4* x, const void* p) {
    asm volatile("ld.relaxed.gpu.global.v4.u32 {%0,%1,%2,%3}, [%28 + 0];\nld.relaxed.gpu.global.v4.u32 {%4,%5,%6,%7}, [%28 + 512];\nld.relaxed.gpu.global.v4.u32 {%8,%9,%10,%11}, [%28 + 1024];\nld.relaxed.gpu.global.v4.u32 {%12,%13,%14,%15}, [%28 + 1536];\nld.relaxed.gpu.global.v4.u32 {%16,%17,%18,%19}, [%28 + 2048];\nld.relaxed.gpu.global.v4.u32 {%20,%21,%22,%23}, [%28 + 2560];\nld.relaxed.gpu.global.v4.u32 {%24,%25,%26,%27}, [%28 + 3072];\n" : "=r"(x[0].x), "=r"(x[0].y), "=r"(x[0].z), "=r"(x[0].w), "=r"(x[1].x), "=r"(x[1].y), "=r"(x[1].z), "=r"(x[1].w), "=r"(x[2].x), "=r"(x[2].y), "=r"(x[2].z), "=r"(x[2].w), "=r"(x[3].x), "=r"(x[3].y), "=r"(x[3].z), "=r"(x[3].w), "=r"(x[4].x), "=r"(x[4].y), "=r"(x[4].z), "=r"(x[4].w), "=r"(x[5].x), "=r"(x[5].y), "=r"(x[5].z), "=r"(x[5].w), "=r"(x[6].x), "=r"(x[6].y), "=r"(x[6].z), "=r"(x[6].w) : "l"(p) : "memory");
}
__device__ __forceinline__ void ld7_relaxed(uint2* x, const void* p) {
    asm volatile("ld.relaxed.gpu.global.v2.u32 {%0,%1}, [%14 + 0];\nld.relaxed.gpu.global.v2.u32 {%2,%3}, [%14 + 512];\nld.relaxed.gpu.global.v2.u32 {%4,%5}, [%14 + 1024];\nld.relaxed.gpu.global.v2.u32 {%6,%7}, [%14 + 1536];\nld.relaxed.gpu.global.v2.u32 {%8,%9}, [%14 + 2048];\nld.relaxed.gpu.global.v2.u32 {%10,%11}, [%14 + 2560];\nld.relaxed.gpu.global.v2.u32 {%12,%13}, [%14 + 3072];\n" : "=r"(x[0].x), "=r"(x[0].y), "=r"(x[1].x), "=r"(x[1].y), "=r"(x[2].x), "=r"(x[2].y), "=r"(x[3].x), "=r"(x[3].y), "=r"(x[4].x), "=r"(x[4].y), "=r"(x[5].x), "=r"(x[5].y), "=r"(x[6].x), "=r"(x[6].y) : "l"(p) : "memory");
}
__device__ __forceinline__ void st_relaxed_v4(void* p, uint32_t a, uint32_t b, uint32_t c, uint32_t d) {
    asm volatile("st.relaxed.gpu.global.v4.u32 [%0], {%1,%2,%3,%4};" ::"l"(p), "r"(a), "r"(b), "r"(c), "r"(d) : "memory");
}
__device__ __forceinline__ void st_relaxed_v2(void* p, uint32_t a, uint32_t b) {
    asm volatile("st.relaxed.gpu.global.v2.u32 [%0], {%1,%2};" ::"l"(p), "r"(a), "r"(b) : "memory");
}
__device__ __forceinline__ uint32_t nz(uint32_t v) { uint32_t r; asm("max.u32 %0, %1, 1;" : "=r"(r) : "r"(v)); return r; }
__device__ __forceinline__ void touch(const void* p) { asm volatile("prefetch.global.L2 [%0];" ::"l"(p) : "memory"); }
__device__ __forceinline__ int ld_relaxed(const int* p) {
    int v;
    asm volatile("ld.relaxed.gpu.global.u32 %0, [%1];" : "=r"(v) : "l"(p) : "memory");
    return v;
}
__device__ __forceinline__ int ld_acquire(const int* p) {
    int v;
    asm volatile("ld.acquire.gpu.global.u32 %0, [%1];" : "=r"(v) : "l"(p) : "memory");
    return v;
}
__device__ __forceinline__ void red_release(int* p, int v) { asm volatile("red.release.gpu.global.add.u32 [%0], %1;" ::"l"(p), "r"(v) : "memory"); }
__device__ __forceinline__ void mbar_init(uint32_t bar, int count) { asm volatile("mbarrier.init.shared::cta.b64 [%0], %1;" ::"r"(bar), "r"(count)); }
__device__ __forceinline__ void mbar_expect_tx(uint32_t bar, uint32_t bytes) {
    asm volatile("mbarrier.arrive.expect_tx.shared::cta.b64 _, [%0], %1;" ::"r"(bar), "r"(bytes) : "memory");
}
__device__ __forceinline__ void mbar_arrive(uint32_t bar) { asm volatile("mbarrier.arrive.shared::cta.b64 _, [%0];" ::"r"(bar) : "memory"); }
__device__ __forceinline__ void mbar_arrive_cluster(uint32_t bar) { asm volatile("mbarrier.arrive.shared::cluster.b64 _, [%0];" ::"r"(bar) : "memory"); }
__device__ __forceinline__ void mslow(uint32_t bar, uint32_t parity) {
    asm volatile(
        "{\n.reg .pred P1;\n.reg .u32 cnt;\n"
        "mov.u32 cnt, 0;\n"
        "LAB_WAIT:\n"
        "mbarrier.try_wait.parity.shared::cta.b64 P1, [%0], %1;\n"
        "@P1 bra DONE;\n"
        "add.u32 cnt, cnt, 1;\n"
        "setp.lt.u32 P1, cnt, 1000000;\n"
        "@P1 bra LAB_WAIT;\n"
        "trap;\n"
        "DONE:\n}\n" ::"r"(bar), "r"(parity) : "memory");
}
__device__ __forceinline__ void mwait(uint32_t bar, uint32_t parity) {
    asm volatile(
        "{\n.reg .pred P1, P2;\n.reg .u32 cnt;\n"
        "mov.u32 cnt, 0;\n"
        "LAB_WAIT:\n"
        "mbarrier.try_wait.parity.shared::cta.b64 P1, [%0], %1;\n"
        "add.u32 cnt, cnt, 1;\n"
        "setp.gt.u32 P2, cnt, 1000000;\n"
        "@P2 trap;\n"
        "@!P1 bra LAB_WAIT;\n"
        "}\n" ::"r"(bar), "r"(parity) : "memory");
}
__device__ __forceinline__ uint32_t mtest(uint32_t bar, uint32_t parity) {
    uint32_t ok;
    asm volatile("{\n.reg .pred P1;\nmbarrier.test_wait.parity.shared::cta.b64 P1, [%1], %2;\nselp.u32 %0, 1, 0, P1;\n}\n" : "=r"(ok) : "r"(bar), "r"(parity) : "memory");
    return ok;
}
__device__ __forceinline__ uint32_t mapa(uint32_t addr, uint32_t rank) {
    uint32_t r;
    asm("mapa.shared::cluster.u32 %0, %1, %2;" : "=r"(r) : "r"(addr), "r"(rank));
    return r;
}
__device__ __forceinline__ void st_async_b32(uint32_t addr, uint32_t a, uint32_t bar) {
    asm volatile("st.async.weak.shared::cluster.mbarrier::complete_tx::bytes.b32 [%0], %1, [%2];" ::"r"(addr), "r"(a), "r"(bar) : "memory");
}
__device__ __forceinline__ void st_async_v2(uint32_t addr, uint32_t a, uint32_t b, uint32_t bar) {
    asm volatile("st.async.weak.shared::cluster.mbarrier::complete_tx::bytes.v2.b32 [%0], {%1,%2}, [%3];" ::"r"(addr), "r"(a), "r"(b), "r"(bar) : "memory");
}
__device__ __forceinline__ void st_async_v4(uint32_t addr, uint32_t a, uint32_t b, uint32_t c, uint32_t d, uint32_t bar) {
    asm volatile("st.async.weak.shared::cluster.mbarrier::complete_tx::bytes.v4.b32 [%0], {%1,%2,%3,%4}, [%5];" ::"r"(addr), "r"(a), "r"(b), "r"(c), "r"(d), "r"(bar) : "memory");
}
__device__ __forceinline__ void st_async_v4p(uint32_t addr, uint32_t a, uint32_t b, uint32_t c, uint32_t d, uint32_t bar) {
    asm volatile("{\n.reg .pred p;\nsetp.ne.u32 p, %5, 0;\n@p st.async.weak.shared::cluster.mbarrier::complete_tx::bytes.v4.b32 [%0], {%1,%2,%3,%4}, [%5];\n}"
                 ::"r"(addr), "r"(a), "r"(b), "r"(c), "r"(d), "r"(bar) : "memory");
}
__device__ __forceinline__ void st_async_v2p(uint32_t addr, uint32_t a, uint32_t b, uint32_t bar) {
    asm volatile("{\n.reg .pred p;\nsetp.ne.u32 p, %3, 0;\n@p st.async.weak.shared::cluster.mbarrier::complete_tx::bytes.v2.b32 [%0], {%1,%2}, [%3];\n}"
                 ::"r"(addr), "r"(a), "r"(b), "r"(bar) : "memory");
}
__device__ __forceinline__ void cluster_arrive() { asm volatile("barrier.cluster.arrive.release.aligned;" ::: "memory"); }
__device__ __forceinline__ void cluster_arrive_relaxed() { asm volatile("barrier.cluster.arrive.relaxed.aligned;" ::: "memory"); }
__device__ __forceinline__ void prefetch_l2(const void* p, uint32_t bytes) { asm volatile("cp.async.bulk.prefetch.L2.global [%0], %1;" ::"l"(p), "r"(bytes) : "memory"); }
__device__ __forceinline__ void cluster_wait() { asm volatile("barrier.cluster.wait.acquire.aligned;" ::: "memory"); }
__device__ __forceinline__ void named_bar(int id, int n) { asm volatile("bar.sync %0, %1;" ::"r"(id), "r"(n) : "memory"); }
__device__ __forceinline__ void named_arrive(int id, int n) { asm volatile("bar.arrive %0, %1;" ::"r"(id), "r"(n) : "memory"); }
__device__ __forceinline__ void fence_async_smem() { asm volatile("fence.proxy.async.shared::cta;" ::: "memory"); }
__device__ __forceinline__ void fence_async_global() { asm volatile("fence.proxy.async.global;" ::: "memory"); }
__device__ __forceinline__ void wg_fence() { asm volatile("wgmma.fence.sync.aligned;" ::: "memory"); }
__device__ __forceinline__ void wg_commit() { asm volatile("wgmma.commit_group.sync.aligned;" ::: "memory"); }
template <int N> __device__ __forceinline__ void wg_wait() { asm volatile("wgmma.wait_group.sync.aligned %0;" ::"n"(N) : "memory"); }
__device__ __forceinline__ float ex2f(float x) { float y; asm("ex2.approx.ftz.f32 %0, %1;" : "=f"(y) : "f"(x)); return y; }
__device__ __forceinline__ float rcpf(float x) { float y; asm("rcp.approx.ftz.f32 %0, %1;" : "=f"(y) : "f"(x)); return y; }
__device__ __forceinline__ uint32_t clk32() { uint32_t c; asm volatile("mov.u32 %0, %clock;" : "=r"(c)); return c; }
__device__ __forceinline__ uint32_t opq(uint32_t x) { uint32_t y; asm volatile("mov.u32 %0, %1;" : "=r"(y) : "r"(x)); return y; }
__device__ __forceinline__ uint64_t mkdesc(uint32_t lo, uint32_t hi) { uint64_t d; asm("mov.b64 %0, {%1,%2};" : "=l"(d) : "r"(lo), "r"(hi)); return d; }
__device__ __forceinline__ void delay(uint32_t n) {
    asm volatile("{\n.reg .pred P;\n.reg .u32 a, b;\nmov.u32 a, %clock;\nadd.u32 a, a, %0;\nDL:\nmov.u32 b, %clock;\nsub.u32 b, b, a;\nsetp.lt.s32 P, b, 0;\n@P bra.uni DL;\n}" ::"r"(n) : "memory");
}
#define UNI(x) __shfl_sync(0xffffffffu, (uint32_t)(x), 0)
__device__ __forceinline__ void wg_n16t(float* d, uint32_t a0, uint32_t a1, uint32_t a2, uint32_t a3, uint64_t db) {
    asm volatile("wgmma.mma_async.sync.aligned.m64n16k16.f32.bf16.bf16 {%0, %1, %2, %3, %4, %5, %6, %7}, {%8, %9, %10, %11}, %12, 1, 1, 1, 1;"
                 : "+f"(d[0]), "+f"(d[1]), "+f"(d[2]), "+f"(d[3]), "+f"(d[4]), "+f"(d[5]), "+f"(d[6]), "+f"(d[7]) : "r"(a0), "r"(a1), "r"(a2), "r"(a3), "l"(db));
}
__device__ __forceinline__ void wg_n16t_first(float* d, uint32_t a0, uint32_t a1, uint32_t a2, uint32_t a3, uint64_t db) {
    asm volatile("wgmma.mma_async.sync.aligned.m64n16k16.f32.bf16.bf16 {%0, %1, %2, %3, %4, %5, %6, %7}, {%8, %9, %10, %11}, %12, 0, 1, 1, 1;"
                 : "=f"(d[0]), "=f"(d[1]), "=f"(d[2]), "=f"(d[3]), "=f"(d[4]), "=f"(d[5]), "=f"(d[6]), "=f"(d[7]) : "r"(a0), "r"(a1), "r"(a2), "r"(a3), "l"(db));
}
__device__ __forceinline__ void wg_n32(float* d, uint32_t a0, uint32_t a1, uint32_t a2, uint32_t a3, uint64_t db) {
    asm volatile("wgmma.mma_async.sync.aligned.m64n32k16.f32.bf16.bf16 {%0, %1, %2, %3, %4, %5, %6, %7, %8, %9, %10, %11, %12, %13, %14, %15}, {%16, %17, %18, %19}, %20, 1, 1, 1, 0;"
                 : "+f"(d[0]), "+f"(d[1]), "+f"(d[2]), "+f"(d[3]), "+f"(d[4]), "+f"(d[5]), "+f"(d[6]), "+f"(d[7]), "+f"(d[8]), "+f"(d[9]), "+f"(d[10]), "+f"(d[11]), "+f"(d[12]), "+f"(d[13]), "+f"(d[14]), "+f"(d[15]) : "r"(a0), "r"(a1), "r"(a2), "r"(a3), "l"(db));
}
__device__ __forceinline__ void wg_n32_first(float* d, uint32_t a0, uint32_t a1, uint32_t a2, uint32_t a3, uint64_t db) {
    asm volatile("wgmma.mma_async.sync.aligned.m64n32k16.f32.bf16.bf16 {%0, %1, %2, %3, %4, %5, %6, %7, %8, %9, %10, %11, %12, %13, %14, %15}, {%16, %17, %18, %19}, %20, 0, 1, 1, 0;"
                 : "=f"(d[0]), "=f"(d[1]), "=f"(d[2]), "=f"(d[3]), "=f"(d[4]), "=f"(d[5]), "=f"(d[6]), "=f"(d[7]), "=f"(d[8]), "=f"(d[9]), "=f"(d[10]), "=f"(d[11]), "=f"(d[12]), "=f"(d[13]), "=f"(d[14]), "=f"(d[15]) : "r"(a0), "r"(a1), "r"(a2), "r"(a3), "l"(db));
}

__device__ __forceinline__ void wg_n16t_sfirst(float* d, uint64_t da, uint64_t db) {
    asm volatile("wgmma.mma_async.sync.aligned.m64n16k16.f32.bf16.bf16 {%0, %1, %2, %3, %4, %5, %6, %7}, %8, %9, 0, 1, 1, 1, 1;"
                 : "=f"(d[0]), "=f"(d[1]), "=f"(d[2]), "=f"(d[3]), "=f"(d[4]), "=f"(d[5]), "=f"(d[6]), "=f"(d[7]) : "l"(da), "l"(db));
}
__device__ __forceinline__ void wg_n32_sfirst(float* d, uint64_t da, uint64_t db) {
    asm volatile("wgmma.mma_async.sync.aligned.m64n32k16.f32.bf16.bf16 {%0, %1, %2, %3, %4, %5, %6, %7, %8, %9, %10, %11, %12, %13, %14, %15}, %16, %17, 0, 1, 1, 1, 0;"
                 : "=f"(d[0]), "=f"(d[1]), "=f"(d[2]), "=f"(d[3]), "=f"(d[4]), "=f"(d[5]), "=f"(d[6]), "=f"(d[7]), "=f"(d[8]), "=f"(d[9]), "=f"(d[10]), "=f"(d[11]), "=f"(d[12]), "=f"(d[13]), "=f"(d[14]), "=f"(d[15]) : "l"(da), "l"(db));
}

__device__ __forceinline__ void wg_n16t_s(float* d, uint64_t da, uint64_t db) {
    asm volatile("wgmma.mma_async.sync.aligned.m64n16k16.f32.bf16.bf16 {%0, %1, %2, %3, %4, %5, %6, %7}, %8, %9, 1, 1, 1, 1, 1;"
                 : "+f"(d[0]), "+f"(d[1]), "+f"(d[2]), "+f"(d[3]), "+f"(d[4]), "+f"(d[5]), "+f"(d[6]), "+f"(d[7]) : "l"(da), "l"(db));
}
__device__ __forceinline__ void wg_n64_sfirst(float* d, uint64_t da, uint64_t db) {
    asm volatile("wgmma.mma_async.sync.aligned.m64n64k16.f32.bf16.bf16 {%0, %1, %2, %3, %4, %5, %6, %7, %8, %9, %10, %11, %12, %13, %14, %15, %16, %17, %18, %19, %20, %21, %22, %23, %24, %25, %26, %27, %28, %29, %30, %31}, %32, %33, 0, 1, 1, 1, 0;"
                 : "=f"(d[0]), "=f"(d[1]), "=f"(d[2]), "=f"(d[3]), "=f"(d[4]), "=f"(d[5]), "=f"(d[6]), "=f"(d[7]), "=f"(d[8]), "=f"(d[9]), "=f"(d[10]), "=f"(d[11]), "=f"(d[12]), "=f"(d[13]), "=f"(d[14]), "=f"(d[15]), "=f"(d[16]), "=f"(d[17]), "=f"(d[18]), "=f"(d[19]), "=f"(d[20]), "=f"(d[21]), "=f"(d[22]), "=f"(d[23]), "=f"(d[24]), "=f"(d[25]), "=f"(d[26]), "=f"(d[27]), "=f"(d[28]), "=f"(d[29]), "=f"(d[30]), "=f"(d[31]) : "l"(da), "l"(db));
}
__device__ __forceinline__ void wg_n64_s(float* d, uint64_t da, uint64_t db) {
    asm volatile("wgmma.mma_async.sync.aligned.m64n64k16.f32.bf16.bf16 {%0, %1, %2, %3, %4, %5, %6, %7, %8, %9, %10, %11, %12, %13, %14, %15, %16, %17, %18, %19, %20, %21, %22, %23, %24, %25, %26, %27, %28, %29, %30, %31}, %32, %33, 1, 1, 1, 1, 0;"
                 : "+f"(d[0]), "+f"(d[1]), "+f"(d[2]), "+f"(d[3]), "+f"(d[4]), "+f"(d[5]), "+f"(d[6]), "+f"(d[7]), "+f"(d[8]), "+f"(d[9]), "+f"(d[10]), "+f"(d[11]), "+f"(d[12]), "+f"(d[13]), "+f"(d[14]), "+f"(d[15]), "+f"(d[16]), "+f"(d[17]), "+f"(d[18]), "+f"(d[19]), "+f"(d[20]), "+f"(d[21]), "+f"(d[22]), "+f"(d[23]), "+f"(d[24]), "+f"(d[25]), "+f"(d[26]), "+f"(d[27]), "+f"(d[28]), "+f"(d[29]), "+f"(d[30]), "+f"(d[31]) : "l"(da), "l"(db));
}
__device__ __forceinline__ void wg_n64(float* d, uint32_t a0, uint32_t a1, uint32_t a2, uint32_t a3, uint64_t db) {
    asm volatile("wgmma.mma_async.sync.aligned.m64n64k16.f32.bf16.bf16 {%0, %1, %2, %3, %4, %5, %6, %7, %8, %9, %10, %11, %12, %13, %14, %15, %16, %17, %18, %19, %20, %21, %22, %23, %24, %25, %26, %27, %28, %29, %30, %31}, {%32, %33, %34, %35}, %36, 1, 1, 1, 0;"
                 : "+f"(d[0]), "+f"(d[1]), "+f"(d[2]), "+f"(d[3]), "+f"(d[4]), "+f"(d[5]), "+f"(d[6]), "+f"(d[7]), "+f"(d[8]), "+f"(d[9]), "+f"(d[10]), "+f"(d[11]), "+f"(d[12]), "+f"(d[13]), "+f"(d[14]), "+f"(d[15]), "+f"(d[16]), "+f"(d[17]), "+f"(d[18]), "+f"(d[19]), "+f"(d[20]), "+f"(d[21]), "+f"(d[22]), "+f"(d[23]), "+f"(d[24]), "+f"(d[25]), "+f"(d[26]), "+f"(d[27]), "+f"(d[28]), "+f"(d[29]), "+f"(d[30]), "+f"(d[31]) : "r"(a0), "r"(a1), "r"(a2), "r"(a3), "l"(db));
}
__device__ __forceinline__ void wg_n64_first(float* d, uint32_t a0, uint32_t a1, uint32_t a2, uint32_t a3, uint64_t db) {
    asm volatile("wgmma.mma_async.sync.aligned.m64n64k16.f32.bf16.bf16 {%0, %1, %2, %3, %4, %5, %6, %7, %8, %9, %10, %11, %12, %13, %14, %15, %16, %17, %18, %19, %20, %21, %22, %23, %24, %25, %26, %27, %28, %29, %30, %31}, {%32, %33, %34, %35}, %36, 0, 1, 1, 0;"
                 : "=f"(d[0]), "=f"(d[1]), "=f"(d[2]), "=f"(d[3]), "=f"(d[4]), "=f"(d[5]), "=f"(d[6]), "=f"(d[7]), "=f"(d[8]), "=f"(d[9]), "=f"(d[10]), "=f"(d[11]), "=f"(d[12]), "=f"(d[13]), "=f"(d[14]), "=f"(d[15]), "=f"(d[16]), "=f"(d[17]), "=f"(d[18]), "=f"(d[19]), "=f"(d[20]), "=f"(d[21]), "=f"(d[22]), "=f"(d[23]), "=f"(d[24]), "=f"(d[25]), "=f"(d[26]), "=f"(d[27]), "=f"(d[28]), "=f"(d[29]), "=f"(d[30]), "=f"(d[31]) : "r"(a0), "r"(a1), "r"(a2), "r"(a3), "l"(db));
}

__device__ __forceinline__ void wg_n32t(float* d, uint32_t a0, uint32_t a1, uint32_t a2, uint32_t a3, uint64_t db) {
    asm volatile("wgmma.mma_async.sync.aligned.m64n32k16.f32.bf16.bf16 {%0, %1, %2, %3, %4, %5, %6, %7, %8, %9, %10, %11, %12, %13, %14, %15}, {%16, %17, %18, %19}, %20, 1, 1, 1, 1;"
                 : "+f"(d[0]), "+f"(d[1]), "+f"(d[2]), "+f"(d[3]), "+f"(d[4]), "+f"(d[5]), "+f"(d[6]), "+f"(d[7]), "+f"(d[8]), "+f"(d[9]), "+f"(d[10]), "+f"(d[11]), "+f"(d[12]), "+f"(d[13]), "+f"(d[14]), "+f"(d[15]) : "r"(a0), "r"(a1), "r"(a2), "r"(a3), "l"(db));
}
__device__ __forceinline__ void wg_n32t_first(float* d, uint32_t a0, uint32_t a1, uint32_t a2, uint32_t a3, uint64_t db) {
    asm volatile("wgmma.mma_async.sync.aligned.m64n32k16.f32.bf16.bf16 {%0, %1, %2, %3, %4, %5, %6, %7, %8, %9, %10, %11, %12, %13, %14, %15}, {%16, %17, %18, %19}, %20, 0, 1, 1, 1;"
                 : "=f"(d[0]), "=f"(d[1]), "=f"(d[2]), "=f"(d[3]), "=f"(d[4]), "=f"(d[5]), "=f"(d[6]), "=f"(d[7]), "=f"(d[8]), "=f"(d[9]), "=f"(d[10]), "=f"(d[11]), "=f"(d[12]), "=f"(d[13]), "=f"(d[14]), "=f"(d[15]) : "r"(a0), "r"(a1), "r"(a2), "r"(a3), "l"(db));
}
__device__ __forceinline__ void wg_n32t_sfirst(float* d, uint64_t da, uint64_t db) {
    asm volatile("wgmma.mma_async.sync.aligned.m64n32k16.f32.bf16.bf16 {%0, %1, %2, %3, %4, %5, %6, %7, %8, %9, %10, %11, %12, %13, %14, %15}, %16, %17, 0, 1, 1, 1, 1;"
                 : "=f"(d[0]), "=f"(d[1]), "=f"(d[2]), "=f"(d[3]), "=f"(d[4]), "=f"(d[5]), "=f"(d[6]), "=f"(d[7]), "=f"(d[8]), "=f"(d[9]), "=f"(d[10]), "=f"(d[11]), "=f"(d[12]), "=f"(d[13]), "=f"(d[14]), "=f"(d[15]) : "l"(da), "l"(db));
}
__device__ __forceinline__ void wg_n32t_s(float* d, uint64_t da, uint64_t db) {
    asm volatile("wgmma.mma_async.sync.aligned.m64n32k16.f32.bf16.bf16 {%0, %1, %2, %3, %4, %5, %6, %7, %8, %9, %10, %11, %12, %13, %14, %15}, %16, %17, 1, 1, 1, 1, 1;"
                 : "+f"(d[0]), "+f"(d[1]), "+f"(d[2]), "+f"(d[3]), "+f"(d[4]), "+f"(d[5]), "+f"(d[6]), "+f"(d[7]), "+f"(d[8]), "+f"(d[9]), "+f"(d[10]), "+f"(d[11]), "+f"(d[12]), "+f"(d[13]), "+f"(d[14]), "+f"(d[15]) : "l"(da), "l"(db));
}

__device__ __forceinline__ void wg_n32_kk(float* d, uint64_t da, uint64_t db) {
    asm volatile("wgmma.mma_async.sync.aligned.m64n32k16.f32.bf16.bf16 {%0, %1, %2, %3, %4, %5, %6, %7, %8, %9, %10, %11, %12, %13, %14, %15}, %16, %17, 1, 1, 1, 0, 0;"
                 : "+f"(d[0]), "+f"(d[1]), "+f"(d[2]), "+f"(d[3]), "+f"(d[4]), "+f"(d[5]), "+f"(d[6]), "+f"(d[7]), "+f"(d[8]), "+f"(d[9]), "+f"(d[10]), "+f"(d[11]), "+f"(d[12]), "+f"(d[13]), "+f"(d[14]), "+f"(d[15]) : "l"(da), "l"(db));
}

}

namespace ws {
#define LAGT 4
constexpr int LAG = LAGT, NT = NSEG + LAG, NCL = 7;
#define P1A 24
#define P1C 10
#define XD 350
#define REG_G 200
#define REG_T 72
#define REG_X 40
template <int V> struct IC { static constexpr int value = V; };
#define POST_NS 20
#define OP_NS 20
#define LN0_AHEAD 8
#define TG_STEPS 40
#define NO_X 0
#define WTA 3
constexpr int WTC = 10 - 2 * WTA;
#define WR 3
#define OBK 2
#define WFLY 2
#define H_NS 20
#define C_REV 2
#define ONE_FENCE 0
#define LN0_BATCH 1
static_assert(LN0_AHEAD + LN0_BATCH + LAG + 1 <= 16 && (NSEG - LN0_AHEAD) % LN0_BATCH == 0, "ring of the scratch buffers");
constexpr int XRS = 3;
constexpr int O_H = 0, O_MEM = 81920, O_RED = 102400, O_BAR = 110080, O_TAB = O_BAR + 192, O_BT = O_TAB + 128, O_TR = O_BAR + 512, O_X = O_TR + 1024;
constexpr int O_QRY = O_X, O_KEY = O_X + 10240, O_OBA = O_KEY + 10240, O_ST = O_OBA + 4096;
constexpr int O_VT = O_X, O_VM = O_VT + 32768, O_SM = O_VM + 4096, O_PB = O_SM + 3072;
constexpr int O_AS = 228352, O_WO = O_AS - 65536, HEAD_SMEM = O_AS + 4096, O_STG = 40960;
static_assert(O_ST + 8192 <= O_WO && O_PB + 10240 <= O_WO && O_AS % 1024 == 0 && O_STG + 163840 <= O_AS && HEAD_SMEM <= 232448, "smem");
constexpr int B_MEM = 0, B_RED = 64, B_SM = 88, B_ST = 96, B_OB = 104, B_HF = 112, B_HE = 128, B_OTF = 144, B_OTE = 160;

constexpr int F_H = 0, F_O = 128, F_P = 256, F_U = 384, F_CV = 392, F_XL = 398, F_Z = 399, NFLAG = 400;
__device__ int g_flags[NFLAG * 8];
#define FLG(i) (g_flags + (i) * 8)
#define RING 16
__device__ __forceinline__ int rslot(int l, int seg) { return l * RING + (seg & (RING - 1)); }
__device__ uint4 g_ht[2 * RING * 2560];
__device__ uint4 g_ot[2 * RING * 256 * 64];
__device__ uint4 g_pt[2 * RING * 5120];
__device__ uint4 g_Y[80 * S_LEN];
__device__ uint4 g_U[DM * S_LEN / 8];
__device__ bf16 g_x[RING * SEG * DM];
__device__ int g_epoch;
__device__ uint4 g_xc[XRS * 16 * 3 * 8 * 32];
#define GT(cond, i)
#define SC(cond, i)
#define SD(x)
#define TS(i)
#define TV(i, v)

}

namespace ws {
__device__ __forceinline__ uint32_t bmul2(uint32_t a, uint32_t b) { uint32_t r; asm("mul.rn.bf16x2 %0, %1, %2;" : "=r"(r) : "r"(a), "r"(b)); return r; }
__device__ __forceinline__ uint32_t bmax2(uint32_t a, uint32_t b) { uint32_t r; asm("max.bf16x2 %0, %1, %2;" : "=r"(r) : "r"(a), "r"(b)); return r; }
__device__ __forceinline__ void flag_wait(const int* f, int tgt, int ns) {
    int guard = 0;
    while (ld_relaxed(f) < tgt) { if (++guard > 4000000) __trap(); __nanosleep(ns); }
}
template <int STRIDE> __device__ __forceinline__ void ld5(uint32_t* w, const void* p) {
#pragma unroll
    for (int r = 0; r < 5; r++) { const uint2 v = __ldcg(reinterpret_cast<const uint2*>(reinterpret_cast<const char*>(p) + r * STRIDE)); w[2 * r] = v.x; w[2 * r + 1] = v.y; }
}
template <int STRIDE> __device__ __forceinline__ void st5(void* p, const uint32_t* w) {
#pragma unroll
    for (int r = 0; r < 5; r++) *reinterpret_cast<uint2*>(reinterpret_cast<char*>(p) + r * STRIDE) = make_uint2(w[2 * r], w[2 * r + 1]);
}
__device__ __forceinline__ void ln_row(const uint32_t* x, uint32_t* y) {
    const float c = blo(__shfl_sync(0xffffffffu, x[0], 0));
    float s0 = 0.f, s1 = 0.f, q0 = 0.f, q1 = 0.f;
#pragma unroll
    for (int i = 0; i < 10; i++) { const float d0 = blo(x[i]) - c, d1 = bhi(x[i]) - c; s0 += d0; s1 += d1; q0 = fmaf(d0, d0, q0); q1 = fmaf(d1, d1, q1); }
    float s = s0 + s1, q = q0 + q1;
#pragma unroll
    for (int o = 16; o > 0; o >>= 1) { s += __shfl_xor_sync(0xffffffffu, s, o); q += __shfl_xor_sync(0xffffffffu, q, o); }
    s *= 1.0f / DM;
    const float mean = c + s;
    q = fmaxf(fmaf(q, 1.0f / DM, -s * s), 0.f);
    const uint32_t nm = pack2(-mean, -mean);
    float sq;
    asm("sqrt.approx.ftz.f32 %0, %1;" : "=f"(sq) : "f"(rbf(rbf(q) + 1e-5f)));
    const float rd = rcpf(rbf(sq));
#pragma unroll
    for (int i = 0; i < 10; i++) { const uint32_t d = badd(x[i], nm); y[i] = pack2(blo(d) * rd, bhi(d) * rd); }
}
__device__ __forceinline__ void clear_acc(int l, int seg, int tok, int lane) {
    uint4* pz = g_pt + rslot(l, seg) * 5120 + (lane >> 4) * 512 + tok * 16 + (lane & 15);
#pragma unroll
    for (int i = 0; i < 5; i++) pz[i * 1024] = make_uint4(0, 0, 0, 0);
}
__device__ __forceinline__ void put_h(int l, int seg, int tok, int lane, const uint32_t* n) {
    st5<8192>(reinterpret_cast<char*>(g_ht + rslot(l, seg) * 2560) + (lane >> 2) * 1024 + tok * 32 + (((lane & 3) * 8) ^ ((tok & 4) << 2)), n);
}
__device__ __forceinline__ void ln0_rows(const bf16* x, int seg, int cnt, int tok, int lane) {
#pragma unroll 1
    for (int i = 0; i < cnt; i++) {
        uint32_t v[10];
        ld5<256>(v, x + (size_t)((seg + i) * SEG + tok) * DM + lane * 4);
        clear_acc(0, seg + i, tok, lane);
        ln_row(v, v);
        put_h(0, seg + i, tok, lane, v);
    }
    __syncwarp();
    if (lane == 0) {
        red_release(FLG(F_H + seg), 1);
        for (int i = 1; i < cnt; i++) asm volatile("red.relaxed.gpu.global.add.u32 [%0], 1;" ::"l"(FLG(F_H + seg + i)) : "memory");
    }
}
__device__ __forceinline__ void post_row(int l, int seg, int tok, int lane, const bf16* xin, bf16* xout, int ep) {
    uint32_t x[10], y[10], n[10];
    const int row = seg * SEG + tok;
    SC(tr, tb);
    const bool first = seg == 0;
    if (seg == 8 || ((seg & 15) == 0 && seg)) flag_wait(FLG(F_CV + (seg >> 4) + 1), 80 * ep, 50);
    const char* yp = reinterpret_cast<const char*>(g_Y) + ((size_t)(lane >> 1) * S_LEN + row) * 16 + (lane & 1) * 8;
    SC(tr, tb + 1);
    if (!first) ld5<16 * S_LEN * 16>(y, yp);
    bf16* xm = g_x + ((seg & (RING - 1)) * SEG + tok) * DM + lane * 4;
    if (l == 0) {
        ld5<256>(x, xin + (size_t)row * DM + lane * 4);
        clear_acc(1, seg, tok, lane);
    } else {
        flag_wait(seg + 1 < NSEG ? FLG(F_H + 65 + seg) : FLG(F_XL), 32 * ep, 50);
        ld5<256>(x, xm);
    }
    flag_wait(FLG(F_P + l * 64 + seg), 40 * ep, POST_NS);
    SC(tr, tb + 2);
    const uint4* pp = g_pt + rslot(l, seg) * 5120 + (lane >> 4) * 512 + tok * 16 + ((lane & 15) ^ ((tok >> 3) << 1));
    {
        uint4 a[5];
#pragma unroll
        for (int i = 0; i < 5; i++) a[i] = __ldcg(pp + i * 1024);
#pragma unroll
        for (int i = 0; i < 5; i++) {
            x[2 * i] = badd(x[2 * i], pack2(__uint_as_float(a[i].x), __uint_as_float(a[i].y)));
            x[2 * i + 1] = badd(x[2 * i + 1], pack2(__uint_as_float(a[i].z), __uint_as_float(a[i].w)));
        }
    }
    SC(tr && x[0] != 0x12345, tb + 3);
    if (first) { flag_wait(FLG(F_CV), 80 * ep, 50); ld5<16 * S_LEN * 16>(y, yp); }
    ln_row(x, n);
#pragma unroll
    for (int i = 0; i < 10; i++) x[i] = badd(x[i], bmul2(n[i], y[i]));
    SC(tr && x[0] != 0x12345, tb + 4);
    if (l) st5<256>(xout + (size_t)row * DM + lane * 4, x);
    else {
        ln_row(x, n);
        SC(tr && n[0] != 0x12345, tb + 5);
        put_h(1, seg, tok, lane, n);
        __syncwarp();
        if (lane == 0) red_release(FLG(F_H + 64 + seg), 1);
        SC(tr, tb + 6);
        st5<256>(xm, x);
        if (seg == NSEG - 1) { __syncwarp(); if (lane == 0) red_release(FLG(F_XL), 1); }
    }
}
__device__ __forceinline__ void u_piece(const bf16* Bk, const bf16* Bv, const bf16* shiftk, int t0, int cp, uint4* o) {
    uint32_t kk[11], vv[8];
    const uint32_t* pk = reinterpret_cast<const uint32_t*>(Bk + (size_t)t0 * DM) + cp;
    const uint32_t* pv = reinterpret_cast<const uint32_t*>(Bv + (size_t)t0 * DM) + cp;
#pragma unroll
    for (int i = 0; i < 11; i++) kk[i] = (i >= 3 || t0 > 0) ? __ldg(pk + (i - 3) * (DM / 2)) : 0u;
#pragma unroll
    for (int i = 0; i < 8; i++) vv[i] = __ldg(pv + i * (DM / 2));
    const uint4 sh0 = __ldg(reinterpret_cast<const uint4*>(shiftk + cp * 8));
    const uint32_t s0 = __byte_perm(sh0.x, sh0.z, 0x5410), s1 = __byte_perm(sh0.x, sh0.z, 0x7632), s2 = __byte_perm(sh0.y, sh0.w, 0x5410), s3 = __byte_perm(sh0.y, sh0.w, 0x7632);
#pragma unroll
    for (int t = 0; t < 8; t++)
        vv[t] = bmul2(badd(badd(badd(bmul2(kk[t], s3), bmul2(kk[t + 1], s2)), bmul2(kk[t + 2], s1)), bmul2(kk[t + 3], s0)), vv[t]);
#pragma unroll
    for (int c = 0; c < 2; c++) {
        const uint32_t sel = c ? 0x7632 : 0x5410;
        o[c] = make_uint4(__byte_perm(vv[7], vv[6], sel), __byte_perm(vv[5], vv[4], sel), __byte_perm(vv[3], vv[2], sel), __byte_perm(vv[1], vv[0], sel));
    }
}
__device__ __forceinline__ int u_pos(int t0) { return (t0 >> 6) * 8 + ((((t0 ^ 56) & 63) >> 3) ^ ((t0 >> 6) & 7)); }
__device__ __forceinline__ void u_half(const bf16* Bk, const bf16* Bv, const bf16* shiftk, int unit, int lane) {
    const int t0 = (unit / 20) * 16 + (lane & 1) * 8, cp = (unit % 20) * 16 + (lane >> 1);
    uint4 o[2];
    u_piece(Bk, Bv, shiftk, t0, cp, o);
    uint4* d = g_U + (size_t)(cp * 2) * (S_LEN / 8) + u_pos(t0);
    d[0] = o[0]; d[S_LEN / 8] = o[1];
}
constexpr int CV_E = 4224, CV_W = 2 * 4096 + 3 * CV_E + 128, CV_HI = O_X, CV_Y = CV_HI + 4 * CV_W, CV_T = CV_Y + 16384, CV_Z = CV_T + 16384;
static_assert(4 * CV_W <= O_RED && CV_W % 128 == 0 && CV_Z + 128 <= HEAD_SMEM, "conv buffers");
__device__ __forceinline__ void conv_unit(uint32_t ub, uint32_t e0, uint32_t e1, uint32_t zrow, uint32_t tt, uint32_t Dv, int rg, int nq, int lane, uint32_t zero, int tb) {
    const int g7 = 7 - (lane >> 2), tq = lane & 3;
    SC(tb >= 0, tb + 3);
    for (int i = lane; i < 32 * nq + 8; i += 32) {
        const uint4 v = lds128(e0 + i * 16);
        const uint32_t nx = lds32(e0 + i * 16 + 16);
        sts128(e1 + i * 16, __byte_perm(v.x, v.y, 0x5432), __byte_perm(v.y, v.z, 0x5432), __byte_perm(v.z, v.w, 0x5432), __byte_perm(v.w, nx, 0x5432));
    }
    __syncwarp();
    SC(tb >= 0, tb + 4);
    float acc[4][4];
#pragma unroll
    for (int i = 0; i < 16; i++) (&acc[0][0])[i] = 0.f;
    uint32_t wb = (g7 & 1) ? e0 + (1 + g7 + 2 * tq) * 2 : e1 + (g7 + 2 * tq) * 2;
    int row = 8 * rg + (lane & 7);
    auto ldb = [&](uint4* b) {
        const uint32_t x = row < 0 ? zrow : ub + row * 128 + (((lane >> 3) ^ (row & 7)) << 4);
        b[0] = ldsm4(x); b[1] = ldsm4(x ^ 64);
        row--;
    };
    uint4 Q[16], b[2][2];
    Q[15].w = lds32(wb);
    auto ldq = [&](int q, int o) { Q[q].y = lds32(wb + o * 32 + 16); Q[q].w = lds32(wb + o * 32 + 32); };
    auto cpq = [&](int q) { Q[q].x = Q[(q + 15) & 15].w + zero; Q[q].z = Q[q].y + zero; };
#pragma unroll
    for (int q = 0; q < 11; q++) ldq(q, q);
#pragma unroll
    for (int q = 0; q < 7; q++) cpq(q);
    ldb(b[0]);
#pragma unroll 1
    for (int D0 = nq; D0 > 0; D0--) {
#pragma unroll
        for (int d = 0; d < 4; d++) {
            ldb(b[(d + 1) & 1]);
#pragma unroll
            for (int q = 11; q < 15; q++) ldq((4 * d + q) & 15, 4 * d + q);
#pragma unroll
            for (int ks = 0; ks < 4; ks++) {
                const uint4& bb_ = b[d & 1][ks >> 1];
#pragma unroll
                for (int m = 0; m < 4; m++) {
                    const uint4& a = Q[(4 * d + m + ks) & 15];
                    mmav(acc[m], a.x, a.y, a.z, a.w, (ks & 1) ? bb_.z : bb_.x, (ks & 1) ? bb_.w : bb_.y);
                }
                cpq((4 * d + 7 + ks) & 15);
            }
        }
        wb += 512;
    }
    SC(tb >= 0 && acc[0][0] != 1.2345f, tb + 5);
    const uint32_t ua = ub + (8 * rg + (lane & 7)) * 128 + (((lane >> 3) ^ (lane & 7)) << 4);
    const uint4 u0 = ldsm4t(ua), u1 = ldsm4t(ua ^ 64);
    auto y = [&](int m, int hf, uint32_t u) { return badd(pack2(acc[m][2 * hf], acc[m][2 * hf + 1]), bmul2(u, Dv)); };
    stsm4t(tt, y(0, 0, u1.w), y(0, 1, u1.z), y(1, 0, u1.y), y(1, 1, u1.x));
    stsm4t(tt ^ 64, y(2, 0, u0.w), y(2, 1, u0.z), y(3, 0, u0.y), y(3, 1, u0.x));
}
}

namespace ws {
__constant__ unsigned char c_tile[48] = {4, 5, 6, 7, 12, 13, 14, 19, 0, 1, 2, 3, 0, 0, 0, 0, 20, 21, 22, 27, 28, 29, 30, 31, 8, 9, 10, 11, 0, 0, 0, 0,
                                         39, 38, 37, 36, 35, 34, 33, 32, 15, 16, 17, 18, 23, 24, 25, 26};
struct HeadArgs { const bf16 *x, *mem0, *Wq, *Wk, *Wv, *Wo, *Bk, *Bv, *shiftk, *ssmk, *ssmD; bf16* out; int h_target; };

__global__ void __launch_bounds__(512, 1) head_kernel(const __grid_constant__ HeadArgs A) {
    extern __shared__ __align__(1024) unsigned char smem_raw[];
    const int tid = threadIdx.x, warp = __shfl_sync(0xffffffffu, tid >> 5, 0), lane = tid & 31;
    const int cq = blockIdx.x >> 4, r = blockIdx.x & 15;
    const int nh = cq < 4 ? 5 : 4, hi = r / 3, role = r - hi * 3;
    const bool head = r < 3 * nh;
    const int p0 = r >> 1;
    const int h = (cq < 4 ? 5 * cq : 4 * cq + 4) + hi;
    const uint32_t sb = smem_u32(smem_raw), bb = sb + O_BAR;
    GT(tid == 0, 1);
    const int sp = cq < 4 ? cq : 4 * cq + r - 24;
    if (tid == 0) {
        if ((sb & 0xFFFFFFu) != 1024) __trap();
        for (int i = 0; i < 12; i++) mbar_init(bb + i * 8, 1);
        mbar_init(bb + B_ST, role == 2 ? 1 : 5);
        mbar_init(bb + B_OB, 1); mbar_init(bb + B_OB + 64, 1);
        mbar_init(bb + B_HF, 1); mbar_init(bb + B_HF + 8, 1);
        mbar_init(bb + B_HE, 6 * nh);
        mbar_init(bb + B_OTF, head ? 4 : 8); mbar_init(bb + B_OTE, 1); mbar_init(bb + B_OTF + 8, head ? 4 : 8); mbar_init(bb + B_OTE + 16, 1);
        asm volatile("fence.mbarrier_init.release.cluster;" ::: "memory");
        mbar_expect_tx(bb + B_RED, nh * 1280);
        mbar_expect_tx(bb + B_SM, 3072); mbar_expect_tx(bb + B_ST, role == 2 ? 5120 : 4096);
        if (role != 2) { mbar_expect_tx(bb + B_OB, 2048); mbar_expect_tx(bb + B_OB + 64, 2048); }
        mbar_expect_tx(bb + B_HF, 40960); mbar_expect_tx(bb + B_HF + 8, 40960);
    }
    asm volatile("griddepcontrol.launch_dependents;");
    __syncwarp();
    cluster_arrive_relaxed();
    if (warp < 8) {
        asm volatile("setmaxnreg.inc.sync.aligned.u32 %0;" ::"n"(REG_G));
        const int wg = warp >> 2, w4 = warp & 3;
        if (head) {
            uint32_t wa[40][4];
            {
                const int t7 = tid & 127;
                const bf16* W = (role == 2 ? A.Wv + wg * 64 : (wg ? A.Wk : A.Wq) + role * 64) + h * DH + (size_t)(t7 >> 3) * HD + (t7 & 7) * 8;
                const uint32_t so = (t7 >> 3) * 128 + (((t7 & 7) ^ ((t7 >> 3) & 7)) << 4), stg = sb + O_STG + wg * 81920;
                const uint32_t la = stg + ((lane & 7) + (lane >> 4) * 8) * 128 + (((w4 * 2 + ((lane >> 3) & 1)) ^ (lane & 7)) << 4);
                GT(tid == 0, 80);
#pragma unroll
                for (int gi = 0; gi < 8 + WFLY; gi++) {
                    if (gi < 8) {
                        const bf16* Wg = W + (size_t)(((p0 - gi) & 7) * 80) * HD;
#pragma unroll
                        for (int u = 0; u < 5; u++) cp_async16((gi == 0 && u == 0 ? sb + O_AS + wg * 2048 : stg + (gi * 5 + u) * 2048) + so, Wg + (size_t)u * 16 * HD);
                    }
                    cp_commit();
                    if (gi >= WFLY) {
                        cp_wait<WFLY>();
                        named_bar(8 + wg, 128);
#pragma unroll
                        for (int u = 0; u < 5; u++) {
                            const int j = (gi - WFLY) * 5 + u;
                            if (j) { const uint4 v = ldsm4t(la + j * 2048); wa[j][0] = v.x; wa[j][1] = v.y; wa[j][2] = v.z; wa[j][3] = v.w; }
                        }
                    }
                }
                GT(tid == 0, 83);
                cluster_wait();
            }
            named_bar(10, 384);
            GT(tid == 0, 2);
            fence_async_smem();
            named_bar(8 + wg, 128);
            cluster_arrive_relaxed();
            float acc[16];
            const uint32_t ep_q = role == 2 ? sb + O_VM + warp * 512 + (lane ^ ((lane >> 3) & 1)) * 16
                                            : sb + O_QRY + wg * 10240 + ((lane >> 1) & 1) * 5120 + (4 * (lane >> 4) + 2 * ((lane >> 2) & 1) + (lane & 1)) * 128 +
                                                  (((2 * w4 + ((lane >> 3) & 1)) ^ (4 * (lane >> 4) + 2 * ((lane >> 2) & 1) + (lane & 1)) ^ ((lane & 2) << 1)) << 4);
            const uint32_t ep_t = role == 2 ? sb + O_VT + warp * 1024 + ((lane >> 3) & 1) * 512 + (lane >> 4) * 128 + (lane & 7) * 16
                                            : sb + O_QRY + wg * 10240 + (8 + 8 * (lane >> 4) + (lane & 7)) * 128 + (((2 * w4 + ((lane >> 3) & 1)) ^ (lane & 7)) << 4);
                        const int pz = role == 2 ? P1C : P1A;
            const uint32_t ab = (1024 + O_AS + wg * 2048) >> 4;
            uint32_t ok = 1;
            const uint32_t tidk = __shfl_sync(0xffffffffu, tid, lane);
            auto token_gemm = [&](auto ll, const bool pause, const uint32_t vo, const uint32_t nbar, const uint32_t npar, const int t) {
                constexpr int l = decltype(ll)::value;
                constexpr uint32_t hb = ((1024 + O_H + l * 40960) >> 4) | (1u << 16);
                const uint32_t pr = opq(p0);
                if (l) TS(15); else TS(14);
                wg_fence();
#pragma unroll
                for (int j = 0; j < 40; j++) {
                    const uint64_t db = mkdesc(hb + ((pr - j / 5) & 7) * 320 + (j % 5) * 64, 0xC0000010u);
                    if (j == 0) wg_n32_sfirst(acc, mkdesc(ab, 0x40000040u), db);
                    else if (j < TG_STEPS) wg_n32(acc, wa[j][0], wa[j][1], wa[j][2], wa[j][3], db);
                    if (l == 0 && (j + 1 == P1A || j + 1 == P1C)) {
                        if (pause && pz == j + 1) {
                            wg_commit();
                            if (role == 2) mwait(bb + B_OTE, vo >> 14);
                            wg_wait<0>();
                            named_arrive(3, 384);
                            named_bar(4, 384);
                            wg_fence();
                        }
                    }
                }
                wg_commit();
                ok = mtest(nbar, npar);
                wg_wait<0>();
                uint32_t pk[8];
#pragma unroll
                for (int i = 0; i < 8; i++) pk[i] = pack2(acc[2 * i], acc[2 * i + 1]);
                if (role == 2) {
                    stsm4(ep_t + l * 8192 + vo, pk[0], pk[1], pk[2], pk[3]);
                    stsm4(ep_t + l * 8192 + vo + 256, pk[4], pk[5], pk[6], pk[7]);
                } else {
                    stsm4t((ep_t ^ (l << 6)) + l * 5120, pk[0], pk[1], pk[2], pk[3]);
                    stsm4t((ep_t ^ (l << 6)) + l * 5120 + 2048, pk[4], pk[5], pk[6], pk[7]);
                }
                asm volatile("{\n.reg .pred p, q;\nsetp.eq.u32 p, %0, 0;\nsetp.eq.u32 q, %1, 0;\n"
                             "@p mbarrier.arrive.expect_tx.shared::cta.b64 _, [%2], %3;\n@q mbarrier.arrive.shared::cluster.b64 _, [%4];\n}"
                             ::"r"(tidk), "r"(tidk & 127), "r"(bb + B_HF + l * 8), "r"(40960), "r"(mapa(bb + B_HE, l)) : "memory");
            };
            GT(tid == 0, 86);
            mwait(bb + B_HF, 0);
            GT(tid == 0, 87);
            token_gemm(IC<0>{}, false, 0, bb + B_MEM, 1, -1);
            GT(tid == 0, 88);
            named_bar(11, 384);
            cluster_wait();
            named_arrive(13, 384);
#pragma unroll 1
            for (int t = 0; t < NT; t++) {
                GT(tid == 0 && blockIdx.x == 98, 100 + t);
                SC(tid == 0 && blockIdx.x == 98, 160 + t);
                TS(0);
                const uint32_t mp = (t & 1) ^ 1;
                const bool tg0 = t + 1 < NSEG, tg1 = t + 1 >= LAG;
                constexpr uint32_t mb = ((1024 + O_MEM) >> 4) | (16u << 16);
#pragma unroll
                for (int G = 0; G < 8; G++) {
                    if (__builtin_expect(!ok, 0)) mwait(bb + B_MEM + G * 8, mp);
                    ok = mtest(G < 7 ? bb + B_MEM + (G + 1) * 8 : bb + B_HF, mp);
                    if (G == 0) { TS(1); wg_fence(); }
                    if (G == 7) TS(2);
                    if (G == 1) TS(8); if (G == 2) TS(9); if (G == 3) TS(10); if (G == 4) TS(11); if (G == 5) TS(12); if (G == 6) TS(13);
#pragma unroll
                    for (int u = 0; u < 5; u++) {
                        const int j = G * 5 + u;
                        const uint64_t db = mkdesc(mb + j * 32, 8);
                        if (j == 0) wg_n16t_sfirst(acc, mkdesc(ab, 0x40000040u), db);
                        else wg_n16t(acc, wa[j][0], wa[j][1], wa[j][2], wa[j][3], db);
                    }
                    wg_commit();
                }
                if (role == 2 && t) named_bar(5, 384);
                wg_wait<0>();
                TS(3);
                if (role == 2) sts128(ep_q, pack2(acc[0], acc[1]), pack2(acc[2], acc[3]), pack2(acc[4], acc[5]), pack2(acc[6], acc[7]));
                else stsm4t(ep_q, pack2(acc[0], acc[1]), pack2(acc[2], acc[3]), pack2(acc[4], acc[5]), pack2(acc[6], acc[7]));
                named_arrive(1, 384);
                if (tidk < 8) mbar_expect_tx(bb + B_MEM + tidk * 8, 2560);
                if (t == NT - 1) break;
                if (tg0) {
                    if (__builtin_expect(!ok, 0)) mwait(bb + B_HF, mp);
                    if (role != 2) named_bar(2, 384);
                    token_gemm(IC<0>{}, true, mp * 16384, tg1 ? bb + B_HF + 8 : bb + B_MEM, tg1 ? (t + 1 - LAG) & 1 : mp ^ 1, t);
                } else {
                    if (role == 2) mwait(bb + B_OTE, mp); else named_bar(2, 384);
                    named_arrive(3, 384); named_bar(4, 384);
                    ok = 0;
                }
                TS(5);
                if (tg1) {
                    if (__builtin_expect(!ok, 0)) mwait(bb + B_HF + 8, (t + 1 - LAG) & 1);
                    token_gemm(IC<1>{}, false, mp * 16384, bb + B_MEM, mp ^ 1, t);
                }
                TS(6);
                named_arrive(13, 384);
            }
        } else {
            cluster_wait(); cluster_arrive_relaxed();
            const int ep = ld_relaxed(&g_epoch) + 1;
            const uint32_t cb = sb + (warp < 4 ? warp * CV_W : CV_HI + (warp - 4) * CV_W), lb = bb + B_MEM + warp * 8;
            auto fetch = [&](int k) {
                const int ps = k / 5, rg = ps ? ps - 1 : 0, ch = (sp * 5 + k - 5 * ps) * 8 + warp;
                if (k == 5 * ps) { flag_wait(FLG(F_U + ps), (ps > 1 ? 20 : (ps ? 32 : 320)) * ep, 50); fence_async_global(); }
                if (lane == 0) {
                    const uint32_t nb = ps ? ps * 1024 : 512;
                    mbar_expect_tx(lb, 2 * nb);
                    asm volatile("cp.async.bulk.shared::cluster.global.mbarrier::complete_tx::bytes [%0], [%1], %2, [%3];" ::"r"(cb + (k & 1) * 4096), "l"(g_U + ch * (S_LEN / 8)), "r"(nb), "r"(lb) : "memory");
                    asm volatile("cp.async.bulk.shared::cluster.global.mbarrier::complete_tx::bytes [%0], [%1], %2, [%3];" ::"r"(cb + 8192 + (k & 1) * CV_E + 128), "l"(A.ssmk + (size_t)ch * S_LEN), "r"(nb), "r"(lb) : "memory");
                }
                __syncwarp();
            };
            sts32(cb + 8192 + lane * 4, 0u); sts32(cb + 8192 + CV_E + lane * 4, 0u);
            if (warp == 0) sts32(sb + CV_Z + lane * 4, 0u);
            uint32_t dv = 0;
            if (lane < 5) {
                prefetch_l2(A.ssmk + (size_t)((sp * 5 + lane) * 8 + warp) * S_LEN, 1024);
                dv = *reinterpret_cast<const unsigned short*>(A.ssmD + (sp * 5 + lane) * 8 + warp) * 0x10001u;
            }
#pragma unroll
            for (int i = 1; i < 5; i++) sts32(cb + 8192 + i * 768 + lane * 4, 0u);
            named_bar(8, 256);
            flag_wait(FLG(F_U), 320 * ep, 50);
            fence_async_global();
            if (lane == 0) mbar_expect_tx(lb, 5120);
            __syncwarp();
            if (lane < 10) {
                const int j = lane >> 1, ch = (sp * 5 + j) * 8 + warp;
                asm volatile("cp.async.bulk.shared::cluster.global.mbarrier::complete_tx::bytes [%0], [%1], %2, [%3];" ::"r"((lane & 1) ? cb + j * 512 : cb + 8192 + j * 768 + 128),
                             "l"((lane & 1) ? (const void*)(g_U + ch * (S_LEN / 8)) : (const void*)(A.ssmk + (size_t)ch * S_LEN)), "r"(512), "r"(lb) : "memory");
            }
            __syncwarp();
#pragma unroll 1
            for (int k = 0; k < 25; k++) {
                const int ps = k / 5, rg = ps ? ps - 1 : 0;
                const uint32_t Dv = __shfl_sync(0xffffffffu, dv, k - 5 * ps);
                const int tb = sp == 0 && tid == 0 && k >= -1 && k < 7 ? 72 + k * 8 : -1;
                SC(tb >= 0, tb);
                if (k == 0 || ps) {
                    mwait(lb, k & 1);
                    SC(tb >= 0, tb + 1);
                    if (ps && k - 5 * ps < 4) { fence_async_smem(); fetch(k + 1); }
                    SC(tb >= 0, tb + 2);
                }
                const uint32_t tt = sb + CV_T + (k & 1) * 8192;
                conv_unit(cb + (ps ? (k & 1) * 4096 : k * 512), cb + 8192 + (ps ? (k & 1) * CV_E : k * 768), cb + 8192 + 2 * CV_E + 64, sb + CV_Z,
                          tt + warp * 1024 + (lane & 7) * 128 + (((lane >> 3) ^ (lane & 7) ^ warp) & 7) * 16, Dv, rg, ps ? 2 * ps : 1, lane, (uint32_t)A.h_target >> 8, tb);
                mwait(bb + B_OTE + (k & 1) * 16, ((k >> 1) & 1) ^ 1);
                named_bar(8, 256);
                {
                    const uint32_t la = tt + (lane & 7) * 1024 + warp * 128 + (((lane >> 3) ^ (lane & 7) ^ warp) & 7) * 16;
                    const uint4 v0 = ldsm4t(la), v1 = ldsm4t(la ^ 64);
                    const uint32_t ya = sb + CV_Y + (k & 1) * 8192 + (warp * 64 + (lane >> 3) * 8 + 7 - (lane & 7)) * 16;
                    stsm4(ya, v0.x, v0.y, v0.z, v0.w);
                    stsm4(ya + 512, v1.x, v1.y, v1.z, v1.w);
                }
                SC(tb >= 0, tb + 6);
                fence_async_smem();
                __syncwarp();
                if (lane == 0) mbar_arrive(bb + B_OTF + (k & 1) * 8);
                if (k - 5 * ps == 4 && k < 24) fetch(k + 1);
                if (k == 0 && lane < 5) prefetch_l2(A.ssmk + (size_t)((sp * 5 + lane) * 8 + warp) * S_LEN + 512, 3072);
            }
            cluster_wait();
        }
    } else if (warp < 12) {
        asm volatile("setmaxnreg.dec.sync.aligned.u32 %0;" ::"n"(REG_T));
        const int w = warp & 3, c = w >> 1, hh = w & 1;
        const uint32_t lane0 = __shfl_sync(0xffffffffu, tid & 31, tid & 31);
        if (head) {
            const int ntile = role == 2 ? 4 * WTC : 4 * WTA;
            auto tile = [&](int i) { return C_REV == 2 ? (int)c_tile[role * 16 + i] : (role == 2 && C_REV ? 39 - i : role * 4 * WTA + i); };
            const uint32_t wo = sb + O_WO;
            uint32_t mi[5][4];
#pragma unroll
            for (int i = 0; i < 5; i++)
#pragma unroll
                for (int q = 0; q < 4; q++) {
                    const unsigned short* mp = reinterpret_cast<const unsigned short*>(A.mem0) + 2 * q * DM + i * 128 + (tid & 127);
                    mi[i][q] = mp[0] | (uint32_t)mp[DM] << 16;
                }
            cluster_wait();
            named_bar(10, 384);
#pragma unroll
            for (int i = 0; i < 5; i++) {
                const int col = i * 128 + (tid & 127), kk = col >> 4, pr = (kk * 13) >> 6;
                const uint32_t ma = sb + O_MEM + (((p0 - pr) & 7) * 5 + kk - 5 * pr) * 512 + (col & 8) * 32 + (col & 7) * 16;
                sts128(ma, mi[i][0], mi[i][0], mi[i][1], mi[i][1]);
                sts128(ma + 128, mi[i][2], mi[i][2], mi[i][3], mi[i][3]);
            }
            fence_async_smem();
            named_arrive(11, 384);
            for (int i = tid & 127; i < ntile * 256; i += 128) {
                const int ti = i >> 8, p = (i >> 1) & 127, ch = i & 1;
                const int ks = p >> 4, kh = (p >> 3) & 1, e8 = p & 7;
                const int dim = 64 * (ks >> 2) + 16 * (e8 >> 1) + 8 * (e8 & 1) + 2 * (ks & 3) + kh;
                cp_async16(wo + ti * 4096 + p * 32 + ((ch ^ ((p >> 2) & 1)) << 4), A.Wo + (size_t)(h * DH + dim) * DM + tile(ti) * 16 + ch * 8);
            }
            cp_commit();
            if (lane < 8) {
                const int u = 2 * tile(w + 4 * (lane >> 1)) + (lane & 1), ow = u / 5;
                const int sl = u - 5 * ow;
                sts32(sb + O_TAB + w * 32 + lane * 4, mapa(sb + O_RED + (sl >> 1) * 2560 + (sl & 1) * 256 + hi * (sl < 4 ? 512 : 256), ow & 15));
            }
            cluster_arrive_relaxed(); cluster_wait();
            cp_wait<0>();
            named_bar(7, 128);
            const uint32_t wo_a = wo + w * 4096 + ((lane >> 4) * 8 + (lane & 7)) * 32 + ((((lane >> 3) & 1) ^ ((lane >> 2) & 1)) << 4);
            const uint32_t ob_0 = sb + (role == 2 ? O_PB : O_OBA) + (lane >> 4) * 2048 + ((lane >> 3) & 1) * 128 + ((lane & 7) ^ ((lane >> 1) & 4)) * 16;
            const float cs = 0.08838834764831845f * 1.4426950408889634f;
            auto w_frag = [&](auto four, int i) {
                return ldsm4t(wo_a + (i < 16 || decltype(four)::value == 4 ? (i >> 4) * 32768 + (i & 1) * 16384 + ((i >> 1) & 7) * 512 : 32768 + (i & 1) * 2048 + ((i >> 1) & 7) * 512));
            };
            auto w_pre = [&](auto four, uint4* wf) {
#pragma unroll
                for (int i = 0; i < 8; i++) wf[i] = w_frag(four, i);
            };
            auto w_run = [&](auto four, auto rem_, uint4* wf, int t, const uint32_t ob_a) {
                constexpr int NTL = decltype(four)::value, NF = 8 * NTL, NP = NTL > 2 ? 2 : 1;
                constexpr bool REMOTE = decltype(rem_)::value;
                const uint32_t ln = opq(lane0), l8 = (ln & 2) * 64 + (ln >> 2) * 16 + (ln & 1) * 8, rb = (bb + B_RED) & 0xFFFFFFu;
                auto slot = [](int i) { return i < 8 ? i : 8 - WR + (i - 8) % WR; };
                uint4 obr[8];
#pragma unroll
                for (int k = 0; k < 4; k++) obr[k] = ldsm4(ob_a + k * 256);
#pragma unroll
                for (int p = 0; p < NP; p++) {
                    const bool split = p == 1 && NTL == 3;
                    const int nk = split ? 4 : 8;
                    float d[4][4];
                    uint4 ta;
#pragma unroll
                    for (int i = 0; i < 16; i++) (&d[0][0])[i] = 0.f;
#pragma unroll
                    for (int ks = 0; ks < 8; ks++) {
                        if (ks >= nk) continue;
                        if (p == 0 && ks == OBK) {
                            if (REMOTE) { mwait(bb + B_OB + 64, t & 1); TS(7); }
#pragma unroll
                            for (int k = 4; k < 8; k++) obr[k] = ldsm4(ob_a + k * 256);
                        }
                        if (ks == nk - 2) ta = lds128(sb + O_TAB + w * 32 + p * 16);
#pragma unroll
                        for (int u = 0; u < 2; u++) {
                            const int i = p * 16 + ks * 2 + u;
                            const uint4& o = obr[split && u ? ks + 4 : ks];
                            const uint4& f = wf[slot(i)];
                            mmav(d[2 * u], f.x, f.y, f.z, f.w, o.x, o.y); mmav(d[2 * u + 1], f.x, f.y, f.z, f.w, o.z, o.w);
                            if (i + WR >= 8 && i + WR < NF) wf[slot(i + WR)] = w_frag(four, i + WR);
                        }
                    }
                    if (p) TS(10); else TS(8);
                    if (split) {
#pragma unroll
                        for (int i = 0; i < 4; i++) { d[0][i] += d[2][i]; d[1][i] += d[3][i]; }
                    }
                    st_async_v2(ta.x + l8, pack2(d[0][0], d[0][1]), pack2(d[1][0], d[1][1]), (ta.x & 0xFF000000u) | rb);
                    st_async_v2(ta.y + l8, pack2(d[0][2], d[0][3]), pack2(d[1][2], d[1][3]), (ta.y & 0xFF000000u) | rb);
                    if (!split) {
                        st_async_v2(ta.z + l8, pack2(d[2][0], d[2][1]), pack2(d[3][0], d[3][1]), (ta.z & 0xFF000000u) | rb);
                        st_async_v2(ta.w + l8, pack2(d[2][2], d[2][3]), pack2(d[3][2], d[3][3]), (ta.w & 0xFF000000u) | rb);
                    }
                }
            };
            if (role != 2) {
#pragma unroll 1
                for (int t = 0; t < NT; t++) {
                    const uint32_t lane = opq(lane0);
                    const uint32_t dc = mapa(sb, hi * 3 + 2), dp = mapa(sb, hi * 3 + (role ^ 1));
                    const uint32_t qa = sb + O_QRY + c * 5120 + (lane & 7) * 128;
                    const uint32_t sw = (((lane >> 3) ^ (lane & 7)) << 4) ^ (c << 6);
                    {
                        const uint32_t ka = qa + 10240;
                        const uint32_t kt = sb + O_KEY + c * 5120 + (lane & 15) * 128, kx = (((lane >> 4) ^ (lane & 7)) << 4) ^ (c << 6);
                        const uint32_t sd = dc + O_SM + role * 1536 + c * 768 + lane * 4, sbar = dc + O_BAR + B_SM;
                        const uint32_t ta = sb + O_QRY + c * 5120 + (8 + 16 * hh + ((lane & 15) ^ (role * 8))) * 128;
                        uint4 a[4], f[4];
                        named_bar(13, 384);
#pragma unroll
                        for (int i = 0; i < 4; i++) f[i] = ldsm4(kt + 1024 + hh * 2048 + (kx ^ (i << 5) ^ (hh << 6)));
#pragma unroll
                        for (int i = 0; i < 4; i++) a[i] = ldsm4(ta + (kx ^ (i << 5)));
                        const uint32_t kd = ka + (1 + 2 * hh) * 1024 + sw;
                        uint4 k[5];
                        k[1] = ldsm4(kd); k[2] = ldsm4(kd + 1024);
                        {
                            const uint32_t qh = qa + (sw ^ (hh << 6)), kh = kt + (kx ^ (hh << 6));
                            named_bar(1, 384);
                            const uint4 q0 = ldsm4(qh), g0 = ldsm4(kh), g1 = ldsm4(kh ^ 32), q1 = ldsm4(qh ^ 64);
                            float s0[4] = {0.f, 0.f, 0.f, 0.f}, s1[4] = {0.f, 0.f, 0.f, 0.f}, s2[4] = {0.f, 0.f, 0.f, 0.f}, s3[4] = {0.f, 0.f, 0.f, 0.f};
                            mmav(s0, f[0].x, f[0].y, f[0].z, f[0].w, q0.x, q0.y); mmav(s1, f[1].x, f[1].y, f[1].z, f[1].w, q0.z, q0.w);
                            mmav(s2, g0.x, g0.y, g0.z, g0.w, q0.x, q0.y); mmav(s3, g1.x, g1.y, g1.z, g1.w, q0.z, q0.w);
                            mmav(s0, f[2].x, f[2].y, f[2].z, f[2].w, q1.x, q1.y); mmav(s1, f[3].x, f[3].y, f[3].z, f[3].w, q1.z, q1.w);
                            k[0] = ldsm4(ka + sw); k[3] = ldsm4(ka + 1024 + sw); k[4] = ldsm4(ka + 2048 + sw);
                            st_async_b32(sd + hh * 128, pack2(s2[0] + s3[0], s2[1] + s3[1]), sbar);
                            st_async_b32(sd + 256 + hh * 256, pack2(s0[0] + s1[0], s0[1] + s1[1]), sbar);
                            st_async_b32(sd + 384 + hh * 256, pack2(s0[2] + s1[2], s0[3] + s1[3]), sbar);
                        }
                        TS(1);
                        float u[5][4];
#pragma unroll
                        for (int i = 0; i < 20; i++) (&u[0][0])[i] = 0.f;
                        auto half = [&](auto nn, const uint4& a0, const uint4& a1, bool more) {
                            constexpr int NU = decltype(nn)::value;
                            constexpr int ord[5] = {1, 2, 0, 3, 4};
#pragma unroll
                            for (int i = 0; i < NU; i++) mmav(u[ord[i]], a0.x, a0.y, a0.z, a0.w, k[ord[i]].x, k[ord[i]].y);
#pragma unroll
                            for (int i = 0; i < NU; i++) {
                                const int n = ord[i];
                                mmav(u[n], a1.x, a1.y, a1.z, a1.w, k[n].z, k[n].w);
                                if (more) k[n] = ldsm4(((n == 0 ? ka + sw : (n < 3 ? kd + (n - 1) * 1024 : ka + (n - 2) * 1024 + sw))) ^ 64);
                            }
                        };
                        auto fu = [](float x) { return __float_as_uint(x); };
                        const uint32_t so = O_ST + c * 2048 + hh * 768, td = dp + so, tb = dp + O_BAR + B_ST, lo = sb + so + 4096;
                        if (hh) {
                            half(IC<5>{}, a[0], a[1], true); half(IC<5>{}, a[2], a[3], false);
                            st_async_v4(td + lane * 16, fu(u[0][2]), fu(u[0][3]), fu(u[1][2]), fu(u[1][3]), tb);
                            st_async_v4(td + 512 + lane * 16, fu(u[2][2]), fu(u[2][3]), fu(u[3][2]), fu(u[3][3]), tb);
                            st_async_v2(td + 1024 + lane * 8, fu(u[4][2]), fu(u[4][3]), tb);
                            sts128(lo + lane * 16, fu(u[0][0]), fu(u[0][1]), fu(u[1][0]), fu(u[1][1]));
                            sts128(lo + 512 + lane * 16, fu(u[2][0]), fu(u[2][1]), fu(u[3][0]), fu(u[3][1]));
                            sts64(lo + 1024 + lane * 8, fu(u[4][0]), fu(u[4][1]));
                        } else {
                            half(IC<3>{}, a[0], a[1], true); half(IC<3>{}, a[2], a[3], false);
                            st_async_v4(td + lane * 16, fu(u[0][2]), fu(u[0][3]), fu(u[1][2]), fu(u[1][3]), tb);
                            st_async_v2(td + 512 + lane * 8, fu(u[2][2]), fu(u[2][3]), tb);
                            sts128(lo + lane * 16, fu(u[0][0]), fu(u[0][1]), fu(u[1][0]), fu(u[1][1]));
                            sts64(lo + 512 + lane * 8, fu(u[2][0]), fu(u[2][1]));
                        }
                        if (t < NT - 1) named_arrive(2, 384);
                        __syncwarp();
                        if (lane == 0) mbar_arrive(bb + B_ST);
                        TS(2);
                    }
                    if (t == NT - 1) break;
                    uint4 wf[8];
                    w_pre(IC<WTA>{}, wf);
                    mwait(bb + B_OB, t & 1);
                    TS(3);
                    named_bar(3, 384);
                    w_run(IC<WTA>{}, IC<1>{}, wf, t, ob_0);
                    named_arrive(4, 384);
                    if (w == 0 && lane == 0) { mbar_expect_tx(bb + B_OB, 2048); mbar_expect_tx(bb + B_OB + 64, 2048); }
                    TS(5);
                }
            } else {
#pragma unroll 1
                for (int t = 0; t < NT; t++) {
                    const uint32_t lane = opq(lane0);
                    const int g = lane >> 2, tq = lane & 3;
                    const uint32_t vm_a = sb + O_VM + (g * 4 + 2 * (tq & 1) + (c ^ ((g >> 1) & 1))) * 16 + (tq >> 1) * 8;
                    const uint32_t vt_a = sb + O_VT + (t & 1) * 16384 + ((lane >> 3) & 1) * 512 + (lane >> 4) * 128 + (lane & 7) * 16;
                    named_bar(13, 384);
                    uint4 va[4][2];
#pragma unroll
                    for (int i = 0; i < 4; i++) {
                        va[i][0] = ldsm4(vt_a + c * 8192 + (4 * hh + i) * 1024);
                        va[i][1] = ldsm4(vt_a + c * 8192 + (4 * hh + i) * 1024 + 256);
                    }
                    const uint32_t sa = opq(sb + O_SM + c * 768 + 256 + lane * 16), sa2 = opq(sb + O_SM + c * 768 + (lane & 15) * 16 + (lane >> 4) * 1536), vm_b = opq(vm_a + hh * 2048);
                    named_bar(1, 384);
                    if (__builtin_expect(t < NT - 1, 1)) {
                        uint2 vm[4];
#pragma unroll
                        for (int i = 0; i < 4; i++) vm[i] = lds64(vm_b + i * 512);
                        mwait(bb + B_SM, t & 1);
                        TS(1);
                        const uint4 x0 = ldsm4t(sa), y0 = ldsm4t(sa + 1536), x1 = ldsm4t(sa2);
                        float s[10];
                        s[2] = blo(x0.x) + blo(y0.x); s[3] = bhi(x0.x) + bhi(y0.x); s[4] = blo(x0.y) + blo(y0.y); s[5] = bhi(x0.y) + bhi(y0.y);
                        s[6] = blo(x0.z) + blo(y0.z); s[7] = bhi(x0.z) + bhi(y0.z); s[8] = blo(x0.w) + blo(y0.w); s[9] = bhi(x0.w) + bhi(y0.w);
                        s[0] = (blo(x1.x) + blo(x1.y)) + (blo(x1.z) + blo(x1.w)); s[1] = (bhi(x1.x) + bhi(x1.y)) + (bhi(x1.z) + bhi(x1.w));
                        float mx = fmaxf(fmaxf(fmaxf(s[0], s[1]), fmaxf(s[2], s[3])), fmaxf(fmaxf(fmaxf(s[4], s[5]), fmaxf(s[6], s[7])), fmaxf(s[8], s[9])));
                        const float m1 = __shfl_xor_sync(0xffffffffu, mx, 1), m2 = __shfl_xor_sync(0xffffffffu, mx, 2), m3 = __shfl_xor_sync(0xffffffffu, mx, 3);
                        mx = fmaxf(fmaxf(mx, m1), fmaxf(m2, m3)) * -cs;
                        uint32_t pb[5];
#pragma unroll
                        for (int i = 0; i < 5; i++) pb[i] = pack2(ex2f(fmaf(s[2 * i], cs, mx)), ex2f(fmaf(s[2 * i + 1], cs, mx)));
                        TS(9);
                        named_bar(3, 384);
                        float o[5][4];
#pragma unroll
                        for (int i = 0; i < 20; i++) (&o[0][0])[i] = 0.f;
                        const uint32_t one2 = 0x3F803F80u;
                        float z[2][4] = {{0.f, 0.f, 0.f, 0.f}, {0.f, 0.f, 0.f, 0.f}};
                        mmav8(o[4], one2, one2, pb[0]);
                        mmav(z[0], one2, one2, one2, one2, pb[1], pb[2]);
                        mmav(z[1], one2, one2, one2, one2, pb[3], pb[4]);
#pragma unroll
                        for (int i = 0; i < 4; i++) mmav8(o[i], vm[i].x, vm[i].y, pb[0]);
#pragma unroll
                        for (int i = 0; i < 4; i++) mmav(o[i], va[i][0].x, va[i][0].y, va[i][0].z, va[i][0].w, pb[1], pb[2]);
#pragma unroll
                        for (int i = 0; i < 4; i++) mmav(o[i], va[i][1].x, va[i][1].y, va[i][1].z, va[i][1].w, pb[3], pb[4]);
                        o[4][0] += z[0][0] + z[1][0]; o[4][1] += z[0][1] + z[1][1];
                        uint4 wf[8];
                        w_pre(IC<WTC>{}, wf);
                        const float r0 = rcpf(o[4][0]), r1 = rcpf(o[4][1]);
                        const uint32_t oo = c * 2048 + hh * 1024 + g * 128 + tq * 16 + (g & 1) * 64;
                        uint32_t e0[4], e1[4];
#pragma unroll
                        for (int i = 0; i < 4; i++) { e0[i] = pack2(o[i][0] * r0, o[i][2] * r0); e1[i] = pack2(o[i][1] * r1, o[i][3] * r1); }
                        sts128(sb + O_PB + (~t & 1) * 5120 + oo, e0[0], e0[1], e0[2], e0[3]);
                        sts128(sb + O_PB + (~t & 1) * 5120 + (oo ^ 64), e1[0], e1[1], e1[2], e1[3]);
                        {
                            const uint32_t da = mapa(sb + O_OBA, r - 2) + oo, ba = mapa(bb + B_OB + hh * 64, r - 2);
                            st_async_v4(da, e0[0], e0[1], e0[2], e0[3], ba);
                            st_async_v4(da + 0x01000000u, e0[0], e0[1], e0[2], e0[3], ba + 0x01000000u);
                            st_async_v4(da ^ 64, e1[0], e1[1], e1[2], e1[3], ba);
                            st_async_v4((da ^ 64) + 0x01000000u, e1[0], e1[1], e1[2], e1[3], ba + 0x01000000u);
                        }
                        TS(3);
                        named_bar(7, 128);
                        w_run(IC<WTC>{}, IC<0>{}, wf, t, ob_0 + (~t & 1) * 5120);
                        named_arrive(4, 384);
                        mwait(bb + B_ST, t & 1);
                        TS(4);
                    } else { mwait(bb + B_SM, t & 1); mwait(bb + B_ST, t & 1); }
                    TS(5);
                    fence_async_smem();
#pragma unroll 1
                    for (int l = t < NSEG ? 0 : 1; l < (t >= LAG ? 2 : 1); l++) {
                        const uint32_t pb_ = ((1024 + O_PB) >> 4) + (t & 1) * 320 + l * 160, va_ = (((1024 + O_VT) >> 4) + (t & 1) * 1024 + l * 512) | (8u << 16);
                        const uint32_t oa = sb + O_VT + (t & 1) * 16384 + l * 8192 + w * 1024 + g * 64 + ((tq ^ (g >> 1)) & 3) * 16;
                        const uint32_t vl = (vm_a ^ ((l ^ c) << 4)) + w * 512;
                        const uint2 a0 = lds64(vl), a1 = lds64(vl + 2048);
                        float d[2][16];
                        wg_fence();
                        wg_n32_first(d[0], a0.x, a0.y, 0u, 0u, mkdesc(pb_, 8));
                        wg_n32_first(d[1], a1.x, a1.y, 0u, 0u, mkdesc(pb_, 8));
#pragma unroll
                        for (int i = 0; i < 4; i++) wg_n32_kk(d[i & 1], mkdesc(va_ + (i & 1) * 256 + (i >> 1) * 16, 32), mkdesc(pb_ + 32 + (i >> 1) * 64 + (32u << 16), 8));
                        wg_commit();
                        if (l) TS(13); else TS(11);
                        wg_wait<0>();
                        if (l) TS(14); else TS(12);
#pragma unroll
                        for (int mt = 0; mt < 2; mt++) {
                            sts128(oa + mt * 4096, pack2(d[mt][0], d[mt][1]), pack2(d[mt][4], d[mt][5]), pack2(d[mt][8], d[mt][9]), pack2(d[mt][12], d[mt][13]));
                            sts128(oa + mt * 4096 + 512, pack2(d[mt][2], d[mt][3]), pack2(d[mt][6], d[mt][7]), pack2(d[mt][10], d[mt][11]), pack2(d[mt][14], d[mt][15]));
                        }
                        if (l == 0) {
                            fence_async_smem();
                            __syncwarp();
                            if (lane == 0) mbar_arrive(bb + B_OTF + 8);
                        }
                    }
                    TS(6);
                    if (w == 0 && lane == 0) { mbar_expect_tx(bb + B_ST, 5120); mbar_expect_tx(bb + B_SM, 3072); }
                    fence_async_smem();
                    __syncwarp();
                    if (lane == 0) mbar_arrive(bb + B_OTF);
                    if (t < NT - 1) named_arrive(5, 384);
                }
            }
        } else {
            cluster_wait(); cluster_arrive_relaxed();
            const int wi = sp * 4 + w, half = wi >> 5, tok = wi & 31, ep = ld_relaxed(&g_epoch) + 1;
            GT(lane == 0, 89);
            if (lane < LN0_AHEAD / 2) prefetch_l2(A.x + (size_t)((half + 2 * lane) * SEG + tok) * DM, 1280);
#pragma unroll 1
            for (int k = -LN0_AHEAD / 2; k < NT; k++) {
                const int s0 = k < 0 ? 2 * k + LN0_AHEAD + half : (half && k % LN0_BATCH == 0 ? k + LN0_AHEAD : NSEG);
                if (s0 < NSEG) { ln0_rows(A.x, s0, k < 0 ? 1 : LN0_BATCH, tok, lane); GT(lane == 0 && k < 0, 30 + s0); }
                if (k == -1 && half) {
#pragma unroll 1
                    for (int u = 320 + tok; u < 640; u += 32) u_half(A.Bk, A.Bv, A.shiftk, u, lane);
                    __syncwarp();
                    if (lane == 0) red_release(FLG(F_U + 1), 1);
                }
                const int n = k - half * LAG;
                if (n >= 0 && n < NSEG && k >= 0) {
                    post_row(half, n, tok, lane, A.x, A.out, ep);
                    GT(lane == 0 && (n & 3) == 0 && k >= 0, 460 + half * 16 + (n >> 2)); GT(lane == 0 && n == 63 && half, 40);
                }
            }
            cluster_wait();
        }
    } else {
        asm volatile("setmaxnreg.dec.sync.aligned.u32 %0;" ::"n"(REG_X));
        cluster_wait();
        const int s = warp - 12;
        const uint32_t lane0 = __shfl_sync(0xffffffffu, tid & 31, tid & 31);
        if (s < 3) {
            cluster_arrive_relaxed();
            GT(lane == 0, 84);
            if (blockIdx.x * 3 + s < 320) {
                u_half(A.Bk, A.Bv, A.shiftk, blockIdx.x * 3 + s, lane);
                GT(lane == 0, 85);
                __syncwarp();
                if (lane == 0) red_release(FLG(F_U), 1);
                GT(lane == 0, 4);
            }
            const int ztgt = 3 * 16 * NCL * (ld_relaxed(&g_epoch) + 1);
#pragma unroll
            for (int i = 0; i < XRS; i++) st_relaxed_v4(g_xc + ((i * 16 + r) * 3 + s) * 256 + cq * 32 + lane, 0, 0, 0, 0);
            __syncwarp();
            if (lane == 0) red_release(FLG(F_Z), 1);
            cluster_wait();
            constexpr uint32_t XSLOT = 16 * 3 * 4096;
            uint32_t xo_ = (r * 3 + s) * 4096;
            if (s == 0) {
                const uint32_t G = lane >> 1, d = ((r + 2 * G) & 15) ^ (lane & 1);
                if (lane < 16) { sts32(sb + O_BT + lane * 8, (d << 24) + G * 2560); sts32(sb + O_BT + lane * 8 + 4, d < 3 * nh ? mapa(bb + B_MEM + G * 8, d) : 0u); }
            }
            while (ld_acquire(FLG(F_Z)) < ztgt) __nanosleep(100);
            named_bar(14, 96);
#pragma unroll 1
            for (int t = 0; t < NT; t++) {
                const uint32_t lane = opq(lane0);
                if (head && role != 2) {
                    auto soft = [&](auto uu, auto vv, int c0, int hh) {
                        constexpr int U = decltype(uu)::value, NV = decltype(vv)::value;
                        const uint32_t dc = mapa(sb, hi * 3 + 2), sa = sb + O_ST + c0 * 2048 + hh * 768;
                        const uint32_t pd = dc + O_PB + (t & 1) * 5120 + c0 * 2560 + (2 * hh + role) * 128 + lane * 4, pbar = dc + O_BAR + B_ST;
                        const int lim = 8 * role + (int)(lane >> 2) - 2 * (int)(lane & 3);
                        auto uf = [](uint32_t x) { return __uint_as_float(x); };
                        mwait(bb + B_ST, t & 1);
                        if (r == 1 && U == 2 && t >= LAG - 1 && t < NT - 1) named_arrive(12, 64);
                        uint32_t z[U][NV];
                        auto zz = [](float x, float y) { const uint32_t w = pack2(x, y); return pack2(blo(w) * 0.08838834764831845f, bhi(w) * 0.08838834764831845f); };
#pragma unroll
                        for (int i = 0; i < U; i++) {
                            const uint4 v = lds128(sa + i * 2048 + lane * 16), w = lds128(sa + i * 2048 + 4096 + lane * 16);
                            z[i][0] = zz(uf(v.x) + uf(w.x), uf(v.y) + uf(w.y));
                            z[i][1] = zz(lim < 0 ? -INFINITY : uf(v.z) + uf(w.z), lim < 1 ? -INFINITY : uf(v.w) + uf(w.w));
                            if (NV == 3) {
                                const uint2 x = lds64(sa + i * 2048 + 512 + lane * 8), y = lds64(sa + i * 2048 + 4608 + lane * 8);
                                z[i][2] = zz(lim < 8 ? -INFINITY : uf(x.x) + uf(y.x), lim < 9 ? -INFINITY : uf(x.y) + uf(y.y));
                            } else {
                                const uint4 x = lds128(sa + 512 + lane * 16), y = lds128(sa + 4608 + lane * 16);
                                const uint2 p = lds64(sa + 1024 + lane * 8), q = lds64(sa + 5120 + lane * 8);
                                z[i][2] = zz(lim < 8 ? -INFINITY : uf(x.x) + uf(y.x), lim < 9 ? -INFINITY : uf(x.y) + uf(y.y));
                                z[i][NV - 2] = zz(uf(x.z) + uf(y.z), uf(x.w) + uf(y.w));
                                z[i][NV - 1] = zz(uf(p.x) + uf(q.x), uf(p.y) + uf(q.y));
                            }
                        }
                        const float l2e = 1.4426950408889634f;
                        float e[U][2 * NV], sum[U];
#pragma unroll
                        for (int i = 0; i < U; i++) {
                            uint32_t zm = bmax2(bmax2(z[i][0], z[i][1]), z[i][2]);
                            if (NV == 5) zm = bmax2(zm, bmax2(z[i][NV - 2], z[i][NV - 1]));
                            zm = bmax2(zm, __shfl_xor_sync(0xffffffffu, zm, 1));
                            zm = bmax2(zm, __shfl_xor_sync(0xffffffffu, zm, 2));
                            const float mx = fmaxf(blo(zm), bhi(zm)) * -l2e;
                            sum[i] = 0.f;
#pragma unroll
                            for (int n = 0; n < NV; n++) { e[i][2 * n] = ex2f(fmaf(blo(z[i][n]), l2e, mx)); e[i][2 * n + 1] = ex2f(fmaf(bhi(z[i][n]), l2e, mx)); }
                            sum[i] = ((e[i][0] + e[i][1]) + (e[i][2] + e[i][3])) + (e[i][4] + e[i][5]);
                            if (NV == 5) sum[i] += (e[i][2 * NV - 4] + e[i][2 * NV - 3]) + (e[i][2 * NV - 2] + e[i][2 * NV - 1]);
                            sum[i] += __shfl_xor_sync(0xffffffffu, sum[i], 1);
                            sum[i] += __shfl_xor_sync(0xffffffffu, sum[i], 2);
                            sum[i] = rcpf(sum[i]);
                        }
#pragma unroll
                        for (int i = 0; i < U; i++)
#pragma unroll
                            for (int n = 0; n < 5; n++)
                                st_async_b32(pd + i * 2560 + (n == 0 ? 0 : (NV == 3 ? n : (n < 3 ? n + 2 : n - 2)) * 512), n < NV ? pack2(e[i][2 * n] * sum[i], e[i][2 * n + 1] * sum[i]) : 0u, pbar);
                    };
                    if (s < 2) soft(IC<1>{}, IC<5>{}, s, 1); else soft(IC<2>{}, IC<3>{}, 0, 0);
                    TS(12);
                    named_bar(14, 96);
                    if (s == 0 && lane == 0) mbar_expect_tx(bb + B_ST, 4096);
                }
                if (t == NT - 1) break;
                uint32_t m0 = 0x80008000u, m1 = 0x80008000u;
                if (t < LAG && cq == 0) {
                    const uint32_t ch = s < 2 ? lane : lane >> 1;
                    const unsigned short* mp = reinterpret_cast<const unsigned short*>(A.mem0) + (((ch >> 3) & 1) * 4 + (s < 2 ? 0 : (lane & 1) * 2)) * DM + (5 * r + 2 * s + (ch >> 4)) * 8 + (ch & 7);
                    m0 = max(mp[0] | (uint32_t)mp[DM] << 16, 1u);
                    if (s < 2) m1 = max(mp[2 * DM] | (uint32_t)mp[3 * DM] << 16, 1u);
                }
                const bool late = t >= LAG;
                auto sum5 = [](uint32_t a, uint32_t b, uint32_t c, uint32_t d, uint32_t e) { return nz(badd(badd(badd(a, b), e), badd(c, d))); };
                auto sum7 = [](uint32_t a, uint32_t b, uint32_t c, uint32_t d, uint32_t e, uint32_t f, uint32_t h_) {
                    return badd(badd(badd(a, b), badd(c, d)), badd(badd(e, f), h_));
                };
                auto min3 = [](uint32_t a, uint32_t b, uint32_t c) { return min(min(a, b), c); };
                auto bcast = [&](auto two, const uint32_t aa, uint32_t x0, uint32_t x1, uint32_t x2, uint32_t x3) {
                    auto send = [&](uint32_t o, uint32_t bar) { if (decltype(two)::value) st_async_v4p(aa + o, x0, x1, x2, x3, bar); else st_async_v2p(aa + o, x0, x1, bar); };
                    uint4 e[5];
                    e[0] = lds128(sb + O_BT);
                    TS(8);
                    send(e[0].x, e[0].y); send(e[0].z, e[0].w);
                    TS(9);
#pragma unroll
                    for (int i = 1; i < 5; i++) e[i] = lds128(sb + O_BT + i * 16);
#pragma unroll
                    for (int i = 1; i < 8; i++) {
                        send(e[(i - 1) % 4 + 1].x, e[(i - 1) % 4 + 1].y); send(e[(i - 1) % 4 + 1].z, e[(i - 1) % 4 + 1].w);
                        if (i < 4) e[i] = lds128(sb + O_BT + (i + 4) * 16);
                    }
                };
                const uint32_t ma = (sb + O_MEM + (5 * (r & 1) + 2 * s) * 256) & 0xFFFFFFu;
                int guard = 0;
                if (s < 2) {
                    const uint32_t ra = sb + O_RED + s * 2560 + lane * 16;
                    uint4* xb = reinterpret_cast<uint4*>(reinterpret_cast<char*>(g_xc) + xo_ + lane * 16);
                    uint4* xo = xb + cq * 32;
                    touch(xo); touch(xb);
                    mwait(bb + B_RED, t & 1);
                    TS(0);
                    uint4 p[5];
#pragma unroll
                    for (int i = 0; i < 5; i++) p[i] = i < 4 || nh == 5 ? lds128(ra + i * 512) : make_uint4(0, 0, 0, 0);
                    const uint32_t u1 = sum5(p[0].y, p[1].y, p[2].y, p[3].y, p[4].y), u3 = sum5(p[0].w, p[1].w, p[2].w, p[3].w, p[4].w);
                    st_relaxed_v4(xo, sum5(p[0].x, p[1].x, p[2].x, p[3].x, p[4].x), late ? u1 : m0, sum5(p[0].z, p[1].z, p[2].z, p[3].z, p[4].z), late ? u3 : m1);
                    TS(1);
                    delay(XD);
                    uint4 x[NCL];
                    while (true) {
                        ld7_relaxed(x, xb);
                        const uint32_t mn = min3(min3(min3(x[0].x, x[0].y, x[0].z), min3(x[0].w, x[1].x, x[1].y), min3(x[1].z, x[1].w, x[2].x)),
                                                 min3(min3(x[2].y, x[2].z, x[2].w), min3(x[3].x, x[3].y, x[3].z), min3(x[3].w, x[4].x, x[4].y)),
                                                 min3(min3(x[4].z, x[4].w, x[5].x), min3(x[5].y, x[5].z, x[5].w), min(min3(x[6].x, x[6].y, x[6].z), x[6].w)));
                        if (NO_X || __all_sync(0xffffffffu, mn != 0)) break;
                        if (++guard > 2000000) __trap();
                    }
                    TS(2);
                    TV(4, guard);
                    bcast(IC<1>{}, ma + lane * 16, sum7(x[0].x, x[1].x, x[2].x, x[3].x, x[4].x, x[5].x, x[6].x), sum7(x[0].y, x[1].y, x[2].y, x[3].y, x[4].y, x[5].y, x[6].y),
                          sum7(x[0].z, x[1].z, x[2].z, x[3].z, x[4].z, x[5].z, x[6].z), sum7(x[0].w, x[1].w, x[2].w, x[3].w, x[4].w, x[5].w, x[6].w));
                } else {
                    const uint32_t ra = sb + O_RED + 5120 + lane * 8;
                    uint2* xb = reinterpret_cast<uint2*>(reinterpret_cast<char*>(g_xc) + xo_ + lane * 8);
                    uint2* xo = xb + cq * 64;
                    touch(xo); touch(xb);
                    mwait(bb + B_RED, t & 1);
                    TS(0);
                    uint2 p[5];
#pragma unroll
                    for (int i = 0; i < 5; i++) p[i] = i < 4 || nh == 5 ? lds64(ra + i * 256) : make_uint2(0, 0);
                    const uint32_t u1 = sum5(p[0].y, p[1].y, p[2].y, p[3].y, p[4].y);
                    st_relaxed_v2(xo, sum5(p[0].x, p[1].x, p[2].x, p[3].x, p[4].x), late ? u1 : m0);
                    if (lane == 0) mbar_expect_tx(bb + B_RED, nh * 1280);
                    TS(1);
                    delay(XD);
                    uint32_t y0, y1;
                    while (true) {
                        uint2 x[NCL];
                        ld7_relaxed(x, xb);
                        const uint32_t mn = min3(min3(min3(x[0].x, x[0].y, x[1].x), min3(x[1].y, x[2].x, x[2].y), min3(x[3].x, x[3].y, x[4].x)), min3(x[4].y, x[5].x, x[5].y), min(x[6].x, x[6].y));
                        y0 = sum7(x[0].x, x[1].x, x[2].x, x[3].x, x[4].x, x[5].x, x[6].x); y1 = sum7(x[0].y, x[1].y, x[2].y, x[3].y, x[4].y, x[5].y, x[6].y);
                        if (NO_X || __all_sync(0xffffffffu, mn != 0)) break;
                        if (++guard > 2000000) __trap();
                    }
                    TS(2);
                    TV(4, guard);
                    bcast(IC<0>{}, ma + lane * 8, y0, y1, 0u, 0u);
                }
                TS(3);
                if (head && role == 2) named_arrive(6, 128);
                xo_ += XSLOT; if (xo_ >= XRS * XSLOT) xo_ -= XRS * XSLOT;
                {
                    const uint32_t zo = xo_ + XSLOT >= XRS * XSLOT ? xo_ + XSLOT - XRS * XSLOT : xo_ + XSLOT;
                    char* zp = reinterpret_cast<char*>(g_xc) + zo + cq * 512 + lane * 16;
                    st_relaxed_v4(zp, 0, 0, 0, 0);
                    if (ld_relaxed_v4(zp).x) __trap();
                }
            }
        } else if (r < 2) {
            const uint16_t mask = (uint16_t)((1u << (3 * nh)) - 1u);
            const int htgt = A.h_target * (ld_relaxed(&g_epoch) + 1);
#pragma unroll 1
            for (int n = 0; n < NSEG; n++) {
                if (n == (r == 0 ? 1 : 0)) { cluster_arrive(); cluster_wait(); }
                int guard = 0;
                while (ld_acquire(FLG(F_H + r * 64 + n)) < htgt) { if (++guard > 2000000) __trap(); __nanosleep(H_NS); }
                fence_async_global();
                if (r == 1) named_bar(12, 64);
                if (n) mwait(bb + B_HE, (n - 1) & 1);
                if (lane < 8)
                    asm volatile("cp.async.bulk.shared::cluster.global.mbarrier::complete_tx::bytes.multicast::cluster [%0], [%1], %2, [%3], %4;" ::"r"(sb + O_H + r * 40960 + lane * 5120),
                                 "l"(g_ht + rslot(r, n) * 2560 + lane * 320), "r"(5120), "r"(bb + B_HF + r * 8), "h"(mask) : "memory");
                __syncwarp();
            }
        } else {
            cluster_arrive(); cluster_wait();
            if (head && role == 2) {
#pragma unroll 1
                for (int t = 0; t < NT; t++) {
                    auto put = [&](int l, int n) {
                        asm volatile("cp.async.bulk.global.shared::cta.bulk_group [%0], [%1], %2;" ::"l"(g_ot + (rslot(l, n) * 256 + h * 8) * 64), "r"(sb + O_VT + (t & 1) * 16384 + l * 8192), "r"(8192) : "memory");
                        asm volatile("cp.async.bulk.commit_group;" ::: "memory");
                    };
                    auto publish = [&](int l, int n) {
                        asm volatile("cp.async.bulk.wait_group 0;" ::: "memory");
                        fence_async_global();
                        red_release(FLG(F_O + l * 64 + n) + (h >> 3), 1);
                        GT(true, 200 + l * 64 + n);
                        if (ONE_FENCE && l == 0 && n > LAG) {
                            asm volatile("red.relaxed.gpu.global.add.u32 [%0], 1;" ::"l"(FLG(F_O + 63 - LAG + n) + (h >> 3)) : "memory");
                            GT(true, 263 - LAG + n);
                        }
                    };
                    if (t < NSEG) {
                        mwait(bb + B_OTF + 8, t & 1);
                        if (lane == 0) { put(0, t); publish(0, t); }
                        __syncwarp();
                    }
                    mwait(bb + B_OTF, t & 1);
                    if (t < NT - 1) named_bar(6, 128);
                    if (lane == 0) {
                        if (t >= LAG) {
                            put(1, t - LAG);
                            asm volatile("cp.async.bulk.wait_group.read 0;" ::: "memory");
                        }
                        mbar_arrive(bb + B_OTE);
                        if (t >= (ONE_FENCE ? NSEG - 1 : LAG)) publish(1, t - LAG);
                    }
                    __syncwarp();
                }
            }
            if (!head && lane == 0) {
#pragma unroll 1
                for (int k = 0; k < 25; k++) {
                    const int rg = k / 5, r0 = rg == 1 ? 256 : 0;
                    mwait(bb + B_OTF + (k & 1) * 8, (k >> 1) & 1);
                    asm volatile("cp.async.bulk.global.shared::cta.bulk_group [%0], [%1], %2;" ::"l"(g_Y + (sp * 5 + k - 5 * rg) * S_LEN + (rg ? rg - 1 : 0) * 512 + r0),
                                 "r"(sb + CV_Y + (k & 1) * 8192 + r0 * 16), "r"(rg < 2 ? 4096 : 8192) : "memory");
                    asm volatile("cp.async.bulk.commit_group;" ::: "memory");
                    asm volatile("cp.async.bulk.wait_group 0;" ::: "memory");
                    mbar_arrive(bb + B_OTE + (k & 1) * 16);
                    fence_async_global();
                    red_release(FLG(F_CV + rg), 1);
                    GT(true, 50 + k);
                }
            }
            __syncwarp();
        }
    }
    cluster_arrive(); cluster_wait();
    if (blockIdx.x == 0 && tid == 0) atomicAdd(&g_epoch, 1);
}
}

namespace ws {
constexpr int OP_SS = 17;
constexpr int P_RING = 0, P_AS = 131072, P_STG = P_AS + 2 * OP_SS * 2048, P_BAR = P_STG + 16384, OP_SMEM = P_BAR + 256;
constexpr int PB_FULL = 0, PB_EMPTY = 128, PB_SF = 144, PB_SE = 176;
static_assert(OP_SMEM <= 232448, "smem");

__global__ void __launch_bounds__(384, 1) op_kernel(const bf16* __restrict__ Wo, const bf16* __restrict__ Bk, const bf16* __restrict__ Bv, const bf16* __restrict__ shiftk) {
    extern __shared__ __align__(1024) unsigned char smem_raw[];
    const int tid = threadIdx.x, warp = __shfl_sync(0xffffffffu, tid >> 5, 0), lane = tid & 31;
    const int nb = blockIdx.x % 5, ks = blockIdx.x / 5;
    const uint32_t sb = smem_u32(smem_raw), bb = sb + P_BAR;
    if (tid == 0) {
        if ((sb & 0xFFFFFFu) != 1024) __trap();
        for (int i = 0; i < 16; i++) mbar_init(bb + PB_FULL + i * 8, 1);
        for (int i = 0; i < 2; i++) mbar_init(bb + PB_EMPTY + i * 8, 2);
        for (int i = 0; i < 4; i++) { mbar_init(bb + PB_SF + i * 8, 4); mbar_init(bb + PB_SE + i * 8, 1); }
        asm volatile("fence.mbarrier_init.release.cluster;" ::: "memory");
    }
    GT(tid == 0, 8);
    __syncthreads();
    if (warp < 4) {
        asm volatile("setmaxnreg.dec.sync.aligned.u32 40;");
        if (warp == 0) {
            named_bar(3, 288);
            GT(lane == 0, 3);
            uint32_t it = 0;
            const int otgt = 8 * (ld_relaxed(&g_epoch) + 1);
#pragma unroll 1
            for (int q = 0; q < 2 * NT + 2; q++) {
                const int l = q & 1, n = (q >> 1) - l * (LAG + ONE_FENCE);
                if (n < 0 || n >= NSEG) continue;
                int guard = 0;
                while (ld_acquire(FLG(F_O + l * 64 + n) + ks) < otgt) { if (++guard > 4000000) __trap(); __nanosleep(OP_NS); }
                fence_async_global();
                mwait(bb + PB_EMPTY + (it & 1) * 8, ((it >> 1) & 1) ^ 1);
                if (lane < 8) {
                    const uint32_t fb = bb + PB_FULL + ((it & 1) * 8 + lane) * 8;
                    mbar_expect_tx(fb, 8192);
                    asm volatile("cp.async.bulk.shared::cluster.global.mbarrier::complete_tx::bytes [%0], [%1], %2, [%3];" ::"r"(sb + P_RING + (it & 1) * 65536 + lane * 8192),
                                 "l"(g_ot + (rslot(l, n) * 256 + (ks * 8 + lane) * 8) * 64), "r"(8192), "r"(fb) : "memory");
                }
                __syncwarp();
                it++;
            }
        } else if (warp == 3) {
#pragma unroll 1
            for (int rg = 1; rg < 4; rg++) {
#pragma unroll 1
                for (int u = rg * 640 + blockIdx.x; u < rg * 640 + 640; u += 20) u_half(Bk, Bv, shiftk, u, lane);
                __syncwarp();
                if (lane == 0) red_release(FLG(F_U + rg + 1), 1);
                GT(lane == 0 && rg, 4 + rg);
            }
        } else if (lane == 0) {
            const int cw = warp - 1;
            uint32_t it = 0;
#pragma unroll 1
            for (int q = 0; q < 2 * NT + 2; q++) {
                const int l = q & 1, n = (q >> 1) - l * (LAG + ONE_FENCE);
                if (n < 0 || n >= NSEG) continue;
                mwait(bb + PB_SF + cw * 8, it & 1);
                asm volatile("cp.reduce.async.bulk.global.shared::cta.bulk_group.add.f32 [%0], [%1], %2;" ::"l"(g_pt + (rslot(l, n) * 10 + nb * 2 + cw) * 512), "r"(sb + P_STG + cw * 8192), "r"(8192) : "memory");
                asm volatile("cp.async.bulk.commit_group;" ::: "memory");
                asm volatile("cp.async.bulk.wait_group.read 0;" ::: "memory");
                mbar_arrive(bb + PB_SE + cw * 8);
                asm volatile("cp.async.bulk.wait_group 0;" ::: "memory");
                fence_async_global();
                red_release(FLG(F_P + l * 64 + n), 1);
                GT(true, 330 + l * 64 + n);
                it++;
            }
        }
    } else {
        asm volatile("setmaxnreg.inc.sync.aligned.u32 232;");
        const int cw = (warp >> 2) - 1, w4 = warp & 3, t7 = tid & 127;
        uint32_t wa[64 - OP_SS][4];
        {
            const bf16* W = Wo + (size_t)ks * 1024 * DM + nb * 128 + cw * 64 + (t7 & 7) * 8;
            const uint32_t so = (t7 >> 3) * 128 + (((t7 & 7) ^ ((t7 >> 3) & 7)) << 4);
            const uint32_t stg = sb + P_RING + cw * 65536;
            const uint32_t la = stg + ((lane & 7) + (lane >> 4) * 8) * 128 + (((w4 * 2 + ((lane >> 3) & 1)) ^ (lane & 7)) << 4);
#pragma unroll 4
            for (int i = 0; i < 32; i++) cp_async16(stg + i * 2048 + so, W + (size_t)((OP_SS + i) * 16 + (t7 >> 3)) * DM);
            cp_commit();
#pragma unroll 1
            for (int i = 0; i < OP_SS; i++) cp_async16(sb + P_AS + cw * OP_SS * 2048 + i * 2048 + so, W + (size_t)(i * 16 + (t7 >> 3)) * DM);
            cp_commit();
            cp_wait<1>();
            named_bar(1 + cw, 128);
#pragma unroll
            for (int j = 0; j < 32; j++) { const uint4 v = ldsm4t(la + j * 2048); wa[j][0] = v.x; wa[j][1] = v.y; wa[j][2] = v.z; wa[j][3] = v.w; }
            named_bar(1 + cw, 128);
#pragma unroll 1
            for (int i = 0; i < 32 - OP_SS; i++) cp_async16(stg + i * 2048 + so, W + (size_t)((OP_SS + 32 + i) * 16 + (t7 >> 3)) * DM);
            cp_commit();
            cp_wait<0>();
            named_bar(1 + cw, 128);
#pragma unroll
            for (int j = 0; j < 32 - OP_SS; j++) { const uint4 v = ldsm4t(la + j * 2048); wa[32 + j][0] = v.x; wa[32 + j][1] = v.y; wa[32 + j][2] = v.z; wa[32 + j][3] = v.w; }
            fence_async_smem();
            named_bar(3, 288);
        }
        const uint32_t ab = (1024 + P_AS + cw * OP_SS * 2048) >> 4;
        const uint32_t ea = sb + P_STG + cw * 8192 + (lane & 3) * 2048 + (((2 * w4) ^ (lane & 3)) << 5) + (lane >> 2) * 4;
#pragma unroll 1
        for (uint32_t it = 0; it < 2 * NSEG; it++) {
            float acc[16];
            const uint32_t fb = bb + PB_FULL + (it & 1) * 64, par = (it >> 1) & 1;
            const uint32_t ob = opq(((1024 + P_RING) >> 4) + (it & 1) * 4096);
            uint32_t ok = 0;
#pragma unroll
            for (int j = 0; j < 64; j++) {
                if ((j & 7) == 0) {
                    if (j) wg_commit();
                    if (!ok) mslow(fb + j, par);
                    ok = j < 56 ? mtest(fb + j + 8, par) : mtest(bb + PB_SE + cw * 8, (it & 1) ^ 1);
                    if (j == 0) wg_fence();
                }
                const uint64_t db = mkdesc(ob + j * 64, 0x80000020u);
                if (j == 0) wg_n32t_sfirst(acc, mkdesc(ab, 0x40000040u), db);
                else if (j < OP_SS) wg_n32t_s(acc, mkdesc(ab + j * 128, 0x40000040u), db);
                else wg_n32t(acc, wa[j - OP_SS][0], wa[j - OP_SS][1], wa[j - OP_SS][2], wa[j - OP_SS][3], db);
            }
            wg_commit();
            if (!ok) mslow(bb + PB_SE + cw * 8, (it & 1) ^ 1);
            wg_wait<0>();
            if (t7 == 0) mbar_arrive(bb + PB_EMPTY + (it & 1) * 8);
#pragma unroll
            for (int i = 0; i < 16; i++) sts32((ea ^ ((i & 2) << 4)) + ((i >> 2) * 2 + (i & 1)) * 256, __float_as_uint(acc[i]));
            fence_async_smem();
            __syncwarp();
            if (lane == 0) mbar_arrive(bb + PB_SF + cw * 8);
        }
    }
}
}

namespace ws {
static bool usable() {
    static int ok = -1;
    if (ok < 0) {
        cudaFuncSetAttribute(head_kernel, cudaFuncAttributeMaxDynamicSharedMemorySize, HEAD_SMEM);
        cudaFuncSetAttribute(head_kernel, cudaFuncAttributeNonPortableClusterSizeAllowed, 1);
        cudaFuncSetAttribute(op_kernel, cudaFuncAttributeMaxDynamicSharedMemorySize, OP_SMEM);
        cudaLaunchConfig_t cfg = {};
        cfg.gridDim = dim3(NCL * 16); cfg.blockDim = dim3(512); cfg.dynamicSmemBytes = HEAD_SMEM;
        cudaLaunchAttribute at[1];
        at[0].id = cudaLaunchAttributeClusterDimension;
        at[0].val.clusterDim.x = 16; at[0].val.clusterDim.y = 1; at[0].val.clusterDim.z = 1;
        cfg.attrs = at; cfg.numAttrs = 1;
        int n = 0, nsm = 0;
        cudaDeviceGetAttribute(&nsm, cudaDevAttrMultiProcessorCount, 0);
        ok = cudaOccupancyMaxActiveClusters(&n, head_kernel, &cfg) == cudaSuccess && n >= NCL && nsm >= NCL * 16 + 20;
        (void)cudaGetLastError();
    }
    return ok > 0;
}
static void launch_all(void* const* d_in, void* d_out) {
    HeadArgs A;
    A.x = (const bf16*)d_in[0]; A.mem0 = (const bf16*)d_in[1]; A.Wq = (const bf16*)d_in[2]; A.Wk = (const bf16*)d_in[3]; A.Wv = (const bf16*)d_in[4]; A.Wo = (const bf16*)d_in[5];
    A.Bk = (const bf16*)d_in[8]; A.Bv = (const bf16*)d_in[9]; A.shiftk = (const bf16*)d_in[10]; A.ssmk = (const bf16*)d_in[11]; A.ssmD = (const bf16*)d_in[12];
    A.out = (bf16*)d_out; A.h_target = 32;
    cudaStream_t s = cudaStreamPerThread;
    {
        cudaLaunchConfig_t cfg = {};
        cfg.gridDim = dim3(NCL * 16); cfg.blockDim = dim3(512); cfg.dynamicSmemBytes = HEAD_SMEM; cfg.stream = s;
        cudaLaunchAttribute at[2];
        at[0].id = cudaLaunchAttributeClusterDimension;
        at[0].val.clusterDim.x = 16; at[0].val.clusterDim.y = 1; at[0].val.clusterDim.z = 1;
        at[1].id = cudaLaunchAttributeProgrammaticStreamSerialization;
        at[1].val.programmaticStreamSerializationAllowed = 1;
        cfg.attrs = at; cfg.numAttrs = 1;
        cudaLaunchKernelEx(&cfg, head_kernel, A);
    }
    {
        cudaLaunchConfig_t cfg = {};
        cfg.gridDim = dim3(20); cfg.blockDim = dim3(384); cfg.dynamicSmemBytes = OP_SMEM; cfg.stream = s;
        cudaLaunchAttribute at[1];
        at[0].id = cudaLaunchAttributeProgrammaticStreamSerialization;
        at[0].val.programmaticStreamSerializationAllowed = 1;
        cfg.attrs = at; cfg.numAttrs = 1;
        cudaLaunchKernelEx(&cfg, op_kernel, A.Wo, A.Bk, A.Bv, A.shiftk);
    }
}
}

#undef C_REV
#undef FLG
#undef GT
#undef H_NS
#undef LAGT
#undef LN0_AHEAD
#undef LN0_BATCH
#undef NO_X
#undef OBK
#undef ONE_FENCE
#undef OP_NS
#undef P1A
#undef P1C
#undef POST_NS
#undef REG_G
#undef REG_T
#undef REG_X
#undef RING
#undef SC
#undef SD
#undef TG_STEPS
#undef TS
#undef TV
#undef UNI
#undef WFLY
#undef WR
#undef WTA
#undef XD
namespace ni {

constexpr int S_LEN = 2048;
constexpr int DM = 640;
constexpr int NH = 32;
constexpr int DH = 128;
constexpr int HD = NH * DH;
constexpr int MEMR = 8;
constexpr int SEG = 32;
constexpr int NSEG = S_LEN / SEG;

__device__ __forceinline__ float bf2f(bf16 v) { return __bfloat162float(v); }
__device__ __forceinline__ bf16 f2bf(float v) { return __float2bfloat16_rn(v); }
__device__ __forceinline__ float rbf(float v) { return __bfloat162float(__float2bfloat16_rn(v)); }
__device__ __forceinline__ uint32_t pack2(float a, float b) {
    __nv_bfloat162 t = __floats2bfloat162_rn(a, b);
    return *reinterpret_cast<uint32_t*>(&t);
}
__device__ __forceinline__ uint32_t smem_u32(const void* p) { return (uint32_t)__cvta_generic_to_shared(p); }
__device__ __forceinline__ void ldsm_x4(uint32_t& r0, uint32_t& r1, uint32_t& r2, uint32_t& r3, uint32_t addr) {
    asm volatile("ldmatrix.sync.aligned.m8n8.x4.shared.b16 {%0,%1,%2,%3}, [%4];"
                 : "=r"(r0), "=r"(r1), "=r"(r2), "=r"(r3) : "r"(addr));
}
__device__ __forceinline__ void ldsm_x2(uint32_t& r0, uint32_t& r1, uint32_t addr) {
    asm volatile("ldmatrix.sync.aligned.m8n8.x2.shared.b16 {%0,%1}, [%2];" : "=r"(r0), "=r"(r1) : "r"(addr));
}
__device__ __forceinline__ void ldsm_x4_t(uint32_t& r0, uint32_t& r1, uint32_t& r2, uint32_t& r3, uint32_t addr) {
    asm volatile("ldmatrix.sync.aligned.m8n8.x4.trans.shared.b16 {%0,%1,%2,%3}, [%4];"
                 : "=r"(r0), "=r"(r1), "=r"(r2), "=r"(r3) : "r"(addr));
}
__device__ __forceinline__ void mma16816(float* c, uint32_t a0, uint32_t a1, uint32_t a2, uint32_t a3,
                                         uint32_t b0, uint32_t b1) {
    asm("mma.sync.aligned.m16n8k16.row.col.f32.bf16.bf16.f32 {%0,%1,%2,%3}, {%4,%5,%6,%7}, {%8,%9}, {%0,%1,%2,%3};"
        : "+f"(c[0]), "+f"(c[1]), "+f"(c[2]), "+f"(c[3])
        : "r"(a0), "r"(a1), "r"(a2), "r"(a3), "r"(b0), "r"(b1));
}
__device__ __forceinline__ void cp_async16(uint32_t dst, const void* src) {
    asm volatile("cp.async.cg.shared.global [%0], [%1], 16;" ::"r"(dst), "l"(src));
}
__device__ __forceinline__ void cp_commit() { asm volatile("cp.async.commit_group;"); }
template <int N> __device__ __forceinline__ void cp_wait() { asm volatile("cp.async.wait_group %0;" ::"n"(N)); }
__device__ __forceinline__ uint4 ld_relaxed_v4(const void* p) {
    uint4 v;
    asm volatile("ld.relaxed.gpu.global.v4.u32 {%0,%1,%2,%3}, [%4];"
                 : "=r"(v.x), "=r"(v.y), "=r"(v.z), "=r"(v.w) : "l"(p) : "memory");
    return v;
}
__device__ __forceinline__ void st_relaxed_v4(void* p, uint32_t a, uint32_t b, uint32_t c, uint32_t d) {
    asm volatile("st.relaxed.gpu.global.v4.u32 [%0], {%1,%2,%3,%4};" ::"l"(p), "r"(a), "r"(b), "r"(c), "r"(d) : "memory");
}
__device__ __forceinline__ int ld_acquire(const int* p) {
    int v;
    asm volatile("ld.acquire.gpu.global.u32 %0, [%1];" : "=r"(v) : "l"(p) : "memory");
    return v;
}
__device__ __forceinline__ void mbar_init(uint32_t bar, int count) {
    asm volatile("mbarrier.init.shared::cta.b64 [%0], %1;" ::"r"(bar), "r"(count));
}
__device__ __forceinline__ void mbar_expect_tx(uint32_t bar, uint32_t bytes) {
    asm volatile("mbarrier.arrive.expect_tx.shared::cta.b64 _, [%0], %1;" ::"r"(bar), "r"(bytes) : "memory");
}
__device__ __forceinline__ void mbar_arrive(uint32_t bar) {
    asm volatile("mbarrier.arrive.shared::cta.b64 _, [%0];" ::"r"(bar) : "memory");
}
constexpr int SPIN_LIMIT = 4000000;
__device__ __forceinline__ void mbar_wait_spin(uint32_t bar, uint32_t parity) {
    uint32_t ok = 0;
    int guard = 0;
    while (!ok && ++guard < SPIN_LIMIT) {
        asm volatile(
            "{\n.reg .pred P1;\n"
            "mbarrier.try_wait.parity.shared::cta.b64 P1, [%1], %2;\n"
            "selp.u32 %0, 1, 0, P1;\n}\n"
            : "=r"(ok) : "r"(bar), "r"(parity) : "memory");
    }
}
__device__ __forceinline__ uint32_t mapa(uint32_t addr, uint32_t rank) {
    uint32_t r;
    asm volatile("mapa.shared::cluster.u32 %0, %1, %2;" : "=r"(r) : "r"(addr), "r"(rank));
    return r;
}
__device__ __forceinline__ void st_async_u32(uint32_t addr, uint32_t v, uint32_t bar) {
    asm volatile("st.async.weak.shared::cluster.mbarrier::complete_tx::bytes.b32 [%0], %1, [%2];" ::"r"(addr), "r"(v), "r"(bar) : "memory");
}
__device__ __forceinline__ void st_async_v2(uint32_t addr, uint32_t a, uint32_t b, uint32_t bar) {
    asm volatile("st.async.weak.shared::cluster.mbarrier::complete_tx::bytes.v2.b32 [%0], {%1,%2}, [%3];" ::"r"(addr), "r"(a), "r"(b), "r"(bar) : "memory");
}
__device__ __forceinline__ void cluster_sync_all() {
    asm volatile("barrier.cluster.arrive.release.aligned;\nbarrier.cluster.wait.acquire.aligned;" ::: "memory");
}
__device__ __forceinline__ void named_bar(int id, int n) { asm volatile("bar.sync %0, %1;" ::"r"(id), "r"(n) : "memory"); }

}

namespace ni {
#define CHAIN_LAG 16
constexpr int CL = 16;
constexpr int OWN = DM / CL;
constexpr int NSRC = CL / 2;
constexpr int NCLU = 64 / CL;
constexpr int CSEG = 4;
constexpr int NCHK = NSEG / CSEG;
constexpr int LAG = CHAIN_LAG;
constexpr int NTICK = NSEG + LAG;

constexpr int F_KV = 0, F_MEM = 32, F_H = 64, F_OP = 96, F_CONV = 128, F_U = 130, F_PROG = 132, F_ZERO = 133, F_CNT = 136;
constexpr int NFLAG = 192;
__device__ int g_flags[NFLAG * 32];
#define FLG(i) (g_flags + (i) * 32)
constexpr int CHAIN_THREADS = 384;
__device__ bf16 g_Y[S_LEN * DM];
__device__ bf16 g_U[DM * S_LEN];
__device__ bf16 g_h[2][S_LEN * DM];
__device__ bf16 g_x[S_LEN * DM];
__device__ bf16 g_kv[2][S_LEN * HD];
#define PRING 4
constexpr int PROWS = PRING * 128, PG = 4;
__device__ bf16 g_part[2 * PROWS * PG * DM];
__device__ uint4 g_kvf[2 * NSEG * NH * 256];
__device__ uint32_t g_xc[2 * 2 * CL * NCLU * 8 * OWN];

#define TVAL(i, v)
#define TSTAMP(i)

#define NRQ 36
#define NRW 8
#define PDQ 4
#define PDW1 0
#define PROBE 2
#define PDW 6
constexpr int NSQ = 60 - NRQ, NSW = 20 - NRW;
__host__ __device__ constexpr bool q_smem(int i) { return ((i + 1) * NSQ) / 60 != (i * NSQ) / 60; }
__host__ __device__ constexpr int q_slot(int i) { return q_smem(i) ? (i * NSQ) / 60 : i - (i * NSQ) / 60; }
__host__ __device__ constexpr int w_tile(int i) { return i < 8 ? ((i & 1) ? 0 : 2) : (i < 16 ? (i & 1) : 1); }
__host__ __device__ constexpr int w_k(int i) { return i < 8 ? i / 2 : (i < 16 ? ((i & 1) ? (i - 8) / 2 : 4 + (i - 8) / 2) : i - 12); }
__host__ __device__ constexpr int w_acc(int i) { return (i >= 16 && (i & 1)) ? 3 : w_tile(i); }
__host__ __device__ constexpr bool w_smem(int i) { return i < PDW || NRW == 0 || ((i - PDW + 1) * NRW) / (20 - PDW) == ((i - PDW) * NRW) / (20 - PDW); }
__host__ __device__ constexpr int w_slot(int i) { return i < PDW ? i : (w_smem(i) ? i - ((i - PDW) * NRW) / (20 - PDW) : ((i - PDW) * NRW) / (20 - PDW)); }
constexpr int O_WQ = 0, O_WW = NSQ * 4096, O_REST = (NSQ + NSW) * 4096;
constexpr int C_TOK = 0, C_MEM = 12288, C_RED = C_MEM + 10240, C_Q = C_RED + 6144, C_K = C_Q + 2048, C_V = C_K + 2048, C_S = C_V + 4096,
              C_BAR = C_S + 3072, C_SIZE = 40960;
constexpr int S_BYTES = 3072 + 4096;
constexpr int B_S = 64, B_R = 72, B_T = 96, B_F = 104;
static_assert(C_BAR + 112 <= C_SIZE, "chain block");
constexpr int O_STB = O_REST - 61440;
static_assert((45 * NSQ) / 60 * 4096 <= O_STB && NSQ <= 32, "staging");
struct ChainSmem { unsigned char b[O_REST + 81920 + 1536]; };
static_assert(sizeof(ChainSmem) <= 232448, "smem");

struct ChainArgs {
    CUtensorMap tk[2], tv[2];
    const bf16 *x, *mem0, *Wq, *Wk, *Wv, *Wo;
    int kv_target;
};
__device__ __forceinline__ uint32_t movmat(uint32_t v) {
    uint32_t r;
    asm volatile("movmatrix.sync.aligned.m8n8.trans.b16 %0, %1;" : "=r"(r) : "r"(v));
    return r;
}
__device__ __forceinline__ void named_arrive(int id, int n) { asm volatile("bar.arrive %0, %1;" ::"r"(id), "r"(n) : "memory"); }
__device__ __forceinline__ void red_release(int* p, int v) { asm volatile("red.release.gpu.global.add.u32 [%0], %1;" ::"l"(p), "r"(v) : "memory"); }

#define CVT(i)
__device__ __forceinline__ uint4 lds128(uint32_t a) {
    uint4 v;
    asm volatile("ld.shared.v4.u32 {%0,%1,%2,%3}, [%4];" : "=r"(v.x), "=r"(v.y), "=r"(v.z), "=r"(v.w) : "r"(a));
    return v;
}
__device__ __forceinline__ uint2 lds64(uint32_t a) {
    uint2 v;
    asm volatile("ld.shared.v2.u32 {%0,%1}, [%2];" : "=r"(v.x), "=r"(v.y) : "r"(a));
    return v;
}
__device__ __forceinline__ uint32_t lds32(uint32_t a) {
    uint32_t v;
    asm volatile("ld.shared.u32 %0, [%1];" : "=r"(v) : "r"(a));
    return v;
}
__device__ __forceinline__ void sts64(uint32_t a, uint32_t x, uint32_t y) { asm volatile("st.shared.v2.u32 [%0], {%1,%2};" ::"r"(a), "r"(x), "r"(y) : "memory"); }
__device__ __forceinline__ void sts128(uint32_t a, uint32_t x, uint32_t y, uint32_t z, uint32_t w) {
    asm volatile("st.shared.v4.u32 [%0], {%1,%2,%3,%4};" ::"r"(a), "r"(x), "r"(y), "r"(z), "r"(w) : "memory");
}
__device__ __forceinline__ void st_async_v4(uint32_t addr, uint32_t a, uint32_t b, uint32_t c, uint32_t d, uint32_t bar) {
    asm volatile("st.async.weak.shared::cluster.mbarrier::complete_tx::bytes.v4.b32 [%0], {%1,%2,%3,%4}, [%5];" ::"r"(addr), "r"(a), "r"(b), "r"(c), "r"(d), "r"(bar) : "memory");
}
__device__ __forceinline__ uint2 ld_relaxed_v2(const void* p) {
    uint2 v;
    asm volatile("ld.relaxed.gpu.global.v2.u32 {%0,%1}, [%2];" : "=r"(v.x), "=r"(v.y) : "l"(p) : "memory");
    return v;
}
__device__ __forceinline__ void st_relaxed_v2(void* p, uint32_t a, uint32_t b) {
    asm volatile("st.relaxed.gpu.global.v2.u32 [%0], {%1,%2};" ::"l"(p), "r"(a), "r"(b) : "memory");
}
__device__ __forceinline__ float blo(uint32_t v) { return __uint_as_float(v << 16); }
__device__ __forceinline__ float bhi(uint32_t v) { return __uint_as_float(v & 0xffff0000u); }
__device__ __forceinline__ uint32_t badd2(uint32_t a, uint32_t b) {
    __nv_bfloat162 r = __hadd2(*reinterpret_cast<__nv_bfloat162*>(&a), *reinterpret_cast<__nv_bfloat162*>(&b));
    return *reinterpret_cast<uint32_t*>(&r);
}
__device__ __forceinline__ void mmau(float* c, const uint4& a, uint32_t b0, uint32_t b1) { mma16816(c, a.x, a.y, a.z, a.w, b0, b1); }

__device__ __forceinline__ void stsm_x4_t(uint32_t a, uint32_t r0, uint32_t r1, uint32_t r2, uint32_t r3) {
    asm volatile("stmatrix.sync.aligned.m8n8.x4.trans.shared.b16 [%0], {%1,%2,%3,%4};" ::"r"(a), "r"(r0), "r"(r1), "r"(r2), "r"(r3) : "memory");
}
__device__ __forceinline__ uint4 ldsm4(uint32_t a) { uint4 v; ldsm_x4(v.x, v.y, v.z, v.w, a); return v; }
__device__ __forceinline__ float ex2f(float x) { float y; asm("ex2.approx.ftz.f32 %0, %1;" : "=f"(y) : "f"(x)); return y; }
__device__ __forceinline__ float rcpf(float x) { float y; asm("rcp.approx.ftz.f32 %0, %1;" : "=f"(y) : "f"(x)); return y; }
#define XD 300
__device__ __forceinline__ void xdelay() {
    uint32_t t0, t1;
    asm volatile("mov.u32 %0, %clock;" : "=r"(t0));
    do { asm volatile("mov.u32 %0, %clock;" : "=r"(t1)); } while (t1 - t0 < XD);
}
template <int V> struct IC { static constexpr int value = V; };
__device__ __forceinline__ uint32_t opq(uint32_t x) { uint32_t y; asm volatile("mov.u32 %0, %1;" : "=r"(y) : "r"(x)); return y; }
#define UNI(x) __shfl_sync(0xffffffffu, (uint32_t)(x), 0)
__device__ __forceinline__ uint32_t mtest(uint32_t bar, uint32_t parity) {
    uint32_t ok;
    asm volatile("{\n.reg .pred P1;\nmbarrier.test_wait.parity.shared::cta.b64 P1, [%1], %2;\nselp.u32 %0, 1, 0, P1;\n}\n" : "=r"(ok) : "r"(bar), "r"(parity) : "memory");
    return ok;
}
__device__ __forceinline__ void mwait(uint32_t bar, uint32_t parity) {
    asm volatile(
        "{\n.reg .pred P1;\n.reg .u32 cnt;\n"
        "mbarrier.try_wait.parity.shared::cta.b64 P1, [%0], %1;\n"
        "@P1 bra DONE;\n"
        "mov.u32 cnt, 0;\n"
        "LAB_WAIT:\n"
        "mbarrier.try_wait.parity.shared::cta.b64 P1, [%0], %1;\n"
        "@P1 bra DONE;\n"
        "add.u32 cnt, cnt, 1;\n"
        "setp.lt.u32 P1, cnt, 4000000;\n"
        "@P1 bra LAB_WAIT;\n"
        "DONE:\n}\n" ::"r"(bar), "r"(parity) : "memory");
}

__global__ void __launch_bounds__(CHAIN_THREADS, 1) chain_kernel(const __grid_constant__ ChainArgs A) {
    extern __shared__ __align__(1024) unsigned char smem_raw[];
    const int tid = threadIdx.x, warp = __shfl_sync(0xffffffffu, tid >> 5, 0), lane = tid & 31;
    const int cq = blockIdx.x / CL, r = blockIdx.x % CL;
    const int h = cq * NSRC + (r >> 1), hf = r & 1;
    const uint32_t sb = smem_u32(smem_raw);
    asm volatile("griddepcontrol.launch_dependents;");
    CVT(0);
    if (warp == 8) {
        if (lane < 8) asm volatile("cp.async.bulk.prefetch.L2.global [%0], %1;" ::"l"(A.x + (size_t)(blockIdx.x * 8 + lane) * 2560), "r"(5120) : "memory");
        asm volatile("cp.async.bulk.prefetch.L2.global [%0], %1;" ::"l"((lane < 16 ? A.Wk : A.Wv) + (size_t)(blockIdx.x * 16 + (lane & 15)) * 2560), "r"(5120) : "memory");
        asm volatile("cp.async.bulk.prefetch.L2.global [%0], %1;" ::"l"((lane < 16 ? A.Wq : A.Wo) + (size_t)(blockIdx.x * 16 + (lane & 15)) * 2560), "r"(5120) : "memory");
    }
    CVT(1);
    if (warp < 8) {
        asm volatile("setmaxnreg.inc.sync.aligned.u32 232;");
        const int j = warp & 3, kh = warp >> 2;
        uint4 wr[NRQ + NRW];
        {
            auto load_round = [&](int gi) {
                const uint32_t buf = sb + ((gi & 1) ? O_STB : O_REST);
#pragma unroll
                for (int it = 0; it < 15; it++) {
                    const int i = tid + it * 256;
                    const int pc = i / 1920, rem = i % 1920, row = rem / 24, ch = rem % 24;
                    const int mat = ch >> 3, pi = ((r >> 1) - (2 * gi + pc)) & 7;
                    const bf16* W = mat == 0 ? A.Wq : (mat == 1 ? A.Wk : A.Wv);
                    cp_async16(buf + pc * 30720 + row * 384 + ((ch ^ (row & 7)) << 4), W + (size_t)(pi * 80 + row) * HD + h * DH + hf * 64 + (ch & 7) * 8);
                }
                cp_commit();
            };
            load_round(0);
            load_round(1);
#pragma unroll
            for (int gi = 0; gi < 4; gi++) {
                cp_wait<1>();
                named_bar(1, 256);
                const uint32_t pb = sb + ((gi & 1) ? O_STB : O_REST) + kh * 30720;
                uint4 tmp[8];
#pragma unroll
                for (int u = 0; u < 5; u++)
#pragma unroll
                    for (int tt = 0; tt < 3; tt++) {
                        const int row = u * 16 + (lane & 7) + (lane >> 4) * 8;
                        const int ch = tt * 8 + j * 2 + ((lane >> 3) & 1);
                        uint4 v;
                        ldsm_x4_t(v.x, v.y, v.z, v.w, pb + row * 384 + ((ch ^ (row & 7)) << 4));
                        const int i = (gi * 5 + u) * 3 + tt;
                        if (q_smem(i)) {
                            if (gi == 3) tmp[q_slot(i) & 7] = v;
                            else sts128(sb + O_WQ + q_slot(i) * 4096 + tid * 16, v.x, v.y, v.z, v.w);
                        } else wr[q_slot(i)] = v;
                    }
                named_bar(1, 256);
                if (gi == 3) {
#pragma unroll
                    for (int i = 45; i < 60; i++)
                        if (q_smem(i)) { const uint4 v = tmp[q_slot(i) & 7]; sts128(sb + O_WQ + q_slot(i) * 4096 + tid * 16, v.x, v.y, v.z, v.w); }
                }
                if (gi < 2) load_round(gi + 2);
                else if (gi == 2) {
                    for (int i = tid; i < 128 * 40; i += 256) {
                        const int row = i / 40, ch = i % 40;
                        cp_async16(sb + O_REST + row * 640 + ((ch ^ (row & 7)) << 4), A.Wo + ((size_t)h * DH + row) * DM + hf * 320 + ch * 8);
                    }
                    cp_commit();
                }
            }
            cp_wait<0>();
            named_bar(1, 256);
#pragma unroll
            for (int i = 0; i < 20; i++) {
                const int tl = w_tile(i), et = (w_k(i) + 4 * (warp & 1)) & 7;
                const int row = et * 16 + (lane & 7) + (lane >> 4) * 8;
                const int ch = (warp >> 1) * 10 + (tl == 2 ? 8 : (warp & 1) * 4 + tl * 2) + ((lane >> 3) & 1);
                uint4 v;
                ldsm_x4_t(v.x, v.y, v.z, v.w, sb + O_REST + row * 640 + ((ch ^ (row & 7)) << 4));
                if (w_smem(i)) sts128(sb + O_WW + w_slot(i) * 4096 + tid * 16, v.x, v.y, v.z, v.w);
                else wr[NRQ + w_slot(i)] = v;
            }
            named_bar(1, 256);
            for (int i = tid; i < 2560; i += 256) {
                const int ks = i >> 6, ln = (i >> 1) & 31, wd = i & 1;
                const int pi = ((r >> 1) - ks / 5) & 7;
                const uint32_t v = *reinterpret_cast<const uint32_t*>(A.mem0 + (ln >> 2) * DM + pi * 80 + (ks % 5) * 16 + wd * 8 + (ln & 3) * 2);
                const int o = ks % 5 == 4 ? ks * 256 + wd * 128 + ln * 4 : i * 4;
                asm volatile("st.shared.u32 [%0], %1;" ::"r"(sb + O_REST + C_MEM + o), "r"(v) : "memory");
                asm volatile("st.shared.u32 [%0], %1;" ::"r"(sb + O_REST + C_SIZE + C_MEM + o), "r"(v) : "memory");
            }
            if (tid < 2) {
                const uint32_t bb = sb + O_REST + tid * C_SIZE + C_BAR;
                for (int i = 0; i < 13; i++) mbar_init(bb + i * 8, 1);
                mbar_init(bb + B_F, 4);
                asm volatile("fence.mbarrier_init.release.cluster;" ::: "memory");
                mbar_expect_tx(bb + B_S, S_BYTES);
                for (int i = 0; i < 3; i++) mbar_expect_tx(bb + B_R + i * 8, 2048);
            }
            asm volatile("fence.proxy.async;" ::: "memory");
        }
        CVT(2);
        cluster_sync_all();
        const uint32_t wq_a = sb + O_WQ + tid * 16;
        const uint32_t cb0 = sb + O_REST;
        const uint32_t qk_a = cb0 + j * 512 + (lane & 7) * 16 + (lane < 16 ? C_Q + (lane >> 3) * 256 + kh * 128 : C_K + kh * 256 + ((lane >> 3) & 1) * 128);
        const uint32_t pd = UNI(mapa(sb, (uint32_t)(r ^ 1)) - sb), sd = UNI(mapa(sb, (uint32_t)r) - sb);
        const uint32_t od = UNI(mapa(sb, (uint32_t)(hf * 8 + warp)) - sb);
        const uint32_t oe = UNI(mapa(sb, (uint32_t)(hf * 8 + (warp & 6))) - sb), oo = UNI(mapa(sb, (uint32_t)(hf * 8 + (warp | 1))) - sb);
        const uint32_t u_mem = UNI(cb0 + C_MEM + kh * 1280), u_bm = UNI(cb0 + C_BAR + kh * 8);
        const uint32_t u_v = UNI(cb0 + C_V + hf * 2048 + j * 512 + kh * 256);
        const uint32_t u_ra = UNI(cb0 + C_RED + (r >> 1) * 256);
        const uint32_t u_ob0 = UNI(cb0 + C_Q + (warp & 1) * 1024), u_ob1 = UNI(cb0 + C_Q + ((warp & 1) ^ 1) * 1024);
        const uint32_t u_role = UNI(warp < 3 ? cb0 + C_S + hf * 1536 + warp * 512 : cb0 + C_V + j * 1024);
        const uint32_t t_tok = cb0 + C_TOK + ((lane & 7) + (lane >> 4) * 8) * 128 +
                               (warp < 3 ? warp * 2048 + ((((lane >> 3) & 1) ^ (lane & 7)) << 4) : 4096 + (j >> 1) * 4096 + ((((j & 1) * 4 + ((lane >> 3) & 1)) ^ (lane & 7)) << 4));
        uint4 qb[PDQ];
#pragma unroll
        for (int s = 0; s < PDQ; s++) qb[s] = lds128(wq_a + s * 4096);
        auto tick = [&](auto cc, const int n) {
            constexpr int c = decltype(cc)::value;
            constexpr uint32_t CO = c * C_SIZE;
            const uint32_t cb = cb0 + CO;
            const uint32_t par = (uint32_t)(n & 1);
            const uint32_t l4 = opq(lane * 4), l8 = l4 * 2, l16 = l4 * 4;
            float acc[3][4];
#pragma unroll
            for (int a = 0; a < 3; a++)
#pragma unroll
                for (int i = 0; i < 4; i++) acc[a][i] = 0.f;
            {
                const uint32_t mb = u_mem + CO + l8;
                uint2 bf[3];
                uint32_t ok = 1;
                auto ldb = [&](int ks) {
                    if (ks == 0) mwait(u_bm + CO, par ^ 1);
                    else if (ks % 5 == 0) { if (!ok) mwait(u_bm + CO + (ks / 5) * 16, par ^ 1); }
                    if (ks % 5 == PROBE && ks < 15) ok = mtest(u_bm + CO + (ks / 5 + 1) * 16, par ^ 1);
                    if (ks % 5 == 4) {
                        bf[ks % 3].x = lds32(u_mem + CO + l4 + (ks / 5) * 2560 + 1024);
                        bf[ks % 3].y = lds32(u_mem + CO + l4 + (ks / 5) * 2560 + 1152);
                    } else bf[ks % 3] = lds64(mb + (ks / 5) * 2560 + (ks % 5) * 256);
                };
                ldb(0);
                TSTAMP(c * 12 + 0);
                ldb(1);
#pragma unroll
                for (int ks = 0; ks < 20; ks++) {
                    if (ks + 2 < 20) ldb(ks + 2);
#pragma unroll
                    for (int tt = 0; tt < 3; tt++) {
                        const int i = ks * 3 + tt;
                        if (q_smem(i)) {
                            const int s = q_slot(i);
                            mmau(acc[tt], qb[s % PDQ], bf[ks % 3].x, bf[ks % 3].y);
                            if (s + PDQ < NSQ) qb[s % PDQ] = lds128(wq_a + (s + PDQ) * 4096);
                        } else mmau(acc[tt], wr[q_slot(i)], bf[ks % 3].x, bf[ks % 3].y);
                    }
                }
            }
            TSTAMP(c * 12 + 1);
            stsm_x4_t(opq(qk_a) + CO, pack2(acc[0][0], acc[0][1]), pack2(acc[0][2], acc[0][3]), pack2(acc[1][0], acc[1][1]), pack2(acc[1][2], acc[1][3]));
            const uint32_t v0 = pack2(acc[2][0], acc[2][1]), v1 = pack2(acc[2][2], acc[2][3]);
            if (n == NSEG - 1) {
                sts64(u_v + CO + l8, v0, v1);
                named_bar(1, 256);
                if (kh == 1 && lane == 0) mbar_arrive(cb + C_BAR + B_F);
#pragma unroll
                for (int s = 0; s < PDQ; s++) qb[s] = lds128(wq_a + s * 4096);
                return;
            }
            named_arrive(1, 384);
            st_async_v2(u_v + CO + l8 + pd, v0, v1, cb + C_BAR + B_S + pd);
            st_async_v2(u_v + CO + l8 + sd, v0, v1, cb + C_BAR + B_S + sd);
            uint4 wb[PDW];
            const uint32_t ww_a = wq_a + (O_WW - O_WQ);
            if (warp < 3) {
                uint4 kb[4];
                const uint32_t t_tk = opq(t_tok);
                mwait(cb + C_BAR + B_T, par);
#pragma unroll
                for (int i = 0; i < 4; i++) kb[i] = ldsm4((t_tk ^ (i << 5)) + CO);
                named_bar(1, 384);
                uint4 qa[4];
#pragma unroll
                for (int i = 0; i < 4; i++) qa[i] = ldsm4(cb + l16 + C_Q + i * 512);
                if (warp == 2) {
#pragma unroll
                    for (int i = 0; i < 4; i++) kb[i] = ldsm4(cb + l16 + C_K + i * 512);
                }
                float s0[4][4], s1[4][4];
#pragma unroll
                for (int i = 0; i < 4; i++) {
#pragma unroll
                    for (int q = 0; q < 4; q++) s0[i][q] = s1[i][q] = 0.f;
                    mmau(s0[i], qa[i], kb[i].x, kb[i].y);
                    mmau(s1[i], qa[i], kb[i].z, kb[i].w);
                }
                const float a0 = ((s0[0][0] + s0[0][2]) + (s0[1][0] + s0[1][2])) + ((s0[2][0] + s0[2][2]) + (s0[3][0] + s0[3][2]));
                const float a1 = ((s0[0][1] + s0[0][3]) + (s0[1][1] + s0[1][3])) + ((s0[2][1] + s0[2][3]) + (s0[3][1] + s0[3][3]));
                const float b0 = ((s1[0][0] + s1[0][2]) + (s1[1][0] + s1[1][2])) + ((s1[2][0] + s1[2][2]) + (s1[3][0] + s1[3][2]));
                const float b1 = ((s1[0][1] + s1[0][3]) + (s1[1][1] + s1[1][3])) + ((s1[2][1] + s1[2][3]) + (s1[3][1] + s1[3][3]));
                const uint32_t so = u_role + CO + l16, bs = cb + C_BAR + B_S;
                const float c0 = warp == 2 ? a0 + b0 : a0, c1 = warp == 2 ? a1 + b1 : a1;
                st_async_v4(so + pd, __float_as_uint(c0), __float_as_uint(c1), __float_as_uint(b0), __float_as_uint(b1), bs + pd);
                st_async_v4(so + sd, __float_as_uint(c0), __float_as_uint(c1), __float_as_uint(b0), __float_as_uint(b1), bs + sd);
                TSTAMP(c * 12 + 2);
#pragma unroll
                for (int s = 0; s < PDW; s++) wb[s] = lds128(ww_a + s * 4096);
            } else if (warp == 3) {
                named_bar(1, 384);
                if (lane < 8) mbar_expect_tx(cb + C_BAR + l8, 1280);
#pragma unroll
                for (int s = 0; s < PDW; s++) wb[s] = lds128(ww_a + s * 4096);
            } else {
                mwait(cb + C_BAR + B_T, par);
                uint4 va[2][2];
                const uint32_t t_tk = opq(t_tok);
#pragma unroll
                for (int e = 0; e < 2; e++)
#pragma unroll
                    for (int k = 0; k < 2; k++)
                        ldsm_x4_t(va[e][k].x, va[e][k].y, va[e][k].z, va[e][k].w, (t_tk ^ (e << 5)) + CO + k * 2048);
#pragma unroll
                for (int s2 = 0; s2 < PDW1; s2++) wb[s2] = lds128(ww_a + s2 * 4096);
                mwait(cb + C_BAR + B_S, par);
                TSTAMP(c * 12 + 3);
                const uint32_t xa = cb + l16 + C_S;
                const uint4 x0 = lds128(xa), y0 = lds128(xa + 1536), x1 = lds128(xa + 512), y1 = lds128(xa + 512 + 1536);
                const uint2 x2 = lds64(xa + 1024), y2 = lds64(xa + 1024 + 1536);
                const uint32_t fv = u_role + CO + l8;
                const float cs = 0.08838834764831845f * 1.4426950408889634f;
                float s[10];
                s[8] = __uint_as_float(x2.x) + __uint_as_float(y2.x); s[9] = __uint_as_float(x2.y) + __uint_as_float(y2.y);
                s[0] = __uint_as_float(x0.x) + __uint_as_float(y0.x); s[1] = __uint_as_float(x0.y) + __uint_as_float(y0.y);
                s[2] = __uint_as_float(x0.z) + __uint_as_float(y0.z); s[3] = __uint_as_float(x0.w) + __uint_as_float(y0.w);
                s[4] = __uint_as_float(x1.x) + __uint_as_float(y1.x); s[5] = __uint_as_float(x1.y) + __uint_as_float(y1.y);
                s[6] = __uint_as_float(x1.z) + __uint_as_float(y1.z); s[7] = __uint_as_float(x1.w) + __uint_as_float(y1.w);
                float mx = fmaxf(fmaxf(fmaxf(s[0], s[1]), fmaxf(s[2], s[3])), fmaxf(fmaxf(fmaxf(s[4], s[5]), fmaxf(s[6], s[7])), fmaxf(s[8], s[9])));
                const float m1 = __shfl_xor_sync(0xffffffffu, mx, 1), m2 = __shfl_xor_sync(0xffffffffu, mx, 2), m3 = __shfl_xor_sync(0xffffffffu, mx, 3);
                const uint2 vm00 = lds64(fv), vm01 = lds64(fv + 256), vm10 = lds64(fv + 512), vm11 = lds64(fv + 768);
                const uint4 vm0 = make_uint4(vm00.x, vm00.y, vm01.x, vm01.y), vm1 = make_uint4(vm10.x, vm10.y, vm11.x, vm11.y);
                mx = fmaxf(fmaxf(mx, m1), fmaxf(m2, m3)) * -cs;
                uint32_t pb[5];
                pb[4] = pack2(ex2f(fmaf(s[8], cs, mx)), ex2f(fmaf(s[9], cs, mx)));
#pragma unroll
                for (int i = 0; i < 4; i++) pb[i] = pack2(ex2f(fmaf(s[2 * i], cs, mx)), ex2f(fmaf(s[2 * i + 1], cs, mx)));
                float o[3][4];
#pragma unroll
                for (int i = 0; i < 4; i++) { o[0][i] = o[1][i] = o[2][i] = 0.f; }
                const uint32_t one2 = 0x3F803F80u;
                mma16816(o[2], one2, one2, one2, one2, pb[4], 0u);
                mmau(o[0], vm0, pb[4], pb[4]);
                mmau(o[1], vm1, pb[4], pb[4]);
                mma16816(o[2], one2, one2, one2, one2, pb[0], pb[1]);
                mmau(o[0], va[0][0], pb[0], pb[1]);
                mmau(o[1], va[1][0], pb[0], pb[1]);
                mma16816(o[2], one2, one2, one2, one2, pb[2], pb[3]);
                mmau(o[0], va[0][1], pb[2], pb[3]);
                mmau(o[1], va[1][1], pb[2], pb[3]);
                const float r0 = rcpf(o[2][0]), r1 = rcpf(o[2][1]);
                stsm_x4_t(cb + l16 + C_Q + j * 512, pack2(o[0][0] * r0, o[0][1] * r1), pack2(o[0][2] * r0, o[0][3] * r1), pack2(o[1][0] * r0, o[1][1] * r1), pack2(o[1][2] * r0, o[1][3] * r1));
                named_arrive(2, 384);
                TSTAMP(c * 12 + 4);
#pragma unroll
                for (int s2 = PDW1; s2 < PDW; s2++) wb[s2] = lds128(ww_a + s2 * 4096);
                if (lane == 0) mbar_arrive(cb + C_BAR + B_F);
                if (warp == 4 && lane == 0) mbar_expect_tx(cb + C_BAR + B_S, S_BYTES);
            }
            named_bar(2, 384);
            TSTAMP(c * 12 + 5);
            {
                uint4 ob[4];
                ob[0] = ldsm4(u_ob0 + CO + l16); ob[1] = ldsm4(u_ob0 + CO + l16 + 512);
                ob[2] = ldsm4(u_ob1 + CO + l16); ob[3] = ldsm4(u_ob1 + CO + l16 + 512);
                float d[4][4];
#pragma unroll
                for (int a = 0; a < 4; a++)
#pragma unroll
                    for (int i = 0; i < 4; i++) d[a][i] = 0.f;
                const uint32_t ra = u_ra + CO + l8, rb = cb + C_BAR + B_R;
#pragma unroll
                for (int i = 0; i < 20; i++) {
                    const int k = w_k(i), ac = w_acc(i);
                    const uint32_t b0 = (k & 1) ? ob[k >> 1].z : ob[k >> 1].x, b1 = (k & 1) ? ob[k >> 1].w : ob[k >> 1].y;
                    if (w_smem(i)) {
                        const int s = w_slot(i);
                        mmau(d[ac], wb[s % PDW], b0, b1);
                        if (s + PDW < NSW) wb[s % PDW] = lds128(ww_a + (s + PDW) * 4096);
                    } else mmau(d[ac], wr[NRQ + w_slot(i)], b0, b1);
                    if (i == 9) {
                        const uint32_t rs = u_ra + CO + l4 + 4096 + (warp & 1) * 128;
                        st_async_u32(rs + oe, pack2(d[2][0], d[2][1]), rb + 16 + oe);
                        st_async_u32(rs + oo, pack2(d[2][2], d[2][3]), rb + 16 + oo);
                    }
                    if (i == 17) st_async_v2(ra + od, pack2(d[0][0], d[0][1]), pack2(d[0][2], d[0][3]), rb + od);
                }
                st_async_v2(ra + 2048 + od, pack2(d[1][0] + d[3][0], d[1][1] + d[3][1]), pack2(d[1][2] + d[3][2], d[1][3] + d[3][3]), rb + 8 + od);
                TSTAMP(c * 12 + 6);
#pragma unroll
                for (int s = 0; s < PDQ; s++) qb[s] = lds128(wq_a + s * 4096);
            }
        };
#pragma unroll 1
        for (int t = 0; t < NTICK; t++) {
            if (t < NSEG) tick(IC<0>{}, t);
            if (t >= LAG) tick(IC<1>{}, t - LAG);
        }
    } else {
        asm volatile("setmaxnreg.dec.sync.aligned.u32 40;");
        const int s = warp - 8;
        cluster_sync_all();
        if (s < 3) {
#pragma unroll 1
            for (int hs = 0; hs < 2 * NTICK; hs++) {
                const int c = hs & 1, t = hs >> 1;
                const int n = t - c * LAG;
                if (n < 0 || n >= NSEG - 1) continue;
                const uint32_t cb = sb + O_REST + c * C_SIZE;
                const uint32_t par = (uint32_t)(n & 1);
                const uint32_t tag = (uint32_t)(n % 13) + 1u;
                uint32_t* xb = g_xc + (size_t)((c * 2 + par) * CL + r) * (NCLU * 320) + s * 128;
                const uint32_t ra = cb + C_RED + s * 2048 + lane * (s < 2 ? 8 : 4);
                mwait(cb + C_BAR + B_R + s * 8, par);
                TSTAMP(c * 12 + 7);
                uint4 p[4];
                if (s < 2) {
#pragma unroll
                    for (int i = 0; i < 4; i++) {
                        const uint2 a = lds64(ra + i * 512), b = lds64(ra + i * 512 + 256);
                        p[i] = make_uint4(a.x, a.y, b.x, b.y);
                    }
                } else {
#pragma unroll
                    for (int i = 0; i < 4; i++) p[i] = make_uint4(lds32(ra + i * 512), lds32(ra + i * 512 + 128), lds32(ra + i * 512 + 256), lds32(ra + i * 512 + 384));
                }
                if (lane == 0) mbar_expect_tx(cb + C_BAR + B_R + s * 8, 2048);
                uint32_t m0, m1;
                if (s < 2) {
                    float f0 = 0.f, f1 = 0.f, f2 = 0.f, f3 = 0.f;
#pragma unroll
                    for (int i = 0; i < 4; i++) {
                        f0 += blo(p[i].x) + blo(p[i].z); f1 += bhi(p[i].x) + bhi(p[i].z);
                        f2 += blo(p[i].y) + blo(p[i].w); f3 += bhi(p[i].y) + bhi(p[i].w);
                    }
                    xb += lane * 4;
                    const uint32_t u0 = (__float_as_uint(f0) & ~0xFu) | tag, u1 = (__float_as_uint(f1) & ~0xFu) | tag;
                    const uint32_t u2 = (__float_as_uint(f2) & ~0xFu) | tag, u3 = (__float_as_uint(f3) & ~0xFu) | tag;
                    st_relaxed_v4(xb + cq * 320, u0, u1, u2, u3);
                    TSTAMP(c * 12 + 8);
                    xdelay();
                    uint4 x[NCLU];
#pragma unroll
                    for (int k = 0; k < NCLU; k++) x[k] = make_uint4(u0, u1, u2, u3);
                    int guard = 0;
                    bool first = true;
                    while (true) {
                        bool ok = true;
#pragma unroll
                        for (int k = 0; k < NCLU; k++) {
                            const bool okk = k == cq || (!first && ((x[k].x ^ tag) | (x[k].y ^ tag) | (x[k].z ^ tag) | (x[k].w ^ tag)) << 28 == 0);
                            if (!okk) { x[k] = ld_relaxed_v4(xb + k * 320); ok = false; }
                        }
                        first = false;
                        if (__all_sync(0xffffffffu, ok) || ++guard > SPIN_LIMIT) break;
                    }
                    TVAL(c * 12 + 11, guard);
                    f0 = f1 = f2 = f3 = 0.f;
#pragma unroll
                    for (int k = 0; k < NCLU; k++) {
                        f0 += __uint_as_float(x[k].x & ~0xFu); f1 += __uint_as_float(x[k].y & ~0xFu);
                        f2 += __uint_as_float(x[k].z & ~0xFu); f3 += __uint_as_float(x[k].w & ~0xFu);
                    }
                    m0 = movmat(pack2(f0, f1)); m1 = movmat(pack2(f2, f3));
                } else {
                    float f0 = 0.f, f1 = 0.f;
#pragma unroll
                    for (int i = 0; i < 4; i++) {
                        f0 += (blo(p[i].x) + blo(p[i].y)) + (blo(p[i].z) + blo(p[i].w));
                        f1 += (bhi(p[i].x) + bhi(p[i].y)) + (bhi(p[i].z) + bhi(p[i].w));
                    }
                    xb += lane * 2;
                    const uint32_t u0 = (__float_as_uint(f0) & ~0xFu) | tag, u1 = (__float_as_uint(f1) & ~0xFu) | tag;
                    st_relaxed_v2(xb + cq * 320, u0, u1);
                    TSTAMP(c * 12 + 8);
                    xdelay();
                    uint2 x[NCLU];
#pragma unroll
                    for (int k = 0; k < NCLU; k++) x[k] = make_uint2(u0, u1);
                    int guard = 0;
                    bool first = true;
                    while (true) {
                        bool ok = true;
#pragma unroll
                        for (int k = 0; k < NCLU; k++) {
                            const bool okk = k == cq || (!first && ((x[k].x ^ tag) | (x[k].y ^ tag)) << 28 == 0);
                            if (!okk) { x[k] = ld_relaxed_v2(xb + k * 320); ok = false; }
                        }
                        first = false;
                        if (__all_sync(0xffffffffu, ok) || ++guard > SPIN_LIMIT) break;
                    }
                    TVAL(c * 12 + 11, guard);
                    f0 = f1 = 0.f;
#pragma unroll
                    for (int k = 0; k < NCLU; k++) { f0 += __uint_as_float(x[k].x & ~0xFu); f1 += __uint_as_float(x[k].y & ~0xFu); }
                    m0 = movmat(pack2(f0, f1)); m1 = 0;
                }
                TSTAMP(c * 12 + 9);
                const uint32_t ma = cb + C_MEM + (s < 2 ? lane * 8 + (hf * 2 + s) * 256 : 1024 + hf * 128 + lane * 4), bm = cb + C_BAR;
                if (s < 2) {
#pragma unroll
                    for (int G = 0; G < 8; G++)
#pragma unroll
                        for (int b = 0; b < 2; b++) {
                            const uint32_t dd = mapa(sb, (uint32_t)(((r + 2 * G) & 15) ^ b)) - sb;
                            st_async_v2(ma + G * 1280 + dd, m0, m1, bm + G * 8 + dd);
                        }
                } else {
#pragma unroll
                    for (int G = 0; G < 8; G++)
#pragma unroll
                        for (int b = 0; b < 2; b++) {
                            const uint32_t dd = mapa(sb, (uint32_t)(((r + 2 * G) & 15) ^ b)) - sb;
                            st_async_u32(ma + G * 1280 + dd, m0, bm + G * 8 + dd);
                        }
                }
                TSTAMP(c * 12 + 10);
            }
        } else {
            auto fetch = [&](int c, int seg) {
                if (lane == 0) {
                    if (seg % CSEG == 0) {
                        int guard = 0;
                        while (ld_acquire(FLG(F_KV + c * NCHK + seg / CSEG)) < A.kv_target && ++guard < SPIN_LIMIT) __nanosleep(64);
                    }
                    asm volatile("fence.proxy.async;" ::: "memory");
                    const uint32_t cb = sb + O_REST + c * C_SIZE;
                    const uint32_t bt = cb + C_BAR + B_T, d = cb + C_TOK;
                    mbar_expect_tx(bt, 12288);
                    const CUtensorMap* mk = &A.tk[c];
                    const CUtensorMap* mv = &A.tv[c];
                    asm volatile("cp.async.bulk.tensor.2d.shared::cluster.global.mbarrier::complete_tx::bytes [%0], [%1, {%3, %4}], [%2];" ::"r"(d),
                                 "l"(mk), "r"(bt), "r"(h * DH + hf * 64), "r"(seg * SEG) : "memory");
#pragma unroll
                    for (int i = 0; i < 2; i++)
                        asm volatile("cp.async.bulk.tensor.2d.shared::cluster.global.mbarrier::complete_tx::bytes [%0], [%1, {%3, %4}], [%2];" ::"r"(d + 4096 + i * 4096),
                                     "l"(mv), "r"(bt), "r"(h * DH + i * 64), "r"(seg * SEG) : "memory");
                }
                __syncwarp();
            };
            fetch(0, 0);
#pragma unroll 1
            for (int hs = 0; hs < 2 * NTICK; hs++) {
                const int c = hs & 1, t = hs >> 1;
                const int n = t - c * LAG;
                if (n < -1 || n >= NSEG) continue;
                if (n >= 0) {
                    const uint32_t cb = sb + O_REST + c * C_SIZE;
                    mwait(cb + C_BAR + B_F, (uint32_t)(n & 1));
                    uint4* fd = g_kvf + (size_t)((c * NSEG + n) * NH + h) * 256 + hf * 64 + lane;
#pragma unroll
                    for (int i = 0; i < 2; i++) {
                        const uint4 k0 = ldsm4(cb + C_K + i * 1024 + lane * 16), k1 = ldsm4(cb + C_K + i * 1024 + 512 + lane * 16);
                        fd[i * 32] = make_uint4(badd2(k0.x, k0.z), badd2(k0.y, k0.w), badd2(k1.x, k1.z), badd2(k1.y, k1.w));
                        const uint32_t va = cb + C_V + hf * 2048 + i * 1024 + lane * 8;
                        const uint2 v0 = lds64(va), v1 = lds64(va + 256), v2 = lds64(va + 512), v3 = lds64(va + 768);
                        fd[128 + i * 32] = make_uint4(badd2(v0.x, v1.x), badd2(v0.y, v1.y), badd2(v2.x, v3.x), badd2(v2.y, v3.y));
                    }
                    if (blockIdx.x == 0 && lane == 0 && (c == 0 || t >= NSEG)) asm volatile("st.relaxed.gpu.global.u32 [%0], %1;" ::"l"(FLG(F_PROG)), "r"(t + 1) : "memory");
                    if ((n % CSEG) == CSEG - 1) {
                        asm volatile("fence.proxy.async;" ::: "memory");
                        __syncwarp();
                        if (lane == 0) { red_release(FLG(F_MEM + c * NCHK + n / CSEG), 1); }
                    }
                }
                if (n + 1 < NSEG - 1) fetch(c, n + 1);
            }
        }
    }
    cluster_sync_all();
}
}

namespace ni {
constexpr int KV_TGT = 32, MEM_TGT = 64, OP_TGT = 16, CONV_TGT = 80, H_TGT = 128;
constexpr int PDIST = (LAG + 3) / 4;
#define QA_PRE 3
#define KV1_W 5
#define KV1_N 16
static_assert(QA_PRE < 4, "inputs of the chunk must be complete");
#define SPLAN 0x102030
#define URGENT 1
#define POST_NS 40

#define ELECT "{\n.reg .pred p;\nelect.sync _|p, 0xffffffff;\n@p "
__device__ __forceinline__ void tma_load_2d(uint32_t dst, const CUtensorMap* map, uint32_t bar, int c0, int c1) {
    asm volatile(ELECT "cp.async.bulk.tensor.2d.shared::cluster.global.mbarrier::complete_tx::bytes [%0], [%1, {%3, %4}], [%2];\n}" ::"r"(dst),
                 "l"(map), "r"(bar), "r"(c0), "r"(c1) : "memory");
}
__device__ __forceinline__ void tma_load_2d_mc(uint32_t dst, const CUtensorMap* map, uint32_t bar, int c0, int c1) {
    asm volatile(ELECT "cp.async.bulk.tensor.2d.shared::cluster.global.mbarrier::complete_tx::bytes.multicast::cluster [%0], [%1, {%3, %4}], [%2], %5;\n}" ::"r"(dst),
                 "l"(map), "r"(bar), "r"(c0), "r"(c1), "h"((unsigned short)3) : "memory");
}
__device__ __forceinline__ void tma_load_3d(uint32_t dst, const CUtensorMap* map, uint32_t bar, int c1, int c2) {
    asm volatile(ELECT "cp.async.bulk.tensor.3d.shared::cluster.global.mbarrier::complete_tx::bytes [%0], [%1, {%5, %3, %4}], [%2];\n}" ::"r"(dst),
                 "l"(map), "r"(bar), "r"(c1), "r"(c2), "r"(0) : "memory");
}
__device__ __forceinline__ void tma_load_3d_mc(uint32_t dst, const CUtensorMap* map, uint32_t bar, int c1, int c2) {
    asm volatile(ELECT "cp.async.bulk.tensor.3d.shared::cluster.global.mbarrier::complete_tx::bytes.multicast::cluster [%0], [%1, {%6, %3, %4}], [%2], %5;\n}" ::"r"(dst),
                 "l"(map), "r"(bar), "r"(c1), "r"(c2), "h"((unsigned short)3), "r"(0) : "memory");
}
__device__ __forceinline__ void bulk_load(uint32_t dst, const void* src, uint32_t bytes, uint32_t bar) {
    asm volatile(ELECT "cp.async.bulk.shared::cluster.global.mbarrier::complete_tx::bytes [%0], [%1], %2, [%3];\n}" ::"r"(dst), "l"(src), "r"(bytes), "r"(bar) : "memory");
}
__device__ __forceinline__ void expect_tx1(uint32_t bar, uint32_t bytes) {
    asm volatile(ELECT "mbarrier.arrive.expect_tx.shared::cta.b64 _, [%0], %1;\n}" ::"r"(bar), "r"(bytes) : "memory");
}
__device__ __forceinline__ void wg_fence() { asm volatile("wgmma.fence.sync.aligned;" ::: "memory"); }
__device__ __forceinline__ void wg_commit() { asm volatile("wgmma.commit_group.sync.aligned;" ::: "memory"); }
template <int N> __device__ __forceinline__ void wg_wait() { asm volatile("wgmma.wait_group.sync.aligned %0;" ::"n"(N) : "memory"); }
__device__ __forceinline__ uint64_t make_desc(uint32_t addr, uint32_t lbo, uint32_t sbo) {
    return (uint64_t)((addr & 0x3FFFF) >> 4) | ((uint64_t)((lbo & 0x3FFFF) >> 4) << 16) |
           ((uint64_t)((sbo & 0x3FFFF) >> 4) << 32) | (1ull << 62);
}
__device__ __forceinline__ void wgmma_m64n256k16(float* d, uint64_t da, uint64_t db) {
    asm volatile("{\n.reg .pred p;\nsetp.ne.b32 p, 1, 0;\n"
                 "wgmma.mma_async.sync.aligned.m64n256k16.f32.bf16.bf16 {%0, %1, %2, %3, %4, %5, %6, %7, %8, %9, %10, %11, %12, %13, %14, %15, %16, %17, %18, %19, %20, %21, %22, %23, %24, %25, %26, %27, %28, %29, %30, %31, %32, %33, %34, %35, %36, %37, %38, %39, %40, %41, %42, %43, %44, %45, %46, %47, %48, %49, %50, %51, %52, %53, %54, %55, %56, %57, %58, %59, %60, %61, %62, %63, %64, %65, %66, %67, %68, %69, %70, %71, %72, %73, %74, %75, %76, %77, %78, %79, %80, %81, %82, %83, %84, %85, %86, %87, %88, %89, %90, %91, %92, %93, %94, %95, %96, %97, %98, %99, %100, %101, %102, %103, %104, %105, %106, %107, %108, %109, %110, %111, %112, %113, %114, %115, %116, %117, %118, %119, %120, %121, %122, %123, %124, %125, %126, %127}, %128, %129, p, 1, 1, 0, 1;\n}\n"
                 : "+f"(d[0]), "+f"(d[1]), "+f"(d[2]), "+f"(d[3]), "+f"(d[4]), "+f"(d[5]), "+f"(d[6]), "+f"(d[7]), "+f"(d[8]), "+f"(d[9]), "+f"(d[10]), "+f"(d[11]), "+f"(d[12]), "+f"(d[13]), "+f"(d[14]), "+f"(d[15]), "+f"(d[16]), "+f"(d[17]), "+f"(d[18]), "+f"(d[19]), "+f"(d[20]), "+f"(d[21]), "+f"(d[22]), "+f"(d[23]), "+f"(d[24]), "+f"(d[25]), "+f"(d[26]), "+f"(d[27]), "+f"(d[28]), "+f"(d[29]), "+f"(d[30]), "+f"(d[31]), "+f"(d[32]), "+f"(d[33]), "+f"(d[34]), "+f"(d[35]), "+f"(d[36]), "+f"(d[37]), "+f"(d[38]), "+f"(d[39]), "+f"(d[40]), "+f"(d[41]), "+f"(d[42]), "+f"(d[43]), "+f"(d[44]), "+f"(d[45]), "+f"(d[46]), "+f"(d[47]), "+f"(d[48]), "+f"(d[49]), "+f"(d[50]), "+f"(d[51]), "+f"(d[52]), "+f"(d[53]), "+f"(d[54]), "+f"(d[55]), "+f"(d[56]), "+f"(d[57]), "+f"(d[58]), "+f"(d[59]), "+f"(d[60]), "+f"(d[61]), "+f"(d[62]), "+f"(d[63]), "+f"(d[64]), "+f"(d[65]), "+f"(d[66]), "+f"(d[67]), "+f"(d[68]), "+f"(d[69]), "+f"(d[70]), "+f"(d[71]), "+f"(d[72]), "+f"(d[73]), "+f"(d[74]), "+f"(d[75]), "+f"(d[76]), "+f"(d[77]), "+f"(d[78]), "+f"(d[79]), "+f"(d[80]), "+f"(d[81]), "+f"(d[82]), "+f"(d[83]), "+f"(d[84]), "+f"(d[85]), "+f"(d[86]), "+f"(d[87]), "+f"(d[88]), "+f"(d[89]), "+f"(d[90]), "+f"(d[91]), "+f"(d[92]), "+f"(d[93]), "+f"(d[94]), "+f"(d[95]), "+f"(d[96]), "+f"(d[97]), "+f"(d[98]), "+f"(d[99]), "+f"(d[100]), "+f"(d[101]), "+f"(d[102]), "+f"(d[103]), "+f"(d[104]), "+f"(d[105]), "+f"(d[106]), "+f"(d[107]), "+f"(d[108]), "+f"(d[109]), "+f"(d[110]), "+f"(d[111]), "+f"(d[112]), "+f"(d[113]), "+f"(d[114]), "+f"(d[115]), "+f"(d[116]), "+f"(d[117]), "+f"(d[118]), "+f"(d[119]), "+f"(d[120]), "+f"(d[121]), "+f"(d[122]), "+f"(d[123]), "+f"(d[124]), "+f"(d[125]), "+f"(d[126]), "+f"(d[127])
                 : "l"(da), "l"(db));
}
__device__ __forceinline__ void wgmma_m64n256k16_first(float* d, uint64_t da, uint64_t db) {
    asm volatile("{\n.reg .pred p;\nsetp.ne.b32 p, 0, 0;\n"
                 "wgmma.mma_async.sync.aligned.m64n256k16.f32.bf16.bf16 {%0, %1, %2, %3, %4, %5, %6, %7, %8, %9, %10, %11, %12, %13, %14, %15, %16, %17, %18, %19, %20, %21, %22, %23, %24, %25, %26, %27, %28, %29, %30, %31, %32, %33, %34, %35, %36, %37, %38, %39, %40, %41, %42, %43, %44, %45, %46, %47, %48, %49, %50, %51, %52, %53, %54, %55, %56, %57, %58, %59, %60, %61, %62, %63, %64, %65, %66, %67, %68, %69, %70, %71, %72, %73, %74, %75, %76, %77, %78, %79, %80, %81, %82, %83, %84, %85, %86, %87, %88, %89, %90, %91, %92, %93, %94, %95, %96, %97, %98, %99, %100, %101, %102, %103, %104, %105, %106, %107, %108, %109, %110, %111, %112, %113, %114, %115, %116, %117, %118, %119, %120, %121, %122, %123, %124, %125, %126, %127}, %128, %129, p, 1, 1, 0, 1;\n}\n"
                 : "=f"(d[0]), "=f"(d[1]), "=f"(d[2]), "=f"(d[3]), "=f"(d[4]), "=f"(d[5]), "=f"(d[6]), "=f"(d[7]), "=f"(d[8]), "=f"(d[9]), "=f"(d[10]), "=f"(d[11]), "=f"(d[12]), "=f"(d[13]), "=f"(d[14]), "=f"(d[15]), "=f"(d[16]), "=f"(d[17]), "=f"(d[18]), "=f"(d[19]), "=f"(d[20]), "=f"(d[21]), "=f"(d[22]), "=f"(d[23]), "=f"(d[24]), "=f"(d[25]), "=f"(d[26]), "=f"(d[27]), "=f"(d[28]), "=f"(d[29]), "=f"(d[30]), "=f"(d[31]), "=f"(d[32]), "=f"(d[33]), "=f"(d[34]), "=f"(d[35]), "=f"(d[36]), "=f"(d[37]), "=f"(d[38]), "=f"(d[39]), "=f"(d[40]), "=f"(d[41]), "=f"(d[42]), "=f"(d[43]), "=f"(d[44]), "=f"(d[45]), "=f"(d[46]), "=f"(d[47]), "=f"(d[48]), "=f"(d[49]), "=f"(d[50]), "=f"(d[51]), "=f"(d[52]), "=f"(d[53]), "=f"(d[54]), "=f"(d[55]), "=f"(d[56]), "=f"(d[57]), "=f"(d[58]), "=f"(d[59]), "=f"(d[60]), "=f"(d[61]), "=f"(d[62]), "=f"(d[63]), "=f"(d[64]), "=f"(d[65]), "=f"(d[66]), "=f"(d[67]), "=f"(d[68]), "=f"(d[69]), "=f"(d[70]), "=f"(d[71]), "=f"(d[72]), "=f"(d[73]), "=f"(d[74]), "=f"(d[75]), "=f"(d[76]), "=f"(d[77]), "=f"(d[78]), "=f"(d[79]), "=f"(d[80]), "=f"(d[81]), "=f"(d[82]), "=f"(d[83]), "=f"(d[84]), "=f"(d[85]), "=f"(d[86]), "=f"(d[87]), "=f"(d[88]), "=f"(d[89]), "=f"(d[90]), "=f"(d[91]), "=f"(d[92]), "=f"(d[93]), "=f"(d[94]), "=f"(d[95]), "=f"(d[96]), "=f"(d[97]), "=f"(d[98]), "=f"(d[99]), "=f"(d[100]), "=f"(d[101]), "=f"(d[102]), "=f"(d[103]), "=f"(d[104]), "=f"(d[105]), "=f"(d[106]), "=f"(d[107]), "=f"(d[108]), "=f"(d[109]), "=f"(d[110]), "=f"(d[111]), "=f"(d[112]), "=f"(d[113]), "=f"(d[114]), "=f"(d[115]), "=f"(d[116]), "=f"(d[117]), "=f"(d[118]), "=f"(d[119]), "=f"(d[120]), "=f"(d[121]), "=f"(d[122]), "=f"(d[123]), "=f"(d[124]), "=f"(d[125]), "=f"(d[126]), "=f"(d[127])
                 : "l"(da), "l"(db));
}
__device__ __forceinline__ void wgmma_rs_m64n128k16(float* d, const uint32_t* a, uint64_t db) {
    asm volatile("{\n.reg .pred p;\nsetp.ne.b32 p, 1, 0;\n"
                 "wgmma.mma_async.sync.aligned.m64n128k16.f32.bf16.bf16 {%0, %1, %2, %3, %4, %5, %6, %7, %8, %9, %10, %11, %12, %13, %14, %15, %16, %17, %18, %19, %20, %21, %22, %23, %24, %25, %26, %27, %28, %29, %30, %31, %32, %33, %34, %35, %36, %37, %38, %39, %40, %41, %42, %43, %44, %45, %46, %47, %48, %49, %50, %51, %52, %53, %54, %55, %56, %57, %58, %59, %60, %61, %62, %63}, {%64, %65, %66, %67}, %68, p, 1, 1, 1;\n}\n"
                 : "+f"(d[0]), "+f"(d[1]), "+f"(d[2]), "+f"(d[3]), "+f"(d[4]), "+f"(d[5]), "+f"(d[6]), "+f"(d[7]), "+f"(d[8]), "+f"(d[9]), "+f"(d[10]), "+f"(d[11]), "+f"(d[12]), "+f"(d[13]), "+f"(d[14]), "+f"(d[15]), "+f"(d[16]), "+f"(d[17]), "+f"(d[18]), "+f"(d[19]), "+f"(d[20]), "+f"(d[21]), "+f"(d[22]), "+f"(d[23]), "+f"(d[24]), "+f"(d[25]), "+f"(d[26]), "+f"(d[27]), "+f"(d[28]), "+f"(d[29]), "+f"(d[30]), "+f"(d[31]), "+f"(d[32]), "+f"(d[33]), "+f"(d[34]), "+f"(d[35]), "+f"(d[36]), "+f"(d[37]), "+f"(d[38]), "+f"(d[39]), "+f"(d[40]), "+f"(d[41]), "+f"(d[42]), "+f"(d[43]), "+f"(d[44]), "+f"(d[45]), "+f"(d[46]), "+f"(d[47]), "+f"(d[48]), "+f"(d[49]), "+f"(d[50]), "+f"(d[51]), "+f"(d[52]), "+f"(d[53]), "+f"(d[54]), "+f"(d[55]), "+f"(d[56]), "+f"(d[57]), "+f"(d[58]), "+f"(d[59]), "+f"(d[60]), "+f"(d[61]), "+f"(d[62]), "+f"(d[63])
                 : "r"(a[0]), "r"(a[1]), "r"(a[2]), "r"(a[3]), "l"(db));
}
__device__ __forceinline__ void wgmma_rs_m64n128k16_first(float* d, const uint32_t* a, uint64_t db) {
    asm volatile("{\n.reg .pred p;\nsetp.ne.b32 p, 0, 0;\n"
                 "wgmma.mma_async.sync.aligned.m64n128k16.f32.bf16.bf16 {%0, %1, %2, %3, %4, %5, %6, %7, %8, %9, %10, %11, %12, %13, %14, %15, %16, %17, %18, %19, %20, %21, %22, %23, %24, %25, %26, %27, %28, %29, %30, %31, %32, %33, %34, %35, %36, %37, %38, %39, %40, %41, %42, %43, %44, %45, %46, %47, %48, %49, %50, %51, %52, %53, %54, %55, %56, %57, %58, %59, %60, %61, %62, %63}, {%64, %65, %66, %67}, %68, p, 1, 1, 1;\n}\n"
                 : "=f"(d[0]), "=f"(d[1]), "=f"(d[2]), "=f"(d[3]), "=f"(d[4]), "=f"(d[5]), "=f"(d[6]), "=f"(d[7]), "=f"(d[8]), "=f"(d[9]), "=f"(d[10]), "=f"(d[11]), "=f"(d[12]), "=f"(d[13]), "=f"(d[14]), "=f"(d[15]), "=f"(d[16]), "=f"(d[17]), "=f"(d[18]), "=f"(d[19]), "=f"(d[20]), "=f"(d[21]), "=f"(d[22]), "=f"(d[23]), "=f"(d[24]), "=f"(d[25]), "=f"(d[26]), "=f"(d[27]), "=f"(d[28]), "=f"(d[29]), "=f"(d[30]), "=f"(d[31]), "=f"(d[32]), "=f"(d[33]), "=f"(d[34]), "=f"(d[35]), "=f"(d[36]), "=f"(d[37]), "=f"(d[38]), "=f"(d[39]), "=f"(d[40]), "=f"(d[41]), "=f"(d[42]), "=f"(d[43]), "=f"(d[44]), "=f"(d[45]), "=f"(d[46]), "=f"(d[47]), "=f"(d[48]), "=f"(d[49]), "=f"(d[50]), "=f"(d[51]), "=f"(d[52]), "=f"(d[53]), "=f"(d[54]), "=f"(d[55]), "=f"(d[56]), "=f"(d[57]), "=f"(d[58]), "=f"(d[59]), "=f"(d[60]), "=f"(d[61]), "=f"(d[62]), "=f"(d[63])
                 : "r"(a[0]), "r"(a[1]), "r"(a[2]), "r"(a[3]), "l"(db));
}

struct BulkMaps { CUtensorMap h, h2, wq, wk, wv, wo, kv, lu; };
struct BulkArgs {
    const bf16 *x, *ssmk, *ssmD, *Bk, *Bv, *shiftk;
    bf16* out;
};
enum { T_KV = 0, T_QA, T_CONV, T_ATT, T_POST, T_LN0 };
constexpr int MAXG = 52, SENT = MAXG - 1;
struct Sched { uint32_t chk[MAXG * 4]; uint32_t info[MAXG]; int sbeg[8]; };

constexpr int BK_STAGES = 4, BK_STAGE_BYTES = 49152, TSLOTS = 4;
struct BulkSmemTail {
    unsigned long long full[BK_STAGES], empty[BK_STAGES], tfull[TSLOTS], tempty[TSLOTS], sfull[4], sempty[4];
    int task[TSLOTS];
    uint32_t tab[MAXG * 5];
};
constexpr int BULK_STG = BK_STAGES * BK_STAGE_BYTES;
constexpr int BULK_TAIL = BULK_STG + 32768;
constexpr int BULK_SMEM = BULK_TAIL + (int)sizeof(BulkSmemTail);
static_assert(BULK_SMEM <= 232448, "bulk smem");
#define PACE 0
#define REG_C 224
#define REG_P 56

#define BT(lead, type, l, c, k)
#define TT(k)
#define FT(k)
#define TTV(k, v)
__device__ __forceinline__ void tma_store_2d(const CUtensorMap* map, uint32_t src, int c0, int c1) {
    asm volatile("cp.async.bulk.tensor.2d.global.shared::cta.bulk_group [%0, {%2, %3}], [%1];" ::"l"(map), "r"(src), "r"(c0), "r"(c1) : "memory");
}
__device__ __forceinline__ void bulk_commit() { asm volatile("cp.async.bulk.commit_group;" ::: "memory"); }
template <int N> __device__ __forceinline__ void bulk_wait_read() { asm volatile("cp.async.bulk.wait_group.read %0;" ::"n"(N) : "memory"); }
template <int N> __device__ __forceinline__ void bulk_wait() { asm volatile("cp.async.bulk.wait_group %0;" ::"n"(N) : "memory"); }
__device__ __forceinline__ void mbar_arrive_cluster(uint32_t bar) {
    asm volatile("mbarrier.arrive.shared::cluster.b64 _, [%0];" ::"r"(bar) : "memory");
}
__device__ __forceinline__ void stsm_x4(uint32_t addr, uint32_t r0, uint32_t r1, uint32_t r2, uint32_t r3) {
    asm volatile("stmatrix.sync.aligned.m8n8.x4.shared.b16 [%0], {%1,%2,%3,%4};" ::"r"(addr), "r"(r0), "r"(r1), "r"(r2), "r"(r3) : "memory");
}
__device__ __forceinline__ void mma1688(float* c, uint32_t a0, uint32_t a1, uint32_t b0) {
    asm("mma.sync.aligned.m16n8k8.row.col.f32.bf16.bf16.f32 {%0,%1,%2,%3}, {%4,%5}, {%6}, {%0,%1,%2,%3};"
        : "+f"(c[0]), "+f"(c[1]), "+f"(c[2]), "+f"(c[3]) : "r"(a0), "r"(a1), "r"(b0));
}
__device__ __forceinline__ int ld_relaxed(const int* p) {
    int v;
    asm volatile("ld.relaxed.gpu.global.u32 %0, [%1];" : "=r"(v) : "l"(p) : "memory");
    return v;
}
__device__ __forceinline__ void flag_wait(const int* f, int tgt, int ns) {
    int guard = 0;
    while (ld_relaxed(f) < tgt && ++guard < 4000000) __nanosleep(ns);
}
__device__ __forceinline__ void fence_async() { asm volatile("fence.proxy.async.global;" ::: "memory"); }
__device__ __forceinline__ uint32_t bmul2(uint32_t a, uint32_t b) { uint32_t r; asm("mul.rn.bf16x2 %0, %1, %2;" : "=r"(r) : "r"(a), "r"(b)); return r; }
__device__ __forceinline__ uint32_t bsum2(uint32_t a, uint32_t b) { uint32_t r; asm("add.rn.bf16x2 %0, %1, %2;" : "=r"(r) : "r"(a), "r"(b)); return r; }
__device__ __forceinline__ uint32_t bmax2(uint32_t a, uint32_t b) { uint32_t r; asm("max.bf16x2 %0, %1, %2;" : "=r"(r) : "r"(a), "r"(b)); return r; }
__device__ __forceinline__ uint32_t rscore(float a, float b) {
    const uint32_t u = pack2(a, b);
    return pack2(blo(u) * 0.08838834764831845f, bhi(u) * 0.08838834764831845f);
}
template <int STRIDE> __device__ __forceinline__ void ld5(uint32_t* w, const bf16* p) {
#pragma unroll
    for (int r = 0; r < 5; r++) { const uint2 v = __ldcg(reinterpret_cast<const uint2*>(p + r * STRIDE)); w[2 * r] = v.x; w[2 * r + 1] = v.y; }
}
__device__ __forceinline__ void st5(bf16* p, const uint32_t* w) {
#pragma unroll
    for (int r = 0; r < 5; r++) *reinterpret_cast<uint2*>(p + r * 128) = make_uint2(w[2 * r], w[2 * r + 1]);
}
__device__ __forceinline__ void ln_row(const uint32_t* x, uint32_t* y) {
    float s = 0.f;
#pragma unroll
    for (int i = 0; i < 10; i++) s += blo(x[i]) + bhi(x[i]);
#pragma unroll
    for (int o = 16; o > 0; o >>= 1) s += __shfl_xor_sync(0xffffffffu, s, o);
    const float mean = s * (1.0f / DM);
    float q = 0.f;
#pragma unroll
    for (int i = 0; i < 10; i++) { const float d0 = blo(x[i]) - mean, d1 = bhi(x[i]) - mean; q = fmaf(d0, d0, q); q = fmaf(d1, d1, q); }
#pragma unroll
    for (int o = 16; o > 0; o >>= 1) q += __shfl_xor_sync(0xffffffffu, q, o);
    const uint32_t nm = pack2(-mean, -mean);
    float sq;
    asm("sqrt.approx.ftz.f32 %0, %1;" : "=f"(sq) : "f"(rbf(rbf(q * (1.0f / DM)) + 1e-5f)));
    const float rd = rcpf(rbf(sq));
#pragma unroll
    for (int i = 0; i < 10; i++) { const uint32_t d = bsum2(x[i], nm); y[i] = pack2(blo(d) * rd, bhi(d) * rd); }
}
__device__ __forceinline__ void red_add8(uint4* p, uint32_t a, uint32_t b, uint32_t c, uint32_t d) {
    asm volatile("red.relaxed.gpu.global.add.noftz.v4.bf16x2 [%0], {%1,%2,%3,%4};" ::"l"(p), "r"(a), "r"(b), "r"(c), "r"(d) : "memory");
}
__device__ __forceinline__ void part_sum(const uint4& v, const uint4& w, int lane, uint32_t& x0, uint32_t& x1) {
    float t[8];
    t[0] = blo(v.x) + blo(w.x); t[1] = bhi(v.x) + bhi(w.x); t[2] = blo(v.y) + blo(w.y); t[3] = bhi(v.y) + bhi(w.y);
    t[4] = blo(v.z) + blo(w.z); t[5] = bhi(v.z) + bhi(w.z); t[6] = blo(v.w) + blo(w.w); t[7] = bhi(v.w) + bhi(w.w);
#pragma unroll
    for (int i = 0; i < 4; i++) t[i] = (lane < 16 ? t[i] : t[4 + i]) + __shfl_xor_sync(0xffffffffu, lane < 16 ? t[4 + i] : t[i], 16);
    const uint32_t r0 = pack2(t[0], t[1]), r1 = pack2(t[2], t[3]);
    const uint32_t ex = __shfl_xor_sync(0xffffffffu, (lane & 1) ? r0 : r1, 1);
    x0 = (lane & 1) ? ex : r0; x1 = (lane & 1) ? r1 : ex;
}
__device__ __forceinline__ void post_row(int l, int row, int lane, const bf16* xin, bf16* xout) {
    uint32_t x[10], y[10], n[10];
    const int cl = (lane & 12) * 8 + (lane >> 4) * 16 + (lane & 1) * 8 + (lane & 2) * 2;
    uint4* pp = reinterpret_cast<uint4*>(g_part + (size_t)(l * PROWS + (row & (PROWS - 1))) * (PG * DM)) + (lane & 15) + (lane >> 4) * 80;
    int* f = FLG(F_OP + l * NCHK + (row >> 7));
    flag_wait(FLG(F_CONV + (row >> 10)), CONV_TGT, 200);
    ld5<128>(x, xin + (size_t)row * DM + cl);
    flag_wait(f + 4, OP_TGT, POST_NS);
    {
        uint4 v[10];
#pragma unroll
        for (int i = 0; i < 10; i++) v[i] = __ldcg(pp + (i >> 1) * 16 + (i & 1) * 160);
#pragma unroll
        for (int r = 0; r < 5; r++) {
            uint32_t s0, s1;
            part_sum(v[2 * r], v[2 * r + 1], lane, s0, s1);
            if (r == 1) ld5<16 * S_LEN * 8>(y, g_Y + ((size_t)(cl >> 3) * S_LEN + (row ^ ((row >> 6) & 7))) * 8 + (cl & 4));
            x[2 * r] = bsum2(x[2 * r], s0); x[2 * r + 1] = bsum2(x[2 * r + 1], s1);
        }
    }
    ln_row(x, n);
#pragma unroll
    for (int i = 0; i < 10; i++) x[i] = bsum2(x[i], bmul2(n[i], y[i]));
    if (l == 0) {
        ln_row(x, n);
        st5(g_h[1] + (size_t)row * DM + cl, n);
        __syncwarp();
        if (lane == 0) red_release(FLG(F_H + NCHK + (row >> 7)), 1);
    }
#pragma unroll
    for (int i = 0; i < 10; i++) pp[(i >> 1) * 16 + (i & 1) * 160] = make_uint4(0, 0, 0, 0);
    st5(xout + (size_t)row * DM + cl, x);
    __syncwarp();
    if (l && lane == 0) red_release(f + 5, 1);
}
__device__ __forceinline__ void u_unit(const bf16* Bk, const bf16* Bv, const bf16* shiftk, int unit, int lane) {
    const int t0 = (unit / 10) * 16, cp = (unit % 10) * 32 + lane;
    uint32_t kk[19], vv[16];
    const uint32_t* pk = reinterpret_cast<const uint32_t*>(Bk + (size_t)t0 * DM) + cp;
    const uint32_t* pv = reinterpret_cast<const uint32_t*>(Bv + (size_t)t0 * DM) + cp;
#pragma unroll
    for (int i = 0; i < 19; i++) kk[i] = (i >= 3 || t0 > 0) ? __ldg(pk + (i - 3) * (DM / 2)) : 0u;
#pragma unroll
    for (int i = 0; i < 16; i++) vv[i] = __ldg(pv + i * (DM / 2));
    const uint4 sh0 = __ldg(reinterpret_cast<const uint4*>(shiftk + cp * 8));
    const uint32_t s0 = __byte_perm(sh0.x, sh0.z, 0x5410), s1 = __byte_perm(sh0.x, sh0.z, 0x7632), s2 = __byte_perm(sh0.y, sh0.w, 0x5410), s3 = __byte_perm(sh0.y, sh0.w, 0x7632);
#pragma unroll
    for (int t = 0; t < 16; t++)
        vv[t] = bmul2(bsum2(bsum2(bsum2(bmul2(kk[t], s3), bmul2(kk[t + 1], s2)), bmul2(kk[t + 2], s1)), bmul2(kk[t + 3], s0)), vv[t]);
    uint4* d = reinterpret_cast<uint4*>(g_U + (size_t)(cp * 2) * S_LEN + (t0 ^ 48));
#pragma unroll
    for (int c = 0; c < 2; c++) {
        const uint32_t sel = c ? 0x7632 : 0x5410;
#pragma unroll
        for (int hh = 0; hh < 2; hh++)
            d[c * (S_LEN / 8) + hh] = make_uint4(__byte_perm(vv[15 - hh * 8], vv[14 - hh * 8], sel), __byte_perm(vv[13 - hh * 8], vv[12 - hh * 8], sel),
                                                 __byte_perm(vv[11 - hh * 8], vv[10 - hh * 8], sel), __byte_perm(vv[9 - hh * 8], vv[8 - hh * 8], sel));
    }
}
constexpr int CV_EP = 4224;
template <class F> __device__ __forceinline__ void conv_unit(uint32_t ub, uint32_t e0, uint32_t e1, uint32_t zrow, uint32_t yt, float Dv, int m, int lane, F&& nearly_done) {
    const int g = lane >> 2, tq = lane & 3;
    asm volatile("st.shared.u32 [%0], %1;" ::"r"(e0 + lane * 4), "r"(0) : "memory");
    asm volatile("st.shared.u32 [%0], %1;" ::"r"(zrow + lane * 4), "r"(0) : "memory");
    __syncwarp();
    for (int i = lane; i < CV_EP / 16; i += 32) {
        const uint4 v = lds128(e0 + i * 16);
        const uint32_t nx = i + 1 < CV_EP / 16 ? lds32(e0 + i * 16 + 16) : 0u;
        sts128(e1 + i * 16, __byte_perm(v.x, v.y, 0x5432), __byte_perm(v.y, v.z, 0x5432), __byte_perm(v.z, v.w, 0x5432), __byte_perm(v.w, nx, 0x5432));
    }
    __syncwarp();
    float acc[8][4];
#pragma unroll
    for (int n = 0; n < 8; n++)
#pragma unroll
        for (int i = 0; i < 4; i++) acc[n][i] = 0.f;
    uint32_t wb = (g & 1) ? e0 + (1 + g + 2 * tq) * 2 : e1 + (g + 2 * tq) * 2;
    uint32_t W[16], a[4][4], an[4][4];
    int row = m * 16 + (lane & 15);
    auto lda = [&](uint32_t (*d)[4]) {
        const uint32_t x = row < 0 ? zrow : ub + row * 128 + (((lane >> 4) ^ (row & 7)) << 4);
#pragma unroll
        for (int ks = 0; ks < 4; ks++) ldsm_x4(d[ks][0], d[ks][1], d[ks][2], d[ks][3], x ^ (ks << 5));
        row--;
    };
#pragma unroll
    for (int i = 0; i < 16; i++) W[i] = lds32(wb + i * 16);
    lda(a);
    const int nD = m == 0 ? 16 : 32;
#pragma unroll 2
    for (int D = 0; D < nD; D++) {
        uint32_t Wn[8];
        wb += 128;
        if (D == nD - 6) nearly_done();
        lda(an);
#pragma unroll
        for (int i = 0; i < 8; i++) Wn[i] = lds32(wb + 128 + i * 16);
#pragma unroll
        for (int ks = 0; ks < 4; ks++)
#pragma unroll
            for (int n = 0; n < 8; n++) mma16816(acc[n], a[ks][0], a[ks][1], a[ks][2], a[ks][3], W[2 * ks + n], W[2 * ks + n + 1]);
#pragma unroll
        for (int i = 0; i < 8; i++) { W[i] = W[i + 8]; W[i + 8] = Wn[i]; }
#pragma unroll
        for (int ks = 0; ks < 4; ks++)
#pragma unroll
            for (int i = 0; i < 4; i++) a[ks][i] = an[ks][i];
    }
#pragma unroll
    for (int n = 0; n < 8; n++)
#pragma unroll
        for (int r = 0; r < 2; r++) {
            const int a_ = g + r * 8, b_ = n * 8 + tq * 2;
            const int ar = m * 16 + a_, p = 62 - b_;
            const uint32_t kv = lds32(ub + ar * 128 + (((p >> 3) ^ (ar & 7)) << 4) + (p & 7) * 2);
            const float y0 = rbf(acc[n][2 * r]) + rbf(bhi(kv) * Dv), y1 = rbf(acc[n][2 * r + 1]) + rbf(blo(kv) * Dv);
            const uint32_t pk = pack2(y0, y1);
            asm volatile("st.shared.u16 [%0], %1;" ::"r"(yt + ((a_ * 64 + b_) ^ g) * 16), "h"((unsigned short)(pk & 0xffff)) : "memory");
            asm volatile("st.shared.u16 [%0], %1;" ::"r"(yt + ((a_ * 64 + b_ + 1) ^ g) * 16), "h"((unsigned short)(pk >> 16)) : "memory");
        }
}

__global__ void __launch_bounds__(384, 1) bulk_kernel(const __grid_constant__ BulkMaps M, const __grid_constant__ BulkArgs A,
                                                      const __grid_constant__ Sched SC) {
    extern __shared__ __align__(1024) unsigned char smem_raw[];
    const uint32_t sb0 = smem_u32(smem_raw);
    const uint32_t full0 = sb0 + BULK_TAIL, empty0 = full0 + 32, tfull0 = full0 + 64, tempty0 = full0 + 96, sfull = full0 + 128, sempty = full0 + 160,
                   task0 = full0 + 192, tab0 = full0 + 208;
    const int tid = threadIdx.x, wid = __shfl_sync(0xffffffffu, tid >> 5, 0), lane = tid & 31;
    const int rank = blockIdx.x & 1;
    if (tid == 0) {
        for (int i = 0; i < BK_STAGES; i++) { mbar_init(full0 + 8 * i, 1); mbar_init(empty0 + 8 * i, 4); }
        for (int i = 0; i < TSLOTS; i++) { mbar_init(tfull0 + 8 * i, 1); mbar_init(tempty0 + 8 * i, 19); }
        for (int i = 0; i < 4; i++) { mbar_init(sfull + 8 * i, 8); mbar_init(sempty + 8 * i, 1); }
        asm volatile("fence.mbarrier_init.release.cluster;" ::: "memory");
        if (rank == 1) for (int i = 0; i < TSLOTS; i++) mbar_expect_tx(tfull0 + 8 * i, 4);
        BT(true, T_LN0, 0, 0, 0);
    }
    if (tid < MAXG * 5) asm volatile("st.shared.u32 [%0], %1;" ::"r"(tab0 + tid * 4), "r"(SC.chk[tid]) : "memory");
    cluster_sync_all();
    uint32_t tc = 0, it = 0;
    if (wid < 4) {
        asm volatile("setmaxnreg.dec.sync.aligned.u32 %0;" ::"n"(REG_P));
        if (wid == 0) {
            int head = SC.sbeg[lane >> 3];
            const int hend = SC.sbeg[(lane >> 3) + 1];
            uint32_t chk = 0; int pv = (blockIdx.x >> 1) & 31, grp = (SC.sbeg[3] + (blockIdx.x >> 6)) << 2 | 3, ncode = 0, code = 3 << 6 | 2, guard = 0;
            auto acquire = [&](uint32_t bytes) -> uint32_t {
                const uint32_t s = it & 3;
                mwait(empty0 + 8 * s, ((it >> 2) & 1) ^ 1);
                it++;
                expect_tx1(full0 + 8 * s, bytes);
                return s;
            };
            auto uwait = [&](const int* f, int tgt) {
                int g2 = 0;
                while ((int)UNI(ld_relaxed(f)) < tgt && ++g2 < 4000000) __nanosleep(32);
                fence_async();
            };
#pragma unroll 1
            while (true) {
                const int type = (code >> 6) & 3;
                const int iend = type == T_KV ? 10 : (type == T_QA ? 24 : 31);
                const int jj = code & 63, g0 = (jj & 15) * 4, lc = (code >> 9) & 31;
                const bool lm = (code >> 8) & 1;
                const CUtensorMap* mb = type == T_QA ? &M.wq : (jj < 16 ? &M.wk : &M.wv);
                bool have = false, ok = (code >> 14) & 1;
                int imem = 16;
#pragma unroll 1
                for (int i = type < T_CONV ? 0 : (type == T_CONV ? 24 : 28 + jj); i < iend; i++) {
                    const int sd = (type < T_CONV ? SPLAN : 0x1230) >> 4 * min(iend - i, 7) & 15;
                    if (rank == 0 && sd) {
                        if (sd == 1) {
                            if (type == T_CONV) mwait(empty0 + 8 * (it & 3), ((it >> 2) & 1) ^ 1);
                            const int gi = head + ((lane >> 2) & 1);
                            chk = lds32(tab0 + ((gi < hend ? gi : SENT) * 4 + (lane & 3)) * 4);
                            pv = ld_relaxed(g_flags + (chk & 0xffff));
                        } else if (sd == 2) {
                            const int tgt = (int)(chk >> 16);
                            const uint32_t b = (__ballot_sync(0xffffffffu, (lane & 3) == 0 ? pv < tgt : pv >= tgt) >> (lane & 24)) & 0xff;
                            const uint32_t cand = (b & 1) ? b & 15 : b >> 4;
                            head += (b & 1) ? 0 : ((b & 16) ? 1 : 2);
                            if (head > hend || guard > 4000000) head = hend;
                            const uint32_t req = lane >= 24 ? 1 : 15;
                            grp = (int)__reduce_min_sync(0xffffffffu, (cand & req) == req ? ((uint32_t)head << 2 | (cand ^ req) >> 2 | ((cand ^ req) & 2 ? 0 : 256)) : (head < hend ? 1000u : 1004u));
                            if (grp < 1000) grp &= 255;
                            if (grp < 1000) asm volatile("{\n.reg .pred p;\nsetp.eq.u32 p, %2, 0;\n@p atom.relaxed.gpu.global.inc.u32 %0, [%1], 0x7fffffff;\n}" : "+r"(pv) : "l"(FLG(F_CNT + (grp >> 2))), "r"(lane) : "memory");
                        } else {
                            if (grp < 1000) {
                                const int tk = (int)UNI(pv);
                                have = tk < (int)(UNI(lds32(tab0 + (grp >> 2) * 16)) >> 16);
                                ncode = (int)UNI(lds32(tab0 + MAXG * 16 + (grp & ~3))) | (grp & 3) << 19 | tk;
                            } else if (grp == 1004) { have = true; ncode = -1; }
                            if (have) {
                                const uint32_t o = (tc & 3) * 4;
                                mwait(tempty0 + 2 * o, ((tc >> 2) & 1) ^ 1);
                                asm volatile(ELECT "st.shared.u32 [%0], %1;\n@p mbarrier.arrive.shared::cta.b64 _, [%2];\n"
                                             "@p st.async.weak.shared::cluster.mbarrier::complete_tx::bytes.b32 [%3], %1, [%4];\n}"
                                             ::"r"(task0 + o), "r"(ncode), "r"(tfull0 + 2 * o), "r"(mapa(task0 + o, 1)), "r"(mapa(tfull0 + 2 * o, 1)) : "memory");
                            }
                        }
                    }
                    if (i >= 28) continue;
                    if (i == 8 && type == T_QA) pv = ld_relaxed(FLG((lane & 1 ? F_MEM : F_KV) + lc));
                    if (i == 10) {
                        const uint32_t b = __ballot_sync(0xffffffffu, pv >= (lane & 1 ? MEM_TGT : KV_TGT));
                        if (b & 2) imem = 13;
                        if (!(b & 1)) uwait(FLG(F_KV + lc), KV_TGT);
                        fence_async();
                    }
                    const uint32_t s = acquire(i < 12 ? 49152 : (i == 24 || i == 27 ? 0 : 32768));
                    const uint32_t sa = sb0 + s * BK_STAGE_BYTES, fb = full0 + 8 * s;
                    if (i == 0) TT(3);
                    if (i < 10) {
                        if (lm) {
                            tma_load_3d(sa + 16384, mb, fb, i * 64, g0);
                            tma_load_3d(sa + 32768, mb, fb, i * 64, g0 + 2);
                        } else tma_load_3d_mc(sa + 16384 + rank * 16384, mb, fb, i * 64, g0 + rank * 2);
                        int d = 0;
                        if (!ok) {
                            d = 1;
                            if (i == 3) {
                                uwait(FLG(F_H + lc), H_TGT);
                                ok = true;
                                d = -3;
                                TT(4);
                            }
                        }
#pragma unroll 1
                        for (; d <= 0; d++) {
                            const uint32_t s2 = (s + d) & 3;
                            if (lm) tma_load_2d_mc(sb0 + s2 * BK_STAGE_BYTES + rank * 8192, &M.h, full0 + 8 * s2, (i + d) * 64, lc * 128 + rank * 64);
                            else tma_load_2d(sb0 + s2 * BK_STAGE_BYTES, &M.h2, full0 + 8 * s2, (i + d) * 64, lc * 128);
                        }
                    } else if (i < 13) {
#pragma unroll 1
                        for (int k = 0, bx = (i - 10) * 3; k < 3 && bx < 8; k++, bx++)
                            tma_load_2d(sa + k * 16384, &M.kv, fb, (g0 + (bx & 3)) * 64, (bx >> 2) * S_LEN + (lc & 15) * 128);
                    } else if (i < 24) {
                        const int cn = ((i - 14) >> 1) * 128, ck = g0 * 64 + (i & 1) * 128;
                        if (i > 13) {
                            if (lm) { tma_load_2d(sa, &M.wo, fb, cn, ck); tma_load_2d(sa + 16384, &M.wo, fb, cn + 64, ck); }
                            else tma_load_2d_mc(sa + rank * 16384, &M.wo, fb, cn + rank * 64, ck);
                        }
                        if (i == imem) {
                            TT(5);
                            if (i == 16) uwait(FLG(F_MEM + lc), MEM_TGT);
                            const uint32_t s2 = (s + (i >> 4)) & 3;
#pragma unroll 1
                            for (int k = 0; k < 4; k++)
                                bulk_load(sb0 + s2 * BK_STAGE_BYTES + k * 8192, g_kvf + (size_t)((lc * CSEG + k) * NH + jj * 2) * 256, 8192, full0 + 8 * s2);
                            TT(6);
                        }
                    } else if (i == 25) {
                        tma_load_2d(sa, &M.lu, fb, 0, (2 * jj + rank) * 256);
                    } else if (i == 26) {
#pragma unroll 1
                        for (int k = 0; k < 8; k++)
                            bulk_load(sa + k * CV_EP + 128, A.ssmk + (size_t)((2 * jj + rank) * 8 + k) * S_LEN, 4096, fb);
                    }
                }
                if (type != 3) TT(7);
                if (rank == 0) {
                    if (!have) {
                        if (type == 3) { guard++; __nanosleep(64); }
                        code = 3 << 6;
                        continue;
                    }
                } else {
                    const uint32_t o = (tc & 3) * 4;
                    mwait(tfull0 + 2 * o, (tc >> 2) & 1);
                    ncode = (int)UNI(lds32(task0 + o));
                    asm volatile(ELECT "mbarrier.arrive.expect_tx.shared::cta.b64 _, [%0], 4;\n@p mbarrier.arrive.shared::cluster.b64 _, [%1];\n}" ::"r"(tfull0 + 2 * o), "r"(mapa(tempty0 + 2 * o, 0)) : "memory");
                    __syncwarp();
                }
                tc++;
                if (ncode < 0) break;
                TT(0); TTV(15, ncode);
                code = ((ncode & 256) ? (2 * ncode + rank) & 63 : ncode & 63) | (ncode & 0x1c0) | ((ncode >> (rank ? 14 : 9)) & 31) << 9 | ((ncode >> (19 + rank)) & 1) << 14;
                fence_async();
            }
        } else if (wid == 1) {
            if (lane < 8) asm volatile("prefetch.tensormap [%0];" ::"l"(&M.h + lane) : "memory");
            __syncwarp();
            if (lane == 0) {
                uint32_t rc = 0;
                while (true) {
                    mwait(tfull0 + 8 * (tc & 3), (tc >> 2) & 1);
                    const int code = (int)lds32(task0 + 4 * (tc & 3));
                    mbar_arrive_cluster(mapa(tempty0 + 8 * (tc & 3), 0));
                    tc++;
                    if (code < 0) break;
                    const int type = (code >> 6) & 3;
                    const int lc = (code >> (rank ? 14 : 9)) & 31;
                    mwait(sfull + 8 * (rc & 3), (rc >> 2) & 1);
                    if (type == T_CONV) {
                        asm volatile("cp.async.bulk.global.shared::cta.bulk_group [%0], [%1], %2;" ::"l"(g_Y + (size_t)((2 * (code & 63) + rank) * S_LEN + lc * 1024) * 8), "r"(sb0 + BULK_STG), "r"(16384) : "memory");
                        bulk_commit();
                        bulk_wait<0>();
                    }
                    mbar_arrive(sempty + 8 * (rc & 3));
                    rc++;
                    FT(0);
                    red_release(type == T_QA ? FLG(F_OP + lc) + 4 : FLG((type == T_KV ? F_KV : F_CONV) + lc), 1);
                    FT(1);
                    BT(true, type, lc >> 4, lc & 15, 2);
                }
            }
        } else {
            const int nw = 2 * gridDim.x, idx = (wid - 2) * gridDim.x + blockIdx.x;
#pragma unroll 1
            for (int hh = 0; hh < 2; hh++) {
#pragma unroll 1
                for (int u = hh * 640 + idx; u < hh * 640 + 640; u += nw) u_unit(A.Bk, A.Bv, A.shiftk, u, lane);
                __syncwarp();
                if (lane == 0) red_release(FLG(F_U + hh), 1);
                BT(lane == 0, T_LN0, hh, 0, 2);
            }
#pragma unroll 1
            for (int q = 0; q < 2 * (NCHK + PDIST); q++) {
                const int l = q & 1, c = (q >> 1) - l * PDIST;
                if (c < 0 || c >= NCHK) continue;
#pragma unroll 1
                for (int rr = idx; rr < 128; rr += nw) post_row(l, c * 128 + rr, lane, l ? g_x : A.x, l ? A.out : g_x);
                BT(lane == 0, T_POST, l, c, 2);
            }
        }
    } else {
        asm volatile("setmaxnreg.inc.sync.aligned.u32 %0;" ::"n"(REG_C));
        const int cw = (wid >> 2) - 1, warp = wid & 3;
        const uint32_t wst = sb0 + BULK_STG + (cw * 4 + warp) * 4096;
        uint32_t rc = 0;
        int npend = 0;
        bool urgent = false;
        uint32_t oofs = 0;
        uint32_t qf[16][4];
        auto release = [&](int s) { if ((tid & 127) == 0) { mbar_arrive(empty0 + 8 * s); mbar_arrive_cluster(mapa(empty0 + 8 * s, rank ^ 1)); } };
        auto next = [&]() -> int { const int s = it & 3; mwait(full0 + 8 * s, (it >> 2) & 1); it++; return s; };
        auto wgbar = [&]() { if (cw == 0) named_bar(2, 128); else named_bar(3, 128); };
        auto handoff = [&]() {
            mwait(sempty + 8 * (rc & 3), ((rc >> 2) & 1) ^ 1);
            asm volatile(ELECT "mbarrier.arrive.shared::cta.b64 _, [%0];\n}" ::"r"(sfull + 8 * (rc & 3)) : "memory");
            rc++;
        };
        auto stg_free = [&]() { mwait(sempty + 8 * ((rc - 1) & 3), ((rc - 1) >> 2) & 1); };
        auto round_q = [&]() {
            if (npend > 4) {
                uint4* d = reinterpret_cast<uint4*>(g_part) + oofs;
                if (npend == 6) {
#pragma unroll
                    for (int i = 0; i < 4; i++) red_add8(d + (i >> 1) * 4 + (i & 1) * (8 * PG * DM / 8), qf[i][0], qf[i][1], qf[i][2], qf[i][3]);
                    npend = 5;
                } else {
#pragma unroll
                    for (int i = 4; i < 8; i++) red_add8(d + (i >> 1) * 4 + (i & 1) * (8 * PG * DM / 8), qf[i][0], qf[i][1], qf[i][2], qf[i][3]);
                    npend = 0;
                    handoff();
                }
                return;
            }
            const uint32_t sst = wst + (lane & 15) * 128 + (((lane >> 4) ^ (lane & 7)) << 4) + (npend & 1) * 2048;
#pragma unroll
            for (int q = 0; q < 4; q++)
                if (npend == 4 - q) {
#pragma unroll
                    for (int i = 0; i < 4; i++) stsm_x4(sst ^ (i << 5), qf[q * 4 + i][0], qf[q * 4 + i][1], qf[q * 4 + i][2], qf[q * 4 + i][3]);
                }
            __syncwarp();
            uint4* d = reinterpret_cast<uint4*>(&g_kv[0][0]) + oofs;
            const uint32_t src = wst + (lane >> 3) * 128 + (((lane & 7) ^ (lane >> 3)) << 4) + (npend & 1) * 2048;
#pragma unroll
            for (int i = 0; i < 4; i++) d[i * (4 * HD / 8)] = lds128((src + i * 512) ^ ((i & 1) << 6));
            oofs += 8;
            if (--npend == 0) handoff();
        };
        auto round_a = [&](const float* a, int hh) {
            uint4* d = reinterpret_cast<uint4*>(g_part) + oofs;
#pragma unroll
            for (int i = hh * 4; i < hh * 4 + 4; i++) {
                const float* b = a + (i >> 1) * 16 + (i & 1) * 2;
                red_add8(d + (i >> 1) * 4 + (i & 1) * (8 * PG * DM / 8), pack2(b[0], b[1]), pack2(b[4], b[5]), pack2(b[8], b[9]), pack2(b[12], b[13]));
            }
            if (hh) oofs += 16;
        };
        while (true) {
            tc++; TT(0); tc--;
            int code;
            while (true) {
                if (npend == 0) mwait(tfull0 + 8 * (tc & 3), (tc >> 2) & 1);
                if (npend == 0 || UNI(mtest(tfull0 + 8 * (tc & 3), (tc >> 2) & 1))) {
                    code = (int)UNI(lds32(task0 + 4 * (tc & 3)));
                    if (npend == 0 || ((code & 0x80) == 0 && !urgent && UNI(mtest(full0 + 8 * (it & 3), (it >> 2) & 1)))) break;
                }
                round_q();
            }
            if (lane == 0) mbar_arrive_cluster(mapa(tempty0 + 8 * (tc & 3), 0));
            tc++;
            TT(2);
            if (code < 0) break;
            const int type = (code >> 6) & 3;
            TTV(15, code);
#define BTC(type, k)
            if (type == T_CONV) {
                const int m = (code >> 9) & 1;
                BT((tid & 127) == 0, T_CONV, 0, m, 0);
                const int u = 2 * (code & 63) + rank, ch = cw * 4 + warp;
                int lane = tid & 31;
                asm volatile("" : "+r"(lane));
                const float Dv = bf2f(A.ssmD[u * 8 + ch]);
                const int sd = next(), s0 = next(), s1 = next(), s2 = next();
                TT(3);
                const uint32_t e1 = sb0 + s2 * BK_STAGE_BYTES;
                conv_unit(sb0 + s0 * BK_STAGE_BYTES + ch * 4096, sb0 + s1 * BK_STAGE_BYTES + ch * CV_EP, e1 + 64 + ch * CV_EP, e1 + 40960 + ch * 128, sb0 + BULK_STG + ch * 2, Dv, m, lane,
                          [&]() { release(sd); stg_free(); });
                asm volatile("fence.proxy.async.shared::cta;" ::: "memory");
                __syncwarp();
                handoff();
                TT(5);
                wgbar();
                release(s0); release(s1); release(s2);
                __syncwarp();
#pragma unroll
                for (int i = 0; i < 64; i++) qf[i >> 2][i & 3] = 0;
                continue;
            }
            float acc[128];
            {
                int s = next();
                TT(3); BTC(type, 0); BTC(type, 1);
                uint32_t sa = sb0 + s * BK_STAGE_BYTES + cw * 8192, sb = sb0 + s * BK_STAGE_BYTES + 16384;
                wg_fence();
                wgmma_m64n256k16_first(acc, make_desc(sa, 16, 1024), make_desc(sb, 8192, 1024));
#pragma unroll 1
                for (int kb = 0;;) {
#pragma unroll
                    for (int k = 1; k < 4; k++) wgmma_m64n256k16(acc, make_desc(sa + k * 32, 16, 1024), make_desc(sb + k * 2048, 8192, 1024));
                    wg_commit();
                    if (npend) round_q();
                    if (kb) { wg_wait<1>(); release((s - 1) & 3); }
                    if (++kb == 10) break;
                    s = next();
                    sa = sb0 + s * BK_STAGE_BYTES + cw * 8192; sb = sb0 + s * BK_STAGE_BYTES + 16384;
                    wg_fence();
                    wgmma_m64n256k16(acc, make_desc(sa, 16, 1024), make_desc(sb, 8192, 1024));
                }
            }
            wg_wait<0>();
            TT(4);
            release((it - 1) & 3);
            stg_free();
#pragma unroll
            for (int i = 0; i < 16; i++)
#pragma unroll
                for (int e = 0; e < 4; e++) qf[i][e] = pack2(acc[i * 8 + e * 2], acc[i * 8 + e * 2 + 1]);
            {
                const int cd = (int)lds32(task0 + 4 * ((tc - 1) & 3)), lc = (cd >> (rank ? 14 : 9)) & 31, jj = (cd & 256) ? (2 * cd + rank) & 63 : cd & 63;
                const int r0 = cw * 64 + warp * 16;
                if (type == T_KV) {
                    oofs = ((jj >> 4) * S_LEN + (lc & 15) * 128 + r0 + (lane >> 3)) * (HD / 8) + (jj & 15) * 32 + (lane & 7);
                    npend = 4;
                    urgent = URGENT && (lc < 2 || lc >= 16);
                    continue;
                }
                oofs = (((lc >> 4) * PRING + (lc & (PRING - 1))) * 128 + r0 + (lane >> 2)) * (PG * DM / 8) + (jj & (PG - 1)) * (DM / 8) + (lane & 3);
            }
            const float cs = 1.4426950408889634f;
            int lane = tid & 31;
            asm volatile("" : "+r"(lane));
            const int g = lane >> 2, tq = lane & 3;
            const int sg = cw * 2 + (warp >> 1), hs = warp & 1;
            float mt[2][2], sum[2][2];
            {
                const int x0 = next(), x1 = next();
                TT(5);
                float s[2][4][4];
#pragma unroll
                for (int hd = 0; hd < 2; hd++)
#pragma unroll
                    for (int n = 0; n < 4; n++)
#pragma unroll
                        for (int e = 0; e < 4; e++) s[hd][n][e] = 0.f;
                const uint32_t krow = (sg * 32 + (lane & 7) + (lane >> 4) * 8) * 128 + ((((lane >> 3) & 1) ^ (lane & 7)) << 4);
#pragma unroll
                for (int ii = 0; ii < 16; ii++) {
                    const int i = (ii >> 1) + (ii & 1) * 8;
                    const uint32_t kb = sb0 + (i < 12 ? x0 * BK_STAGE_BYTES + (i >> 2) * 16384 : x1 * BK_STAGE_BYTES) + (krow ^ ((i & 3) << 5));
                    const uint4 k0 = ldsm4(kb), k1 = ldsm4(kb + 2048);
                    mma16816(s[i >> 3][0], qf[i][0], qf[i][1], qf[i][2], qf[i][3], k0.x, k0.y);
                    mma16816(s[i >> 3][1], qf[i][0], qf[i][1], qf[i][2], qf[i][3], k0.z, k0.w);
                    mma16816(s[i >> 3][2], qf[i][0], qf[i][1], qf[i][2], qf[i][3], k1.x, k1.y);
                    mma16816(s[i >> 3][3], qf[i][0], qf[i][1], qf[i][2], qf[i][3], k1.z, k1.w);
                }
#pragma unroll
                for (int i = 0; i < 8; i++) sts128(wst + i * 512 + lane * 16, qf[8 + i][0], qf[8 + i][1], qf[8 + i][2], qf[8 + i][3]);
                wgbar();
                release(x0);
                TT(6);
                uint32_t pa[2][4][2];
#pragma unroll
                for (int hd = 0; hd < 2; hd++) {
                    uint32_t mx[2] = {0xff80ff80u, 0xff80ff80u};
#pragma unroll
                    for (int n = 0; n < 4; n++)
#pragma unroll
                        for (int r = 0; r < 2; r++) {
                            const int d = hs * 16 + g + r * 8 - n * 8 - tq * 2;
                            pa[hd][n][r] = rscore(d < 0 ? -INFINITY : s[hd][n][2 * r], d < 1 ? -INFINITY : s[hd][n][2 * r + 1]);
                            mx[r] = bmax2(mx[r], pa[hd][n][r]);
                        }
#pragma unroll
                    for (int r = 0; r < 2; r++) {
                        mx[r] = bmax2(mx[r], __shfl_xor_sync(0xffffffffu, mx[r], 1));
                        mx[r] = bmax2(mx[r], __shfl_xor_sync(0xffffffffu, mx[r], 2));
                        mt[hd][r] = fmaxf(blo(mx[r]), bhi(mx[r])) * cs;
                        sum[hd][r] = 0.f;
                    }
#pragma unroll
                    for (int n = 0; n < 4; n++)
#pragma unroll
                        for (int r = 0; r < 2; r++) {
                            const float p0 = ex2f(fmaf(blo(pa[hd][n][r]), cs, -mt[hd][r])), p1 = ex2f(fmaf(bhi(pa[hd][n][r]), cs, -mt[hd][r]));
                            sum[hd][r] += p0 + p1;
                            pa[hd][n][r] = pack2(p0, p1);
                        }
                }
                const uint32_t vrow = (sg * 32 + (lane & 15)) * 128 + (((lane >> 4) ^ (lane & 7)) << 4);
                int xv = x1;
#pragma unroll
                for (int hd = 0; hd < 2; hd++) {
                    if (hd == 1) xv = next();
#pragma unroll
                    for (int i = 0; i < 8; i++) {
                        const uint32_t vb = sb0 + xv * BK_STAGE_BYTES + (hd == 0 ? 16384 : 0) + (i >> 2) * 16384 + (vrow ^ ((i & 3) << 5));
                        uint4 v0, v1;
                        ldsm_x4_t(v0.x, v0.y, v0.z, v0.w, vb);
                        ldsm_x4_t(v1.x, v1.y, v1.z, v1.w, vb + 2048);
                        float* o = acc + hd * 64 + i * 8;
#pragma unroll
                        for (int e = 0; e < 8; e++) o[e] = 0.f;
                        mma16816(o, pa[hd][0][0], pa[hd][0][1], pa[hd][1][0], pa[hd][1][1], v0.x, v0.y);
                        mma16816(o + 4, pa[hd][0][0], pa[hd][0][1], pa[hd][1][0], pa[hd][1][1], v0.z, v0.w);
                        mma16816(o, pa[hd][2][0], pa[hd][2][1], pa[hd][3][0], pa[hd][3][1], v1.x, v1.y);
                        mma16816(o + 4, pa[hd][2][0], pa[hd][2][1], pa[hd][3][0], pa[hd][3][1], v1.z, v1.w);
                    }
                    wgbar();
                    release(xv);
                }
            }
            TT(7);
            BTC(T_ATT, 0);
            {
                const int xm = next();
                TT(8);
                BTC(T_ATT, 1);
                const uint32_t mb = sb0 + xm * BK_STAGE_BYTES + sg * 8192 + lane * 16;
                float sm[2][2][4];
#pragma unroll
                for (int i = 0; i < 16; i++) (&sm[0][0][0])[i] = 0.f;
#pragma unroll
                for (int q = 0; q < 4; q++) {
                    const uint4 k0 = lds128(mb + q * 512), k1 = lds128(mb + 4096 + q * 512);
                    const uint4 qa = lds128(wst + q * 1024 + lane * 16), qb = lds128(wst + q * 1024 + 512 + lane * 16);
                    mma16816(sm[0][0], qf[2 * q][0], qf[2 * q][1], qf[2 * q][2], qf[2 * q][3], k0.x, k0.y);
                    mma16816(sm[0][1], qf[2 * q + 1][0], qf[2 * q + 1][1], qf[2 * q + 1][2], qf[2 * q + 1][3], k0.z, k0.w);
                    mmau(sm[1][0], qa, k1.x, k1.y);
                    mmau(sm[1][1], qb, k1.z, k1.w);
                }
                float f[2][2];
                uint32_t pm[2][2];
#pragma unroll
                for (int hd = 0; hd < 2; hd++)
#pragma unroll
                    for (int r = 0; r < 2; r++) {
                        const uint32_t w = rscore(sm[hd][0][2 * r] + sm[hd][1][2 * r], sm[hd][0][2 * r + 1] + sm[hd][1][2 * r + 1]);
                        const float s0 = blo(w) * cs, s1 = bhi(w) * cs;
                        float m = fmaxf(s0, s1);
                        m = fmaxf(m, __shfl_xor_sync(0xffffffffu, m, 1));
                        m = fmaxf(fmaxf(m, __shfl_xor_sync(0xffffffffu, m, 2)), mt[hd][r]);
                        const float a = ex2f(mt[hd][r] - m), p0 = ex2f(s0 - m), p1 = ex2f(s1 - m);
                        float t = fmaf(sum[hd][r], a, p0 + p1);
                        t += __shfl_xor_sync(0xffffffffu, t, 1);
                        t += __shfl_xor_sync(0xffffffffu, t, 2);
                        t = rcpf(t);
                        f[hd][r] = a * t;
                        pm[hd][r] = pack2(p0 * t, p1 * t);
                    }
#pragma unroll
                for (int q = 0; q < 8; q++) {
                    const int hd = q >> 2;
                    const uint4 vm = lds128(mb + hd * 4096 + 2048 + (q & 3) * 512);
                    float* o = acc + q * 16;
#pragma unroll
                    for (int e = 0; e < 16; e++) o[e] *= f[hd][(e >> 1) & 1];
                    mma1688(o, pm[hd][0], pm[hd][1], vm.x);
                    mma1688(o + 4, pm[hd][0], pm[hd][1], vm.y);
                    mma1688(o + 8, pm[hd][0], pm[hd][1], vm.z);
                    mma1688(o + 12, pm[hd][0], pm[hd][1], vm.w);
#pragma unroll
                    for (int e = 0; e < 8; e++) qf[q * 2 + (e >> 2)][e & 3] = pack2(o[2 * e], o[2 * e + 1]);
                }
                wgbar();
                release(xm);
            }
            TT(9);
#pragma unroll
            for (int t = 0; t < 10; t++) {
                const int s = next();
                const uint32_t sb = sb0 + s * BK_STAGE_BYTES;
                float* d = acc + ((t >> 1) & 1) * 64;
                wg_fence();
#pragma unroll
                for (int k = 0; k < 8; k++) {
                    const uint64_t db = make_desc(sb + k * 2048, 16384, 1024);
                    if (k == 0 && !(t & 1)) wgmma_rs_m64n128k16_first(d, qf[k], db);
                    else wgmma_rs_m64n128k16(d, qf[(t & 1) * 8 + k], db);
                }
                wg_commit();
                if (t) {
                    wg_wait<1>();
                    release((s - 1) & 3);
                    if (t > 1) round_a(acc + (((t >> 1) & 1) ^ 1) * 64, t & 1);
                }
            }
            wg_wait<0>();
            release((it - 1) & 3);
            TT(10);
#pragma unroll
            for (int i = 0; i < 32; i++) qf[i >> 2][i & 3] = pack2(acc[(i >> 3) * 16 + (i & 4) / 2 + (i & 3) * 4], acc[(i >> 3) * 16 + (i & 4) / 2 + (i & 3) * 4 + 1]);
            npend = 6;
            urgent = URGENT > 1;
        }
    }
    cluster_sync_all();
}

__global__ void __launch_bounds__(256) reset_kernel(const bf16* x, int g0, int ncl) {
    const int lane = threadIdx.x & 31, row = blockIdx.x * 8 + (threadIdx.x >> 5);
    uint32_t r[10];
    ld5<128>(r, x + (size_t)row * DM + lane * 4);
    if (blockIdx.x == 0)
        for (int i = threadIdx.x; i < NFLAG * 2; i += blockDim.x) reinterpret_cast<uint4*>(FLG(i >> 1))[i & 1] = make_uint4(i == g0 ? min(ncl, 32) : (i == g0 + 2 ? max(ncl - 32, 0) : 0), 0, 0, 0);
    for (int i = blockIdx.x * 256 + threadIdx.x; i < 2 * PROWS * PG * DM / 8; i += S_LEN * 32) reinterpret_cast<uint4*>(g_part)[i] = make_uint4(0, 0, 0, 0);
    ln_row(r, r);
    st5(g_h[0] + (size_t)row * DM + lane * 4, r);
    if (blockIdx.x) return;
}

typedef CUresult (*PFN_encodeTiled)(CUtensorMap*, CUtensorMapDataType, cuuint32_t, void*, const cuuint64_t*, const cuuint64_t*,
                                    const cuuint32_t*, const cuuint32_t*, CUtensorMapInterleave, CUtensorMapSwizzle,
                                    CUtensorMapL2promotion, CUtensorMapFloatOOBfill);
static PFN_encodeTiled get_encode() {
    static PFN_encodeTiled fn = nullptr;
    if (!fn) {
        void* p = nullptr;
        cudaDriverEntryPointQueryResult qr;
        cudaGetDriverEntryPoint("cuTensorMapEncodeTiled", &p, cudaEnableDefault, &qr);
        fn = (PFN_encodeTiled)p;
    }
    return fn;
}
static void make_map(CUtensorMap* m, const void* ptr, uint64_t rows, uint64_t cols, uint32_t box_rows) {
    cuuint64_t dims[2] = {cols, rows};
    cuuint64_t strides[1] = {cols * 2};
    cuuint32_t box[2] = {64u, box_rows};
    cuuint32_t es[2] = {1, 1};
    get_encode()(m, CU_TENSOR_MAP_DATA_TYPE_BFLOAT16, 2, const_cast<void*>(ptr), dims, strides, box, es,
                 CU_TENSOR_MAP_INTERLEAVE_NONE, CU_TENSOR_MAP_SWIZZLE_128B, CU_TENSOR_MAP_L2_PROMOTION_L2_128B,
                 CU_TENSOR_MAP_FLOAT_OOB_FILL_NONE);
}
static void make_map3(CUtensorMap* m, const void* ptr) {
    cuuint64_t dims[3] = {64, DM, HD / 64};
    cuuint64_t strides[2] = {HD * 2, 128};
    cuuint32_t box[3] = {64u, 64u, 2u};
    cuuint32_t es[3] = {1, 1, 1};
    get_encode()(m, CU_TENSOR_MAP_DATA_TYPE_BFLOAT16, 3, const_cast<void*>(ptr), dims, strides, box, es,
                 CU_TENSOR_MAP_INTERLEAVE_NONE, CU_TENSOR_MAP_SWIZZLE_128B, CU_TENSOR_MAP_L2_PROMOTION_L2_128B,
                 CU_TENSOR_MAP_FLOAT_OOB_FILL_NONE);
}
#define QA_PRE0 4
#define KV1_E 1
#define KV1_L 16
#define KV0_X 6
#define CONV0_AT 1
#define CONV1_AT 9
static void build_sched(Sched& S, int naux) {
    int n = 0;
    auto ck = [](int f, int t) { return (uint32_t)(f * 32) | (uint32_t)t << 16; };
    auto add = [&](int lm, int type, int la, int ca, int lb, int cb, int ntask, uint32_t soft) {
        S.info[n] = (uint32_t)(type << 6 | lm << 8 | (la * 16 + ca) << 9 | (lb * 16 + cb) << 14);
        S.chk[n * 4] = ck(F_CNT + n, ntask); S.chk[n * 4 + 1] = soft;
        S.chk[n * 4 + 2] = ck(F_H + la * NCHK + ca, H_TGT); S.chk[n * 4 + 3] = ck(F_H + lb * NCHK + cb, H_TGT);
        n++;
    };
    for (int i = 0; i < MAXG * 4; i++) S.chk[i] = ck(F_ZERO, 0);
    for (int i = 0; i < MAXG; i++) S.info[i] = 0;
    S.sbeg[0] = n;
    for (int i = 0; i < NCHK; i++) {
        add(1, T_KV, 1, i, 1, i, 16, i < KV1_E || i >= KV1_L ? ck(F_OP + i, 14) + 4 : ck(F_H + NCHK + i, KV1_N));
        S.chk[n * 4 - 2] = S.chk[n * 4 - 1] = ck(F_CONV + i / 8, CONV_TGT);
    }
    S.sbeg[1] = n;
    auto addqa = [&]() {
    for (int p = 0; p < NCHK + PDIST; p++) {
        const bool h0 = p < NCHK, h1 = p >= PDIST;
        const int la = h0 ? 0 : 1, ca = h0 ? p : p - PDIST, lb = h1 ? 1 : 0, cb = h1 ? p - PDIST : p;
        const int ta = ca * CSEG + CSEG + la * LAG;
        add(!(h0 && h1), T_QA, la, ca, lb, cb, h0 && h1 ? 16 : 8,
            ck(F_PROG, h1 ? ta - QA_PRE : (ta > QA_PRE0 ? ta - QA_PRE0 : 0)));
        S.info[n - 1] |= 3u << 19;
        S.chk[n * 4 - 2] = h0 && ca >= PRING ? ck(F_H + NCHK + ca - PRING + 1, H_TGT) : ck(F_ZERO, 0);
        S.chk[n * 4 - 1] = !h1 ? ck(F_KV + ca, KV_TGT) : (cb >= PRING ? ck(F_OP + NCHK + cb - PRING, 128) + 5 : ck(F_ZERO, 0));
    }
    };
    auto addkv = [&]() {
    for (int i = 0; i < NCHK; i += 2) add(0, T_KV, 0, i, 0, i + 1, 32, ck(F_PROG, 4 * i > KV0_X + 1 ? 4 * i - KV0_X : 1)), S.chk[n * 4 - 2] = S.chk[n * 4 - 1] = ck(F_ZERO, 0);
    };
    addqa();
    S.sbeg[2] = n;
    for (int m = 0; m < 2; m++) {
        add(0, T_CONV, 0, m, 0, m, 40, ck(F_U + m, naux));
        S.chk[n * 4 - 2] = S.chk[n * 4 - 1] = ck(F_CNT + S.sbeg[2] + 2 + (m ? CONV1_AT : CONV0_AT) / 2, 32);
    }
    S.sbeg[3] = n;
    addkv();
    S.sbeg[4] = n;
}

static void launch_all(void* const* d_in, void* d_out) {
    const bf16* x = (const bf16*)d_in[0];
    const bf16* mem0 = (const bf16*)d_in[1];
    const bf16* Wq = (const bf16*)d_in[2];
    const bf16* Wk = (const bf16*)d_in[3];
    const bf16* Wv = (const bf16*)d_in[4];
    const bf16* Wo = (const bf16*)d_in[5];
    static bool inited = false;
    static int nsm = 132;
    static Sched SC;
    bf16 *p_h, *p_kv, *p_u;
    cudaGetSymbolAddress((void**)&p_h, g_h);
    cudaGetSymbolAddress((void**)&p_kv, g_kv);
    cudaGetSymbolAddress((void**)&p_u, g_U);
    if (!inited) {
        inited = true;
        cudaDeviceGetAttribute(&nsm, cudaDevAttrMultiProcessorCount, 0);
        cudaFuncSetAttribute(chain_kernel, cudaFuncAttributeMaxDynamicSharedMemorySize, (int)sizeof(ChainSmem));
        cudaFuncSetAttribute(chain_kernel, cudaFuncAttributeNonPortableClusterSizeAllowed, 1);
        cudaFuncSetAttribute(bulk_kernel, cudaFuncAttributeMaxDynamicSharedMemorySize, BULK_SMEM);
        build_sched(SC, 2 * ((nsm - 64) & ~1));
    }
    const size_t QS = (size_t)S_LEN * HD;
    BulkMaps M;
    make_map(&M.h, p_h, 2 * S_LEN, DM, 64);
    make_map(&M.h2, p_h, 2 * S_LEN, DM, 128);
    make_map3(&M.wq, Wq);
    make_map3(&M.wk, Wk);
    make_map3(&M.wv, Wv);
    make_map(&M.wo, Wo, HD, DM, 128);
    make_map(&M.kv, p_kv, 2 * S_LEN, HD, 128);
    make_map(&M.lu, p_u, DM * 32, 64, 256);
    BulkArgs BA;
    BA.x = x; BA.out = (bf16*)d_out;
    BA.Bk = (const bf16*)d_in[8]; BA.Bv = (const bf16*)d_in[9]; BA.shiftk = (const bf16*)d_in[10];
    BA.ssmk = (const bf16*)d_in[11]; BA.ssmD = (const bf16*)d_in[12];
    ChainArgs ca;
    for (int l = 0; l < 2; l++) {
        make_map(&ca.tk[l], p_kv, S_LEN, HD, 32);
        make_map(&ca.tv[l], p_kv + QS, S_LEN, HD, 32);
    }
    ca.x = x; ca.mem0 = mem0; ca.Wq = Wq; ca.Wk = Wk; ca.Wv = Wv; ca.Wo = Wo; ca.kv_target = KV_TGT;
    cudaStream_t s = cudaStreamPerThread;
    reset_kernel<<<S_LEN / 8, 256, 0, s>>>(x, 2 * (F_CNT + SC.sbeg[3]), (nsm - 64) / 2);
    {
        cudaLaunchConfig_t cfg = {};
        cfg.gridDim = dim3(64); cfg.blockDim = dim3(CHAIN_THREADS); cfg.dynamicSmemBytes = sizeof(ChainSmem); cfg.stream = s;
        cudaLaunchAttribute at[1];
        at[0].id = cudaLaunchAttributeClusterDimension;
        at[0].val.clusterDim.x = CL; at[0].val.clusterDim.y = 1; at[0].val.clusterDim.z = 1;
        cfg.attrs = at; cfg.numAttrs = 1;
        cudaLaunchKernelEx(&cfg, chain_kernel, ca);
    }
    {
        cudaLaunchConfig_t cfg = {};
        cfg.gridDim = dim3((nsm - 64) & ~1); cfg.blockDim = dim3(384); cfg.dynamicSmemBytes = BULK_SMEM; cfg.stream = s;
        cudaLaunchAttribute at[2];
        at[0].id = cudaLaunchAttributeProgrammaticStreamSerialization;
        at[0].val.programmaticStreamSerializationAllowed = 1;
        at[1].id = cudaLaunchAttributeClusterDimension;
        at[1].val.clusterDim.x = 2; at[1].val.clusterDim.y = 1; at[1].val.clusterDim.z = 1;
        cfg.attrs = at; cfg.numAttrs = 2;
        cudaLaunchKernelEx(&cfg, bulk_kernel, M, BA, SC);
    }
}
}

extern "C" void kernel_launch(void* const* d_in, const int* in_sizes, int n_in, void* d_out, int out_size) {
    (void)in_sizes; (void)n_in; (void)out_size;
    if (ws::usable()) ws::launch_all(d_in, d_out);
    else ni::launch_all(d_in, d_out);
}
```

```cpp
#include <cuda_runtime.h>
#include <cuda_bf16.h>
#include <stdint.h>
#include <cuda.h>

typedef __nv_bfloat16 bf16;
namespace ws {
constexpr int S_LEN = 2048, DM = 640, NH = 32, DH = 128, HD = NH * DH, SEG = 32, NSEG = S_LEN / SEG;

__device__ __forceinline__ float bf2f(bf16 v) { return __bfloat162float(v); }
__device__ __forceinline__ float rbf(float v) { return __bfloat162float(__float2bfloat16_rn(v)); }
__device__ __forceinline__ uint32_t pack2(float a, float b) {
    __nv_bfloat162 t = __floats2bfloat162_rn(a, b);
    return *reinterpret_cast<uint32_t*>(&t);
}
__device__ __forceinline__ float blo(uint32_t v) { return __uint_as_float(v << 16); }
__device__ __forceinline__ float bhi(uint32_t v) { return __uint_as_float(v & 0xffff0000u); }
__device__ __forceinline__ uint32_t badd(uint32_t a, uint32_t b) { uint32_t r; asm("add.rn.bf16x2 %0, %1, %2;" : "=r"(r) : "r"(a), "r"(b)); return r; }
__device__ __forceinline__ uint32_t smem_u32(const void* p) { return (uint32_t)__cvta_generic_to_shared(p); }
__device__ __forceinline__ uint4 ldsm4(uint32_t a) {
    uint4 v;
    asm volatile("ldmatrix.sync.aligned.m8n8.x4.shared.b16 {%0,%1,%2,%3}, [%4];" : "=r"(v.x), "=r"(v.y), "=r"(v.z), "=r"(v.w) : "r"(a));
    return v;
}
__device__ __forceinline__ uint4 ldsm4t(uint32_t a) {
    uint4 v;
    asm volatile("ldmatrix.sync.aligned.m8n8.x4.trans.shared.b16 {%0,%1,%2,%3}, [%4];" : "=r"(v.x), "=r"(v.y), "=r"(v.z), "=r"(v.w) : "r"(a));
    return v;
}
__device__ __forceinline__ void stsm4(uint32_t a, uint32_t r0, uint32_t r1, uint32_t r2, uint32_t r3) {
    asm volatile("stmatrix.sync.aligned.m8n8.x4.shared.b16 [%0], {%1,%2,%3,%4};" ::"r"(a), "r"(r0), "r"(r1), "r"(r2), "r"(r3) : "memory");
}
__device__ __forceinline__ void stsm4t(uint32_t a, uint32_t r0, uint32_t r1, uint32_t r2, uint32_t r3) {
    asm volatile("stmatrix.sync.aligned.m8n8.x4.trans.shared.b16 [%0], {%1,%2,%3,%4};" ::"r"(a), "r"(r0), "r"(r1), "r"(r2), "r"(r3) : "memory");
}
__device__ __forceinline__ void mma16816(float* c, uint32_t a0, uint32_t a1, uint32_t a2, uint32_t a3, uint32_t b0, uint32_t b1) {
    asm("mma.sync.aligned.m16n8k16.row.col.f32.bf16.bf16.f32 {%0,%1,%2,%3}, {%4,%5,%6,%7}, {%8,%9}, {%0,%1,%2,%3};"
        : "+f"(c[0]), "+f"(c[1]), "+f"(c[2]), "+f"(c[3]) : "r"(a0), "r"(a1), "r"(a2), "r"(a3), "r"(b0), "r"(b1));
}
__device__ __forceinline__ void mmav(float* c, uint32_t a0, uint32_t a1, uint32_t a2, uint32_t a3, uint32_t b0, uint32_t b1) {
    asm volatile("mma.sync.aligned.m16n8k16.row.col.f32.bf16.bf16.f32 {%0,%1,%2,%3}, {%4,%5,%6,%7}, {%8,%9}, {%0,%1,%2,%3};"
        : "+f"(c[0]), "+f"(c[1]), "+f"(c[2]), "+f"(c[3]) : "r"(a0), "r"(a1), "r"(a2), "r"(a3), "r"(b0), "r"(b1));
}
__device__ __forceinline__ void mmau(float* c, const uint4& a, uint32_t b0, uint32_t b1) { mma16816(c, a.x, a.y, a.z, a.w, b0, b1); }
__device__ __forceinline__ void mma1688(float* c, uint32_t a0, uint32_t a1, uint32_t b0) {
    asm("mma.sync.aligned.m16n8k8.row.col.f32.bf16.bf16.f32 {%0,%1,%2,%3}, {%4,%5}, {%6}, {%0,%1,%2,%3};"
        : "+f"(c[0]), "+f"(c[1]), "+f"(c[2]), "+f"(c[3]) : "r"(a0), "r"(a1), "r"(b0));
}
__device__ __forceinline__ void mmav8(float* c, uint32_t a0, uint32_t a1, uint32_t b0) {
    asm volatile("mma.sync.aligned.m16n8k8.row.col.f32.bf16.bf16.f32 {%0,%1,%2,%3}, {%4,%5}, {%6}, {%0,%1,%2,%3};"
        : "+f"(c[0]), "+f"(c[1]), "+f"(c[2]), "+f"(c[3]) : "r"(a0), "r"(a1), "r"(b0));
}
__device__ __forceinline__ void cp_async16(uint32_t dst, const void* src) { asm volatile("cp.async.cg.shared.global [%0], [%1], 16;" ::"r"(dst), "l"(src)); }
__device__ __forceinline__ void cp_commit() { asm volatile("cp.async.commit_group;"); }
template <int N> __device__ __forceinline__ void cp_wait() { asm volatile("cp.async.wait_group %0;" ::"n"(N)); }
__device__ __forceinline__ uint4 lds128(uint32_t a) {
    uint4 v;
    asm volatile("ld.shared.v4.u32 {%0,%1,%2,%3}, [%4];" : "=r"(v.x), "=r"(v.y), "=r"(v.z), "=r"(v.w) : "r"(a));
    return v;
}
__device__ __forceinline__ uint2 lds64(uint32_t a) {
    uint2 v;
    asm volatile("ld.shared.v2.u32 {%0,%1}, [%2];" : "=r"(v.x), "=r"(v.y) : "r"(a));
    return v;
}
__device__ __forceinline__ uint32_t lds32(uint32_t a) { uint32_t v; asm volatile("ld.shared.u32 %0, [%1];" : "=r"(v) : "r"(a)); return v; }
__device__ __forceinline__ void sts32(uint32_t a, uint32_t x) { asm volatile("st.shared.u32 [%0], %1;" ::"r"(a), "r"(x) : "memory"); }
__device__ __forceinline__ void sts64(uint32_t a, uint32_t x, uint32_t y) { asm volatile("st.shared.v2.u32 [%0], {%1,%2};" ::"r"(a), "r"(x), "r"(y) : "memory"); }
__device__ __forceinline__ void sts128(uint32_t a, uint32_t x, uint32_t y, uint32_t z, uint32_t w) {
    asm volatile("st.shared.v4.u32 [%0], {%1,%2,%3,%4};" ::"r"(a), "r"(x), "r"(y), "r"(z), "r"(w) : "memory");
}
__device__ __forceinline__ uint4 ld_relaxed_v4(const void* p) {
    uint4 v;
    asm volatile("ld.relaxed.gpu.global.v4.u32 {%0,%1,%2,%3}, [%4];" : "=r"(v.x), "=r"(v.y), "=r"(v.z), "=r"(v.w) : "l"(p) : "memory");
    return v;
}
__device__ __forceinline__ uint2 ld_relaxed_v2(const void* p) {
    uint2 v;
    asm volatile("ld.relaxed.gpu.global.v2.u32 {%0,%1}, [%2];" : "=r"(v.x), "=r"(v.y) : "l"(p) : "memory");
    return v;
}
__device__ __forceinline__ void ld7_relaxed(uint4* x, const void* p) {
    asm volatile("ld.relaxed.gpu.global.v4.u32 {%0,%1,%2,%3}, [%28 + 0];\nld.relaxed.gpu.global.v4.u32 {%4,%5,%6,%7}, [%28 + 512];\nld.relaxed.gpu.global.v4.u32 {%8,%9,%10,%11}, [%28 + 1024];\nld.relaxed.gpu.global.v4.u32 {%12,%13,%14,%15}, [%28 + 1536];\nld.relaxed.gpu.global.v4.u32 {%16,%17,%18,%19}, [%28 + 2048];\nld.relaxed.gpu.global.v4.u32 {%20,%21,%22,%23}, [%28 + 2560];\nld.relaxed.gpu.global.v4.u32 {%24,%25,%26,%27}, [%28 + 3072];\n" : "=r"(x[0].x), "=r"(x[0].y), "=r"(x[0].z), "=r"(x[0].w), "=r"(x[1].x), "=r"(x[1].y), "=r"(x[1].z), "=r"(x[1].w), "=r"(x[2].x), "=r"(x[2].y), "=r"(x[2].z), "=r"(x[2].w), "=r"(x[3].x), "=r"(x[3].y), "=r"(x[3].z), "=r"(x[3].w), "=r"(x[4].x), "=r"(x[4].y), "=r"(x[4].z), "=r"(x[4].w), "=r"(x[5].x), "=r"(x[5].y), "=r"(x[5].z), "=r"(x[5].w), "=r"(x[6].x), "=r"(x[6].y), "=r"(x[6].z), "=r"(x[6].w) : "l"(p) : "memory");
}
__device__ __forceinline__ void ld7_relaxed(uint2* x, const void* p) {
    asm volatile("ld.relaxed.gpu.global.v2.u32 {%0,%1}, [%14 + 0];\nld.relaxed.gpu.global.v2.u32 {%2,%3}, [%14 + 512];\nld.relaxed.gpu.global.v2.u32 {%4,%5}, [%14 + 1024];\nld.relaxed.gpu.global.v2.u32 {%6,%7}, [%14 + 1536];\nld.relaxed.gpu.global.v2.u32 {%8,%9}, [%14 + 2048];\nld.relaxed.gpu.global.v2.u32 {%10,%11}, [%14 + 2560];\nld.relaxed.gpu.global.v2.u32 {%12,%13}, [%14 + 3072];\n" : "=r"(x[0].x), "=r"(x[0].y), "=r"(x[1].x), "=r"(x[1].y), "=r"(x[2].x), "=r"(x[2].y), "=r"(x[3].x), "=r"(x[3].y), "=r"(x[4].x), "=r"(x[4].y), "=r"(x[5].x), "=r"(x[5].y), "=r"(x[6].x), "=r"(x[6].y) : "l"(p) : "memory");
}
__device__ __forceinline__ void st_relaxed_v4(void* p, uint32_t a, uint32_t b, uint32_t c, uint32_t d) {
    asm volatile("st.relaxed.gpu.global.v4.u32 [%0], {%1,%2,%3,%4};" ::"l"(p), "r"(a), "r"(b), "r"(c), "r"(d) : "memory");
}
__device__ __forceinline__ void st_relaxed_v2(void* p, uint32_t a, uint32_t b) {
    asm volatile("st.relaxed.gpu.global.v2.u32 [%0], {%1,%2};" ::"l"(p), "r"(a), "r"(b) : "memory");
}
__device__ __forceinline__ uint32_t nz(uint32_t v) { uint32_t r; asm("max.u32 %0, %1, 1;" : "=r"(r) : "r"(v)); return r; }
__device__ __forceinline__ void touch(const void* p) { asm volatile("prefetch.global.L2 [%0];" ::"l"(p) : "memory"); }
__device__ __forceinline__ int ld_relaxed(const int* p) {
    int v;
    asm volatile("ld.relaxed.gpu.global.u32 %0, [%1];" : "=r"(v) : "l"(p) : "memory");
    return v;
}
__device__ __forceinline__ int ld_acquire(const int* p) {
    int v;
    asm volatile("ld.acquire.gpu.global.u32 %0, [%1];" : "=r"(v) : "l"(p) : "memory");
    return v;
}
__device__ __forceinline__ void red_release(int* p, int v) { asm volatile("red.release.gpu.global.add.u32 [%0], %1;" ::"l"(p), "r"(v) : "memory"); }
__device__ __forceinline__ void mbar_init(uint32_t bar, int count) { asm volatile("mbarrier.init.shared::cta.b64 [%0], %1;" ::"r"(bar), "r"(count)); }
__device__ __forceinline__ void mbar_expect_tx(uint32_t bar, uint32_t bytes) {
    asm volatile("mbarrier.arrive.expect_tx.shared::cta.b64 _, [%0], %1;" ::"r"(bar), "r"(bytes) : "memory");
}
__device__ __forceinline__ void mbar_arrive(uint32_t bar) { asm volatile("mbarrier.arrive.shared::cta.b64 _, [%0];" ::"r"(bar) : "memory"); }
__device__ __forceinline__ void mbar_arrive_cluster(uint32_t bar) { asm volatile("mbarrier.arrive.shared::cluster.b64 _, [%0];" ::"r"(bar) : "memory"); }
__device__ __forceinline__ void mslow(uint32_t bar, uint32_t parity) {
    asm volatile(
        "{\n.reg .pred P1;\n.reg .u32 cnt;\n"
        "mov.u32 cnt, 0;\n"
        "LAB_WAIT:\n"
        "mbarrier.try_wait.parity.shared::cta.b64 P1, [%0], %1;\n"
        "@P1 bra DONE;\n"
        "add.u32 cnt, cnt, 1;\n"
        "setp.lt.u32 P1, cnt, 1000000;\n"
        "@P1 bra LAB_WAIT;\n"
        "trap;\n"
        "DONE:\n}\n" ::"r"(bar), "r"(parity) : "memory");
}
__device__ __forceinline__ void mwait(uint32_t bar, uint32_t parity) {
    asm volatile(
        "{\n.reg .pred P1, P2;\n.reg .u32 cnt;\n"
        "mov.u32 cnt, 0;\n"
        "LAB_WAIT:\n"
        "mbarrier.try_wait.parity.shared::cta.b64 P1, [%0], %1;\n"
        "add.u32 cnt, cnt, 1;\n"
        "setp.gt.u32 P2, cnt, 1000000;\n"
        "@P2 trap;\n"
        "@!P1 bra LAB_WAIT;\n"
        "}\n" ::"r"(bar), "r"(parity) : "memory");
}
__device__ __forceinline__ uint32_t mtest(uint32_t bar, uint32_t parity) {
    uint32_t ok;
    asm volatile("{\n.reg .pred P1;\nmbarrier.test_wait.parity.shared::cta.b64 P1, [%1], %2;\nselp.u32 %0, 1, 0, P1;\n}\n" : "=r"(ok) : "r"(bar), "r"(parity) : "memory");
    return ok;
}
__device__ __forceinline__ uint32_t mapa(uint32_t addr, uint32_t rank) {
    uint32_t r;
    asm("mapa.shared::cluster.u32 %0, %1, %2;" : "=r"(r) : "r"(addr), "r"(rank));
    return r;
}
__device__ __forceinline__ void st_async_b32(uint32_t addr, uint32_t a, uint32_t bar) {
    asm volatile("st.async.weak.shared::cluster.mbarrier::complete_tx::bytes.b32 [%0], %1, [%2];" ::"r"(addr), "r"(a), "r"(bar) : "memory");
}
__device__ __forceinline__ void st_async_v2(uint32_t addr, uint32_t a, uint32_t b, uint32_t bar) {
    asm volatile("st.async.weak.shared::cluster.mbarrier::complete_tx::bytes.v2.b32 [%0], {%1,%2}, [%3];" ::"r"(addr), "r"(a), "r"(b), "r"(bar) : "memory");
}
__device__ __forceinline__ void st_async_v4(uint32_t addr, uint32_t a, uint32_t b, uint32_t c, uint32_t d, uint32_t bar) {
    asm volatile("st.async.weak.shared::cluster.mbarrier::complete_tx::bytes.v4.b32 [%0], {%1,%2,%3,%4}, [%5];" ::"r"(addr), "r"(a), "r"(b), "r"(c), "r"(d), "r"(bar) : "memory");
}
__device__ __forceinline__ void st_async_v4p(uint32_t addr, uint32_t a, uint32_t b, uint32_t c, uint32_t d, uint32_t bar) {
    asm volatile("{\n.reg .pred p;\nsetp.ne.u32 p, %5, 0;\n@p st.async.weak.shared::cluster.mbarrier::complete_tx::bytes.v4.b32 [%0], {%1,%2,%3,%4}, [%5];\n}"
                 ::"r"(addr), "r"(a), "r"(b), "r"(c), "r"(d), "r"(bar) : "memory");
}
__device__ __forceinline__ void st_async_v2p(uint32_t addr, uint32_t a, uint32_t b, uint32_t bar) {
    asm volatile("{\n.reg .pred p;\nsetp.ne.u32 p, %3, 0;\n@p st.async.weak.shared::cluster.mbarrier::complete_tx::bytes.v2.b32 [%0], {%1,%2}, [%3];\n}"
                 ::"r"(addr), "r"(a), "r"(b), "r"(bar) : "memory");
}
__device__ __forceinline__ void cluster_arrive() { asm volatile("barrier.cluster.arrive.release.aligned;" ::: "memory"); }
__device__ __forceinline__ void cluster_arrive_relaxed() { asm volatile("barrier.cluster.arrive.relaxed.aligned;" ::: "memory"); }
__device__ __forceinline__ void prefetch_l2(const void* p, uint32_t bytes) { asm volatile("cp.async.bulk.prefetch.L2.global [%0], %1;" ::"l"(p), "r"(bytes) : "memory"); }
__device__ __forceinline__ void cluster_wait() { asm volatile("barrier.cluster.wait.acquire.aligned;" ::: "memory"); }
__device__ __forceinline__ void named_bar(int id, int n) { asm volatile("bar.sync %0, %1;" ::"r"(id), "r"(n) : "memory"); }
__device__ __forceinline__ void named_arrive(int id, int n) { asm volatile("bar.arrive %0, %1;" ::"r"(id), "r"(n) : "memory"); }
__device__ __forceinline__ void fence_async_smem() { asm volatile("fence.proxy.async.shared::cta;" ::: "memory"); }
__device__ __forceinline__ void fence_async_global() { asm volatile("fence.proxy.async.global;" ::: "memory"); }
__device__ __forceinline__ void wg_fence() { asm volatile("wgmma.fence.sync.aligned;" ::: "memory"); }
__device__ __forceinline__ void wg_commit() { asm volatile("wgmma.commit_group.sync.aligned;" ::: "memory"); }
template <int N> __device__ __forceinline__ void wg_wait() { asm volatile("wgmma.wait_group.sync.aligned %0;" ::"n"(N) : "memory"); }
__device__ __forceinline__ float ex2f(float x) { float y; asm("ex2.approx.ftz.f32 %0, %1;" : "=f"(y) : "f"(x)); return y; }
__device__ __forceinline__ float rcpf(float x) { float y; asm("rcp.approx.ftz.f32 %0, %1;" : "=f"(y) : "f"(x)); return y; }
__device__ __forceinline__ uint32_t clk32() { uint32_t c; asm volatile("mov.u32 %0, %clock;" : "=r"(c)); return c; }
__device__ __forceinline__ uint32_t opq(uint32_t x) { uint32_t y; asm volatile("mov.u32 %0, %1;" : "=r"(y) : "r"(x)); return y; }
__device__ __forceinline__ uint64_t mkdesc(uint32_t lo, uint32_t hi) { uint64_t d; asm("mov.b64 %0, {%1,%2};" : "=l"(d) : "r"(lo), "r"(hi)); return d; }
__device__ __forceinline__ void delay(uint32_t n) {
    asm volatile("{\n.reg .pred P;\n.reg .u32 a, b;\nmov.u32 a, %clock;\nadd.u32 a, a, %0;\nDL:\nmov.u32 b, %clock;\nsub.u32 b, b, a;\nsetp.lt.s32 P, b, 0;\n@P bra.uni DL;\n}" ::"r"(n) : "memory");
}
#define UNI(x) __shfl_sync(0xffffffffu, (uint32_t)(x), 0)
__device__ __forceinline__ void wg_n16t(float* d, uint32_t a0, uint32_t a1, uint32_t a2, uint32_t a3, uint64_t db) {
    asm volatile("wgmma.mma_async.sync.aligned.m64n16k16.f32.bf16.bf16 {%0, %1, %2, %3, %4, %5, %6, %7}, {%8, %9, %10, %11}, %12, 1, 1, 1, 1;"
                 : "+f"(d[0]), "+f"(d[1]), "+f"(d[2]), "+f"(d[3]), "+f"(d[4]), "+f"(d[5]), "+f"(d[6]), "+f"(d[7]) : "r"(a0), "r"(a1), "r"(a2), "r"(a3), "l"(db));
}
__device__ __forceinline__ void wg_n16t_first(float* d, uint32_t a0, uint32_t a1, uint32_t a2, uint32_t a3, uint64_t db) {
    asm volatile("wgmma.mma_async.sync.aligned.m64n16k16.f32.bf16.bf16 {%0, %1, %2, %3, %4, %5, %6, %7}, {%8, %9, %10, %11}, %12, 0, 1, 1, 1;"
                 : "=f"(d[0]), "=f"(d[1]), "=f"(d[2]), "=f"(d[3]), "=f"(d[4]), "=f"(d[5]), "=f"(d[6]), "=f"(d[7]) : "r"(a0), "r"(a1), "r"(a2), "r"(a3), "l"(db));
}
__device__ __forceinline__ void wg_n32(float* d, uint32_t a0, uint32_t a1, uint32_t a2, uint32_t a3, uint64_t db) {
    asm volatile("wgmma.mma_async.sync.aligned.m64n32k16.f32.bf16.bf16 {%0, %1, %2, %3, %4, %5, %6, %7, %8, %9, %10, %11, %12, %13, %14, %15}, {%16, %17, %18, %19}, %20, 1, 1, 1, 0;"
                 : "+f"(d[0]), "+f"(d[1]), "+f"(d[2]), "+f"(d[3]), "+f"(d[4]), "+f"(d[5]), "+f"(d[6]), "+f"(d[7]), "+f"(d[8]), "+f"(d[9]), "+f"(d[10]), "+f"(d[11]), "+f"(d[12]), "+f"(d[13]), "+f"(d[14]), "+f"(d[15]) : "r"(a0), "r"(a1), "r"(a2), "r"(a3), "l"(db));
}
__device__ __forceinline__ void wg_n32_first(float* d, uint32_t a0, uint32_t a1, uint32_t a2, uint32_t a3, uint64_t db) {
    asm volatile("wgmma.mma_async.sync.aligned.m64n32k16.f32.bf16.bf16 {%0, %1, %2, %3, %4, %5, %6, %7, %8, %9, %10, %11, %12, %13, %14, %15}, {%16, %17, %18, %19}, %20, 0, 1, 1, 0;"
                 : "=f"(d[0]), "=f"(d[1]), "=f"(d[2]), "=f"(d[3]), "=f"(d[4]), "=f"(d[5]), "=f"(d[6]), "=f"(d[7]), "=f"(d[8]), "=f"(d[9]), "=f"(d[10]), "=f"(d[11]), "=f"(d[12]), "=f"(d[13]), "=f"(d[14]), "=f"(d[15]) : "r"(a0), "r"(a1), "r"(a2), "r"(a3), "l"(db));
}

__device__ __forceinline__ void wg_n16t_sfirst(float* d, uint64_t da, uint64_t db) {
    asm volatile("wgmma.mma_async.sync.aligned.m64n16k16.f32.bf16.bf16 {%0, %1, %2, %3, %4, %5, %6, %7}, %8, %9, 0, 1, 1, 1, 1;"
                 : "=f"(d[0]), "=f"(d[1]), "=f"(d[2]), "=f"(d[3]), "=f"(d[4]), "=f"(d[5]), "=f"(d[6]), "=f"(d[7]) : "l"(da), "l"(db));
}
__device__ __forceinline__ void wg_n32_sfirst(float* d, uint64_t da, uint64_t db) {
    asm volatile("wgmma.mma_async.sync.aligned.m64n32k16.f32.bf16.bf16 {%0, %1, %2, %3, %4, %5, %6, %7, %8, %9, %10, %11, %12, %13, %14, %15}, %16, %17, 0, 1, 1, 1, 0;"
                 : "=f"(d[0]), "=f"(d[1]), "=f"(d[2]), "=f"(d[3]), "=f"(d[4]), "=f"(d[5]), "=f"(d[6]), "=f"(d[7]), "=f"(d[8]), "=f"(d[9]), "=f"(d[10]), "=f"(d[11]), "=f"(d[12]), "=f"(d[13]), "=f"(d[14]), "=f"(d[15]) : "l"(da), "l"(db));
}

__device__ __forceinline__ void wg_n16t_s(float* d, uint64_t da, uint64_t db) {
    asm volatile("wgmma.mma_async.sync.aligned.m64n16k16.f32.bf16.bf16 {%0, %1, %2, %3, %4, %5, %6, %7}, %8, %9, 1, 1, 1, 1, 1;"
                 : "+f"(d[0]), "+f"(d[1]), "+f"(d[2]), "+f"(d[3]), "+f"(d[4]), "+f"(d[5]), "+f"(d[6]), "+f"(d[7]) : "l"(da), "l"(db));
}
__device__ __forceinline__ void wg_n64_sfirst(float* d, uint64_t da, uint64_t db) {
    asm volatile("wgmma.mma_async.sync.aligned.m64n64k16.f32.bf16.bf16 {%0, %1, %2, %3, %4, %5, %6, %7, %8, %9, %10, %11, %12, %13, %14, %15, %16, %17, %18, %19, %20, %21, %22, %23, %24, %25, %26, %27, %28, %29, %30, %31}, %32, %33, 0, 1, 1, 1, 0;"
                 : "=f"(d[0]), "=f"(d[1]), "=f"(d[2]), "=f"(d[3]), "=f"(d[4]), "=f"(d[5]), "=f"(d[6]), "=f"(d[7]), "=f"(d[8]), "=f"(d[9]), "=f"(d[10]), "=f"(d[11]), "=f"(d[12]), "=f"(d[13]), "=f"(d[14]), "=f"(d[15]), "=f"(d[16]), "=f"(d[17]), "=f"(d[18]), "=f"(d[19]), "=f"(d[20]), "=f"(d[21]), "=f"(d[22]), "=f"(d[23]), "=f"(d[24]), "=f"(d[25]), "=f"(d[26]), "=f"(d[27]), "=f"(d[28]), "=f"(d[29]), "=f"(d[30]), "=f"(d[31]) : "l"(da), "l"(db));
}
__device__ __forceinline__ void wg_n64_s(float* d, uint64_t da, uint64_t db) {
    asm volatile("wgmma.mma_async.sync.aligned.m64n64k16.f32.bf16.bf16 {%0, %1, %2, %3, %4, %5, %6, %7, %8, %9, %10, %11, %12, %13, %14, %15, %16, %17, %18, %19, %20, %21, %22, %23, %24, %25, %26, %27, %28, %29, %30, %31}, %32, %33, 1, 1, 1, 1, 0;"
                 : "+f"(d[0]), "+f"(d[1]), "+f"(d[2]), "+f"(d[3]), "+f"(d[4]), "+f"(d[5]), "+f"(d[6]), "+f"(d[7]), "+f"(d[8]), "+f"(d[9]), "+f"(d[10]), "+f"(d[11]), "+f"(d[12]), "+f"(d[13]), "+f"(d[14]), "+f"(d[15]), "+f"(d[16]), "+f"(d[17]), "+f"(d[18]), "+f"(d[19]), "+f"(d[20]), "+f"(d[21]), "+f"(d[22]), "+f"(d[23]), "+f"(d[24]), "+f"(d[25]), "+f"(d[26]), "+f"(d[27]), "+f"(d[28]), "+f"(d[29]), "+f"(d[30]), "+f"(d[31]) : "l"(da), "l"(db));
}
__device__ __forceinline__ void wg_n64(float* d, uint32_t a0, uint32_t a1, uint32_t a2, uint32_t a3, uint64_t db) {
    asm volatile("wgmma.mma_async.sync.aligned.m64n64k16.f32.bf16.bf16 {%0, %1, %2, %3, %4, %5, %6, %7, %8, %9, %10, %11, %12, %13, %14, %15, %16, %17, %18, %19, %20, %21, %22, %23, %24, %25, %26, %27, %28, %29, %30, %31}, {%32, %33, %34, %35}, %36, 1, 1, 1, 0;"
                 : "+f"(d[0]), "+f"(d[1]), "+f"(d[2]), "+f"(d[3]), "+f"(d[4]), "+f"(d[5]), "+f"(d[6]), "+f"(d[7]), "+f"(d[8]), "+f"(d[9]), "+f"(d[10]), "+f"(d[11]), "+f"(d[12]), "+f"(d[13]), "+f"(d[14]), "+f"(d[15]), "+f"(d[16]), "+f"(d[17]), "+f"(d[18]), "+f"(d[19]), "+f"(d[20]), "+f"(d[21]), "+f"(d[22]), "+f"(d[23]), "+f"(d[24]), "+f"(d[25]), "+f"(d[26]), "+f"(d[27]), "+f"(d[28]), "+f"(d[29]), "+f"(d[30]), "+f"(d[31]) : "r"(a0), "r"(a1), "r"(a2), "r"(a3), "l"(db));
}
__device__ __forceinline__ void wg_n64_first(float* d, uint32_t a0, uint32_t a1, uint32_t a2, uint32_t a3, uint64_t db) {
    asm volatile("wgmma.mma_async.sync.aligned.m64n64k16.f32.bf16.bf16 {%0, %1, %2, %3, %4, %5, %6, %7, %8, %9, %10, %11, %12, %13, %14, %15, %16, %17, %18, %19, %20, %21, %22, %23, %24, %25, %26, %27, %28, %29, %30, %31}, {%32, %33, %34, %35}, %36, 0, 1, 1, 0;"
                 : "=f"(d[0]), "=f"(d[1]), "=f"(d[2]), "=f"(d[3]), "=f"(d[4]), "=f"(d[5]), "=f"(d[6]), "=f"(d[7]), "=f"(d[8]), "=f"(d[9]), "=f"(d[10]), "=f"(d[11]), "=f"(d[12]), "=f"(d[13]), "=f"(d[14]), "=f"(d[15]), "=f"(d[16]), "=f"(d[17]), "=f"(d[18]), "=f"(d[19]), "=f"(d[20]), "=f"(d[21]), "=f"(d[22]), "=f"(d[23]), "=f"(d[24]), "=f"(d[25]), "=f"(d[26]), "=f"(d[27]), "=f"(d[28]), "=f"(d[29]), "=f"(d[30]), "=f"(d[31]) : "r"(a0), "r"(a1), "r"(a2), "r"(a3), "l"(db));
}

__device__ __forceinline__ void wg_n32t(float* d, uint32_t a0, uint32_t a1, uint32_t a2, uint32_t a3, uint64_t db) {
    asm volatile("wgmma.mma_async.sync.aligned.m64n32k16.f32.bf16.bf16 {%0, %1, %2, %3, %4, %5, %6, %7, %8, %9, %10, %11, %12, %13, %14, %15}, {%16, %17, %18, %19}, %20, 1, 1, 1, 1;"
                 : "+f"(d[0]), "+f"(d[1]), "+f"(d[2]), "+f"(d[3]), "+f"(d[4]), "+f"(d[5]), "+f"(d[6]), "+f"(d[7]), "+f"(d[8]), "+f"(d[9]), "+f"(d[10]), "+f"(d[11]), "+f"(d[12]), "+f"(d[13]), "+f"(d[14]), "+f"(d[15]) : "r"(a0), "r"(a1), "r"(a2), "r"(a3), "l"(db));
}
__device__ __forceinline__ void wg_n32t_first(float* d, uint32_t a0, uint32_t a1, uint32_t a2, uint32_t a3, uint64_t db) {
    asm volatile("wgmma.mma_async.sync.aligned.m64n32k16.f32.bf16.bf16 {%0, %1, %2, %3, %4, %5, %6, %7, %8, %9, %10, %11, %12, %13, %14, %15}, {%16, %17, %18, %19}, %20, 0, 1, 1, 1;"
                 : "=f"(d[0]), "=f"(d[1]), "=f"(d[2]), "=f"(d[3]), "=f"(d[4]), "=f"(d[5]), "=f"(d[6]), "=f"(d[7]), "=f"(d[8]), "=f"(d[9]), "=f"(d[10]), "=f"(d[11]), "=f"(d[12]), "=f"(d[13]), "=f"(d[14]), "=f"(d[15]) : "r"(a0), "r"(a1), "r"(a2), "r"(a3), "l"(db));
}
__device__ __forceinline__ void wg_n32t_sfirst(float* d, uint64_t da, uint64_t db) {
    asm volatile("wgmma.mma_async.sync.aligned.m64n32k16.f32.bf16.bf16 {%0, %1, %2, %3, %4, %5, %6, %7, %8, %9, %10, %11, %12, %13, %14, %15}, %16, %17, 0, 1, 1, 1, 1;"
                 : "=f"(d[0]), "=f"(d[1]), "=f"(d[2]), "=f"(d[3]), "=f"(d[4]), "=f"(d[5]), "=f"(d[6]), "=f"(d[7]), "=f"(d[8]), "=f"(d[9]), "=f"(d[10]), "=f"(d[11]), "=f"(d[12]), "=f"(d[13]), "=f"(d[14]), "=f"(d[15]) : "l"(da), "l"(db));
}
__device__ __forceinline__ void wg_n32t_s(float* d, uint64_t da, uint64_t db) {
    asm volatile("wgmma.mma_async.sync.aligned.m64n32k16.f32.bf16.bf16 {%0, %1, %2, %3, %4, %5, %6, %7, %8, %9, %10, %11, %12, %13, %14, %15}, %16, %17, 1, 1, 1, 1, 1;"
                 : "+f"(d[0]), "+f"(d[1]), "+f"(d[2]), "+f"(d[3]), "+f"(d[4]), "+f"(d[5]), "+f"(d[6]), "+f"(d[7]), "+f"(d[8]), "+f"(d[9]), "+f"(d[10]), "+f"(d[11]), "+f"(d[12]), "+f"(d[13]), "+f"(d[14]), "+f"(d[15]) : "l"(da), "l"(db));
}

__device__ __forceinline__ void wg_n32_kk(float* d, uint64_t da, uint64_t db) {
    asm volatile("wgmma.mma_async.sync.aligned.m64n32k16.f32.bf16.bf16 {%0, %1, %2, %3, %4, %5, %6, %7, %8, %9, %10, %11, %12, %13, %14, %15}, %16, %17, 1, 1, 1, 0, 0;"
                 : "+f"(d[0]), "+f"(d[1]), "+f"(d[2]), "+f"(d[3]), "+f"(d[4]), "+f"(d[5]), "+f"(d[6]), "+f"(d[7]), "+f"(d[8]), "+f"(d[9]), "+f"(d[10]), "+f"(d[11]), "+f"(d[12]), "+f"(d[13]), "+f"(d[14]), "+f"(d[15]) : "l"(da), "l"(db));
}

}

namespace ws {
#define LAGT 4
constexpr int LAG = LAGT, NT = NSEG + LAG, NCL = 7;
#define P1A 24
#define P1C 10
#define XD 350
#define REG_G 200
#define REG_T 72
#define REG_X 40
template <int V> struct IC { static constexpr int value = V; };
#define POST_NS 20
#define OP_NS 20
#define LN0_AHEAD 8
#define TG_STEPS 40
#define NO_X 0
#define WTA 3
constexpr int WTC = 10 - 2 * WTA;
#define WR 3
#define OBK 2
#define WFLY 2
#define H_NS 20
#define C_REV 2
#define ONE_FENCE 0
#define LN0_BATCH 1
static_assert(LN0_AHEAD + LN0_BATCH + LAG + 1 <= 16 && (NSEG - LN0_AHEAD) % LN0_BATCH == 0, "ring of the scratch buffers");
constexpr int XRS = 3;
constexpr int O_H = 0, O_MEM = 81920, O_RED = 102400, O_BAR = 110080, O_TAB = O_BAR + 192, O_BT = O_TAB + 128, O_TR = O_BAR + 512, O_X = O_TR + 1024;
constexpr int O_QRY = O_X, O_KEY = O_X + 10240, O_OBA = O_KEY + 10240, O_ST = O_OBA + 4096;
constexpr int O_VT = O_X, O_VM = O_VT + 32768, O_SM = O_VM + 4096, O_PB = O_SM + 3072;
constexpr int O_AS = 228352, O_WO = O_AS - 65536, HEAD_SMEM = O_AS + 4096, O_STG = 40960;
static_assert(O_ST + 8192 <= O_WO && O_PB + 10240 <= O_WO && O_AS % 1024 == 0 && O_STG + 163840 <= O_AS && HEAD_SMEM <= 232448, "smem");
constexpr int B_MEM = 0, B_RED = 64, B_SM = 88, B_ST = 96, B_OB = 104, B_HF = 112, B_HE = 128, B_OTF = 144, B_OTE = 160;

constexpr int F_H = 0, F_O = 128, F_P = 256, F_U = 384, F_CV = 392, F_XL = 398, F_Z = 399, NFLAG = 400;
__device__ int g_flags[NFLAG * 8];
#define FLG(i) (g_flags + (i) * 8)
#define RING 16
__device__ __forceinline__ int rslot(int l, int seg) { return l * RING + (seg & (RING - 1)); }
__device__ uint4 g_ht[2 * RING * 2560];
__device__ uint4 g_ot[2 * RING * 256 * 64];
__device__ uint4 g_pt[2 * RING * 5120];
__device__ uint4 g_Y[80 * S_LEN];
__device__ uint4 g_U[DM * S_LEN / 8];
__device__ bf16 g_x[RING * SEG * DM];
__device__ int g_epoch;
__device__ uint4 g_xc[XRS * 16 * 3 * 8 * 32];
#define GT(cond, i)
#define SC(cond, i)
#define SD(x)
#define TS(i)
#define TV(i, v)

}

namespace ws {
__device__ __forceinline__ uint32_t bmul2(uint32_t a, uint32_t b) { uint32_t r; asm("mul.rn.bf16x2 %0, %1, %2;" : "=r"(r) : "r"(a), "r"(b)); return r; }
__device__ __forceinline__ uint32_t bmax2(uint32_t a, uint32_t b) { uint32_t r; asm("max.bf16x2 %0, %1, %2;" : "=r"(r) : "r"(a), "r"(b)); return r; }
__device__ __forceinline__ void flag_wait(const int* f, int tgt, int ns) {
    int guard = 0;
    while (ld_relaxed(f) < tgt) { if (++guard > 4000000) __trap(); __nanosleep(ns); }
}
template <int STRIDE> __device__ __forceinline__ void ld5(uint32_t* w, const void* p) {
#pragma unroll
    for (int r = 0; r < 5; r++) { const uint2 v = __ldcg(reinterpret_cast<const uint2*>(reinterpret_cast<const char*>(p) + r * STRIDE)); w[2 * r] = v.x; w[2 * r + 1] = v.y; }
}
template <int STRIDE> __device__ __forceinline__ void st5(void* p, const uint32_t* w) {
#pragma unroll
    for (int r = 0; r < 5; r++) *reinterpret_cast<uint2*>(reinterpret_cast<char*>(p) + r * STRIDE) = make_uint2(w[2 * r], w[2 * r + 1]);
}
__device__ __forceinline__ void ln_row(const uint32_t* x, uint32_t* y) {
    const float c = blo(__shfl_sync(0xffffffffu, x[0], 0));
    float s0 = 0.f, s1 = 0.f, q0 = 0.f, q1 = 0.f;
#pragma unroll
    for (int i = 0; i < 10; i++) { const float d0 = blo(x[i]) - c, d1 = bhi(x[i]) - c; s0 += d0; s1 += d1; q0 = fmaf(d0, d0, q0); q1 = fmaf(d1, d1, q1); }
    float s = s0 + s1, q = q0 + q1;
#pragma unroll
    for (int o = 16; o > 0; o >>= 1) { s += __shfl_xor_sync(0xffffffffu, s, o); q += __shfl_xor_sync(0xffffffffu, q, o); }
    s *= 1.0f / DM;
    const float mean = c + s;
    q = fmaxf(fmaf(q, 1.0f / DM, -s * s), 0.f);
    const uint32_t nm = pack2(-mean, -mean);
    float sq;
    asm("sqrt.approx.ftz.f32 %0, %1;" : "=f"(sq) : "f"(rbf(rbf(q) + 1e-5f)));
    const float rd = rcpf(rbf(sq));
#pragma unroll
    for (int i = 0; i < 10; i++) { const uint32_t d = badd(x[i], nm); y[i] = pack2(blo(d) * rd, bhi(d) * rd); }
}
__device__ __forceinline__ void clear_acc(int l, int seg, int tok, int lane) {
    uint4* pz = g_pt + rslot(l, seg) * 5120 + (lane >> 4) * 512 + tok * 16 + (lane & 15);
#pragma unroll
    for (int i = 0; i < 5; i++) pz[i * 1024] = make_uint4(0, 0, 0, 0);
}
__device__ __forceinline__ void put_h(int l, int seg, int tok, int lane, const uint32_t* n) {
    st5<8192>(reinterpret_cast<char*>(g_ht + rslot(l, seg) * 2560) + (lane >> 2) * 1024 + tok * 32 + (((lane & 3) * 8) ^ ((tok & 4) << 2)), n);
}
__device__ __forceinline__ void ln0_rows(const bf16* x, int seg, int cnt, int tok, int lane) {
#pragma unroll 1
    for (int i = 0; i < cnt; i++) {
        uint32_t v[10];
        ld5<256>(v, x + (size_t)((seg + i) * SEG + tok) * DM + lane * 4);
        clear_acc(0, seg + i, tok, lane);
        ln_row(v, v);
        put_h(0, seg + i, tok, lane, v);
    }
    __syncwarp();
    if (lane == 0) {
        red_release(FLG(F_H + seg), 1);
        for (int i = 1; i < cnt; i++) asm volatile("red.relaxed.gpu.global.add.u32 [%0], 1;" ::"l"(FLG(F_H + seg + i)) : "memory");
    }
}
__device__ __forceinline__ void post_row(int l, int seg, int tok, int lane, const bf16* xin, bf16* xout, int ep) {
    uint32_t x[10], y[10], n[10];
    const int row = seg * SEG + tok;
    SC(tr, tb);
    const bool first = seg == 0;
    if (seg == 8 || ((seg & 15) == 0 && seg)) flag_wait(FLG(F_CV + (seg >> 4) + 1), 80 * ep, 50);
    const char* yp = reinterpret_cast<const char*>(g_Y) + ((size_t)(lane >> 1) * S_LEN + row) * 16 + (lane & 1) * 8;
    SC(tr, tb + 1);
    if (!first) ld5<16 * S_LEN * 16>(y, yp);
    bf16* xm = g_x + ((seg & (RING - 1)) * SEG + tok) * DM + lane * 4;
    if (l == 0) {
        ld5<256>(x, xin + (size_t)row * DM + lane * 4);
        clear_acc(1, seg, tok, lane);
    } else {
        flag_wait(seg + 1 < NSEG ? FLG(F_H + 65 + seg) : FLG(F_XL), 32 * ep, 50);
        ld5<256>(x, xm);
    }
    flag_wait(FLG(F_P + l * 64 + seg), 40 * ep, POST_NS);
    SC(tr, tb + 2);
    const uint4* pp = g_pt + rslot(l, seg) * 5120 + (lane >> 4) * 512 + tok * 16 + ((lane & 15) ^ ((tok >> 3) << 1));
    {
        uint4 a[5];
#pragma unroll
        for (int i = 0; i < 5; i++) a[i] = __ldcg(pp + i * 1024);
#pragma unroll
        for (int i = 0; i < 5; i++) {
            x[2 * i] = badd(x[2 * i], pack2(__uint_as_float(a[i].x), __uint_as_float(a[i].y)));
            x[2 * i + 1] = badd(x[2 * i + 1], pack2(__uint_as_float(a[i].z), __uint_as_float(a[i].w)));
        }
    }
    SC(tr && x[0] != 0x12345, tb + 3);
    if (first) { flag_wait(FLG(F_CV), 80 * ep, 50); ld5<16 * S_LEN * 16>(y, yp); }
    ln_row(x, n);
#pragma unroll
    for (int i = 0; i < 10; i++) x[i] = badd(x[i], bmul2(n[i], y[i]));
    SC(tr && x[0] != 0x12345, tb + 4);
    if (l) st5<256>(xout + (size_t)row * DM + lane * 4, x);
    else {
        ln_row(x, n);
        SC(tr && n[0] != 0x12345, tb + 5);
        put_h(1, seg, tok, lane, n);
        __syncwarp();
        if (lane == 0) red_release(FLG(F_H + 64 + seg), 1);
        SC(tr, tb + 6);
        st5<256>(xm, x);
        if (seg == NSEG - 1) { __syncwarp(); if (lane == 0) red_release(FLG(F_XL), 1); }
    }
}
__device__ __forceinline__ void u_piece(const bf16* Bk, const bf16* Bv, const bf16* shiftk, int t0, int cp, uint4* o) {
    uint32_t kk[11], vv[8];
    const uint32_t* pk = reinterpret_cast<const uint32_t*>(Bk + (size_t)t0 * DM) + cp;
    const uint32_t* pv = reinterpret_cast<const uint32_t*>(Bv + (size_t)t0 * DM) + cp;
#pragma unroll
    for (int i = 0; i < 11; i++) kk[i] = (i >= 3 || t0 > 0) ? __ldg(pk + (i - 3) * (DM / 2)) : 0u;
#pragma unroll
    for (int i = 0; i < 8; i++) vv[i] = __ldg(pv + i * (DM / 2));
    const uint4 sh0 = __ldg(reinterpret_cast<const uint4*>(shiftk + cp * 8));
    const uint32_t s0 = __byte_perm(sh0.x, sh0.z, 0x5410), s1 = __byte_perm(sh0.x, sh0.z, 0x7632), s2 = __byte_perm(sh0.y, sh0.w, 0x5410), s3 = __byte_perm(sh0.y, sh0.w, 0x7632);
#pragma unroll
    for (int t = 0; t < 8; t++)
        vv[t] = bmul2(badd(badd(badd(bmul2(kk[t], s3), bmul2(kk[t + 1], s2)), bmul2(kk[t + 2], s1)), bmul2(kk[t + 3], s0)), vv[t]);
#pragma unroll
    for (int c = 0; c < 2; c++) {
        const uint32_t sel = c ? 0x7632 : 0x5410;
        o[c] = make_uint4(__byte_perm(vv[7], vv[6], sel), __byte_perm(vv[5], vv[4], sel), __byte_perm(vv[3], vv[2], sel), __byte_perm(vv[1], vv[0], sel));
    }
}
__device__ __forceinline__ int u_pos(int t0) { return (t0 >> 6) * 8 + ((((t0 ^ 56) & 63) >> 3) ^ ((t0 >> 6) & 7)); }
__device__ __forceinline__ void u_half(const bf16* Bk, const bf16* Bv, const bf16* shiftk, int unit, int lane) {
    const int t0 = (unit / 20) * 16 + (lane & 1) * 8, cp = (unit % 20) * 16 + (lane >> 1);
    uint4 o[2];
    u_piece(Bk, Bv, shiftk, t0, cp, o);
    uint4* d = g_U + (size_t)(cp * 2) * (S_LEN / 8) + u_pos(t0);
    d[0] = o[0]; d[S_LEN / 8] = o[1];
}
constexpr int CV_E = 4224, CV_W = 2 * 4096 + 3 * CV_E + 128, CV_HI = O_X, CV_Y = CV_HI + 4 * CV_W, CV_T = CV_Y + 16384, CV_Z = CV_T + 16384;
static_assert(4 * CV_W <= O_RED && CV_W % 128 == 0 && CV_Z + 128 <= HEAD_SMEM, "conv buffers");
__device__ __forceinline__ void conv_unit(uint32_t ub, uint32_t e0, uint32_t e1, uint32_t zrow, uint32_t tt, uint32_t Dv, int rg, int nq, int lane, uint32_t zero, int tb) {
    const int g7 = 7 - (lane >> 2), tq = lane & 3;
    SC(tb >= 0, tb + 3);
    for (int i = lane; i < 32 * nq + 8; i += 32) {
        const uint4 v = lds128(e0 + i * 16);
        const uint32_t nx = lds32(e0 + i * 16 + 16);
        sts128(e1 + i * 16, __byte_perm(v.x, v.y, 0x5432), __byte_perm(v.y, v.z, 0x5432), __byte_perm(v.z, v.w, 0x5432), __byte_perm(v.w, nx, 0x5432));
    }
    __syncwarp();
    SC(tb >= 0, tb + 4);
    float acc[4][4];
#pragma unroll
    for (int i = 0; i < 16; i++) (&acc[0][0])[i] = 0.f;
    uint32_t wb = (g7 & 1) ? e0 + (1 + g7 + 2 * tq) * 2 : e1 + (g7 + 2 * tq) * 2;
    int row = 8 * rg + (lane & 7);
    auto ldb = [&](uint4* b) {
        const uint32_t x = row < 0 ? zrow : ub + row * 128 + (((lane >> 3) ^ (row & 7)) << 4);
        b[0] = ldsm4(x); b[1] = ldsm4(x ^ 64);
        row--;
    };
    uint4 Q[16], b[2][2];
    Q[15].w = lds32(wb);
    auto ldq = [&](int q, int o) { Q[q].y = lds32(wb + o * 32 + 16); Q[q].w = lds32(wb + o * 32 + 32); };
    auto cpq = [&](int q) { Q[q].x = Q[(q + 15) & 15].w + zero; Q[q].z = Q[q].y + zero; };
#pragma unroll
    for (int q = 0; q < 11; q++) ldq(q, q);
#pragma unroll
    for (int q = 0; q < 7; q++) cpq(q);
    ldb(b[0]);
#pragma unroll 1
    for (int D0 = nq; D0 > 0; D0--) {
#pragma unroll
        for (int d = 0; d < 4; d++) {
            ldb(b[(d + 1) & 1]);
#pragma unroll
            for (int q = 11; q < 15; q++) ldq((4 * d + q) & 15, 4 * d + q);
#pragma unroll
            for (int ks = 0; ks < 4; ks++) {
                const uint4& bb_ = b[d & 1][ks >> 1];
#pragma unroll
                for (int m = 0; m < 4; m++) {
                    const uint4& a = Q[(4 * d + m + ks) & 15];
                    mmav(acc[m], a.x, a.y, a.z, a.w, (ks & 1) ? bb_.z : bb_.x, (ks & 1) ? bb_.w : bb_.y);
                }
                cpq((4 * d + 7 + ks) & 15);
            }
        }
        wb += 512;
    }
    SC(tb >= 0 && acc[0][0] != 1.2345f, tb + 5);
    const uint32_t ua = ub + (8 * rg + (lane & 7)) * 128 + (((lane >> 3) ^ (lane & 7)) << 4);
    const uint4 u0 = ldsm4t(ua), u1 = ldsm4t(ua ^ 64);
    auto y = [&](int m, int hf, uint32_t u) { return badd(pack2(acc[m][2 * hf], acc[m][2 * hf + 1]), bmul2(u, Dv)); };
    stsm4t(tt, y(0, 0, u1.w), y(0, 1, u1.z), y(1, 0, u1.y), y(1, 1, u1.x));
    stsm4t(tt ^ 64, y(2, 0, u0.w), y(2, 1, u0.z), y(3, 0, u0.y), y(3, 1, u0.x));
}
}

namespace ws {
__constant__ unsigned char c_tile[48] = {4, 5, 6, 7, 12, 13, 14, 19, 0, 1, 2, 3, 0, 0, 0, 0, 20, 21, 22, 27, 28, 29, 30, 31, 8, 9, 10, 11, 0, 0, 0, 0,
                                         39, 38, 37, 36, 35, 34, 33, 32, 15, 16, 17, 18, 23, 24, 25, 26};
struct HeadArgs { const bf16 *x, *mem0, *Wq, *Wk, *Wv, *Wo, *Bk, *Bv, *shiftk, *ssmk, *ssmD; bf16* out; int h_target; };

__global__ void __launch_bounds__(512, 1) head_kernel(const __grid_constant__ HeadArgs A) {
    extern __shared__ __align__(1024) unsigned char smem_raw[];
    const int tid = threadIdx.x, warp = __shfl_sync(0xffffffffu, tid >> 5, 0), lane = tid & 31;
    const int cq = blockIdx.x >> 4, r = blockIdx.x & 15;
    const int nh = cq < 4 ? 5 : 4, hi = r / 3, role = r - hi * 3;
    const bool head = r < 3 * nh;
    const int p0 = r >> 1;
    const int h = (cq < 4 ? 5 * cq : 4 * cq + 4) + hi;
    const uint32_t sb = smem_u32(smem_raw), bb = sb + O_BAR;
    GT(tid == 0, 1);
    const int sp = cq < 4 ? cq : 4 * cq + r - 24;
    if (tid == 0) {
        if ((sb & 0xFFFFFFu) != 1024) __trap();
        for (int i = 0; i < 12; i++) mbar_init(bb + i * 8, 1);
        mbar_init(bb + B_ST, role == 2 ? 1 : 5);
        mbar_init(bb + B_OB, 1); mbar_init(bb + B_OB + 64, 1);
        mbar_init(bb + B_HF, 1); mbar_init(bb + B_HF + 8, 1);
        mbar_init(bb + B_HE, 6 * nh);
        mbar_init(bb + B_OTF, head ? 4 : 8); mbar_init(bb + B_OTE, 1); mbar_init(bb + B_OTF + 8, head ? 4 : 8); mbar_init(bb + B_OTE + 16, 1);
        asm volatile("fence.mbarrier_init.release.cluster;" ::: "memory");
        mbar_expect_tx(bb + B_RED, nh * 1280);
        mbar_expect_tx(bb + B_SM, 3072); mbar_expect_tx(bb + B_ST, role == 2 ? 5120 : 4096);
        if (role != 2) { mbar_expect_tx(bb + B_OB, 2048); mbar_expect_tx(bb + B_OB + 64, 2048); }
        mbar_expect_tx(bb + B_HF, 40960); mbar_expect_tx(bb + B_HF + 8, 40960);
    }
    asm volatile("griddepcontrol.launch_dependents;");
    __syncwarp();
    cluster_arrive_relaxed();
    if (warp < 8) {
        asm volatile("setmaxnreg.inc.sync.aligned.u32 %0;" ::"n"(REG_G));
        const int wg = warp >> 2, w4 = warp & 3;
        if (head) {
            uint32_t wa[40][4];
            {
                const int t7 = tid & 127;
                const bf16* W = (role == 2 ? A.Wv + wg * 64 : (wg ? A.Wk : A.Wq) + role * 64) + h * DH + (size_t)(t7 >> 3) * HD + (t7 & 7) * 8;
                const uint32_t so = (t7 >> 3) * 128 + (((t7 & 7) ^ ((t7 >> 3) & 7)) << 4), stg = sb + O_STG + wg * 81920;
                const uint32_t la = stg + ((lane & 7) + (lane >> 4) * 8) * 128 + (((w4 * 2 + ((lane >> 3) & 1)) ^ (lane & 7)) << 4);
                GT(tid == 0, 80);
#pragma unroll
                for (int gi = 0; gi < 8 + WFLY; gi++) {
                    if (gi < 8) {
                        const bf16* Wg = W + (size_t)(((p0 - gi) & 7) * 80) * HD;
#pragma unroll
                        for (int u = 0; u < 5; u++) cp_async16((gi == 0 && u == 0 ? sb + O_AS + wg * 2048 : stg + (gi * 5 + u) * 2048) + so, Wg + (size_t)u * 16 * HD);
                    }
                    cp_commit();
                    if (gi >= WFLY) {
                        cp_wait<WFLY>();
                        named_bar(8 + wg, 128);
#pragma unroll
                        for (int u = 0; u < 5; u++) {
                            const int j = (gi - WFLY) * 5 + u;
                            if (j) { const uint4 v = ldsm4t(la + j * 2048); wa[j][0] = v.x; wa[j][1] = v.y; wa[j][2] = v.z; wa[j][3] = v.w; }
                        }
                    }
                }
                GT(tid == 0, 83);
                cluster_wait();
            }
            named_bar(10, 384);
            GT(tid == 0, 2);
            fence_async_smem();
            named_bar(8 + wg, 128);
            cluster_arrive_relaxed();
            float acc[16];
            const uint32_t ep_q = role == 2 ? sb + O_VM + warp * 512 + (lane ^ ((lane >> 3) & 1)) * 16
                                            : sb + O_QRY + wg * 10240 + ((lane >> 1) & 1) * 5120 + (4 * (lane >> 4) + 2 * ((lane >> 2) & 1) + (lane & 1)) * 128 +
                                                  (((2 * w4 + ((lane >> 3) & 1)) ^ (4 * (lane >> 4) + 2 * ((lane >> 2) & 1) + (lane & 1)) ^ ((lane & 2) << 1)) << 4);
            const uint32_t ep_t = role == 2 ? sb + O_VT + warp * 1024 + ((lane >> 3) & 1) * 512 + (lane >> 4) * 128 + (lane & 7) * 16
                                            : sb + O_QRY + wg * 10240 + (8 + 8 * (lane >> 4) + (lane & 7)) * 128 + (((2 * w4 + ((lane >> 3) & 1)) ^ (lane & 7)) << 4);
                        const int pz = role == 2 ? P1C : P1A;
            const uint32_t ab = (1024 + O_AS + wg * 2048) >> 4;
            uint32_t ok = 1;
            const uint32_t tidk = __shfl_sync(0xffffffffu, tid, lane);
            auto token_gemm = [&](auto ll, const bool pause, const uint32_t vo, const uint32_t nbar, const uint32_t npar, const int t) {
                constexpr int l = decltype(ll)::value;
                constexpr uint32_t hb = ((1024 + O_H + l * 40960) >> 4) | (1u << 16);
                const uint32_t pr = opq(p0);
                if (l) TS(15); else TS(14);
                wg_fence();
#pragma unroll
                for (int j = 0; j < 40; j++) {
                    const uint64_t db = mkdesc(hb + ((pr - j / 5) & 7) * 320 + (j % 5) * 64, 0xC0000010u);
                    if (j == 0) wg_n32_sfirst(acc, mkdesc(ab, 0x40000040u), db);
                    else if (j < TG_STEPS) wg_n32(acc, wa[j][0], wa[j][1], wa[j][2], wa[j][3], db);
                    if (l == 0 && (j + 1 == P1A || j + 1 == P1C)) {
                        if (pause && pz == j + 1) {
                            wg_commit();
                            if (role == 2) mwait(bb + B_OTE, vo >> 14);
                            wg_wait<0>();
                            named_arrive(3, 384);
                            named_bar(4, 384);
                            wg_fence();
                        }
                    }
                }
                wg_commit();
                ok = mtest(nbar, npar);
                wg_wait<0>();
                uint32_t pk[8];
#pragma unroll
                for (int i = 0; i < 8; i++) pk[i] = pack2(acc[2 * i], acc[2 * i + 1]);
                if (role == 2) {
                    stsm4(ep_t + l * 8192 + vo, pk[0], pk[1], pk[2], pk[3]);
                    stsm4(ep_t + l * 8192 + vo + 256, pk[4], pk[5], pk[6], pk[7]);
                } else {
                    stsm4t((ep_t ^ (l << 6)) + l * 5120, pk[0], pk[1], pk[2], pk[3]);
                    stsm4t((ep_t ^ (l << 6)) + l * 5120 + 2048, pk[4], pk[5], pk[6], pk[7]);
                }
                asm volatile("{\n.reg .pred p, q;\nsetp.eq.u32 p, %0, 0;\nsetp.eq.u32 q, %1, 0;\n"
                             "@p mbarrier.arrive.expect_tx.shared::cta.b64 _, [%2], %3;\n@q mbarrier.arrive.shared::cluster.b64 _, [%4];\n}"
                             ::"r"(tidk), "r"(tidk & 127), "r"(bb + B_HF + l * 8), "r"(40960), "r"(mapa(bb + B_HE, l)) : "memory");
            };
            GT(tid == 0, 86);
            mwait(bb + B_HF, 0);
            GT(tid == 0, 87);
            token_gemm(IC<0>{}, false, 0, bb + B_MEM, 1, -1);
            GT(tid == 0, 88);
            named_bar(11, 384);
            cluster_wait();
            named_arrive(13, 384);
#pragma unroll 1
            for (int t = 0; t < NT; t++) {
                GT(tid == 0 && blockIdx.x == 98, 100 + t);
                SC(tid == 0 && blockIdx.x == 98, 160 + t);
                TS(0);
                const uint32_t mp = (t & 1) ^ 1;
                const bool tg0 = t + 1 < NSEG, tg1 = t + 1 >= LAG;
                constexpr uint32_t mb = ((1024 + O_MEM) >> 4) | (16u << 16);
#pragma unroll
                for (int G = 0; G < 8; G++) {
                    if (__builtin_expect(!ok, 0)) mwait(bb + B_MEM + G * 8, mp);
                    ok = mtest(G < 7 ? bb + B_MEM + (G + 1) * 8 : bb + B_HF, mp);
                    if (G == 0) { TS(1); wg_fence(); }
                    if (G == 7) TS(2);
                    if (G == 1) TS(8); if (G == 2) TS(9); if (G == 3) TS(10); if (G == 4) TS(11); if (G == 5) TS(12); if (G == 6) TS(13);
#pragma unroll
                    for (int u = 0; u < 5; u++) {
                        const int j = G * 5 + u;
                        const uint64_t db = mkdesc(mb + j * 32, 8);
                        if (j == 0) wg_n16t_sfirst(acc, mkdesc(ab, 0x40000040u), db);
                        else wg_n16t(acc, wa[j][0], wa[j][1], wa[j][2], wa[j][3], db);
                    }
                    wg_commit();
                }
                if (role == 2 && t) named_bar(5, 384);
                wg_wait<0>();
                TS(3);
                if (role == 2) sts128(ep_q, pack2(acc[0], acc[1]), pack2(acc[2], acc[3]), pack2(acc[4], acc[5]), pack2(acc[6], acc[7]));
                else stsm4t(ep_q, pack2(acc[0], acc[1]), pack2(acc[2], acc[3]), pack2(acc[4], acc[5]), pack2(acc[6], acc[7]));
                named_arrive(1, 384);
                if (tidk < 8) mbar_expect_tx(bb + B_MEM + tidk * 8, 2560);
                if (t == NT - 1) break;
                if (tg0) {
                    if (__builtin_expect(!ok, 0)) mwait(bb + B_HF, mp);
                    if (role != 2) named_bar(2, 384);
                    token_gemm(IC<0>{}, true, mp * 16384, tg1 ? bb + B_HF + 8 : bb + B_MEM, tg1 ? (t + 1 - LAG) & 1 : mp ^ 1, t);
                } else {
                    if (role == 2) mwait(bb + B_OTE, mp); else named_bar(2, 384);
                    named_arrive(3, 384); named_bar(4, 384);
                    ok = 0;
                }
                TS(5);
                if (tg1) {
                    if (__builtin_expect(!ok, 0)) mwait(bb + B_HF + 8, (t + 1 - LAG) & 1);
                    token_gemm(IC<1>{}, false, mp * 16384, bb + B_MEM, mp ^ 1, t);
                }
                TS(6);
                named_arrive(13, 384);
            }
        } else {
            cluster_wait(); cluster_arrive_relaxed();
            const int ep = ld_relaxed(&g_epoch) + 1;
            const uint32_t cb = sb + (warp < 4 ? warp * CV_W : CV_HI + (warp - 4) * CV_W), lb = bb + B_MEM + warp * 8;
            auto fetch = [&](int k) {
                const int ps = k / 5, rg = ps ? ps - 1 : 0, ch = (sp * 5 + k - 5 * ps) * 8 + warp;
                if (k == 5 * ps) { flag_wait(FLG(F_U + ps), (ps > 1 ? 20 : (ps ? 32 : 320)) * ep, 50); fence_async_global(); }
                if (lane == 0) {
                    const uint32_t nb = ps ? ps * 1024 : 512;
                    mbar_expect_tx(lb, 2 * nb);
                    asm volatile("cp.async.bulk.shared::cluster.global.mbarrier::complete_tx::bytes [%0], [%1], %2, [%3];" ::"r"(cb + (k & 1) * 4096), "l"(g_U + ch * (S_LEN / 8)), "r"(nb), "r"(lb) : "memory");
                    asm volatile("cp.async.bulk.shared::cluster.global.mbarrier::complete_tx::bytes [%0], [%1], %2, [%3];" ::"r"(cb + 8192 + (k & 1) * CV_E + 128), "l"(A.ssmk + (size_t)ch * S_LEN), "r"(nb), "r"(lb) : "memory");
                }
                __syncwarp();
            };
            sts32(cb + 8192 + lane * 4, 0u); sts32(cb + 8192 + CV_E + lane * 4, 0u);
            if (warp == 0) sts32(sb + CV_Z + lane * 4, 0u);
            uint32_t dv = 0;
            if (lane < 5) {
                prefetch_l2(A.ssmk + (size_t)((sp * 5 + lane) * 8 + warp) * S_LEN, 1024);
                dv = *reinterpret_cast<const unsigned short*>(A.ssmD + (sp * 5 + lane) * 8 + warp) * 0x10001u;
            }
#pragma unroll
            for (int i = 1; i < 5; i++) sts32(cb + 8192 + i * 768 + lane * 4, 0u);
            named_bar(8, 256);
            flag_wait(FLG(F_U), 320 * ep, 50);
            fence_async_global();
            if (lane == 0) mbar_expect_tx(lb, 5120);
            __syncwarp();
            if (lane < 10) {
                const int j = lane >> 1, ch = (sp * 5 + j) * 8 + warp;
                asm volatile("cp.async.bulk.shared::cluster.global.mbarrier::complete_tx::bytes [%0], [%1], %2, [%3];" ::"r"((lane & 1) ? cb + j * 512 : cb + 8192 + j * 768 + 128),
                             "l"((lane & 1) ? (const void*)(g_U + ch * (S_LEN / 8)) : (const void*)(A.ssmk + (size_t)ch * S_LEN)), "r"(512), "r"(lb) : "memory");
            }
            __syncwarp();
#pragma unroll 1
            for (int k = 0; k < 25; k++) {
                const int ps = k / 5, rg = ps ? ps - 1 : 0;
                const uint32_t Dv = __shfl_sync(0xffffffffu, dv, k - 5 * ps);
                const int tb = sp == 0 && tid == 0 && k >= -1 && k < 7 ? 72 + k * 8 : -1;
                SC(tb >= 0, tb);
                if (k == 0 || ps) {
                    mwait(lb, k & 1);
                    SC(tb >= 0, tb + 1);
                    if (ps && k - 5 * ps < 4) { fence_async_smem(); fetch(k + 1); }
                    SC(tb >= 0, tb + 2);
                }
                const uint32_t tt = sb + CV_T + (k & 1) * 8192;
                conv_unit(cb + (ps ? (k & 1) * 4096 : k * 512), cb + 8192 + (ps ? (k & 1) * CV_E : k * 768), cb + 8192 + 2 * CV_E + 64, sb + CV_Z,
                          tt + warp * 1024 + (lane & 7) * 128 + (((lane >> 3) ^ (lane & 7) ^ warp) & 7) * 16, Dv, rg, ps ? 2 * ps : 1, lane, (uint32_t)A.h_target >> 8, tb);
                mwait(bb + B_OTE + (k & 1) * 16, ((k >> 1) & 1) ^ 1);
                named_bar(8, 256);
                {
                    const uint32_t la = tt + (lane & 7) * 1024 + warp * 128 + (((lane >> 3) ^ (lane & 7) ^ warp) & 7) * 16;
                    const uint4 v0 = ldsm4t(la), v1 = ldsm4t(la ^ 64);
                    const uint32_t ya = sb + CV_Y + (k & 1) * 8192 + (warp * 64 + (lane >> 3) * 8 + 7 - (lane & 7)) * 16;
                    stsm4(ya, v0.x, v0.y, v0.z, v0.w);
                    stsm4(ya + 512, v1.x, v1.y, v1.z, v1.w);
                }
                SC(tb >= 0, tb + 6);
                fence_async_smem();
                __syncwarp();
                if (lane == 0) mbar_arrive(bb + B_OTF + (k & 1) * 8);
                if (k - 5 * ps == 4 && k < 24) fetch(k + 1);
                if (k == 0 && lane < 5) prefetch_l2(A.ssmk + (size_t)((sp * 5 + lane) * 8 + warp) * S_LEN + 512, 3072);
            }
            cluster_wait();
        }
    } else if (warp < 12) {
        asm volatile("setmaxnreg.dec.sync.aligned.u32 %0;" ::"n"(REG_T));
        const int w = warp & 3, c = w >> 1, hh = w & 1;
        const uint32_t lane0 = __shfl_sync(0xffffffffu, tid & 31, tid & 31);
        if (head) {
            const int ntile = role == 2 ? 4 * WTC : 4 * WTA;
            auto tile = [&](int i) { return C_REV == 2 ? (int)c_tile[role * 16 + i] : (role == 2 && C_REV ? 39 - i : role * 4 * WTA + i); };
            const uint32_t wo = sb + O_WO;
            uint32_t mi[5][4];
#pragma unroll
            for (int i = 0; i < 5; i++)
#pragma unroll
                for (int q = 0; q < 4; q++) {
                    const unsigned short* mp = reinterpret_cast<const unsigned short*>(A.mem0) + 2 * q * DM + i * 128 + (tid & 127);
                    mi[i][q] = mp[0] | (uint32_t)mp[DM] << 16;
                }
            cluster_wait();
            named_bar(10, 384);
#pragma unroll
            for (int i = 0; i < 5; i++) {
                const int col = i * 128 + (tid & 127), kk = col >> 4, pr = (kk * 13) >> 6;
                const uint32_t ma = sb + O_MEM + (((p0 - pr) & 7) * 5 + kk - 5 * pr) * 512 + (col & 8) * 32 + (col & 7) * 16;
                sts128(ma, mi[i][0], mi[i][0], mi[i][1], mi[i][1]);
                sts128(ma + 128, mi[i][2], mi[i][2], mi[i][3], mi[i][3]);
            }
            fence_async_smem();
            named_arrive(11, 384);
            for (int i = tid & 127; i < ntile * 256; i += 128) {
                const int ti = i >> 8, p = (i >> 1) & 127, ch = i & 1;
                const int ks = p >> 4, kh = (p >> 3) & 1, e8 = p & 7;
                const int dim = 64 * (ks >> 2) + 16 * (e8 >> 1) + 8 * (e8 & 1) + 2 * (ks & 3) + kh;
                cp_async16(wo + ti * 4096 + p * 32 + ((ch ^ ((p >> 2) & 1)) << 4), A.Wo + (size_t)(h * DH + dim) * DM + tile(ti) * 16 + ch * 8);
            }
            cp_commit();
            if (lane < 8) {
                const int u = 2 * tile(w + 4 * (lane >> 1)) + (lane & 1), ow = u / 5;
                const int sl = u - 5 * ow;
                sts32(sb + O_TAB + w * 32 + lane * 4, mapa(sb + O_RED + (sl >> 1) * 2560 + (sl & 1) * 256 + hi * (sl < 4 ? 512 : 256), ow & 15));
            }
            cluster_arrive_relaxed(); cluster_wait();
            cp_wait<0>();
            named_bar(7, 128);
            const uint32_t wo_a = wo + w * 4096 + ((lane >> 4) * 8 + (lane & 7)) * 32 + ((((lane >> 3) & 1) ^ ((lane >> 2) & 1)) << 4);
            const uint32_t ob_0 = sb + (role == 2 ? O_PB : O_OBA) + (lane >> 4) * 2048 + ((lane >> 3) & 1) * 128 + ((lane & 7) ^ ((lane >> 1) & 4)) * 16;
            const float cs = 0.08838834764831845f * 1.4426950408889634f;
            auto w_frag = [&](auto four, int i) {
                return ldsm4t(wo_a + (i < 16 || decltype(four)::value == 4 ? (i >> 4) * 32768 + (i & 1) * 16384 + ((i >> 1) & 7) * 512 : 32768 + (i & 1) * 2048 + ((i >> 1) & 7) * 512));
            };
            auto w_pre = [&](auto four, uint4* wf) {
#pragma unroll
                for (int i = 0; i < 8; i++) wf[i] = w_frag(four, i);
            };
            auto w_run = [&](auto four, auto rem_, uint4* wf, int t, const uint32_t ob_a) {
                constexpr int NTL = decltype(four)::value, NF = 8 * NTL, NP = NTL > 2 ? 2 : 1;
                constexpr bool REMOTE = decltype(rem_)::value;
                const uint32_t ln = opq(lane0), l8 = (ln & 2) * 64 + (ln >> 2) * 16 + (ln & 1) * 8, rb = (bb + B_RED) & 0xFFFFFFu;
                auto slot = [](int i) { return i < 8 ? i : 8 - WR + (i - 8) % WR; };
                uint4 obr[8];
#pragma unroll
                for (int k = 0; k < 4; k++) obr[k] = ldsm4(ob_a + k * 256);
#pragma unroll
                for (int p = 0; p < NP; p++) {
                    const bool split = p == 1 && NTL == 3;
                    const int nk = split ? 4 : 8;
                    float d[4][4];
                    uint4 ta;
#pragma unroll
                    for (int i = 0; i < 16; i++) (&d[0][0])[i] = 0.f;
#pragma unroll
                    for (int ks = 0; ks < 8; ks++) {
                        if (ks >= nk) continue;
                        if (p == 0 && ks == OBK) {
                            if (REMOTE) { mwait(bb + B_OB + 64, t & 1); TS(7); }
#pragma unroll
                            for (int k = 4; k < 8; k++) obr[k] = ldsm4(ob_a + k * 256);
                        }
                        if (ks == nk - 2) ta = lds128(sb + O_TAB + w * 32 + p * 16);
#pragma unroll
                        for (int u = 0; u < 2; u++) {
                            const int i = p * 16 + ks * 2 + u;
                            const uint4& o = obr[split && u ? ks + 4 : ks];
                            const uint4& f = wf[slot(i)];
                            mmav(d[2 * u], f.x, f.y, f.z, f.w, o.x, o.y); mmav(d[2 * u + 1], f.x, f.y, f.z, f.w, o.z, o.w);
                            if (i + WR >= 8 && i + WR < NF) wf[slot(i + WR)] = w_frag(four, i + WR);
                        }
                    }
                    if (p) TS(10); else TS(8);
                    if (split) {
#pragma unroll
                        for (int i = 0; i < 4; i++) { d[0][i] += d[2][i]; d[1][i] += d[3][i]; }
                    }
                    st_async_v2(ta.x + l8, pack2(d[0][0], d[0][1]), pack2(d[1][0], d[1][1]), (ta.x & 0xFF000000u) | rb);
                    st_async_v2(ta.y + l8, pack2(d[0][2], d[0][3]), pack2(d[1][2], d[1][3]), (ta.y & 0xFF000000u) | rb);
                    if (!split) {
                        st_async_v2(ta.z + l8, pack2(d[2][0], d[2][1]), pack2(d[3][0], d[3][1]), (ta.z & 0xFF000000u) | rb);
                        st_async_v2(ta.w + l8, pack2(d[2][2], d[2][3]), pack2(d[3][2], d[3][3]), (ta.w & 0xFF000000u) | rb);
                    }
                }
            };
            if (role != 2) {
#pragma unroll 1
                for (int t = 0; t < NT; t++) {
                    const uint32_t lane = opq(lane0);
                    const uint32_t dc = mapa(sb, hi * 3 + 2), dp = mapa(sb, hi * 3 + (role ^ 1));
                    const uint32_t qa = sb + O_QRY + c * 5120 + (lane & 7) * 128;
                    const uint32_t sw = (((lane >> 3) ^ (lane & 7)) << 4) ^ (c << 6);
                    {
                        const uint32_t ka = qa + 10240;
                        const uint32_t kt = sb + O_KEY + c * 5120 + (lane & 15) * 128, kx = (((lane >> 4) ^ (lane & 7)) << 4) ^ (c << 6);
                        const uint32_t sd = dc + O_SM + role * 1536 + c * 768 + lane * 4, sbar = dc + O_BAR + B_SM;
                        const uint32_t ta = sb + O_QRY + c * 5120 + (8 + 16 * hh + ((lane & 15) ^ (role * 8))) * 128;
                        uint4 a[4], f[4];
                        named_bar(13, 384);
#pragma unroll
                        for (int i = 0; i < 4; i++) f[i] = ldsm4(kt + 1024 + hh * 2048 + (kx ^ (i << 5) ^ (hh << 6)));
#pragma unroll
                        for (int i = 0; i < 4; i++) a[i] = ldsm4(ta + (kx ^ (i << 5)));
                        const uint32_t kd = ka + (1 + 2 * hh) * 1024 + sw;
                        uint4 k[5];
                        k[1] = ldsm4(kd); k[2] = ldsm4(kd + 1024);
                        {
                            const uint32_t qh = qa + (sw ^ (hh << 6)), kh = kt + (kx ^ (hh << 6));
                            named_bar(1, 384);
                            const uint4 q0 = ldsm4(qh), g0 = ldsm4(kh), g1 = ldsm4(kh ^ 32), q1 = ldsm4(qh ^ 64);
                            float s0[4] = {0.f, 0.f, 0.f, 0.f}, s1[4] = {0.f, 0.f, 0.f, 0.f}, s2[4] = {0.f, 0.f, 0.f, 0.f}, s3[4] = {0.f, 0.f, 0.f, 0.f};
                            mmav(s0, f[0].x, f[0].y, f[0].z, f[0].w, q0.x, q0.y); mmav(s1, f[1].x, f[1].y, f[1].z, f[1].w, q0.z, q0.w);
                            mmav(s2, g0.x, g0.y, g0.z, g0.w, q0.x, q0.y); mmav(s3, g1.x, g1.y, g1.z, g1.w, q0.z, q0.w);
                            mmav(s0, f[2].x, f[2].y, f[2].z, f[2].w, q1.x, q1.y); mmav(s1, f[3].x, f[3].y, f[3].z, f[3].w, q1.z, q1.w);
                            k[0] = ldsm4(ka + sw); k[3] = ldsm4(ka + 1024 + sw); k[4] = ldsm4(ka + 2048 + sw);
                            st_async_b32(sd + hh * 128, pack2(s2[0] + s3[0], s2[1] + s3[1]), sbar);
                            st_async_b32(sd + 256 + hh * 256, pack2(s0[0] + s1[0], s0[1] + s1[1]), sbar);
                            st_async_b32(sd + 384 + hh * 256, pack2(s0[2] + s1[2], s0[3] + s1[3]), sbar);
                        }
                        TS(1);
                        float u[5][4];
#pragma unroll
                        for (int i = 0; i < 20; i++) (&u[0][0])[i] = 0.f;
                        auto half = [&](auto nn, const uint4& a0, const uint4& a1, bool more) {
                            constexpr int NU = decltype(nn)::value;
                            constexpr int ord[5] = {1, 2, 0, 3, 4};
#pragma unroll
                            for (int i = 0; i < NU; i++) mmav(u[ord[i]], a0.x, a0.y, a0.z, a0.w, k[ord[i]].x, k[ord[i]].y);
#pragma unroll
                            for (int i = 0; i < NU; i++) {
                                const int n = ord[i];
                                mmav(u[n], a1.x, a1.y, a1.z, a1.w, k[n].z, k[n].w);
                                if (more) k[n] = ldsm4(((n == 0 ? ka + sw : (n < 3 ? kd + (n - 1) * 1024 : ka + (n - 2) * 1024 + sw))) ^ 64);
                            }
                        };
                        auto fu = [](float x) { return __float_as_uint(x); };
                        const uint32_t so = O_ST + c * 2048 + hh * 768, td = dp + so, tb = dp + O_BAR + B_ST, lo = sb + so + 4096;
                        if (hh) {
                            half(IC<5>{}, a[0], a[1], true); half(IC<5>{}, a[2], a[3], false);
                            st_async_v4(td + lane * 16, fu(u[0][2]), fu(u[0][3]), fu(u[1][2]), fu(u[1][3]), tb);
                            st_async_v4(td + 512 + lane * 16, fu(u[2][2]), fu(u[2][3]), fu(u[3][2]), fu(u[3][3]), tb);
                            st_async_v2(td + 1024 + lane * 8, fu(u[4][2]), fu(u[4][3]), tb);
                            sts128(lo + lane * 16, fu(u[0][0]), fu(u[0][1]), fu(u[1][0]), fu(u[1][1]));
                            sts128(lo + 512 + lane * 16, fu(u[2][0]), fu(u[2][1]), fu(u[3][0]), fu(u[3][1]));
                            sts64(lo + 1024 + lane * 8, fu(u[4][0]), fu(u[4][1]));
                        } else {
                            half(IC<3>{}, a[0], a[1], true); half(IC<3>{}, a[2], a[3], false);
                            st_async_v4(td + lane * 16, fu(u[0][2]), fu(u[0][3]), fu(u[1][2]), fu(u[1][3]), tb);
                            st_async_v2(td + 512 + lane * 8, fu(u[2][2]), fu(u[2][3]), tb);
                            sts128(lo + lane * 16, fu(u[0][0]), fu(u[0][1]), fu(u[1][0]), fu(u[1][1]));
                            sts64(lo + 512 + lane * 8, fu(u[2][0]), fu(u[2][1]));
                        }
                        if (t < NT - 1) named_arrive(2, 384);
                        __syncwarp();
                        if (lane == 0) mbar_arrive(bb + B_ST);
                        TS(2);
                    }
                    if (t == NT - 1) break;
                    uint4 wf[8];
                    w_pre(IC<WTA>{}, wf);
                    mwait(bb + B_OB, t & 1);
                    TS(3);
                    named_bar(3, 384);
                    w_run(IC<WTA>{}, IC<1>{}, wf, t, ob_0);
                    named_arrive(4, 384);
                    if (w == 0 && lane == 0) { mbar_expect_tx(bb + B_OB, 2048); mbar_expect_tx(bb + B_OB + 64, 2048); }
                    TS(5);
                }
            } else {
#pragma unroll 1
                for (int t = 0; t < NT; t++) {
                    const uint32_t lane = opq(lane0);
                    const int g = lane >> 2, tq = lane & 3;
                    const uint32_t vm_a = sb + O_VM + (g * 4 + 2 * (tq & 1) + (c ^ ((g >> 1) & 1))) * 16 + (tq >> 1) * 8;
                    const uint32_t vt_a = sb + O_VT + (t & 1) * 16384 + ((lane >> 3) & 1) * 512 + (lane >> 4) * 128 + (lane & 7) * 16;
                    named_bar(13, 384);
                    uint4 va[4][2];
#pragma unroll
                    for (int i = 0; i < 4; i++) {
                        va[i][0] = ldsm4(vt_a + c * 8192 + (4 * hh + i) * 1024);
                        va[i][1] = ldsm4(vt_a + c * 8192 + (4 * hh + i) * 1024 + 256);
                    }
                    const uint32_t sa = opq(sb + O_SM + c * 768 + 256 + lane * 16), sa2 = opq(sb + O_SM + c * 768 + (lane & 15) * 16 + (lane >> 4) * 1536), vm_b = opq(vm_a + hh * 2048);
                    named_bar(1, 384);
                    if (__builtin_expect(t < NT - 1, 1)) {
                        uint2 vm[4];
#pragma unroll
                        for (int i = 0; i < 4; i++) vm[i] = lds64(vm_b + i * 512);
                        mwait(bb + B_SM, t & 1);
                        TS(1);
                        const uint4 x0 = ldsm4t(sa), y0 = ldsm4t(sa + 1536), x1 = ldsm4t(sa2);
                        float s[10];
                        s[2] = blo(x0.x) + blo(y0.x); s[3] = bhi(x0.x) + bhi(y0.x); s[4] = blo(x0.y) + blo(y0.y); s[5] = bhi(x0.y) + bhi(y0.y);
                        s[6] = blo(x0.z) + blo(y0.z); s[7] = bhi(x0.z) + bhi(y0.z); s[8] = blo(x0.w) + blo(y0.w); s[9] = bhi(x0.w) + bhi(y0.w);
                        s[0] = (blo(x1.x) + blo(x1.y)) + (blo(x1.z) + blo(x1.w)); s[1] = (bhi(x1.x) + bhi(x1.y)) + (bhi(x1.z) + bhi(x1.w));
                        float mx = fmaxf(fmaxf(fmaxf(s[0], s[1]), fmaxf(s[2], s[3])), fmaxf(fmaxf(fmaxf(s[4], s[5]), fmaxf(s[6], s[7])), fmaxf(s[8], s[9])));
                        const float m1 = __shfl_xor_sync(0xffffffffu, mx, 1), m2 = __shfl_xor_sync(0xffffffffu, mx, 2), m3 = __shfl_xor_sync(0xffffffffu, mx, 3);
                        mx = fmaxf(fmaxf(mx, m1), fmaxf(m2, m3)) * -cs;
                        uint32_t pb[5];
#pragma unroll
                        for (int i = 0; i < 5; i++) pb[i] = pack2(ex2f(fmaf(s[2 * i], cs, mx)), ex2f(fmaf(s[2 * i + 1], cs, mx)));
                        TS(9);
                        named_bar(3, 384);
                        float o[5][4];
#pragma unroll
                        for (int i = 0; i < 20; i++) (&o[0][0])[i] = 0.f;
                        const uint32_t one2 = 0x3F803F80u;
                        float z[2][4] = {{0.f, 0.f, 0.f, 0.f}, {0.f, 0.f, 0.f, 0.f}};
                        mmav8(o[4], one2, one2, pb[0]);
                        mmav(z[0], one2, one2, one2, one2, pb[1], pb[2]);
                        mmav(z[1], one2, one2, one2, one2, pb[3], pb[4]);
#pragma unroll
                        for (int i = 0; i < 4; i++) mmav8(o[i], vm[i].x, vm[i].y, pb[0]);
#pragma unroll
                        for (int i = 0; i < 4; i++) mmav(o[i], va[i][0].x, va[i][0].y, va[i][0].z, va[i][0].w, pb[1], pb[2]);
#pragma unroll
                        for (int i = 0; i < 4; i++) mmav(o[i], va[i][1].x, va[i][1].y, va[i][1].z, va[i][1].w, pb[3], pb[4]);
                        o[4][0] += z[0][0] + z[1][0]; o[4][1] += z[0][1] + z[1][1];
                        uint4 wf[8];
                        w_pre(IC<WTC>{}, wf);
                        const float r0 = rcpf(o[4][0]), r1 = rcpf(o[4][1]);
                        const uint32_t oo = c * 2048 + hh * 1024 + g * 128 + tq * 16 + (g & 1) * 64;
                        uint32_t e0[4], e1[4];
#pragma unroll
                        for (int i = 0; i < 4; i++) { e0[i] = pack2(o[i][0] * r0, o[i][2] * r0); e1[i] = pack2(o[i][1] * r1, o[i][3] * r1); }
                        sts128(sb + O_PB + (~t & 1) * 5120 + oo, e0[0], e0[1], e0[2], e0[3]);
                        sts128(sb + O_PB + (~t & 1) * 5120 + (oo ^ 64), e1[0], e1[1], e1[2], e1[3]);
                        {
                            const uint32_t da = mapa(sb + O_OBA, r - 2) + oo, ba = mapa(bb + B_OB + hh * 64, r - 2);
                            st_async_v4(da, e0[0], e0[1], e0[2], e0[3], ba);
                            st_async_v4(da + 0x01000000u, e0[0], e0[1], e0[2], e0[3], ba + 0x01000000u);
                            st_async_v4(da ^ 64, e1[0], e1[1], e1[2], e1[3], ba);
                            st_async_v4((da ^ 64) + 0x01000000u, e1[0], e1[1], e1[2], e1[3], ba + 0x01000000u);
                        }
                        TS(3);
                        named_bar(7, 128);
                        w_run(IC<WTC>{}, IC<0>{}, wf, t, ob_0 + (~t & 1) * 5120);
                        named_arrive(4, 384);
                        mwait(bb + B_ST, t & 1);
                        TS(4);
                    } else { mwait(bb + B_SM, t & 1); mwait(bb + B_ST, t & 1); }
                    TS(5);
                    fence_async_smem();
#pragma unroll 1
                    for (int l = t < NSEG ? 0 : 1; l < (t >= LAG ? 2 : 1); l++) {
                        const uint32_t pb_ = ((1024 + O_PB) >> 4) + (t & 1) * 320 + l * 160, va_ = (((1024 + O_VT) >> 4) + (t & 1) * 1024 + l * 512) | (8u << 16);
                        const uint32_t oa = sb + O_VT + (t & 1) * 16384 + l * 8192 + w * 1024 + g * 64 + ((tq ^ (g >> 1)) & 3) * 16;
                        const uint32_t vl = (vm_a ^ ((l ^ c) << 4)) + w * 512;
                        const uint2 a0 = lds64(vl), a1 = lds64(vl + 2048);
                        float d[2][16];
                        wg_fence();
                        wg_n32_first(d[0], a0.x, a0.y, 0u, 0u, mkdesc(pb_, 8));
                        wg_n32_first(d[1], a1.x, a1.y, 0u, 0u, mkdesc(pb_, 8));
#pragma unroll
                        for (int i = 0; i < 4; i++) wg_n32_kk(d[i & 1], mkdesc(va_ + (i & 1) * 256 + (i >> 1) * 16, 32), mkdesc(pb_ + 32 + (i >> 1) * 64 + (32u << 16), 8));
                        wg_commit();
                        if (l) TS(13); else TS(11);
                        wg_wait<0>();
                        if (l) TS(14); else TS(12);
#pragma unroll
                        for (int mt = 0; mt < 2; mt++) {
                            sts128(oa + mt * 4096, pack2(d[mt][0], d[mt][1]), pack2(d[mt][4], d[mt][5]), pack2(d[mt][8], d[mt][9]), pack2(d[mt][12], d[mt][13]));
                            sts128(oa + mt * 4096 + 512, pack2(d[mt][2], d[mt][3]), pack2(d[mt][6], d[mt][7]), pack2(d[mt][10], d[mt][11]), pack2(d[mt][14], d[mt][15]));
                        }
                        if (l == 0) {
                            fence_async_smem();
                            __syncwarp();
                            if (lane == 0) mbar_arrive(bb + B_OTF + 8);
                        }
                    }
                    TS(6);
                    if (w == 0 && lane == 0) { mbar_expect_tx(bb + B_ST, 5120); mbar_expect_tx(bb + B_SM, 3072); }
                    fence_async_smem();
                    __syncwarp();
                    if (lane == 0) mbar_arrive(bb + B_OTF);
                    if (t < NT - 1) named_arrive(5, 384);
                }
            }
        } else {
            cluster_wait(); cluster_arrive_relaxed();
            const int wi = sp * 4 + w, half = wi >> 5, tok = wi & 31, ep = ld_relaxed(&g_epoch) + 1;
            GT(lane == 0, 89);
            if (lane < LN0_AHEAD / 2) prefetch_l2(A.x + (size_t)((half + 2 * lane) * SEG + tok) * DM, 1280);
#pragma unroll 1
            for (int k = -LN0_AHEAD / 2; k < NT; k++) {
                const int s0 = k < 0 ? 2 * k + LN0_AHEAD + half : (half && k % LN0_BATCH == 0 ? k + LN0_AHEAD : NSEG);
                if (s0 < NSEG) { ln0_rows(A.x, s0, k < 0 ? 1 : LN0_BATCH, tok, lane); GT(lane == 0 && k < 0, 30 + s0); }
                if (k == -1 && half) {
#pragma unroll 1
                    for (int u = 320 + tok; u < 640; u += 32) u_half(A.Bk, A.Bv, A.shiftk, u, lane);
                    __syncwarp();
                    if (lane == 0) red_release(FLG(F_U + 1), 1);
                }
                const int n = k - half * LAG;
                if (n >= 0 && n < NSEG && k >= 0) {
                    post_row(half, n, tok, lane, A.x, A.out, ep);
                    GT(lane == 0 && (n & 3) == 0 && k >= 0, 460 + half * 16 + (n >> 2)); GT(lane == 0 && n == 63 && half, 40);
                }
            }
            cluster_wait();
        }
    } else {
        asm volatile("setmaxnreg.dec.sync.aligned.u32 %0;" ::"n"(REG_X));
        cluster_wait();
        const int s = warp - 12;
        const uint32_t lane0 = __shfl_sync(0xffffffffu, tid & 31, tid & 31);
        if (s < 3) {
            cluster_arrive_relaxed();
            GT(lane == 0, 84);
            if (blockIdx.x * 3 + s < 320) {
                u_half(A.Bk, A.Bv, A.shiftk, blockIdx.x * 3 + s, lane);
                GT(lane == 0, 85);
                __syncwarp();
                if (lane == 0) red_release(FLG(F_U), 1);
                GT(lane == 0, 4);
            }
            const int ztgt = 3 * 16 * NCL * (ld_relaxed(&g_epoch) + 1);
#pragma unroll
            for (int i = 0; i < XRS; i++) st_relaxed_v4(g_xc + ((i * 16 + r) * 3 + s) * 256 + cq * 32 + lane, 0, 0, 0, 0);
            __syncwarp();
            if (lane == 0) red_release(FLG(F_Z), 1);
            cluster_wait();
            constexpr uint32_t XSLOT = 16 * 3 * 4096;
            uint32_t xo_ = (r * 3 + s) * 4096;
            if (s == 0) {
                const uint32_t G = lane >> 1, d = ((r + 2 * G) & 15) ^ (lane & 1);
                if (lane < 16) { sts32(sb + O_BT + lane * 8, (d << 24) + G * 2560); sts32(sb + O_BT + lane * 8 + 4, d < 3 * nh ? mapa(bb + B_MEM + G * 8, d) : 0u); }
            }
            while (ld_acquire(FLG(F_Z)) < ztgt) __nanosleep(100);
            named_bar(14, 96);
#pragma unroll 1
            for (int t = 0; t < NT; t++) {
                const uint32_t lane = opq(lane0);
                if (head && role != 2) {
                    auto soft = [&](auto uu, auto vv, int c0, int hh) {
                        constexpr int U = decltype(uu)::value, NV = decltype(vv)::value;
                        const uint32_t dc = mapa(sb, hi * 3 + 2), sa = sb + O_ST + c0 * 2048 + hh * 768;
                        const uint32_t pd = dc + O_PB + (t & 1) * 5120 + c0 * 2560 + (2 * hh + role) * 128 + lane * 4, pbar = dc + O_BAR + B_ST;
                        const int lim = 8 * role + (int)(lane >> 2) - 2 * (int)(lane & 3);
                        auto uf = [](uint32_t x) { return __uint_as_float(x); };
                        mwait(bb + B_ST, t & 1);
                        if (r == 1 && U == 2 && t >= LAG - 1 && t < NT - 1) named_arrive(12, 64);
                        uint32_t z[U][NV];
                        auto zz = [](float x, float y) { const uint32_t w = pack2(x, y); return pack2(blo(w) * 0.08838834764831845f, bhi(w) * 0.08838834764831845f); };
#pragma unroll
                        for (int i = 0; i < U; i++) {
                            const uint4 v = lds128(sa + i * 2048 + lane * 16), w = lds128(sa + i * 2048 + 4096 + lane * 16);
                            z[i][0] = zz(uf(v.x) + uf(w.x), uf(v.y) + uf(w.y));
                            z[i][1] = zz(lim < 0 ? -INFINITY : uf(v.z) + uf(w.z), lim < 1 ? -INFINITY : uf(v.w) + uf(w.w));
                            if (NV == 3) {
                                const uint2 x = lds64(sa + i * 2048 + 512 + lane * 8), y = lds64(sa + i * 2048 + 4608 + lane * 8);
                                z[i][2] = zz(lim < 8 ? -INFINITY : uf(x.x) + uf(y.x), lim < 9 ? -INFINITY : uf(x.y) + uf(y.y));
                            } else {
                                const uint4 x = lds128(sa + 512 + lane * 16), y = lds128(sa + 4608 + lane * 16);
                                const uint2 p = lds64(sa + 1024 + lane * 8), q = lds64(sa + 5120 + lane * 8);
                                z[i][2] = zz(lim < 8 ? -INFINITY : uf(x.x) + uf(y.x), lim < 9 ? -INFINITY : uf(x.y) + uf(y.y));
                                z[i][NV - 2] = zz(uf(x.z) + uf(y.z), uf(x.w) + uf(y.w));
                                z[i][NV - 1] = zz(uf(p.x) + uf(q.x), uf(p.y) + uf(q.y));
                            }
                        }
                        const float l2e = 1.4426950408889634f;
                        float e[U][2 * NV], sum[U];
#pragma unroll
                        for (int i = 0; i < U; i++) {
                            uint32_t zm = bmax2(bmax2(z[i][0], z[i][1]), z[i][2]);
                            if (NV == 5) zm = bmax2(zm, bmax2(z[i][NV - 2], z[i][NV - 1]));
                            zm = bmax2(zm, __shfl_xor_sync(0xffffffffu, zm, 1));
                            zm = bmax2(zm, __shfl_xor_sync(0xffffffffu, zm, 2));
                            const float mx = fmaxf(blo(zm), bhi(zm)) * -l2e;
                            sum[i] = 0.f;
#pragma unroll
                            for (int n = 0; n < NV; n++) { e[i][2 * n] = ex2f(fmaf(blo(z[i][n]), l2e, mx)); e[i][2 * n + 1] = ex2f(fmaf(bhi(z[i][n]), l2e, mx)); }
                            sum[i] = ((e[i][0] + e[i][1]) + (e[i][2] + e[i][3])) + (e[i][4] + e[i][5]);
                            if (NV == 5) sum[i] += (e[i][2 * NV - 4] + e[i][2 * NV - 3]) + (e[i][2 * NV - 2] + e[i][2 * NV - 1]);
                            sum[i] += __shfl_xor_sync(0xffffffffu, sum[i], 1);
                            sum[i] += __shfl_xor_sync(0xffffffffu, sum[i], 2);
                            sum[i] = rcpf(sum[i]);
                        }
#pragma unroll
                        for (int i = 0; i < U; i++)
#pragma unroll
                            for (int n = 0; n < 5; n++)
                                st_async_b32(pd + i * 2560 + (n == 0 ? 0 : (NV == 3 ? n : (n < 3 ? n + 2 : n - 2)) * 512), n < NV ? pack2(e[i][2 * n] * sum[i], e[i][2 * n + 1] * sum[i]) : 0u, pbar);
                    };
                    if (s < 2) soft(IC<1>{}, IC<5>{}, s, 1); else soft(IC<2>{}, IC<3>{}, 0, 0);
                    TS(12);
                    named_bar(14, 96);
                    if (s == 0 && lane == 0) mbar_expect_tx(bb + B_ST, 4096);
                }
                if (t == NT - 1) break;
                uint32_t m0 = 0x80008000u, m1 = 0x80008000u;
                if (t < LAG && cq == 0) {
                    const uint32_t ch = s < 2 ? lane : lane >> 1;
                    const unsigned short* mp = reinterpret_cast<const unsigned short*>(A.mem0) + (((ch >> 3) & 1) * 4 + (s < 2 ? 0 : (lane & 1) * 2)) * DM + (5 * r + 2 * s + (ch >> 4)) * 8 + (ch & 7);
                    m0 = max(mp[0] | (uint32_t)mp[DM] << 16, 1u);
                    if (s < 2) m1 = max(mp[2 * DM] | (uint32_t)mp[3 * DM] << 16, 1u);
                }
                const bool late = t >= LAG;
                auto sum5 = [](uint32_t a, uint32_t b, uint32_t c, uint32_t d, uint32_t e) { return nz(badd(badd(badd(a, b), e), badd(c, d))); };
                auto sum7 = [](uint32_t a, uint32_t b, uint32_t c, uint32_t d, uint32_t e, uint32_t f, uint32_t h_) {
                    return badd(badd(badd(a, b), badd(c, d)), badd(badd(e, f), h_));
                };
                auto min3 = [](uint32_t a, uint32_t b, uint32_t c) { return min(min(a, b), c); };
                auto bcast = [&](auto two, const uint32_t aa, uint32_t x0, uint32_t x1, uint32_t x2, uint32_t x3) {
                    auto send = [&](uint32_t o, uint32_t bar) { if (decltype(two)::value) st_async_v4p(aa + o, x0, x1, x2, x3, bar); else st_async_v2p(aa + o, x0, x1, bar); };
                    uint4 e[5];
                    e[0] = lds128(sb + O_BT);
                    TS(8);
                    send(e[0].x, e[0].y); send(e[0].z, e[0].w);
                    TS(9);
#pragma unroll
                    for (int i = 1; i < 5; i++) e[i] = lds128(sb + O_BT + i * 16);
#pragma unroll
                    for (int i = 1; i < 8; i++) {
                        send(e[(i - 1) % 4 + 1].x, e[(i - 1) % 4 + 1].y); send(e[(i - 1) % 4 + 1].z, e[(i - 1) % 4 + 1].w);
                        if (i < 4) e[i] = lds128(sb + O_BT + (i + 4) * 16);
                    }
                };
                const uint32_t ma = (sb + O_MEM + (5 * (r & 1) + 2 * s) * 256) & 0xFFFFFFu;
                int guard = 0;
                if (s < 2) {
                    const uint32_t ra = sb + O_RED + s * 2560 + lane * 16;
                    uint4* xb = reinterpret_cast<uint4*>(reinterpret_cast<char*>(g_xc) + xo_ + lane * 16);
                    uint4* xo = xb + cq * 32;
                    touch(xo); touch(xb);
                    mwait(bb + B_RED, t & 1);
                    TS(0);
                    uint4 p[5];
#pragma unroll
                    for (int i = 0; i < 5; i++) p[i] = i < 4 || nh == 5 ? lds128(ra + i * 512) : make_uint4(0, 0, 0, 0);
                    const uint32_t u1 = sum5(p[0].y, p[1].y, p[2].y, p[3].y, p[4].y), u3 = sum5(p[0].w, p[1].w, p[2].w, p[3].w, p[4].w);
                    st_relaxed_v4(xo, sum5(p[0].x, p[1].x, p[2].x, p[3].x, p[4].x), late ? u1 : m0, sum5(p[0].z, p[1].z, p[2].z, p[3].z, p[4].z), late ? u3 : m1);
                    TS(1);
                    delay(XD);
                    uint4 x[NCL];
                    while (true) {
                        ld7_relaxed(x, xb);
                        const uint32_t mn = min3(min3(min3(x[0].x, x[0].y, x[0].z), min3(x[0].w, x[1].x, x[1].y), min3(x[1].z, x[1].w, x[2].x)),
                                                 min3(min3(x[2].y, x[2].z, x[2].w), min3(x[3].x, x[3].y, x[3].z), min3(x[3].w, x[4].x, x[4].y)),
                                                 min3(min3(x[4].z, x[4].w, x[5].x), min3(x[5].y, x[5].z, x[5].w), min(min3(x[6].x, x[6].y, x[6].z), x[6].w)));
                        if (NO_X || __all_sync(0xffffffffu, mn != 0)) break;
                        if (++guard > 2000000) __trap();
                    }
                    TS(2);
                    TV(4, guard);
                    bcast(IC<1>{}, ma + lane * 16, sum7(x[0].x, x[1].x, x[2].x, x[3].x, x[4].x, x[5].x, x[6].x), sum7(x[0].y, x[1].y, x[2].y, x[3].y, x[4].y, x[5].y, x[6].y),
                          sum7(x[0].z, x[1].z, x[2].z, x[3].z, x[4].z, x[5].z, x[6].z), sum7(x[0].w, x[1].w, x[2].w, x[3].w, x[4].w, x[5].w, x[6].w));
                } else {
                    const uint32_t ra = sb + O_RED + 5120 + lane * 8;
                    uint2* xb = reinterpret_cast<uint2*>(reinterpret_cast<char*>(g_xc) + xo_ + lane * 8);
                    uint2* xo = xb + cq * 64;
                    touch(xo); touch(xb);
                    mwait(bb + B_RED, t & 1);
                    TS(0);
                    uint2 p[5];
#pragma unroll
                    for (int i = 0; i < 5; i++) p[i] = i < 4 || nh == 5 ? lds64(ra + i * 256) : make_uint2(0, 0);
                    const uint32_t u1 = sum5(p[0].y, p[1].y, p[2].y, p[3].y, p[4].y);
                    st_relaxed_v2(xo, sum5(p[0].x, p[1].x, p[2].x, p[3].x, p[4].x), late ? u1 : m0);
                    if (lane == 0) mbar_expect_tx(bb + B_RED, nh * 1280);
                    TS(1);
                    delay(XD);
                    uint32_t y0, y1;
                    while (true) {
                        uint2 x[NCL];
                        ld7_relaxed(x, xb);
                        const uint32_t mn = min3(min3(min3(x[0].x, x[0].y, x[1].x), min3(x[1].y, x[2].x, x[2].y), min3(x[3].x, x[3].y, x[4].x)), min3(x[4].y, x[5].x, x[5].y), min(x[6].x, x[6].y));
                        y0 = sum7(x[0].x, x[1].x, x[2].x, x[3].x, x[4].x, x[5].x, x[6].x); y1 = sum7(x[0].y, x[1].y, x[2].y, x[3].y, x[4].y, x[5].y, x[6].y);
                        if (NO_X || __all_sync(0xffffffffu, mn != 0)) break;
                        if (++guard > 2000000) __trap();
                    }
                    TS(2);
                    TV(4, guard);
                    bcast(IC<0>{}, ma + lane * 8, y0, y1, 0u, 0u);
                }
                TS(3);
                if (head && role == 2) named_arrive(6, 128);
                xo_ += XSLOT; if (xo_ >= XRS * XSLOT) xo_ -= XRS * XSLOT;
                {
                    const uint32_t zo = xo_ + XSLOT >= XRS * XSLOT ? xo_ + XSLOT - XRS * XSLOT : xo_ + XSLOT;
                    char* zp = reinterpret_cast<char*>(g_xc) + zo + cq * 512 + lane * 16;
                    st_relaxed_v4(zp, 0, 0, 0, 0);
                    if (ld_relaxed_v4(zp).x) __trap();
                }
            }
        } else if (r < 2) {
            const uint16_t mask = (uint16_t)((1u << (3 * nh)) - 1u);
            const int htgt = A.h_target * (ld_relaxed(&g_epoch) + 1);
#pragma unroll 1
            for (int n = 0; n < NSEG; n++) {
                if (n == (r == 0 ? 1 : 0)) { cluster_arrive(); cluster_wait(); }
                int guard = 0;
                while (ld_acquire(FLG(F_H + r * 64 + n)) < htgt) { if (++guard > 2000000) __trap(); __nanosleep(H_NS); }
                fence_async_global();
                if (r == 1) named_bar(12, 64);
                if (n) mwait(bb + B_HE, (n - 1) & 1);
                if (lane < 8)
                    asm volatile("cp.async.bulk.shared::cluster.global.mbarrier::complete_tx::bytes.multicast::cluster [%0], [%1], %2, [%3], %4;" ::"r"(sb + O_H + r * 40960 + lane * 5120),
                                 "l"(g_ht + rslot(r, n) * 2560 + lane * 320), "r"(5120), "r"(bb + B_HF + r * 8), "h"(mask) : "memory");
                __syncwarp();
            }
        } else {
            cluster_arrive(); cluster_wait();
            if (head && role == 2) {
#pragma unroll 1
                for (int t = 0; t < NT; t++) {
                    auto put = [&](int l, int n) {
                        asm volatile("cp.async.bulk.global.shared::cta.bulk_group [%0], [%1], %2;" ::"l"(g_ot + (rslot(l, n) * 256 + h * 8) * 64), "r"(sb + O_VT + (t & 1) * 16384 + l * 8192), "r"(8192) : "memory");
                        asm volatile("cp.async.bulk.commit_group;" ::: "memory");
                    };
                    auto publish = [&](int l, int n) {
                        asm volatile("cp.async.bulk.wait_group 0;" ::: "memory");
                        fence_async_global();
                        red_release(FLG(F_O + l * 64 + n) + (h >> 3), 1);
                        GT(true, 200 + l * 64 + n);
                        if (ONE_FENCE && l == 0 && n > LAG) {
                            asm volatile("red.relaxed.gpu.global.add.u32 [%0], 1;" ::"l"(FLG(F_O + 63 - LAG + n) + (h >> 3)) : "memory");
                            GT(true, 263 - LAG + n);
                        }
                    };
                    if (t < NSEG) {
                        mwait(bb + B_OTF + 8, t & 1);
                        if (lane == 0) { put(0, t); publish(0, t); }
                        __syncwarp();
                    }
                    mwait(bb + B_OTF, t & 1);
                    if (t < NT - 1) named_bar(6, 128);
                    if (lane == 0) {
                        if (t >= LAG) {
                            put(1, t - LAG);
                            asm volatile("cp.async.bulk.wait_group.read 0;" ::: "memory");
                        }
                        mbar_arrive(bb + B_OTE);
                        if (t >= (ONE_FENCE ? NSEG - 1 : LAG)) publish(1, t - LAG);
                    }
                    __syncwarp();
                }
            }
            if (!head && lane == 0) {
#pragma unroll 1
                for (int k = 0; k < 25; k++) {
                    const int rg = k / 5, r0 = rg == 1 ? 256 : 0;
                    mwait(bb + B_OTF + (k & 1) * 8, (k >> 1) & 1);
                    asm volatile("cp.async.bulk.global.shared::cta.bulk_group [%0], [%1], %2;" ::"l"(g_Y + (sp * 5 + k - 5 * rg) * S_LEN + (rg ? rg - 1 : 0) * 512 + r0),
                                 "r"(sb + CV_Y + (k & 1) * 8192 + r0 * 16), "r"(rg < 2 ? 4096 : 8192) : "memory");
                    asm volatile("cp.async.bulk.commit_group;" ::: "memory");
                    asm volatile("cp.async.bulk.wait_group 0;" ::: "memory");
                    mbar_arrive(bb + B_OTE + (k & 1) * 16);
                    fence_async_global();
                    red_release(FLG(F_CV + rg), 1);
                    GT(true, 50 + k);
                }
            }
            __syncwarp();
        }
    }
    cluster_arrive(); cluster_wait();
    if (blockIdx.x == 0 && tid == 0) atomicAdd(&g_epoch, 1);
}
}

namespace ws {
constexpr int OP_SS = 17;
constexpr int P_RING = 0, P_AS = 131072, P_STG = P_AS + 2 * OP_SS * 2048, P_BAR = P_STG + 16384, OP_SMEM = P_BAR + 256;
constexpr int PB_FULL = 0, PB_EMPTY = 128, PB_SF = 144, PB_SE = 176;
static_assert(OP_SMEM <= 232448, "smem");
#define OP_MIX 1
__host__ __device__ constexpr bool op_ss(int j) { return OP_MIX ? (j % 4 == 0 || j == 63) : j < OP_SS; }
__host__ __device__ constexpr int op_idx(int j) { return OP_MIX ? (op_ss(j) ? (j + 1) / 4 : j - (j + 3) / 4) : (j < OP_SS ? j : j - OP_SS); }
__device__ __forceinline__ int op_rs_step(int i) { return OP_MIX ? i + i / 3 + 1 : OP_SS + i; }
__device__ __forceinline__ int op_ss_step(int i) { return OP_MIX ? (i < 16 ? 4 * i : 63) : i; }

__global__ void __launch_bounds__(384, 1) op_kernel(const bf16* __restrict__ Wo, const bf16* __restrict__ Bk, const bf16* __restrict__ Bv, const bf16* __restrict__ shiftk) {
    extern __shared__ __align__(1024) unsigned char smem_raw[];
    const int tid = threadIdx.x, warp = __shfl_sync(0xffffffffu, tid >> 5, 0), lane = tid & 31;
    const int nb = blockIdx.x % 5, ks = blockIdx.x / 5;
    const uint32_t sb = smem_u32(smem_raw), bb = sb + P_BAR;
    if (tid == 0) {
        if ((sb & 0xFFFFFFu) != 1024) __trap();
        for (int i = 0; i < 16; i++) mbar_init(bb + PB_FULL + i * 8, 1);
        for (int i = 0; i < 2; i++) mbar_init(bb + PB_EMPTY + i * 8, 2);
        for (int i = 0; i < 4; i++) { mbar_init(bb + PB_SF + i * 8, 4); mbar_init(bb + PB_SE + i * 8, 1); }
        asm volatile("fence.mbarrier_init.release.cluster;" ::: "memory");
    }
    GT(tid == 0, 8);
    __syncthreads();
    if (warp < 4) {
        asm volatile("setmaxnreg.dec.sync.aligned.u32 40;");
        if (warp == 0) {
            named_bar(3, 288);
            GT(lane == 0, 3);
            uint32_t it = 0;
            const int otgt = 8 * (ld_relaxed(&g_epoch) + 1);
#pragma unroll 1
            for (int q = 0; q < 2 * NT + 2; q++) {
                const int l = q & 1, n = (q >> 1) - l * (LAG + ONE_FENCE);
                if (n < 0 || n >= NSEG) continue;
                int guard = 0;
                while (ld_acquire(FLG(F_O + l * 64 + n) + ks) < otgt) { if (++guard > 4000000) __trap(); __nanosleep(OP_NS); }
                SC(blockIdx.x == 7 && lane == 0 && it == 127, 240);
                fence_async_global();
                SC(blockIdx.x == 7 && lane == 0 && it == 127, 241);
                mwait(bb + PB_EMPTY + (it & 1) * 8, ((it >> 1) & 1) ^ 1);
                if (lane < 8) {
                    const uint32_t fb = bb + PB_FULL + ((it & 1) * 8 + lane) * 8;
                    mbar_expect_tx(fb, 8192);
                    asm volatile("cp.async.bulk.shared::cluster.global.mbarrier::complete_tx::bytes [%0], [%1], %2, [%3];" ::"r"(sb + P_RING + (it & 1) * 65536 + lane * 8192),
                                 "l"(g_ot + (rslot(l, n) * 256 + (ks * 8 + lane) * 8) * 64), "r"(8192), "r"(fb) : "memory");
                }
                __syncwarp();
                SC(blockIdx.x == 7 && lane == 0 && it == 127, 242);
                it++;
            }
        } else if (warp == 3) {
#pragma unroll 1
            for (int rg = 1; rg < 4; rg++) {
#pragma unroll 1
                for (int u = rg * 640 + blockIdx.x; u < rg * 640 + 640; u += 20) u_half(Bk, Bv, shiftk, u, lane);
                __syncwarp();
                if (lane == 0) red_release(FLG(F_U + rg + 1), 1);
                GT(lane == 0 && rg, 4 + rg);
            }
        } else if (lane == 0) {
            const int cw = warp - 1;
            uint32_t it = 0;
#pragma unroll 1
            for (int q = 0; q < 2 * NT + 2; q++) {
                const int l = q & 1, n = (q >> 1) - l * (LAG + ONE_FENCE);
                if (n < 0 || n >= NSEG) continue;
                mwait(bb + PB_SF + cw * 8, it & 1);
                SC(blockIdx.x == 7 && cw == 0 && it == 127, 246);
                asm volatile("cp.reduce.async.bulk.global.shared::cta.bulk_group.add.f32 [%0], [%1], %2;" ::"l"(g_pt + (rslot(l, n) * 10 + nb * 2 + cw) * 512), "r"(sb + P_STG + cw * 8192), "r"(8192) : "memory");
                asm volatile("cp.async.bulk.commit_group;" ::: "memory");
                asm volatile("cp.async.bulk.wait_group.read 0;" ::: "memory");
                mbar_arrive(bb + PB_SE + cw * 8);
                asm volatile("cp.async.bulk.wait_group 0;" ::: "memory");
                SC(blockIdx.x == 7 && cw == 0 && it == 127, 247);
                fence_async_global();
                SC(blockIdx.x == 7 && cw == 0 && it == 127, 248);
                red_release(FLG(F_P + l * 64 + n), 1);
                SC(blockIdx.x == 7 && cw == 0 && it == 127, 249);
                GT(true, 330 + l * 64 + n);
                it++;
            }
        }
    } else {
        asm volatile("setmaxnreg.inc.sync.aligned.u32 232;");
        const int cw = (warp >> 2) - 1, w4 = warp & 3, t7 = tid & 127;
        uint32_t wa[64 - OP_SS][4];
        {
            const bf16* W = Wo + (size_t)ks * 1024 * DM + nb * 128 + cw * 64 + (t7 & 7) * 8;
            const uint32_t so = (t7 >> 3) * 128 + (((t7 & 7) ^ ((t7 >> 3) & 7)) << 4);
            const uint32_t stg = sb + P_RING + cw * 65536;
            const uint32_t la = stg + ((lane & 7) + (lane >> 4) * 8) * 128 + (((w4 * 2 + ((lane >> 3) & 1)) ^ (lane & 7)) << 4);
#pragma unroll 4
            for (int i = 0; i < 32; i++) cp_async16(stg + i * 2048 + so, W + (size_t)(op_rs_step(i) * 16 + (t7 >> 3)) * DM);
            cp_commit();
#pragma unroll 1
            for (int i = 0; i < OP_SS; i++) cp_async16(sb + P_AS + cw * OP_SS * 2048 + i * 2048 + so, W + (size_t)(op_ss_step(i) * 16 + (t7 >> 3)) * DM);
            cp_commit();
            cp_wait<1>();
            named_bar(1 + cw, 128);
#pragma unroll
            for (int j = 0; j < 32; j++) { const uint4 v = ldsm4t(la + j * 2048); wa[j][0] = v.x; wa[j][1] = v.y; wa[j][2] = v.z; wa[j][3] = v.w; }
            named_bar(1 + cw, 128);
#pragma unroll 1
            for (int i = 0; i < 32 - OP_SS; i++) cp_async16(stg + i * 2048 + so, W + (size_t)(op_rs_step(32 + i) * 16 + (t7 >> 3)) * DM);
            cp_commit();
            cp_wait<0>();
            named_bar(1 + cw, 128);
#pragma unroll
            for (int j = 0; j < 32 - OP_SS; j++) { const uint4 v = ldsm4t(la + j * 2048); wa[32 + j][0] = v.x; wa[32 + j][1] = v.y; wa[32 + j][2] = v.z; wa[32 + j][3] = v.w; }
            fence_async_smem();
            named_bar(3, 288);
        }
        const uint32_t ab = (1024 + P_AS + cw * OP_SS * 2048) >> 4;
        const uint32_t ea = sb + P_STG + cw * 8192 + (lane & 3) * 2048 + (((2 * w4) ^ (lane & 3)) << 5) + (lane >> 2) * 4;
#pragma unroll 1
        for (uint32_t it = 0; it < 2 * NSEG; it++) {
            float acc[16];
            const uint32_t fb = bb + PB_FULL + (it & 1) * 64, par = (it >> 1) & 1;
            const uint32_t ob = opq(((1024 + P_RING) >> 4) + (it & 1) * 4096);
            uint32_t ok = 0;
#pragma unroll
            for (int j = 0; j < 64; j++) {
                if ((j & 7) == 0) {
                    if (j) wg_commit();
                    if (!ok) mslow(fb + j, par);
                    ok = j < 56 ? mtest(fb + j + 8, par) : mtest(bb + PB_SE + cw * 8, (it & 1) ^ 1);
                    if (j == 0) { SC(blockIdx.x == 7 && tid == 128 && it == 127, 243); wg_fence(); }
                    if (j == 56) SC(blockIdx.x == 7 && tid == 128 && it == 127, 244);
                }
                const uint64_t db = mkdesc(ob + j * 64, 0x80000020u);
                if (j == 0) wg_n32t_sfirst(acc, mkdesc(ab, 0x40000040u), db);
                else if (op_ss(j)) wg_n32t_s(acc, mkdesc(ab + op_idx(j) * 128, 0x40000040u), db);
                else wg_n32t(acc, wa[op_idx(j)][0], wa[op_idx(j)][1], wa[op_idx(j)][2], wa[op_idx(j)][3], db);
            }
            wg_commit();
            if (!ok) mslow(bb + PB_SE + cw * 8, (it & 1) ^ 1);
            wg_wait<0>();
            SC(blockIdx.x == 7 && tid == 128 && it == 127, 245);
            if (t7 == 0) mbar_arrive(bb + PB_EMPTY + (it & 1) * 8);
#pragma unroll
            for (int i = 0; i < 16; i++) sts32((ea ^ ((i & 2) << 4)) + ((i >> 2) * 2 + (i & 1)) * 256, __float_as_uint(acc[i]));
            fence_async_smem();
            __syncwarp();
            if (lane == 0) mbar_arrive(bb + PB_SF + cw * 8);
        }
    }
}
}

namespace ws {
static bool usable() {
    static int ok = -1;
    if (ok < 0) {
        cudaFuncSetAttribute(head_kernel, cudaFuncAttributeMaxDynamicSharedMemorySize, HEAD_SMEM);
        cudaFuncSetAttribute(head_kernel, cudaFuncAttributeNonPortableClusterSizeAllowed, 1);
        cudaFuncSetAttribute(op_kernel, cudaFuncAttributeMaxDynamicSharedMemorySize, OP_SMEM);
        cudaLaunchConfig_t cfg = {};
        cfg.gridDim = dim3(NCL * 16); cfg.blockDim = dim3(512); cfg.dynamicSmemBytes = HEAD_SMEM;
        cudaLaunchAttribute at[1];
        at[0].id = cudaLaunchAttributeClusterDimension;
        at[0].val.clusterDim.x = 16; at[0].val.clusterDim.y = 1; at[0].val.clusterDim.z = 1;
        cfg.attrs = at; cfg.numAttrs = 1;
        int n = 0, nsm = 0;
        cudaDeviceGetAttribute(&nsm, cudaDevAttrMultiProcessorCount, 0);
        ok = cudaOccupancyMaxActiveClusters(&n, head_kernel, &cfg) == cudaSuccess && n >= NCL && nsm >= NCL * 16 + 20;
        (void)cudaGetLastError();
    }
    return ok > 0;
}
static void launch_all(void* const* d_in, void* d_out) {
    HeadArgs A;
    A.x = (const bf16*)d_in[0]; A.mem0 = (const bf16*)d_in[1]; A.Wq = (const bf16*)d_in[2]; A.Wk = (const bf16*)d_in[3]; A.Wv = (const bf16*)d_in[4]; A.Wo = (const bf16*)d_in[5];
    A.Bk = (const bf16*)d_in[8]; A.Bv = (const bf16*)d_in[9]; A.shiftk = (const bf16*)d_in[10]; A.ssmk = (const bf16*)d_in[11]; A.ssmD = (const bf16*)d_in[12];
    A.out = (bf16*)d_out; A.h_target = 32;
    cudaStream_t s = cudaStreamPerThread;
    {
        cudaLaunchConfig_t cfg = {};
        cfg.gridDim = dim3(NCL * 16); cfg.blockDim = dim3(512); cfg.dynamicSmemBytes = HEAD_SMEM; cfg.stream = s;
        cudaLaunchAttribute at[2];
        at[0].id = cudaLaunchAttributeClusterDimension;
        at[0].val.clusterDim.x = 16; at[0].val.clusterDim.y = 1; at[0].val.clusterDim.z = 1;
        at[1].id = cudaLaunchAttributeProgrammaticStreamSerialization;
        at[1].val.programmaticStreamSerializationAllowed = 1;
        cfg.attrs = at; cfg.numAttrs = 1;
        cudaLaunchKernelEx(&cfg, head_kernel, A);
    }
    {
        cudaLaunchConfig_t cfg = {};
        cfg.gridDim = dim3(20); cfg.blockDim = dim3(384); cfg.dynamicSmemBytes = OP_SMEM; cfg.stream = s;
        cudaLaunchAttribute at[1];
        at[0].id = cudaLaunchAttributeProgrammaticStreamSerialization;
        at[0].val.programmaticStreamSerializationAllowed = 1;
        cfg.attrs = at; cfg.numAttrs = 1;
        cudaLaunchKernelEx(&cfg, op_kernel, A.Wo, A.Bk, A.Bv, A.shiftk);
    }
}
}

#undef C_REV
#undef FLG
#undef GT
#undef H_NS
#undef LAGT
#undef LN0_AHEAD
#undef LN0_BATCH
#undef NO_X
#undef OBK
#undef ONE_FENCE
#undef OP_MIX
#undef OP_NS
#undef P1A
#undef P1C
#undef POST_NS
#undef REG_G
#undef REG_T
#undef REG_X
#undef RING
#undef SC
#undef SD
#undef TG_STEPS
#undef TS
#undef TV
#undef UNI
#undef WFLY
#undef WR
#undef WTA
#undef XD
namespace ni {

constexpr int S_LEN = 2048;
constexpr int DM = 640;
constexpr int NH = 32;
constexpr int DH = 128;
constexpr int HD = NH * DH;
constexpr int MEMR = 8;
constexpr int SEG = 32;
constexpr int NSEG = S_LEN / SEG;

__device__ __forceinline__ float bf2f(bf16 v) { return __bfloat162float(v); }
__device__ __forceinline__ bf16 f2bf(float v) { return __float2bfloat16_rn(v); }
__device__ __forceinline__ float rbf(float v) { return __bfloat162float(__float2bfloat16_rn(v)); }
__device__ __forceinline__ uint32_t pack2(float a, float b) {
    __nv_bfloat162 t = __floats2bfloat162_rn(a, b);
    return *reinterpret_cast<uint32_t*>(&t);
}
__device__ __forceinline__ uint32_t smem_u32(const void* p) { return (uint32_t)__cvta_generic_to_shared(p); }
__device__ __forceinline__ void ldsm_x4(uint32_t& r0, uint32_t& r1, uint32_t& r2, uint32_t& r3, uint32_t addr) {
    asm volatile("ldmatrix.sync.aligned.m8n8.x4.shared.b16 {%0,%1,%2,%3}, [%4];"
                 : "=r"(r0), "=r"(r1), "=r"(r2), "=r"(r3) : "r"(addr));
}
__device__ __forceinline__ void ldsm_x2(uint32_t& r0, uint32_t& r1, uint32_t addr) {
    asm volatile("ldmatrix.sync.aligned.m8n8.x2.shared.b16 {%0,%1}, [%2];" : "=r"(r0), "=r"(r1) : "r"(addr));
}
__device__ __forceinline__ void ldsm_x4_t(uint32_t& r0, uint32_t& r1, uint32_t& r2, uint32_t& r3, uint32_t addr) {
    asm volatile("ldmatrix.sync.aligned.m8n8.x4.trans.shared.b16 {%0,%1,%2,%3}, [%4];"
                 : "=r"(r0), "=r"(r1), "=r"(r2), "=r"(r3) : "r"(addr));
}
__device__ __forceinline__ void mma16816(float* c, uint32_t a0, uint32_t a1, uint32_t a2, uint32_t a3,
                                         uint32_t b0, uint32_t b1) {
    asm("mma.sync.aligned.m16n8k16.row.col.f32.bf16.bf16.f32 {%0,%1,%2,%3}, {%4,%5,%6,%7}, {%8,%9}, {%0,%1,%2,%3};"
        : "+f"(c[0]), "+f"(c[1]), "+f"(c[2]), "+f"(c[3])
        : "r"(a0), "r"(a1), "r"(a2), "r"(a3), "r"(b0), "r"(b1));
}
__device__ __forceinline__ void cp_async16(uint32_t dst, const void* src) {
    asm volatile("cp.async.cg.shared.global [%0], [%1], 16;" ::"r"(dst), "l"(src));
}
__device__ __forceinline__ void cp_commit() { asm volatile("cp.async.commit_group;"); }
template <int N> __device__ __forceinline__ void cp_wait() { asm volatile("cp.async.wait_group %0;" ::"n"(N)); }
__device__ __forceinline__ uint4 ld_relaxed_v4(const void* p) {
    uint4 v;
    asm volatile("ld.relaxed.gpu.global.v4.u32 {%0,%1,%2,%3}, [%4];"
                 : "=r"(v.x), "=r"(v.y), "=r"(v.z), "=r"(v.w) : "l"(p) : "memory");
    return v;
}
__device__ __forceinline__ void st_relaxed_v4(void* p, uint32_t a, uint32_t b, uint32_t c, uint32_t d) {
    asm volatile("st.relaxed.gpu.global.v4.u32 [%0], {%1,%2,%3,%4};" ::"l"(p), "r"(a), "r"(b), "r"(c), "r"(d) : "memory");
}
__device__ __forceinline__ int ld_acquire(const int* p) {
    int v;
    asm volatile("ld.acquire.gpu.global.u32 %0, [%1];" : "=r"(v) : "l"(p) : "memory");
    return v;
}
__device__ __forceinline__ void mbar_init(uint32_t bar, int count) {
    asm volatile("mbarrier.init.shared::cta.b64 [%0], %1;" ::"r"(bar), "r"(count));
}
__device__ __forceinline__ void mbar_expect_tx(uint32_t bar, uint32_t bytes) {
    asm volatile("mbarrier.arrive.expect_tx.shared::cta.b64 _, [%0], %1;" ::"r"(bar), "r"(bytes) : "memory");
}
__device__ __forceinline__ void mbar_arrive(uint32_t bar) {
    asm volatile("mbarrier.arrive.shared::cta.b64 _, [%0];" ::"r"(bar) : "memory");
}
constexpr int SPIN_LIMIT = 4000000;
__device__ __forceinline__ void mbar_wait_spin(uint32_t bar, uint32_t parity) {
    uint32_t ok = 0;
    int guard = 0;
    while (!ok && ++guard < SPIN_LIMIT) {
        asm volatile(
            "{\n.reg .pred P1;\n"
            "mbarrier.try_wait.parity.shared::cta.b64 P1, [%1], %2;\n"
            "selp.u32 %0, 1, 0, P1;\n}\n"
            : "=r"(ok) : "r"(bar), "r"(parity) : "memory");
    }
}
__device__ __forceinline__ uint32_t mapa(uint32_t addr, uint32_t rank) {
    uint32_t r;
    asm volatile("mapa.shared::cluster.u32 %0, %1, %2;" : "=r"(r) : "r"(addr), "r"(rank));
    return r;
}
__device__ __forceinline__ void st_async_u32(uint32_t addr, uint32_t v, uint32_t bar) {
    asm volatile("st.async.weak.shared::cluster.mbarrier::complete_tx::bytes.b32 [%0], %1, [%2];" ::"r"(addr), "r"(v), "r"(bar) : "memory");
}
__device__ __forceinline__ void st_async_v2(uint32_t addr, uint32_t a, uint32_t b, uint32_t bar) {
    asm volatile("st.async.weak.shared::cluster.mbarrier::complete_tx::bytes.v2.b32 [%0], {%1,%2}, [%3];" ::"r"(addr), "r"(a), "r"(b), "r"(bar) : "memory");
}
__device__ __forceinline__ void cluster_sync_all() {
    asm volatile("barrier.cluster.arrive.release.aligned;\nbarrier.cluster.wait.acquire.aligned;" ::: "memory");
}
__device__ __forceinline__ void named_bar(int id, int n) { asm volatile("bar.sync %0, %1;" ::"r"(id), "r"(n) : "memory"); }

}

namespace ni {
#define CHAIN_LAG 16
constexpr int CL = 16;
constexpr int OWN = DM / CL;
constexpr int NSRC = CL / 2;
constexpr int NCLU = 64 / CL;
constexpr int CSEG = 4;
constexpr int NCHK = NSEG / CSEG;
constexpr int LAG = CHAIN_LAG;
constexpr int NTICK = NSEG + LAG;

constexpr int F_KV = 0, F_MEM = 32, F_H = 64, F_OP = 96, F_CONV = 128, F_U = 130, F_PROG = 132, F_ZERO = 133, F_CNT = 136;
constexpr int NFLAG = 192;
__device__ int g_flags[NFLAG * 32];
#define FLG(i) (g_flags + (i) * 32)
constexpr int CHAIN_THREADS = 384;
__device__ bf16 g_Y[S_LEN * DM];
__device__ bf16 g_U[DM * S_LEN];
__device__ bf16 g_h[2][S_LEN * DM];
__device__ bf16 g_x[S_LEN * DM];
__device__ bf16 g_kv[2][S_LEN * HD];
#define PRING 4
constexpr int PROWS = PRING * 128, PG = 4;
__device__ bf16 g_part[2 * PROWS * PG * DM];
__device__ uint4 g_kvf[2 * NSEG * NH * 256];
__device__ uint32_t g_xc[2 * 2 * CL * NCLU * 8 * OWN];

#define TVAL(i, v)
#define TSTAMP(i)

#define NRQ 36
#define NRW 8
#define PDQ 4
#define PDW1 0
#define PROBE 2
#define PDW 6
constexpr int NSQ = 60 - NRQ, NSW = 20 - NRW;
__host__ __device__ constexpr bool q_smem(int i) { return ((i + 1) * NSQ) / 60 != (i * NSQ) / 60; }
__host__ __device__ constexpr int q_slot(int i) { return q_smem(i) ? (i * NSQ) / 60 : i - (i * NSQ) / 60; }
__host__ __device__ constexpr int w_tile(int i) { return i < 8 ? ((i & 1) ? 0 : 2) : (i < 16 ? (i & 1) : 1); }
__host__ __device__ constexpr int w_k(int i) { return i < 8 ? i / 2 : (i < 16 ? ((i & 1) ? (i - 8) / 2 : 4 + (i - 8) / 2) : i - 12); }
__host__ __device__ constexpr int w_acc(int i) { return (i >= 16 && (i & 1)) ? 3 : w_tile(i); }
__host__ __device__ constexpr bool w_smem(int i) { return i < PDW || NRW == 0 || ((i - PDW + 1) * NRW) / (20 - PDW) == ((i - PDW) * NRW) / (20 - PDW); }
__host__ __device__ constexpr int w_slot(int i) { return i < PDW ? i : (w_smem(i) ? i - ((i - PDW) * NRW) / (20 - PDW) : ((i - PDW) * NRW) / (20 - PDW)); }
constexpr int O_WQ = 0, O_WW = NSQ * 4096, O_REST = (NSQ + NSW) * 4096;
constexpr int C_TOK = 0, C_MEM = 12288, C_RED = C_MEM + 10240, C_Q = C_RED + 6144, C_K = C_Q + 2048, C_V = C_K + 2048, C_S = C_V + 4096,
              C_BAR = C_S + 3072, C_SIZE = 40960;
constexpr int S_BYTES = 3072 + 4096;
constexpr int B_S = 64, B_R = 72, B_T = 96, B_F = 104;
static_assert(C_BAR + 112 <= C_SIZE, "chain block");
constexpr int O_STB = O_REST - 61440;
static_assert((45 * NSQ) / 60 * 4096 <= O_STB && NSQ <= 32, "staging");
struct ChainSmem { unsigned char b[O_REST + 81920 + 1536]; };
static_assert(sizeof(ChainSmem) <= 232448, "smem");

struct ChainArgs {
    CUtensorMap tk[2], tv[2];
    const bf16 *x, *mem0, *Wq, *Wk, *Wv, *Wo;
    int kv_target;
};
__device__ __forceinline__ uint32_t movmat(uint32_t v) {
    uint32_t r;
    asm volatile("movmatrix.sync.aligned.m8n8.trans.b16 %0, %1;" : "=r"(r) : "r"(v));
    return r;
}
__device__ __forceinline__ void named_arrive(int id, int n) { asm volatile("bar.arrive %0, %1;" ::"r"(id), "r"(n) : "memory"); }
__device__ __forceinline__ void red_release(int* p, int v) { asm volatile("red.release.gpu.global.add.u32 [%0], %1;" ::"l"(p), "r"(v) : "memory"); }

#define CVT(i)
__device__ __forceinline__ uint4 lds128(uint32_t a) {
    uint4 v;
    asm volatile("ld.shared.v4.u32 {%0,%1,%2,%3}, [%4];" : "=r"(v.x), "=r"(v.y), "=r"(v.z), "=r"(v.w) : "r"(a));
    return v;
}
__device__ __forceinline__ uint2 lds64(uint32_t a) {
    uint2 v;
    asm volatile("ld.shared.v2.u32 {%0,%1}, [%2];" : "=r"(v.x), "=r"(v.y) : "r"(a));
    return v;
}
__device__ __forceinline__ uint32_t lds32(uint32_t a) {
    uint32_t v;
    asm volatile("ld.shared.u32 %0, [%1];" : "=r"(v) : "r"(a));
    return v;
}
__device__ __forceinline__ void sts64(uint32_t a, uint32_t x, uint32_t y) { asm volatile("st.shared.v2.u32 [%0], {%1,%2};" ::"r"(a), "r"(x), "r"(y) : "memory"); }
__device__ __forceinline__ void sts128(uint32_t a, uint32_t x, uint32_t y, uint32_t z, uint32_t w) {
    asm volatile("st.shared.v4.u32 [%0], {%1,%2,%3,%4};" ::"r"(a), "r"(x), "r"(y), "r"(z), "r"(w) : "memory");
}
__device__ __forceinline__ void st_async_v4(uint32_t addr, uint32_t a, uint32_t b, uint32_t c, uint32_t d, uint32_t bar) {
    asm volatile("st.async.weak.shared::cluster.mbarrier::complete_tx::bytes.v4.b32 [%0], {%1,%2,%3,%4}, [%5];" ::"r"(addr), "r"(a), "r"(b), "r"(c), "r"(d), "r"(bar) : "memory");
}
__device__ __forceinline__ uint2 ld_relaxed_v2(const void* p) {
    uint2 v;
    asm volatile("ld.relaxed.gpu.global.v2.u32 {%0,%1}, [%2];" : "=r"(v.x), "=r"(v.y) : "l"(p) : "memory");
    return v;
}
__device__ __forceinline__ void st_relaxed_v2(void* p, uint32_t a, uint32_t b) {
    asm volatile("st.relaxed.gpu.global.v2.u32 [%0], {%1,%2};" ::"l"(p), "r"(a), "r"(b) : "memory");
}
__device__ __forceinline__ float blo(uint32_t v) { return __uint_as_float(v << 16); }
__device__ __forceinline__ float bhi(uint32_t v) { return __uint_as_float(v & 0xffff0000u); }
__device__ __forceinline__ uint32_t badd2(uint32_t a, uint32_t b) {
    __nv_bfloat162 r = __hadd2(*reinterpret_cast<__nv_bfloat162*>(&a), *reinterpret_cast<__nv_bfloat162*>(&b));
    return *reinterpret_cast<uint32_t*>(&r);
}
__device__ __forceinline__ void mmau(float* c, const uint4& a, uint32_t b0, uint32_t b1) { mma16816(c, a.x, a.y, a.z, a.w, b0, b1); }

__device__ __forceinline__ void stsm_x4_t(uint32_t a, uint32_t r0, uint32_t r1, uint32_t r2, uint32_t r3) {
    asm volatile("stmatrix.sync.aligned.m8n8.x4.trans.shared.b16 [%0], {%1,%2,%3,%4};" ::"r"(a), "r"(r0), "r"(r1), "r"(r2), "r"(r3) : "memory");
}
__device__ __forceinline__ uint4 ldsm4(uint32_t a) { uint4 v; ldsm_x4(v.x, v.y, v.z, v.w, a); return v; }
__device__ __forceinline__ float ex2f(float x) { float y; asm("ex2.approx.ftz.f32 %0, %1;" : "=f"(y) : "f"(x)); return y; }
__device__ __forceinline__ float rcpf(float x) { float y; asm("rcp.approx.ftz.f32 %0, %1;" : "=f"(y) : "f"(x)); return y; }
#define XD 300
__device__ __forceinline__ void xdelay() {
    uint32_t t0, t1;
    asm volatile("mov.u32 %0, %clock;" : "=r"(t0));
    do { asm volatile("mov.u32 %0, %clock;" : "=r"(t1)); } while (t1 - t0 < XD);
}
template <int V> struct IC { static constexpr int value = V; };
__device__ __forceinline__ uint32_t opq(uint32_t x) { uint32_t y; asm volatile("mov.u32 %0, %1;" : "=r"(y) : "r"(x)); return y; }
#define UNI(x) __shfl_sync(0xffffffffu, (uint32_t)(x), 0)
__device__ __forceinline__ uint32_t mtest(uint32_t bar, uint32_t parity) {
    uint32_t ok;
    asm volatile("{\n.reg .pred P1;\nmbarrier.test_wait.parity.shared::cta.b64 P1, [%1], %2;\nselp.u32 %0, 1, 0, P1;\n}\n" : "=r"(ok) : "r"(bar), "r"(parity) : "memory");
    return ok;
}
__device__ __forceinline__ void mwait(uint32_t bar, uint32_t parity) {
    asm volatile(
        "{\n.reg .pred P1;\n.reg .u32 cnt;\n"
        "mbarrier.try_wait.parity.shared::cta.b64 P1, [%0], %1;\n"
        "@P1 bra DONE;\n"
        "mov.u32 cnt, 0;\n"
        "LAB_WAIT:\n"
        "mbarrier.try_wait.parity.shared::cta.b64 P1, [%0], %1;\n"
        "@P1 bra DONE;\n"
        "add.u32 cnt, cnt, 1;\n"
        "setp.lt.u32 P1, cnt, 4000000;\n"
        "@P1 bra LAB_WAIT;\n"
        "DONE:\n}\n" ::"r"(bar), "r"(parity) : "memory");
}

__global__ void __launch_bounds__(CHAIN_THREADS, 1) chain_kernel(const __grid_constant__ ChainArgs A) {
    extern __shared__ __align__(1024) unsigned char smem_raw[];
    const int tid = threadIdx.x, warp = __shfl_sync(0xffffffffu, tid >> 5, 0), lane = tid & 31;
    const int cq = blockIdx.x / CL, r = blockIdx.x % CL;
    const int h = cq * NSRC + (r >> 1), hf = r & 1;
    const uint32_t sb = smem_u32(smem_raw);
    asm volatile("griddepcontrol.launch_dependents;");
    CVT(0);
    if (warp == 8) {
        if (lane < 8) asm volatile("cp.async.bulk.prefetch.L2.global [%0], %1;" ::"l"(A.x + (size_t)(blockIdx.x * 8 + lane) * 2560), "r"(5120) : "memory");
        asm volatile("cp.async.bulk.prefetch.L2.global [%0], %1;" ::"l"((lane < 16 ? A.Wk : A.Wv) + (size_t)(blockIdx.x * 16 + (lane & 15)) * 2560), "r"(5120) : "memory");
        asm volatile("cp.async.bulk.prefetch.L2.global [%0], %1;" ::"l"((lane < 16 ? A.Wq : A.Wo) + (size_t)(blockIdx.x * 16 + (lane & 15)) * 2560), "r"(5120) : "memory");
    }
    CVT(1);
    if (warp < 8) {
        asm volatile("setmaxnreg.inc.sync.aligned.u32 232;");
        const int j = warp & 3, kh = warp >> 2;
        uint4 wr[NRQ + NRW];
        {
            auto load_round = [&](int gi) {
                const uint32_t buf = sb + ((gi & 1) ? O_STB : O_REST);
#pragma unroll
                for (int it = 0; it < 15; it++) {
                    const int i = tid + it * 256;
                    const int pc = i / 1920, rem = i % 1920, row = rem / 24, ch = rem % 24;
                    const int mat = ch >> 3, pi = ((r >> 1) - (2 * gi + pc)) & 7;
                    const bf16* W = mat == 0 ? A.Wq : (mat == 1 ? A.Wk : A.Wv);
                    cp_async16(buf + pc * 30720 + row * 384 + ((ch ^ (row & 7)) << 4), W + (size_t)(pi * 80 + row) * HD + h * DH + hf * 64 + (ch & 7) * 8);
                }
                cp_commit();
            };
            load_round(0);
            load_round(1);
#pragma unroll
            for (int gi = 0; gi < 4; gi++) {
                cp_wait<1>();
                named_bar(1, 256);
                const uint32_t pb = sb + ((gi & 1) ? O_STB : O_REST) + kh * 30720;
                uint4 tmp[8];
#pragma unroll
                for (int u = 0; u < 5; u++)
#pragma unroll
                    for (int tt = 0; tt < 3; tt++) {
                        const int row = u * 16 + (lane & 7) + (lane >> 4) * 8;
                        const int ch = tt * 8 + j * 2 + ((lane >> 3) & 1);
                        uint4 v;
                        ldsm_x4_t(v.x, v.y, v.z, v.w, pb + row * 384 + ((ch ^ (row & 7)) << 4));
                        const int i = (gi * 5 + u) * 3 + tt;
                        if (q_smem(i)) {
                            if (gi == 3) tmp[q_slot(i) & 7] = v;
                            else sts128(sb + O_WQ + q_slot(i) * 4096 + tid * 16, v.x, v.y, v.z, v.w);
                        } else wr[q_slot(i)] = v;
                    }
                named_bar(1, 256);
                if (gi == 3) {
#pragma unroll
                    for (int i = 45; i < 60; i++)
                        if (q_smem(i)) { const uint4 v = tmp[q_slot(i) & 7]; sts128(sb + O_WQ + q_slot(i) * 4096 + tid * 16, v.x, v.y, v.z, v.w); }
                }
                if (gi < 2) load_round(gi + 2);
                else if (gi == 2) {
                    for (int i = tid; i < 128 * 40; i += 256) {
                        const int row = i / 40, ch = i % 40;
                        cp_async16(sb + O_REST + row * 640 + ((ch ^ (row & 7)) << 4), A.Wo + ((size_t)h * DH + row) * DM + hf * 320 + ch * 8);
                    }
                    cp_commit();
                }
            }
            cp_wait<0>();
            named_bar(1, 256);
#pragma unroll
            for (int i = 0; i < 20; i++) {
                const int tl = w_tile(i), et = (w_k(i) + 4 * (warp & 1)) & 7;
                const int row = et * 16 + (lane & 7) + (lane >> 4) * 8;
                const int ch = (warp >> 1) * 10 + (tl == 2 ? 8 : (warp & 1) * 4 + tl * 2) + ((lane >> 3) & 1);
                uint4 v;
                ldsm_x4_t(v.x, v.y, v.z, v.w, sb + O_REST + row * 640 + ((ch ^ (row & 7)) << 4));
                if (w_smem(i)) sts128(sb + O_WW + w_slot(i) * 4096 + tid * 16, v.x, v.y, v.z, v.w);
                else wr[NRQ + w_slot(i)] = v;
            }
            named_bar(1, 256);
            for (int i = tid; i < 2560; i += 256) {
                const int ks = i >> 6, ln = (i >> 1) & 31, wd = i & 1;
                const int pi = ((r >> 1) - ks / 5) & 7;
                const uint32_t v = *reinterpret_cast<const uint32_t*>(A.mem0 + (ln >> 2) * DM + pi * 80 + (ks % 5) * 16 + wd * 8 + (ln & 3) * 2);
                const int o = ks % 5 == 4 ? ks * 256 + wd * 128 + ln * 4 : i * 4;
                asm volatile("st.shared.u32 [%0], %1;" ::"r"(sb + O_REST + C_MEM + o), "r"(v) : "memory");
                asm volatile("st.shared.u32 [%0], %1;" ::"r"(sb + O_REST + C_SIZE + C_MEM + o), "r"(v) : "memory");
            }
            if (tid < 2) {
                const uint32_t bb = sb + O_REST + tid * C_SIZE + C_BAR;
                for (int i = 0; i < 13; i++) mbar_init(bb + i * 8, 1);
                mbar_init(bb + B_F, 4);
                asm volatile("fence.mbarrier_init.release.cluster;" ::: "memory");
                mbar_expect_tx(bb + B_S, S_BYTES);
                for (int i = 0; i < 3; i++) mbar_expect_tx(bb + B_R + i * 8, 2048);
            }
            asm volatile("fence.proxy.async;" ::: "memory");
        }
        CVT(2);
        cluster_sync_all();
        const uint32_t wq_a = sb + O_WQ + tid * 16;
        const uint32_t cb0 = sb + O_REST;
        const uint32_t qk_a = cb0 + j * 512 + (lane & 7) * 16 + (lane < 16 ? C_Q + (lane >> 3) * 256 + kh * 128 : C_K + kh * 256 + ((lane >> 3) & 1) * 128);
        const uint32_t pd = UNI(mapa(sb, (uint32_t)(r ^ 1)) - sb), sd = UNI(mapa(sb, (uint32_t)r) - sb);
        const uint32_t od = UNI(mapa(sb, (uint32_t)(hf * 8 + warp)) - sb);
        const uint32_t oe = UNI(mapa(sb, (uint32_t)(hf * 8 + (warp & 6))) - sb), oo = UNI(mapa(sb, (uint32_t)(hf * 8 + (warp | 1))) - sb);
        const uint32_t u_mem = UNI(cb0 + C_MEM + kh * 1280), u_bm = UNI(cb0 + C_BAR + kh * 8);
        const uint32_t u_v = UNI(cb0 + C_V + hf * 2048 + j * 512 + kh * 256);
        const uint32_t u_ra = UNI(cb0 + C_RED + (r >> 1) * 256);
        const uint32_t u_ob0 = UNI(cb0 + C_Q + (warp & 1) * 1024), u_ob1 = UNI(cb0 + C_Q + ((warp & 1) ^ 1) * 1024);
        const uint32_t u_role = UNI(warp < 3 ? cb0 + C_S + hf * 1536 + warp * 512 : cb0 + C_V + j * 1024);
        const uint32_t t_tok = cb0 + C_TOK + ((lane & 7) + (lane >> 4) * 8) * 128 +
                               (warp < 3 ? warp * 2048 + ((((lane >> 3) & 1) ^ (lane & 7)) << 4) : 4096 + (j >> 1) * 4096 + ((((j & 1) * 4 + ((lane >> 3) & 1)) ^ (lane & 7)) << 4));
        uint4 qb[PDQ];
#pragma unroll
        for (int s = 0; s < PDQ; s++) qb[s] = lds128(wq_a + s * 4096);
        auto tick = [&](auto cc, const int n) {
            constexpr int c = decltype(cc)::value;
            constexpr uint32_t CO = c * C_SIZE;
            const uint32_t cb = cb0 + CO;
            const uint32_t par = (uint32_t)(n & 1);
            const uint32_t l4 = opq(lane * 4), l8 = l4 * 2, l16 = l4 * 4;
            float acc[3][4];
#pragma unroll
            for (int a = 0; a < 3; a++)
#pragma unroll
                for (int i = 0; i < 4; i++) acc[a][i] = 0.f;
            {
                const uint32_t mb = u_mem + CO + l8;
                uint2 bf[3];
                uint32_t ok = 1;
                auto ldb = [&](int ks) {
                    if (ks == 0) mwait(u_bm + CO, par ^ 1);
                    else if (ks % 5 == 0) { if (!ok) mwait(u_bm + CO + (ks / 5) * 16, par ^ 1); }
                    if (ks % 5 == PROBE && ks < 15) ok = mtest(u_bm + CO + (ks / 5 + 1) * 16, par ^ 1);
                    if (ks % 5 == 4) {
                        bf[ks % 3].x = lds32(u_mem + CO + l4 + (ks / 5) * 2560 + 1024);
                        bf[ks % 3].y = lds32(u_mem + CO + l4 + (ks / 5) * 2560 + 1152);
                    } else bf[ks % 3] = lds64(mb + (ks / 5) * 2560 + (ks % 5) * 256);
                };
                ldb(0);
                TSTAMP(c * 12 + 0);
                ldb(1);
#pragma unroll
                for (int ks = 0; ks < 20; ks++) {
                    if (ks + 2 < 20) ldb(ks + 2);
#pragma unroll
                    for (int tt = 0; tt < 3; tt++) {
                        const int i = ks * 3 + tt;
                        if (q_smem(i)) {
                            const int s = q_slot(i);
                            mmau(acc[tt], qb[s % PDQ], bf[ks % 3].x, bf[ks % 3].y);
                            if (s + PDQ < NSQ) qb[s % PDQ] = lds128(wq_a + (s + PDQ) * 4096);
                        } else mmau(acc[tt], wr[q_slot(i)], bf[ks % 3].x, bf[ks % 3].y);
                    }
                }
            }
            TSTAMP(c * 12 + 1);
            stsm_x4_t(opq(qk_a) + CO, pack2(acc[0][0], acc[0][1]), pack2(acc[0][2], acc[0][3]), pack2(acc[1][0], acc[1][1]), pack2(acc[1][2], acc[1][3]));
            const uint32_t v0 = pack2(acc[2][0], acc[2][1]), v1 = pack2(acc[2][2], acc[2][3]);
            if (n == NSEG - 1) {
                sts64(u_v + CO + l8, v0, v1);
                named_bar(1, 256);
                if (kh == 1 && lane == 0) mbar_arrive(cb + C_BAR + B_F);
#pragma unroll
                for (int s = 0; s < PDQ; s++) qb[s] = lds128(wq_a + s * 4096);
                return;
            }
            named_arrive(1, 384);
            st_async_v2(u_v + CO + l8 + pd, v0, v1, cb + C_BAR + B_S + pd);
            st_async_v2(u_v + CO + l8 + sd, v0, v1, cb + C_BAR + B_S + sd);
            uint4 wb[PDW];
            const uint32_t ww_a = wq_a + (O_WW - O_WQ);
            if (warp < 3) {
                uint4 kb[4];
                const uint32_t t_tk = opq(t_tok);
                mwait(cb + C_BAR + B_T, par);
#pragma unroll
                for (int i = 0; i < 4; i++) kb[i] = ldsm4((t_tk ^ (i << 5)) + CO);
                named_bar(1, 384);
                uint4 qa[4];
#pragma unroll
                for (int i = 0; i < 4; i++) qa[i] = ldsm4(cb + l16 + C_Q + i * 512);
                if (warp == 2) {
#pragma unroll
                    for (int i = 0; i < 4; i++) kb[i] = ldsm4(cb + l16 + C_K + i * 512);
                }
                float s0[4][4], s1[4][4];
#pragma unroll
                for (int i = 0; i < 4; i++) {
#pragma unroll
                    for (int q = 0; q < 4; q++) s0[i][q] = s1[i][q] = 0.f;
                    mmau(s0[i], qa[i], kb[i].x, kb[i].y);
                    mmau(s1[i], qa[i], kb[i].z, kb[i].w);
                }
                const float a0 = ((s0[0][0] + s0[0][2]) + (s0[1][0] + s0[1][2])) + ((s0[2][0] + s0[2][2]) + (s0[3][0] + s0[3][2]));
                const float a1 = ((s0[0][1] + s0[0][3]) + (s0[1][1] + s0[1][3])) + ((s0[2][1] + s0[2][3]) + (s0[3][1] + s0[3][3]));
                const float b0 = ((s1[0][0] + s1[0][2]) + (s1[1][0] + s1[1][2])) + ((s1[2][0] + s1[2][2]) + (s1[3][0] + s1[3][2]));
                const float b1 = ((s1[0][1] + s1[0][3]) + (s1[1][1] + s1[1][3])) + ((s1[2][1] + s1[2][3]) + (s1[3][1] + s1[3][3]));
                const uint32_t so = u_role + CO + l16, bs = cb + C_BAR + B_S;
                const float c0 = warp == 2 ? a0 + b0 : a0, c1 = warp == 2 ? a1 + b1 : a1;
                st_async_v4(so + pd, __float_as_uint(c0), __float_as_uint(c1), __float_as_uint(b0), __float_as_uint(b1), bs + pd);
                st_async_v4(so + sd, __float_as_uint(c0), __float_as_uint(c1), __float_as_uint(b0), __float_as_uint(b1), bs + sd);
                TSTAMP(c * 12 + 2);
#pragma unroll
                for (int s = 0; s < PDW; s++) wb[s] = lds128(ww_a + s * 4096);
            } else if (warp == 3) {
                named_bar(1, 384);
                if (lane < 8) mbar_expect_tx(cb + C_BAR + l8, 1280);
#pragma unroll
                for (int s = 0; s < PDW; s++) wb[s] = lds128(ww_a + s * 4096);
            } else {
                mwait(cb + C_BAR + B_T, par);
                uint4 va[2][2];
                const uint32_t t_tk = opq(t_tok);
#pragma unroll
                for (int e = 0; e < 2; e++)
#pragma unroll
                    for (int k = 0; k < 2; k++)
                        ldsm_x4_t(va[e][k].x, va[e][k].y, va[e][k].z, va[e][k].w, (t_tk ^ (e << 5)) + CO + k * 2048);
#pragma unroll
                for (int s2 = 0; s2 < PDW1; s2++) wb[s2] = lds128(ww_a + s2 * 4096);
                mwait(cb + C_BAR + B_S, par);
                TSTAMP(c * 12 + 3);
                const uint32_t xa = cb + l16 + C_S;
                const uint4 x0 = lds128(xa), y0 = lds128(xa + 1536), x1 = lds128(xa + 512), y1 = lds128(xa + 512 + 1536);
                const uint2 x2 = lds64(xa + 1024), y2 = lds64(xa + 1024 + 1536);
                const uint32_t fv = u_role + CO + l8;
                const float cs = 0.08838834764831845f * 1.4426950408889634f;
                float s[10];
                s[8] = __uint_as_float(x2.x) + __uint_as_float(y2.x); s[9] = __uint_as_float(x2.y) + __uint_as_float(y2.y);
                s[0] = __uint_as_float(x0.x) + __uint_as_float(y0.x); s[1] = __uint_as_float(x0.y) + __uint_as_float(y0.y);
                s[2] = __uint_as_float(x0.z) + __uint_as_float(y0.z); s[3] = __uint_as_float(x0.w) + __uint_as_float(y0.w);
                s[4] = __uint_as_float(x1.x) + __uint_as_float(y1.x); s[5] = __uint_as_float(x1.y) + __uint_as_float(y1.y);
                s[6] = __uint_as_float(x1.z) + __uint_as_float(y1.z); s[7] = __uint_as_float(x1.w) + __uint_as_float(y1.w);
                float mx = fmaxf(fmaxf(fmaxf(s[0], s[1]), fmaxf(s[2], s[3])), fmaxf(fmaxf(fmaxf(s[4], s[5]), fmaxf(s[6], s[7])), fmaxf(s[8], s[9])));
                const float m1 = __shfl_xor_sync(0xffffffffu, mx, 1), m2 = __shfl_xor_sync(0xffffffffu, mx, 2), m3 = __shfl_xor_sync(0xffffffffu, mx, 3);
                const uint2 vm00 = lds64(fv), vm01 = lds64(fv + 256), vm10 = lds64(fv + 512), vm11 = lds64(fv + 768);
                const uint4 vm0 = make_uint4(vm00.x, vm00.y, vm01.x, vm01.y), vm1 = make_uint4(vm10.x, vm10.y, vm11.x, vm11.y);
                mx = fmaxf(fmaxf(mx, m1), fmaxf(m2, m3)) * -cs;
                uint32_t pb[5];
                pb[4] = pack2(ex2f(fmaf(s[8], cs, mx)), ex2f(fmaf(s[9], cs, mx)));
#pragma unroll
                for (int i = 0; i < 4; i++) pb[i] = pack2(ex2f(fmaf(s[2 * i], cs, mx)), ex2f(fmaf(s[2 * i + 1], cs, mx)));
                float o[3][4];
#pragma unroll
                for (int i = 0; i < 4; i++) { o[0][i] = o[1][i] = o[2][i] = 0.f; }
                const uint32_t one2 = 0x3F803F80u;
                mma16816(o[2], one2, one2, one2, one2, pb[4], 0u);
                mmau(o[0], vm0, pb[4], pb[4]);
                mmau(o[1], vm1, pb[4], pb[4]);
                mma16816(o[2], one2, one2, one2, one2, pb[0], pb[1]);
                mmau(o[0], va[0][0], pb[0], pb[1]);
                mmau(o[1], va[1][0], pb[0], pb[1]);
                mma16816(o[2], one2, one2, one2, one2, pb[2], pb[3]);
                mmau(o[0], va[0][1], pb[2], pb[3]);
                mmau(o[1], va[1][1], pb[2], pb[3]);
                const float r0 = rcpf(o[2][0]), r1 = rcpf(o[2][1]);
                stsm_x4_t(cb + l16 + C_Q + j * 512, pack2(o[0][0] * r0, o[0][1] * r1), pack2(o[0][2] * r0, o[0][3] * r1), pack2(o[1][0] * r0, o[1][1] * r1), pack2(o[1][2] * r0, o[1][3] * r1));
                named_arrive(2, 384);
                TSTAMP(c * 12 + 4);
#pragma unroll
                for (int s2 = PDW1; s2 < PDW; s2++) wb[s2] = lds128(ww_a + s2 * 4096);
                if (lane == 0) mbar_arrive(cb + C_BAR + B_F);
                if (warp == 4 && lane == 0) mbar_expect_tx(cb + C_BAR + B_S, S_BYTES);
            }
            named_bar(2, 384);
            TSTAMP(c * 12 + 5);
            {
                uint4 ob[4];
                ob[0] = ldsm4(u_ob0 + CO + l16); ob[1] = ldsm4(u_ob0 + CO + l16 + 512);
                ob[2] = ldsm4(u_ob1 + CO + l16); ob[3] = ldsm4(u_ob1 + CO + l16 + 512);
                float d[4][4];
#pragma unroll
                for (int a = 0; a < 4; a++)
#pragma unroll
                    for (int i = 0; i < 4; i++) d[a][i] = 0.f;
                const uint32_t ra = u_ra + CO + l8, rb = cb + C_BAR + B_R;
#pragma unroll
                for (int i = 0; i < 20; i++) {
                    const int k = w_k(i), ac = w_acc(i);
                    const uint32_t b0 = (k & 1) ? ob[k >> 1].z : ob[k >> 1].x, b1 = (k & 1) ? ob[k >> 1].w : ob[k >> 1].y;
                    if (w_smem(i)) {
                        const int s = w_slot(i);
                        mmau(d[ac], wb[s % PDW], b0, b1);
                        if (s + PDW < NSW) wb[s % PDW] = lds128(ww_a + (s + PDW) * 4096);
                    } else mmau(d[ac], wr[NRQ + w_slot(i)], b0, b1);
                    if (i == 9) {
                        const uint32_t rs = u_ra + CO + l4 + 4096 + (warp & 1) * 128;
                        st_async_u32(rs + oe, pack2(d[2][0], d[2][1]), rb + 16 + oe);
                        st_async_u32(rs + oo, pack2(d[2][2], d[2][3]), rb + 16 + oo);
                    }
                    if (i == 17) st_async_v2(ra + od, pack2(d[0][0], d[0][1]), pack2(d[0][2], d[0][3]), rb + od);
                }
                st_async_v2(ra + 2048 + od, pack2(d[1][0] + d[3][0], d[1][1] + d[3][1]), pack2(d[1][2] + d[3][2], d[1][3] + d[3][3]), rb + 8 + od);
                TSTAMP(c * 12 + 6);
#pragma unroll
                for (int s = 0; s < PDQ; s++) qb[s] = lds128(wq_a + s * 4096);
            }
        };
#pragma unroll 1
        for (int t = 0; t < NTICK; t++) {
            if (t < NSEG) tick(IC<0>{}, t);
            if (t >= LAG) tick(IC<1>{}, t - LAG);
        }
    } else {
        asm volatile("setmaxnreg.dec.sync.aligned.u32 40;");
        const int s = warp - 8;
        cluster_sync_all();
        if (s < 3) {
#pragma unroll 1
            for (int hs = 0; hs < 2 * NTICK; hs++) {
                const int c = hs & 1, t = hs >> 1;
                const int n = t - c * LAG;
                if (n < 0 || n >= NSEG - 1) continue;
                const uint32_t cb = sb + O_REST + c * C_SIZE;
                const uint32_t par = (uint32_t)(n & 1);
                const uint32_t tag = (uint32_t)(n % 13) + 1u;
                uint32_t* xb = g_xc + (size_t)((c * 2 + par) * CL + r) * (NCLU * 320) + s * 128;
                const uint32_t ra = cb + C_RED + s * 2048 + lane * (s < 2 ? 8 : 4);
                mwait(cb + C_BAR + B_R + s * 8, par);
                TSTAMP(c * 12 + 7);
                uint4 p[4];
                if (s < 2) {
#pragma unroll
                    for (int i = 0; i < 4; i++) {
                        const uint2 a = lds64(ra + i * 512), b = lds64(ra + i * 512 + 256);
                        p[i] = make_uint4(a.x, a.y, b.x, b.y);
                    }
                } else {
#pragma unroll
                    for (int i = 0; i < 4; i++) p[i] = make_uint4(lds32(ra + i * 512), lds32(ra + i * 512 + 128), lds32(ra + i * 512 + 256), lds32(ra + i * 512 + 384));
                }
                if (lane == 0) mbar_expect_tx(cb + C_BAR + B_R + s * 8, 2048);
                uint32_t m0, m1;
                if (s < 2) {
                    float f0 = 0.f, f1 = 0.f, f2 = 0.f, f3 = 0.f;
#pragma unroll
                    for (int i = 0; i < 4; i++) {
                        f0 += blo(p[i].x) + blo(p[i].z); f1 += bhi(p[i].x) + bhi(p[i].z);
                        f2 += blo(p[i].y) + blo(p[i].w); f3 += bhi(p[i].y) + bhi(p[i].w);
                    }
                    xb += lane * 4;
                    const uint32_t u0 = (__float_as_uint(f0) & ~0xFu) | tag, u1 = (__float_as_uint(f1) & ~0xFu) | tag;
                    const uint32_t u2 = (__float_as_uint(f2) & ~0xFu) | tag, u3 = (__float_as_uint(f3) & ~0xFu) | tag;
                    st_relaxed_v4(xb + cq * 320, u0, u1, u2, u3);
                    TSTAMP(c * 12 + 8);
                    xdelay();
                    uint4 x[NCLU];
#pragma unroll
                    for (int k = 0; k < NCLU; k++) x[k] = make_uint4(u0, u1, u2, u3);
                    int guard = 0;
                    bool first = true;
                    while (true) {
                        bool ok = true;
#pragma unroll
                        for (int k = 0; k < NCLU; k++) {
                            const bool okk = k == cq || (!first && ((x[k].x ^ tag) | (x[k].y ^ tag) | (x[k].z ^ tag) | (x[k].w ^ tag)) << 28 == 0);
                            if (!okk) { x[k] = ld_relaxed_v4(xb + k * 320); ok = false; }
                        }
                        first = false;
                        if (__all_sync(0xffffffffu, ok) || ++guard > SPIN_LIMIT) break;
                    }
                    TVAL(c * 12 + 11, guard);
                    f0 = f1 = f2 = f3 = 0.f;
#pragma unroll
                    for (int k = 0; k < NCLU; k++) {
                        f0 += __uint_as_float(x[k].x & ~0xFu); f1 += __uint_as_float(x[k].y & ~0xFu);
                        f2 += __uint_as_float(x[k].z & ~0xFu); f3 += __uint_as_float(x[k].w & ~0xFu);
                    }
                    m0 = movmat(pack2(f0, f1)); m1 = movmat(pack2(f2, f3));
                } else {
                    float f0 = 0.f, f1 = 0.f;
#pragma unroll
                    for (int i = 0; i < 4; i++) {
                        f0 += (blo(p[i].x) + blo(p[i].y)) + (blo(p[i].z) + blo(p[i].w));
                        f1 += (bhi(p[i].x) + bhi(p[i].y)) + (bhi(p[i].z) + bhi(p[i].w));
                    }
                    xb += lane * 2;
                    const uint32_t u0 = (__float_as_uint(f0) & ~0xFu) | tag, u1 = (__float_as_uint(f1) & ~0xFu) | tag;
                    st_relaxed_v2(xb + cq * 320, u0, u1);
                    TSTAMP(c * 12 + 8);
                    xdelay();
                    uint2 x[NCLU];
#pragma unroll
                    for (int k = 0; k < NCLU; k++) x[k] = make_uint2(u0, u1);
                    int guard = 0;
                    bool first = true;
                    while (true) {
                        bool ok = true;
#pragma unroll
                        for (int k = 0; k < NCLU; k++) {
                            const bool okk = k == cq || (!first && ((x[k].x ^ tag) | (x[k].y ^ tag)) << 28 == 0);
                            if (!okk) { x[k] = ld_relaxed_v2(xb + k * 320); ok = false; }
                        }
                        first = false;
                        if (__all_sync(0xffffffffu, ok) || ++guard > SPIN_LIMIT) break;
                    }
                    TVAL(c * 12 + 11, guard);
                    f0 = f1 = 0.f;
#pragma unroll
                    for (int k = 0; k < NCLU; k++) { f0 += __uint_as_float(x[k].x & ~0xFu); f1 += __uint_as_float(x[k].y & ~0xFu); }
                    m0 = movmat(pack2(f0, f1)); m1 = 0;
                }
                TSTAMP(c * 12 + 9);
                const uint32_t ma = cb + C_MEM + (s < 2 ? lane * 8 + (hf * 2 + s) * 256 : 1024 + hf * 128 + lane * 4), bm = cb + C_BAR;
                if (s < 2) {
#pragma unroll
                    for (int G = 0; G < 8; G++)
#pragma unroll
                        for (int b = 0; b < 2; b++) {
                            const uint32_t dd = mapa(sb, (uint32_t)(((r + 2 * G) & 15) ^ b)) - sb;
                            st_async_v2(ma + G * 1280 + dd, m0, m1, bm + G * 8 + dd);
                        }
                } else {
#pragma unroll
                    for (int G = 0; G < 8; G++)
#pragma unroll
                        for (int b = 0; b < 2; b++) {
                            const uint32_t dd = mapa(sb, (uint32_t)(((r + 2 * G) & 15) ^ b)) - sb;
                            st_async_u32(ma + G * 1280 + dd, m0, bm + G * 8 + dd);
                        }
                }
                TSTAMP(c * 12 + 10);
            }
        } else {
            auto fetch = [&](int c, int seg) {
                if (lane == 0) {
                    if (seg % CSEG == 0) {
                        int guard = 0;
                        while (ld_acquire(FLG(F_KV + c * NCHK + seg / CSEG)) < A.kv_target && ++guard < SPIN_LIMIT) __nanosleep(64);
                    }
                    asm volatile("fence.proxy.async;" ::: "memory");
                    const uint32_t cb = sb + O_REST + c * C_SIZE;
                    const uint32_t bt = cb + C_BAR + B_T, d = cb + C_TOK;
                    mbar_expect_tx(bt, 12288);
                    const CUtensorMap* mk = &A.tk[c];
                    const CUtensorMap* mv = &A.tv[c];
                    asm volatile("cp.async.bulk.tensor.2d.shared::cluster.global.mbarrier::complete_tx::bytes [%0], [%1, {%3, %4}], [%2];" ::"r"(d),
                                 "l"(mk), "r"(bt), "r"(h * DH + hf * 64), "r"(seg * SEG) : "memory");
#pragma unroll
                    for (int i = 0; i < 2; i++)
                        asm volatile("cp.async.bulk.tensor.2d.shared::cluster.global.mbarrier::complete_tx::bytes [%0], [%1, {%3, %4}], [%2];" ::"r"(d + 4096 + i * 4096),
                                     "l"(mv), "r"(bt), "r"(h * DH + i * 64), "r"(seg * SEG) : "memory");
                }
                __syncwarp();
            };
            fetch(0, 0);
#pragma unroll 1
            for (int hs = 0; hs < 2 * NTICK; hs++) {
                const int c = hs & 1, t = hs >> 1;
                const int n = t - c * LAG;
                if (n < -1 || n >= NSEG) continue;
                if (n >= 0) {
                    const uint32_t cb = sb + O_REST + c * C_SIZE;
                    mwait(cb + C_BAR + B_F, (uint32_t)(n & 1));
                    uint4* fd = g_kvf + (size_t)((c * NSEG + n) * NH + h) * 256 + hf * 64 + lane;
#pragma unroll
                    for (int i = 0; i < 2; i++) {
                        const uint4 k0 = ldsm4(cb + C_K + i * 1024 + lane * 16), k1 = ldsm4(cb + C_K + i * 1024 + 512 + lane * 16);
                        fd[i * 32] = make_uint4(badd2(k0.x, k0.z), badd2(k0.y, k0.w), badd2(k1.x, k1.z), badd2(k1.y, k1.w));
                        const uint32_t va = cb + C_V + hf * 2048 + i * 1024 + lane * 8;
                        const uint2 v0 = lds64(va), v1 = lds64(va + 256), v2 = lds64(va + 512), v3 = lds64(va + 768);
                        fd[128 + i * 32] = make_uint4(badd2(v0.x, v1.x), badd2(v0.y, v1.y), badd2(v2.x, v3.x), badd2(v2.y, v3.y));
                    }
                    if (blockIdx.x == 0 && lane == 0 && (c == 0 || t >= NSEG)) asm volatile("st.relaxed.gpu.global.u32 [%0], %1;" ::"l"(FLG(F_PROG)), "r"(t + 1) : "memory");
                    if ((n % CSEG) == CSEG - 1) {
                        asm volatile("fence.proxy.async;" ::: "memory");
                        __syncwarp();
                        if (lane == 0) { red_release(FLG(F_MEM + c * NCHK + n / CSEG), 1); }
                    }
                }
                if (n + 1 < NSEG - 1) fetch(c, n + 1);
            }
        }
    }
    cluster_sync_all();
}
}

namespace ni {
constexpr int KV_TGT = 32, MEM_TGT = 64, OP_TGT = 16, CONV_TGT = 80, H_TGT = 128;
constexpr int PDIST = (LAG + 3) / 4;
#define QA_PRE 3
#define KV1_W 5
#define KV1_N 16
static_assert(QA_PRE < 4, "inputs of the chunk must be complete");
#define SPLAN 0x102030
#define URGENT 1
#define POST_NS 40

#define ELECT "{\n.reg .pred p;\nelect.sync _|p, 0xffffffff;\n@p "
__device__ __forceinline__ void tma_load_2d(uint32_t dst, const CUtensorMap* map, uint32_t bar, int c0, int c1) {
    asm volatile(ELECT "cp.async.bulk.tensor.2d.shared::cluster.global.mbarrier::complete_tx::bytes [%0], [%1, {%3, %4}], [%2];\n}" ::"r"(dst),
                 "l"(map), "r"(bar), "r"(c0), "r"(c1) : "memory");
}
__device__ __forceinline__ void tma_load_2d_mc(uint32_t dst, const CUtensorMap* map, uint32_t bar, int c0, int c1) {
    asm volatile(ELECT "cp.async.bulk.tensor.2d.shared::cluster.global.mbarrier::complete_tx::bytes.multicast::cluster [%0], [%1, {%3, %4}], [%2], %5;\n}" ::"r"(dst),
                 "l"(map), "r"(bar), "r"(c0), "r"(c1), "h"((unsigned short)3) : "memory");
}
__device__ __forceinline__ void tma_load_3d(uint32_t dst, const CUtensorMap* map, uint32_t bar, int c1, int c2) {
    asm volatile(ELECT "cp.async.bulk.tensor.3d.shared::cluster.global.mbarrier::complete_tx::bytes [%0], [%1, {%5, %3, %4}], [%2];\n}" ::"r"(dst),
                 "l"(map), "r"(bar), "r"(c1), "r"(c2), "r"(0) : "memory");
}
__device__ __forceinline__ void tma_load_3d_mc(uint32_t dst, const CUtensorMap* map, uint32_t bar, int c1, int c2) {
    asm volatile(ELECT "cp.async.bulk.tensor.3d.shared::cluster.global.mbarrier::complete_tx::bytes.multicast::cluster [%0], [%1, {%6, %3, %4}], [%2], %5;\n}" ::"r"(dst),
                 "l"(map), "r"(bar), "r"(c1), "r"(c2), "h"((unsigned short)3), "r"(0) : "memory");
}
__device__ __forceinline__ void bulk_load(uint32_t dst, const void* src, uint32_t bytes, uint32_t bar) {
    asm volatile(ELECT "cp.async.bulk.shared::cluster.global.mbarrier::complete_tx::bytes [%0], [%1], %2, [%3];\n}" ::"r"(dst), "l"(src), "r"(bytes), "r"(bar) : "memory");
}
__device__ __forceinline__ void expect_tx1(uint32_t bar, uint32_t bytes) {
    asm volatile(ELECT "mbarrier.arrive.expect_tx.shared::cta.b64 _, [%0], %1;\n}" ::"r"(bar), "r"(bytes) : "memory");
}
__device__ __forceinline__ void wg_fence() { asm volatile("wgmma.fence.sync.aligned;" ::: "memory"); }
__device__ __forceinline__ void wg_commit() { asm volatile("wgmma.commit_group.sync.aligned;" ::: "memory"); }
template <int N> __device__ __forceinline__ void wg_wait() { asm volatile("wgmma.wait_group.sync.aligned %0;" ::"n"(N) : "memory"); }
__device__ __forceinline__ uint64_t make_desc(uint32_t addr, uint32_t lbo, uint32_t sbo) {
    return (uint64_t)((addr & 0x3FFFF) >> 4) | ((uint64_t)((lbo & 0x3FFFF) >> 4) << 16) |
           ((uint64_t)((sbo & 0x3FFFF) >> 4) << 32) | (1ull << 62);
}
__device__ __forceinline__ void wgmma_m64n256k16(float* d, uint64_t da, uint64_t db) {
    asm volatile("{\n.reg .pred p;\nsetp.ne.b32 p, 1, 0;\n"
                 "wgmma.mma_async.sync.aligned.m64n256k16.f32.bf16.bf16 {%0, %1, %2, %3, %4, %5, %6, %7, %8, %9, %10, %11, %12, %13, %14, %15, %16, %17, %18, %19, %20, %21, %22, %23, %24, %25, %26, %27, %28, %29, %30, %31, %32, %33, %34, %35, %36, %37, %38, %39, %40, %41, %42, %43, %44, %45, %46, %47, %48, %49, %50, %51, %52, %53, %54, %55, %56, %57, %58, %59, %60, %61, %62, %63, %64, %65, %66, %67, %68, %69, %70, %71, %72, %73, %74, %75, %76, %77, %78, %79, %80, %81, %82, %83, %84, %85, %86, %87, %88, %89, %90, %91, %92, %93, %94, %95, %96, %97, %98, %99, %100, %101, %102, %103, %104, %105, %106, %107, %108, %109, %110, %111, %112, %113, %114, %115, %116, %117, %118, %119, %120, %121, %122, %123, %124, %125, %126, %127}, %128, %129, p, 1, 1, 0, 1;\n}\n"
                 : "+f"(d[0]), "+f"(d[1]), "+f"(d[2]), "+f"(d[3]), "+f"(d[4]), "+f"(d[5]), "+f"(d[6]), "+f"(d[7]), "+f"(d[8]), "+f"(d[9]), "+f"(d[10]), "+f"(d[11]), "+f"(d[12]), "+f"(d[13]), "+f"(d[14]), "+f"(d[15]), "+f"(d[16]), "+f"(d[17]), "+f"(d[18]), "+f"(d[19]), "+f"(d[20]), "+f"(d[21]), "+f"(d[22]), "+f"(d[23]), "+f"(d[24]), "+f"(d[25]), "+f"(d[26]), "+f"(d[27]), "+f"(d[28]), "+f"(d[29]), "+f"(d[30]), "+f"(d[31]), "+f"(d[32]), "+f"(d[33]), "+f"(d[34]), "+f"(d[35]), "+f"(d[36]), "+f"(d[37]), "+f"(d[38]), "+f"(d[39]), "+f"(d[40]), "+f"(d[41]), "+f"(d[42]), "+f"(d[43]), "+f"(d[44]), "+f"(d[45]), "+f"(d[46]), "+f"(d[47]), "+f"(d[48]), "+f"(d[49]), "+f"(d[50]), "+f"(d[51]), "+f"(d[52]), "+f"(d[53]), "+f"(d[54]), "+f"(d[55]), "+f"(d[56]), "+f"(d[57]), "+f"(d[58]), "+f"(d[59]), "+f"(d[60]), "+f"(d[61]), "+f"(d[62]), "+f"(d[63]), "+f"(d[64]), "+f"(d[65]), "+f"(d[66]), "+f"(d[67]), "+f"(d[68]), "+f"(d[69]), "+f"(d[70]), "+f"(d[71]), "+f"(d[72]), "+f"(d[73]), "+f"(d[74]), "+f"(d[75]), "+f"(d[76]), "+f"(d[77]), "+f"(d[78]), "+f"(d[79]), "+f"(d[80]), "+f"(d[81]), "+f"(d[82]), "+f"(d[83]), "+f"(d[84]), "+f"(d[85]), "+f"(d[86]), "+f"(d[87]), "+f"(d[88]), "+f"(d[89]), "+f"(d[90]), "+f"(d[91]), "+f"(d[92]), "+f"(d[93]), "+f"(d[94]), "+f"(d[95]), "+f"(d[96]), "+f"(d[97]), "+f"(d[98]), "+f"(d[99]), "+f"(d[100]), "+f"(d[101]), "+f"(d[102]), "+f"(d[103]), "+f"(d[104]), "+f"(d[105]), "+f"(d[106]), "+f"(d[107]), "+f"(d[108]), "+f"(d[109]), "+f"(d[110]), "+f"(d[111]), "+f"(d[112]), "+f"(d[113]), "+f"(d[114]), "+f"(d[115]), "+f"(d[116]), "+f"(d[117]), "+f"(d[118]), "+f"(d[119]), "+f"(d[120]), "+f"(d[121]), "+f"(d[122]), "+f"(d[123]), "+f"(d[124]), "+f"(d[125]), "+f"(d[126]), "+f"(d[127])
                 : "l"(da), "l"(db));
}
__device__ __forceinline__ void wgmma_m64n256k16_first(float* d, uint64_t da, uint64_t db) {
    asm volatile("{\n.reg .pred p;\nsetp.ne.b32 p, 0, 0;\n"
                 "wgmma.mma_async.sync.aligned.m64n256k16.f32.bf16.bf16 {%0, %1, %2, %3, %4, %5, %6, %7, %8, %9, %10, %11, %12, %13, %14, %15, %16, %17, %18, %19, %20, %21, %22, %23, %24, %25, %26, %27, %28, %29, %30, %31, %32, %33, %34, %35, %36, %37, %38, %39, %40, %41, %42, %43, %44, %45, %46, %47, %48, %49, %50, %51, %52, %53, %54, %55, %56, %57, %58, %59, %60, %61, %62, %63, %64, %65, %66, %67, %68, %69, %70, %71, %72, %73, %74, %75, %76, %77, %78, %79, %80, %81, %82, %83, %84, %85, %86, %87, %88, %89, %90, %91, %92, %93, %94, %95, %96, %97, %98, %99, %100, %101, %102, %103, %104, %105, %106, %107, %108, %109, %110, %111, %112, %113, %114, %115, %116, %117, %118, %119, %120, %121, %122, %123, %124, %125, %126, %127}, %128, %129, p, 1, 1, 0, 1;\n}\n"
                 : "=f"(d[0]), "=f"(d[1]), "=f"(d[2]), "=f"(d[3]), "=f"(d[4]), "=f"(d[5]), "=f"(d[6]), "=f"(d[7]), "=f"(d[8]), "=f"(d[9]), "=f"(d[10]), "=f"(d[11]), "=f"(d[12]), "=f"(d[13]), "=f"(d[14]), "=f"(d[15]), "=f"(d[16]), "=f"(d[17]), "=f"(d[18]), "=f"(d[19]), "=f"(d[20]), "=f"(d[21]), "=f"(d[22]), "=f"(d[23]), "=f"(d[24]), "=f"(d[25]), "=f"(d[26]), "=f"(d[27]), "=f"(d[28]), "=f"(d[29]), "=f"(d[30]), "=f"(d[31]), "=f"(d[32]), "=f"(d[33]), "=f"(d[34]), "=f"(d[35]), "=f"(d[36]), "=f"(d[37]), "=f"(d[38]), "=f"(d[39]), "=f"(d[40]), "=f"(d[41]), "=f"(d[42]), "=f"(d[43]), "=f"(d[44]), "=f"(d[45]), "=f"(d[46]), "=f"(d[47]), "=f"(d[48]), "=f"(d[49]), "=f"(d[50]), "=f"(d[51]), "=f"(d[52]), "=f"(d[53]), "=f"(d[54]), "=f"(d[55]), "=f"(d[56]), "=f"(d[57]), "=f"(d[58]), "=f"(d[59]), "=f"(d[60]), "=f"(d[61]), "=f"(d[62]), "=f"(d[63]), "=f"(d[64]), "=f"(d[65]), "=f"(d[66]), "=f"(d[67]), "=f"(d[68]), "=f"(d[69]), "=f"(d[70]), "=f"(d[71]), "=f"(d[72]), "=f"(d[73]), "=f"(d[74]), "=f"(d[75]), "=f"(d[76]), "=f"(d[77]), "=f"(d[78]), "=f"(d[79]), "=f"(d[80]), "=f"(d[81]), "=f"(d[82]), "=f"(d[83]), "=f"(d[84]), "=f"(d[85]), "=f"(d[86]), "=f"(d[87]), "=f"(d[88]), "=f"(d[89]), "=f"(d[90]), "=f"(d[91]), "=f"(d[92]), "=f"(d[93]), "=f"(d[94]), "=f"(d[95]), "=f"(d[96]), "=f"(d[97]), "=f"(d[98]), "=f"(d[99]), "=f"(d[100]), "=f"(d[101]), "=f"(d[102]), "=f"(d[103]), "=f"(d[104]), "=f"(d[105]), "=f"(d[106]), "=f"(d[107]), "=f"(d[108]), "=f"(d[109]), "=f"(d[110]), "=f"(d[111]), "=f"(d[112]), "=f"(d[113]), "=f"(d[114]), "=f"(d[115]), "=f"(d[116]), "=f"(d[117]), "=f"(d[118]), "=f"(d[119]), "=f"(d[120]), "=f"(d[121]), "=f"(d[122]), "=f"(d[123]), "=f"(d[124]), "=f"(d[125]), "=f"(d[126]), "=f"(d[127])
                 : "l"(da), "l"(db));
}
__device__ __forceinline__ void wgmma_rs_m64n128k16(float* d, const uint32_t* a, uint64_t db) {
    asm volatile("{\n.reg .pred p;\nsetp.ne.b32 p, 1, 0;\n"
                 "wgmma.mma_async.sync.aligned.m64n128k16.f32.bf16.bf16 {%0, %1, %2, %3, %4, %5, %6, %7, %8, %9, %10, %11, %12, %13, %14, %15, %16, %17, %18, %19, %20, %21, %22, %23, %24, %25, %26, %27, %28, %29, %30, %31, %32, %33, %34, %35, %36, %37, %38, %39, %40, %41, %42, %43, %44, %45, %46, %47, %48, %49, %50, %51, %52, %53, %54, %55, %56, %57, %58, %59, %60, %61, %62, %63}, {%64, %65, %66, %67}, %68, p, 1, 1, 1;\n}\n"
                 : "+f"(d[0]), "+f"(d[1]), "+f"(d[2]), "+f"(d[3]), "+f"(d[4]), "+f"(d[5]), "+f"(d[6]), "+f"(d[7]), "+f"(d[8]), "+f"(d[9]), "+f"(d[10]), "+f"(d[11]), "+f"(d[12]), "+f"(d[13]), "+f"(d[14]), "+f"(d[15]), "+f"(d[16]), "+f"(d[17]), "+f"(d[18]), "+f"(d[19]), "+f"(d[20]), "+f"(d[21]), "+f"(d[22]), "+f"(d[23]), "+f"(d[24]), "+f"(d[25]), "+f"(d[26]), "+f"(d[27]), "+f"(d[28]), "+f"(d[29]), "+f"(d[30]), "+f"(d[31]), "+f"(d[32]), "+f"(d[33]), "+f"(d[34]), "+f"(d[35]), "+f"(d[36]), "+f"(d[37]), "+f"(d[38]), "+f"(d[39]), "+f"(d[40]), "+f"(d[41]), "+f"(d[42]), "+f"(d[43]), "+f"(d[44]), "+f"(d[45]), "+f"(d[46]), "+f"(d[47]), "+f"(d[48]), "+f"(d[49]), "+f"(d[50]), "+f"(d[51]), "+f"(d[52]), "+f"(d[53]), "+f"(d[54]), "+f"(d[55]), "+f"(d[56]), "+f"(d[57]), "+f"(d[58]), "+f"(d[59]), "+f"(d[60]), "+f"(d[61]), "+f"(d[62]), "+f"(d[63])
                 : "r"(a[0]), "r"(a[1]), "r"(a[2]), "r"(a[3]), "l"(db));
}
__device__ __forceinline__ void wgmma_rs_m64n128k16_first(float* d, const uint32_t* a, uint64_t db) {
    asm volatile("{\n.reg .pred p;\nsetp.ne.b32 p, 0, 0;\n"
                 "wgmma.mma_async.sync.aligned.m64n128k16.f32.bf16.bf16 {%0, %1, %2, %3, %4, %5, %6, %7, %8, %9, %10, %11, %12, %13, %14, %15, %16, %17, %18, %19, %20, %21, %22, %23, %24, %25, %26, %27, %28, %29, %30, %31, %32, %33, %34, %35, %36, %37, %38, %39, %40, %41, %42, %43, %44, %45, %46, %47, %48, %49, %50, %51, %52, %53, %54, %55, %56, %57, %58, %59, %60, %61, %62, %63}, {%64, %65, %66, %67}, %68, p, 1, 1, 1;\n}\n"
                 : "=f"(d[0]), "=f"(d[1]), "=f"(d[2]), "=f"(d[3]), "=f"(d[4]), "=f"(d[5]), "=f"(d[6]), "=f"(d[7]), "=f"(d[8]), "=f"(d[9]), "=f"(d[10]), "=f"(d[11]), "=f"(d[12]), "=f"(d[13]), "=f"(d[14]), "=f"(d[15]), "=f"(d[16]), "=f"(d[17]), "=f"(d[18]), "=f"(d[19]), "=f"(d[20]), "=f"(d[21]), "=f"(d[22]), "=f"(d[23]), "=f"(d[24]), "=f"(d[25]), "=f"(d[26]), "=f"(d[27]), "=f"(d[28]), "=f"(d[29]), "=f"(d[30]), "=f"(d[31]), "=f"(d[32]), "=f"(d[33]), "=f"(d[34]), "=f"(d[35]), "=f"(d[36]), "=f"(d[37]), "=f"(d[38]), "=f"(d[39]), "=f"(d[40]), "=f"(d[41]), "=f"(d[42]), "=f"(d[43]), "=f"(d[44]), "=f"(d[45]), "=f"(d[46]), "=f"(d[47]), "=f"(d[48]), "=f"(d[49]), "=f"(d[50]), "=f"(d[51]), "=f"(d[52]), "=f"(d[53]), "=f"(d[54]), "=f"(d[55]), "=f"(d[56]), "=f"(d[57]), "=f"(d[58]), "=f"(d[59]), "=f"(d[60]), "=f"(d[61]), "=f"(d[62]), "=f"(d[63])
                 : "r"(a[0]), "r"(a[1]), "r"(a[2]), "r"(a[3]), "l"(db));
}

struct BulkMaps { CUtensorMap h, h2, wq, wk, wv, wo, kv, lu; };
struct BulkArgs {
    const bf16 *x, *ssmk, *ssmD, *Bk, *Bv, *shiftk;
    bf16* out;
};
enum { T_KV = 0, T_QA, T_CONV, T_ATT, T_POST, T_LN0 };
constexpr int MAXG = 52, SENT = MAXG - 1;
struct Sched { uint32_t chk[MAXG * 4]; uint32_t info[MAXG]; int sbeg[8]; };

constexpr int BK_STAGES = 4, BK_STAGE_BYTES = 49152, TSLOTS = 4;
struct BulkSmemTail {
    unsigned long long full[BK_STAGES], empty[BK_STAGES], tfull[TSLOTS], tempty[TSLOTS], sfull[4], sempty[4];
    int task[TSLOTS];
    uint32_t tab[MAXG * 5];
};
constexpr int BULK_STG = BK_STAGES * BK_STAGE_BYTES;
constexpr int BULK_TAIL = BULK_STG + 32768;
constexpr int BULK_SMEM = BULK_TAIL + (int)sizeof(BulkSmemTail);
static_assert(BULK_SMEM <= 232448, "bulk smem");
#define PACE 0
#define REG_C 224
#define REG_P 56

#define BT(lead, type, l, c, k)
#define TT(k)
#define FT(k)
#define TTV(k, v)
__device__ __forceinline__ void tma_store_2d(const CUtensorMap* map, uint32_t src, int c0, int c1) {
    asm volatile("cp.async.bulk.tensor.2d.global.shared::cta.bulk_group [%0, {%2, %3}], [%1];" ::"l"(map), "r"(src), "r"(c0), "r"(c1) : "memory");
}
__device__ __forceinline__ void bulk_commit() { asm volatile("cp.async.bulk.commit_group;" ::: "memory"); }
template <int N> __device__ __forceinline__ void bulk_wait_read() { asm volatile("cp.async.bulk.wait_group.read %0;" ::"n"(N) : "memory"); }
template <int N> __device__ __forceinline__ void bulk_wait() { asm volatile("cp.async.bulk.wait_group %0;" ::"n"(N) : "memory"); }
__device__ __forceinline__ void mbar_arrive_cluster(uint32_t bar) {
    asm volatile("mbarrier.arrive.shared::cluster.b64 _, [%0];" ::"r"(bar) : "memory");
}
__device__ __forceinline__ void stsm_x4(uint32_t addr, uint32_t r0, uint32_t r1, uint32_t r2, uint32_t r3) {
    asm volatile("stmatrix.sync.aligned.m8n8.x4.shared.b16 [%0], {%1,%2,%3,%4};" ::"r"(addr), "r"(r0), "r"(r1), "r"(r2), "r"(r3) : "memory");
}
__device__ __forceinline__ void mma1688(float* c, uint32_t a0, uint32_t a1, uint32_t b0) {
    asm("mma.sync.aligned.m16n8k8.row.col.f32.bf16.bf16.f32 {%0,%1,%2,%3}, {%4,%5}, {%6}, {%0,%1,%2,%3};"
        : "+f"(c[0]), "+f"(c[1]), "+f"(c[2]), "+f"(c[3]) : "r"(a0), "r"(a1), "r"(b0));
}
__device__ __forceinline__ int ld_relaxed(const int* p) {
    int v;
    asm volatile("ld.relaxed.gpu.global.u32 %0, [%1];" : "=r"(v) : "l"(p) : "memory");
    return v;
}
__device__ __forceinline__ void flag_wait(const int* f, int tgt, int ns) {
    int guard = 0;
    while (ld_relaxed(f) < tgt && ++guard < 4000000) __nanosleep(ns);
}
__device__ __forceinline__ void fence_async() { asm volatile("fence.proxy.async.global;" ::: "memory"); }
__device__ __forceinline__ uint32_t bmul2(uint32_t a, uint32_t b) { uint32_t r; asm("mul.rn.bf16x2 %0, %1, %2;" : "=r"(r) : "r"(a), "r"(b)); return r; }
__device__ __forceinline__ uint32_t bsum2(uint32_t a, uint32_t b) { uint32_t r; asm("add.rn.bf16x2 %0, %1, %2;" : "=r"(r) : "r"(a), "r"(b)); return r; }
__device__ __forceinline__ uint32_t bmax2(uint32_t a, uint32_t b) { uint32_t r; asm("max.bf16x2 %0, %1, %2;" : "=r"(r) : "r"(a), "r"(b)); return r; }
__device__ __forceinline__ uint32_t rscore(float a, float b) {
    const uint32_t u = pack2(a, b);
    return pack2(blo(u) * 0.08838834764831845f, bhi(u) * 0.08838834764831845f);
}
template <int STRIDE> __device__ __forceinline__ void ld5(uint32_t* w, const bf16* p) {
#pragma unroll
    for (int r = 0; r < 5; r++) { const uint2 v = __ldcg(reinterpret_cast<const uint2*>(p + r * STRIDE)); w[2 * r] = v.x; w[2 * r + 1] = v.y; }
}
__device__ __forceinline__ void st5(bf16* p, const uint32_t* w) {
#pragma unroll
    for (int r = 0; r < 5; r++) *reinterpret_cast<uint2*>(p + r * 128) = make_uint2(w[2 * r], w[2 * r + 1]);
}
__device__ __forceinline__ void ln_row(const uint32_t* x, uint32_t* y) {
    float s = 0.f;
#pragma unroll
    for (int i = 0; i < 10; i++) s += blo(x[i]) + bhi(x[i]);
#pragma unroll
    for (int o = 16; o > 0; o >>= 1) s += __shfl_xor_sync(0xffffffffu, s, o);
    const float mean = s * (1.0f / DM);
    float q = 0.f;
#pragma unroll
    for (int i = 0; i < 10; i++) { const float d0 = blo(x[i]) - mean, d1 = bhi(x[i]) - mean; q = fmaf(d0, d0, q); q = fmaf(d1, d1, q); }
#pragma unroll
    for (int o = 16; o > 0; o >>= 1) q += __shfl_xor_sync(0xffffffffu, q, o);
    const uint32_t nm = pack2(-mean, -mean);
    float sq;
    asm("sqrt.approx.ftz.f32 %0, %1;" : "=f"(sq) : "f"(rbf(rbf(q * (1.0f / DM)) + 1e-5f)));
    const float rd = rcpf(rbf(sq));
#pragma unroll
    for (int i = 0; i < 10; i++) { const uint32_t d = bsum2(x[i], nm); y[i] = pack2(blo(d) * rd, bhi(d) * rd); }
}
__device__ __forceinline__ void red_add8(uint4* p, uint32_t a, uint32_t b, uint32_t c, uint32_t d) {
    asm volatile("red.relaxed.gpu.global.add.noftz.v4.bf16x2 [%0], {%1,%2,%3,%4};" ::"l"(p), "r"(a), "r"(b), "r"(c), "r"(d) : "memory");
}
__device__ __forceinline__ void part_sum(const uint4& v, const uint4& w, int lane, uint32_t& x0, uint32_t& x1) {
    float t[8];
    t[0] = blo(v.x) + blo(w.x); t[1] = bhi(v.x) + bhi(w.x); t[2] = blo(v.y) + blo(w.y); t[3] = bhi(v.y) + bhi(w.y);
    t[4] = blo(v.z) + blo(w.z); t[5] = bhi(v.z) + bhi(w.z); t[6] = blo(v.w) + blo(w.w); t[7] = bhi(v.w) + bhi(w.w);
#pragma unroll
    for (int i = 0; i < 4; i++) t[i] = (lane < 16 ? t[i] : t[4 + i]) + __shfl_xor_sync(0xffffffffu, lane < 16 ? t[4 + i] : t[i], 16);
    const uint32_t r0 = pack2(t[0], t[1]), r1 = pack2(t[2], t[3]);
    const uint32_t ex = __shfl_xor_sync(0xffffffffu, (lane & 1) ? r0 : r1, 1);
    x0 = (lane & 1) ? ex : r0; x1 = (lane & 1) ? r1 : ex;
}
__device__ __forceinline__ void post_row(int l, int row, int lane, const bf16* xin, bf16* xout) {
    uint32_t x[10], y[10], n[10];
    const int cl = (lane & 12) * 8 + (lane >> 4) * 16 + (lane & 1) * 8 + (lane & 2) * 2;
    uint4* pp = reinterpret_cast<uint4*>(g_part + (size_t)(l * PROWS + (row & (PROWS - 1))) * (PG * DM)) + (lane & 15) + (lane >> 4) * 80;
    int* f = FLG(F_OP + l * NCHK + (row >> 7));
    flag_wait(FLG(F_CONV + (row >> 10)), CONV_TGT, 200);
    ld5<128>(x, xin + (size_t)row * DM + cl);
    flag_wait(f + 4, OP_TGT, POST_NS);
    {
        uint4 v[10];
#pragma unroll
        for (int i = 0; i < 10; i++) v[i] = __ldcg(pp + (i >> 1) * 16 + (i & 1) * 160);
#pragma unroll
        for (int r = 0; r < 5; r++) {
            uint32_t s0, s1;
            part_sum(v[2 * r], v[2 * r + 1], lane, s0, s1);
            if (r == 1) ld5<16 * S_LEN * 8>(y, g_Y + ((size_t)(cl >> 3) * S_LEN + (row ^ ((row >> 6) & 7))) * 8 + (cl & 4));
            x[2 * r] = bsum2(x[2 * r], s0); x[2 * r + 1] = bsum2(x[2 * r + 1], s1);
        }
    }
    ln_row(x, n);
#pragma unroll
    for (int i = 0; i < 10; i++) x[i] = bsum2(x[i], bmul2(n[i], y[i]));
    if (l == 0) {
        ln_row(x, n);
        st5(g_h[1] + (size_t)row * DM + cl, n);
        __syncwarp();
        if (lane == 0) red_release(FLG(F_H + NCHK + (row >> 7)), 1);
    }
#pragma unroll
    for (int i = 0; i < 10; i++) pp[(i >> 1) * 16 + (i & 1) * 160] = make_uint4(0, 0, 0, 0);
    st5(xout + (size_t)row * DM + cl, x);
    __syncwarp();
    if (l && lane == 0) red_release(f + 5, 1);
}
__device__ __forceinline__ void u_unit(const bf16* Bk, const bf16* Bv, const bf16* shiftk, int unit, int lane) {
    const int t0 = (unit / 10) * 16, cp = (unit % 10) * 32 + lane;
    uint32_t kk[19], vv[16];
    const uint32_t* pk = reinterpret_cast<const uint32_t*>(Bk + (size_t)t0 * DM) + cp;
    const uint32_t* pv = reinterpret_cast<const uint32_t*>(Bv + (size_t)t0 * DM) + cp;
#pragma unroll
    for (int i = 0; i < 19; i++) kk[i] = (i >= 3 || t0 > 0) ? __ldg(pk + (i - 3) * (DM / 2)) : 0u;
#pragma unroll
    for (int i = 0; i < 16; i++) vv[i] = __ldg(pv + i * (DM / 2));
    const uint4 sh0 = __ldg(reinterpret_cast<const uint4*>(shiftk + cp * 8));
    const uint32_t s0 = __byte_perm(sh0.x, sh0.z, 0x5410), s1 = __byte_perm(sh0.x, sh0.z, 0x7632), s2 = __byte_perm(sh0.y, sh0.w, 0x5410), s3 = __byte_perm(sh0.y, sh0.w, 0x7632);
#pragma unroll
    for (int t = 0; t < 16; t++)
        vv[t] = bmul2(bsum2(bsum2(bsum2(bmul2(kk[t], s3), bmul2(kk[t + 1], s2)), bmul2(kk[t + 2], s1)), bmul2(kk[t + 3], s0)), vv[t]);
    uint4* d = reinterpret_cast<uint4*>(g_U + (size_t)(cp * 2) * S_LEN + (t0 ^ 48));
#pragma unroll
    for (int c = 0; c < 2; c++) {
        const uint32_t sel = c ? 0x7632 : 0x5410;
#pragma unroll
        for (int hh = 0; hh < 2; hh++)
            d[c * (S_LEN / 8) + hh] = make_uint4(__byte_perm(vv[15 - hh * 8], vv[14 - hh * 8], sel), __byte_perm(vv[13 - hh * 8], vv[12 - hh * 8], sel),
                                                 __byte_perm(vv[11 - hh * 8], vv[10 - hh * 8], sel), __byte_perm(vv[9 - hh * 8], vv[8 - hh * 8], sel));
    }
}
constexpr int CV_EP = 4224;
template <class F> __device__ __forceinline__ void conv_unit(uint32_t ub, uint32_t e0, uint32_t e1, uint32_t zrow, uint32_t yt, float Dv, int m, int lane, F&& nearly_done) {
    const int g = lane >> 2, tq = lane & 3;
    asm volatile("st.shared.u32 [%0], %1;" ::"r"(e0 + lane * 4), "r"(0) : "memory");
    asm volatile("st.shared.u32 [%0], %1;" ::"r"(zrow + lane * 4), "r"(0) : "memory");
    __syncwarp();
    for (int i = lane; i < CV_EP / 16; i += 32) {
        const uint4 v = lds128(e0 + i * 16);
        const uint32_t nx = i + 1 < CV_EP / 16 ? lds32(e0 + i * 16 + 16) : 0u;
        sts128(e1 + i * 16, __byte_perm(v.x, v.y, 0x5432), __byte_perm(v.y, v.z, 0x5432), __byte_perm(v.z, v.w, 0x5432), __byte_perm(v.w, nx, 0x5432));
    }
    __syncwarp();
    float acc[8][4];
#pragma unroll
    for (int n = 0; n < 8; n++)
#pragma unroll
        for (int i = 0; i < 4; i++) acc[n][i] = 0.f;
    uint32_t wb = (g & 1) ? e0 + (1 + g + 2 * tq) * 2 : e1 + (g + 2 * tq) * 2;
    uint32_t W[16], a[4][4], an[4][4];
    int row = m * 16 + (lane & 15);
    auto lda = [&](uint32_t (*d)[4]) {
        const uint32_t x = row < 0 ? zrow : ub + row * 128 + (((lane >> 4) ^ (row & 7)) << 4);
#pragma unroll
        for (int ks = 0; ks < 4; ks++) ldsm_x4(d[ks][0], d[ks][1], d[ks][2], d[ks][3], x ^ (ks << 5));
        row--;
    };
#pragma unroll
    for (int i = 0; i < 16; i++) W[i] = lds32(wb + i * 16);
    lda(a);
    const int nD = m == 0 ? 16 : 32;
#pragma unroll 2
    for (int D = 0; D < nD; D++) {
        uint32_t Wn[8];
        wb += 128;
        if (D == nD - 6) nearly_done();
        lda(an);
#pragma unroll
        for (int i = 0; i < 8; i++) Wn[i] = lds32(wb + 128 + i * 16);
#pragma unroll
        for (int ks = 0; ks < 4; ks++)
#pragma unroll
            for (int n = 0; n < 8; n++) mma16816(acc[n], a[ks][0], a[ks][1], a[ks][2], a[ks][3], W[2 * ks + n], W[2 * ks + n + 1]);
#pragma unroll
        for (int i = 0; i < 8; i++) { W[i] = W[i + 8]; W[i + 8] = Wn[i]; }
#pragma unroll
        for (int ks = 0; ks < 4; ks++)
#pragma unroll
            for (int i = 0; i < 4; i++) a[ks][i] = an[ks][i];
    }
#pragma unroll
    for (int n = 0; n < 8; n++)
#pragma unroll
        for (int r = 0; r < 2; r++) {
            const int a_ = g + r * 8, b_ = n * 8 + tq * 2;
            const int ar = m * 16 + a_, p = 62 - b_;
            const uint32_t kv = lds32(ub + ar * 128 + (((p >> 3) ^ (ar & 7)) << 4) + (p & 7) * 2);
            const float y0 = rbf(acc[n][2 * r]) + rbf(bhi(kv) * Dv), y1 = rbf(acc[n][2 * r + 1]) + rbf(blo(kv) * Dv);
            const uint32_t pk = pack2(y0, y1);
            asm volatile("st.shared.u16 [%0], %1;" ::"r"(yt + ((a_ * 64 + b_) ^ g) * 16), "h"((unsigned short)(pk & 0xffff)) : "memory");
            asm volatile("st.shared.u16 [%0], %1;" ::"r"(yt + ((a_ * 64 + b_ + 1) ^ g) * 16), "h"((unsigned short)(pk >> 16)) : "memory");
        }
}

__global__ void __launch_bounds__(384, 1) bulk_kernel(const __grid_constant__ BulkMaps M, const __grid_constant__ BulkArgs A,
                                                      const __grid_constant__ Sched SC) {
    extern __shared__ __align__(1024) unsigned char smem_raw[];
    const uint32_t sb0 = smem_u32(smem_raw);
    const uint32_t full0 = sb0 + BULK_TAIL, empty0 = full0 + 32, tfull0 = full0 + 64, tempty0 = full0 + 96, sfull = full0 + 128, sempty = full0 + 160,
                   task0 = full0 + 192, tab0 = full0 + 208;
    const int tid = threadIdx.x, wid = __shfl_sync(0xffffffffu, tid >> 5, 0), lane = tid & 31;
    const int rank = blockIdx.x & 1;
    if (tid == 0) {
        for (int i = 0; i < BK_STAGES; i++) { mbar_init(full0 + 8 * i, 1); mbar_init(empty0 + 8 * i, 4); }
        for (int i = 0; i < TSLOTS; i++) { mbar_init(tfull0 + 8 * i, 1); mbar_init(tempty0 + 8 * i, 19); }
        for (int i = 0; i < 4; i++) { mbar_init(sfull + 8 * i, 8); mbar_init(sempty + 8 * i, 1); }
        asm volatile("fence.mbarrier_init.release.cluster;" ::: "memory");
        if (rank == 1) for (int i = 0; i < TSLOTS; i++) mbar_expect_tx(tfull0 + 8 * i, 4);
        BT(true, T_LN0, 0, 0, 0);
    }
    if (tid < MAXG * 5) asm volatile("st.shared.u32 [%0], %1;" ::"r"(tab0 + tid * 4), "r"(SC.chk[tid]) : "memory");
    cluster_sync_all();
    uint32_t tc = 0, it = 0;
    if (wid < 4) {
        asm volatile("setmaxnreg.dec.sync.aligned.u32 %0;" ::"n"(REG_P));
        if (wid == 0) {
            int head = SC.sbeg[lane >> 3];
            const int hend = SC.sbeg[(lane >> 3) + 1];
            uint32_t chk = 0; int pv = (blockIdx.x >> 1) & 31, grp = (SC.sbeg[3] + (blockIdx.x >> 6)) << 2 | 3, ncode = 0, code = 3 << 6 | 2, guard = 0;
            auto acquire = [&](uint32_t bytes) -> uint32_t {
                const uint32_t s = it & 3;
                mwait(empty0 + 8 * s, ((it >> 2) & 1) ^ 1);
                it++;
                expect_tx1(full0 + 8 * s, bytes);
                return s;
            };
            auto uwait = [&](const int* f, int tgt) {
                int g2 = 0;
                while ((int)UNI(ld_relaxed(f)) < tgt && ++g2 < 4000000) __nanosleep(32);
                fence_async();
            };
#pragma unroll 1
            while (true) {
                const int type = (code >> 6) & 3;
                const int iend = type == T_KV ? 10 : (type == T_QA ? 24 : 31);
                const int jj = code & 63, g0 = (jj & 15) * 4, lc = (code >> 9) & 31;
                const bool lm = (code >> 8) & 1;
                const CUtensorMap* mb = type == T_QA ? &M.wq : (jj < 16 ? &M.wk : &M.wv);
                bool have = false, ok = (code >> 14) & 1;
                int imem = 16;
#pragma unroll 1
                for (int i = type < T_CONV ? 0 : (type == T_CONV ? 24 : 28 + jj); i < iend; i++) {
                    const int sd = (type < T_CONV ? SPLAN : 0x1230) >> 4 * min(iend - i, 7) & 15;
                    if (rank == 0 && sd) {
                        if (sd == 1) {
                            if (type == T_CONV) mwait(empty0 + 8 * (it & 3), ((it >> 2) & 1) ^ 1);
                            const int gi = head + ((lane >> 2) & 1);
                            chk = lds32(tab0 + ((gi < hend ? gi : SENT) * 4 + (lane & 3)) * 4);
                            pv = ld_relaxed(g_flags + (chk & 0xffff));
                        } else if (sd == 2) {
                            const int tgt = (int)(chk >> 16);
                            const uint32_t b = (__ballot_sync(0xffffffffu, (lane & 3) == 0 ? pv < tgt : pv >= tgt) >> (lane & 24)) & 0xff;
                            const uint32_t cand = (b & 1) ? b & 15 : b >> 4;
                            head += (b & 1) ? 0 : ((b & 16) ? 1 : 2);
                            if (head > hend || guard > 4000000) head = hend;
                            const uint32_t req = lane >= 24 ? 1 : 15;
                            grp = (int)__reduce_min_sync(0xffffffffu, (cand & req) == req ? ((uint32_t)head << 2 | (cand ^ req) >> 2 | ((cand ^ req) & 2 ? 0 : 256)) : (head < hend ? 1000u : 1004u));
                            if (grp < 1000) grp &= 255;
                            if (grp < 1000) asm volatile("{\n.reg .pred p;\nsetp.eq.u32 p, %2, 0;\n@p atom.relaxed.gpu.global.inc.u32 %0, [%1], 0x7fffffff;\n}" : "+r"(pv) : "l"(FLG(F_CNT + (grp >> 2))), "r"(lane) : "memory");
                        } else {
                            if (grp < 1000) {
                                const int tk = (int)UNI(pv);
                                have = tk < (int)(UNI(lds32(tab0 + (grp >> 2) * 16)) >> 16);
                                ncode = (int)UNI(lds32(tab0 + MAXG * 16 + (grp & ~3))) | (grp & 3) << 19 | tk;
                            } else if (grp == 1004) { have = true; ncode = -1; }
                            if (have) {
                                const uint32_t o = (tc & 3) * 4;
                                mwait(tempty0 + 2 * o, ((tc >> 2) & 1) ^ 1);
                                asm volatile(ELECT "st.shared.u32 [%0], %1;\n@p mbarrier.arrive.shared::cta.b64 _, [%2];\n"
                                             "@p st.async.weak.shared::cluster.mbarrier::complete_tx::bytes.b32 [%3], %1, [%4];\n}"
                                             ::"r"(task0 + o), "r"(ncode), "r"(tfull0 + 2 * o), "r"(mapa(task0 + o, 1)), "r"(mapa(tfull0 + 2 * o, 1)) : "memory");
                            }
                        }
                    }
                    if (i >= 28) continue;
                    if (i == 8 && type == T_QA) pv = ld_relaxed(FLG((lane & 1 ? F_MEM : F_KV) + lc));
                    if (i == 10) {
                        const uint32_t b = __ballot_sync(0xffffffffu, pv >= (lane & 1 ? MEM_TGT : KV_TGT));
                        if (b & 2) imem = 13;
                        if (!(b & 1)) uwait(FLG(F_KV + lc), KV_TGT);
                        fence_async();
                    }
                    const uint32_t s = acquire(i < 12 ? 49152 : (i == 24 || i == 27 ? 0 : 32768));
                    const uint32_t sa = sb0 + s * BK_STAGE_BYTES, fb = full0 + 8 * s;
                    if (i == 0) TT(3);
                    if (i < 10) {
                        if (lm) {
                            tma_load_3d(sa + 16384, mb, fb, i * 64, g0);
                            tma_load_3d(sa + 32768, mb, fb, i * 64, g0 + 2);
                        } else tma_load_3d_mc(sa + 16384 + rank * 16384, mb, fb, i * 64, g0 + rank * 2);
                        int d = 0;
                        if (!ok) {
                            d = 1;
                            if (i == 3) {
                                uwait(FLG(F_H + lc), H_TGT);
                                ok = true;
                                d = -3;
                                TT(4);
                            }
                        }
#pragma unroll 1
                        for (; d <= 0; d++) {
                            const uint32_t s2 = (s + d) & 3;
                            if (lm) tma_load_2d_mc(sb0 + s2 * BK_STAGE_BYTES + rank * 8192, &M.h, full0 + 8 * s2, (i + d) * 64, lc * 128 + rank * 64);
                            else tma_load_2d(sb0 + s2 * BK_STAGE_BYTES, &M.h2, full0 + 8 * s2, (i + d) * 64, lc * 128);
                        }
                    } else if (i < 13) {
#pragma unroll 1
                        for (int k = 0, bx = (i - 10) * 3; k < 3 && bx < 8; k++, bx++)
                            tma_load_2d(sa + k * 16384, &M.kv, fb, (g0 + (bx & 3)) * 64, (bx >> 2) * S_LEN + (lc & 15) * 128);
                    } else if (i < 24) {
                        const int cn = ((i - 14) >> 1) * 128, ck = g0 * 64 + (i & 1) * 128;
                        if (i > 13) {
                            if (lm) { tma_load_2d(sa, &M.wo, fb, cn, ck); tma_load_2d(sa + 16384, &M.wo, fb, cn + 64, ck); }
                            else tma_load_2d_mc(sa + rank * 16384, &M.wo, fb, cn + rank * 64, ck);
                        }
                        if (i == imem) {
                            TT(5);
                            if (i == 16) uwait(FLG(F_MEM + lc), MEM_TGT);
                            const uint32_t s2 = (s + (i >> 4)) & 3;
#pragma unroll 1
                            for (int k = 0; k < 4; k++)
                                bulk_load(sb0 + s2 * BK_STAGE_BYTES + k * 8192, g_kvf + (size_t)((lc * CSEG + k) * NH + jj * 2) * 256, 8192, full0 + 8 * s2);
                            TT(6);
                        }
                    } else if (i == 25) {
                        tma_load_2d(sa, &M.lu, fb, 0, (2 * jj + rank) * 256);
                    } else if (i == 26) {
#pragma unroll 1
                        for (int k = 0; k < 8; k++)
                            bulk_load(sa + k * CV_EP + 128, A.ssmk + (size_t)((2 * jj + rank) * 8 + k) * S_LEN, 4096, fb);
                    }
                }
                if (type != 3) TT(7);
                if (rank == 0) {
                    if (!have) {
                        if (type == 3) { guard++; __nanosleep(64); }
                        code = 3 << 6;
                        continue;
                    }
                } else {
                    const uint32_t o = (tc & 3) * 4;
                    mwait(tfull0 + 2 * o, (tc >> 2) & 1);
                    ncode = (int)UNI(lds32(task0 + o));
                    asm volatile(ELECT "mbarrier.arrive.expect_tx.shared::cta.b64 _, [%0], 4;\n@p mbarrier.arrive.shared::cluster.b64 _, [%1];\n}" ::"r"(tfull0 + 2 * o), "r"(mapa(tempty0 + 2 * o, 0)) : "memory");
                    __syncwarp();
                }
                tc++;
                if (ncode < 0) break;
                TT(0); TTV(15, ncode);
                code = ((ncode & 256) ? (2 * ncode + rank) & 63 : ncode & 63) | (ncode & 0x1c0) | ((ncode >> (rank ? 14 : 9)) & 31) << 9 | ((ncode >> (19 + rank)) & 1) << 14;
                fence_async();
            }
        } else if (wid == 1) {
            if (lane < 8) asm volatile("prefetch.tensormap [%0];" ::"l"(&M.h + lane) : "memory");
            __syncwarp();
            if (lane == 0) {
                uint32_t rc = 0;
                while (true) {
                    mwait(tfull0 + 8 * (tc & 3), (tc >> 2) & 1);
                    const int code = (int)lds32(task0 + 4 * (tc & 3));
                    mbar_arrive_cluster(mapa(tempty0 + 8 * (tc & 3), 0));
                    tc++;
                    if (code < 0) break;
                    const int type = (code >> 6) & 3;
                    const int lc = (code >> (rank ? 14 : 9)) & 31;
                    mwait(sfull + 8 * (rc & 3), (rc >> 2) & 1);
                    if (type == T_CONV) {
                        asm volatile("cp.async.bulk.global.shared::cta.bulk_group [%0], [%1], %2;" ::"l"(g_Y + (size_t)((2 * (code & 63) + rank) * S_LEN + lc * 1024) * 8), "r"(sb0 + BULK_STG), "r"(16384) : "memory");
                        bulk_commit();
                        bulk_wait<0>();
                    }
                    mbar_arrive(sempty + 8 * (rc & 3));
                    rc++;
                    FT(0);
                    red_release(type == T_QA ? FLG(F_OP + lc) + 4 : FLG((type == T_KV ? F_KV : F_CONV) + lc), 1);
                    FT(1);
                    BT(true, type, lc >> 4, lc & 15, 2);
                }
            }
        } else {
            const int nw = 2 * gridDim.x, idx = (wid - 2) * gridDim.x + blockIdx.x;
#pragma unroll 1
            for (int hh = 0; hh < 2; hh++) {
#pragma unroll 1
                for (int u = hh * 640 + idx; u < hh * 640 + 640; u += nw) u_unit(A.Bk, A.Bv, A.shiftk, u, lane);
                __syncwarp();
                if (lane == 0) red_release(FLG(F_U + hh), 1);
                BT(lane == 0, T_LN0, hh, 0, 2);
            }
#pragma unroll 1
            for (int q = 0; q < 2 * (NCHK + PDIST); q++) {
                const int l = q & 1, c = (q >> 1) - l * PDIST;
                if (c < 0 || c >= NCHK) continue;
#pragma unroll 1
                for (int rr = idx; rr < 128; rr += nw) post_row(l, c * 128 + rr, lane, l ? g_x : A.x, l ? A.out : g_x);
                BT(lane == 0, T_POST, l, c, 2);
            }
        }
    } else {
        asm volatile("setmaxnreg.inc.sync.aligned.u32 %0;" ::"n"(REG_C));
        const int cw = (wid >> 2) - 1, warp = wid & 3;
        const uint32_t wst = sb0 + BULK_STG + (cw * 4 + warp) * 4096;
        uint32_t rc = 0;
        int npend = 0;
        bool urgent = false;
        uint32_t oofs = 0;
        uint32_t qf[16][4];
        auto release = [&](int s) { if ((tid & 127) == 0) { mbar_arrive(empty0 + 8 * s); mbar_arrive_cluster(mapa(empty0 + 8 * s, rank ^ 1)); } };
        auto next = [&]() -> int { const int s = it & 3; mwait(full0 + 8 * s, (it >> 2) & 1); it++; return s; };
        auto wgbar = [&]() { if (cw == 0) named_bar(2, 128); else named_bar(3, 128); };
        auto handoff = [&]() {
            mwait(sempty + 8 * (rc & 3), ((rc >> 2) & 1) ^ 1);
            asm volatile(ELECT "mbarrier.arrive.shared::cta.b64 _, [%0];\n}" ::"r"(sfull + 8 * (rc & 3)) : "memory");
            rc++;
        };
        auto stg_free = [&]() { mwait(sempty + 8 * ((rc - 1) & 3), ((rc - 1) >> 2) & 1); };
        auto round_q = [&]() {
            if (npend > 4) {
                uint4* d = reinterpret_cast<uint4*>(g_part) + oofs;
                if (npend == 6) {
#pragma unroll
                    for (int i = 0; i < 4; i++) red_add8(d + (i >> 1) * 4 + (i & 1) * (8 * PG * DM / 8), qf[i][0], qf[i][1], qf[i][2], qf[i][3]);
                    npend = 5;
                } else {
#pragma unroll
                    for (int i = 4; i < 8; i++) red_add8(d + (i >> 1) * 4 + (i & 1) * (8 * PG * DM / 8), qf[i][0], qf[i][1], qf[i][2], qf[i][3]);
                    npend = 0;
                    handoff();
                }
                return;
            }
            const uint32_t sst = wst + (lane & 15) * 128 + (((lane >> 4) ^ (lane & 7)) << 4) + (npend & 1) * 2048;
#pragma unroll
            for (int q = 0; q < 4; q++)
                if (npend == 4 - q) {
#pragma unroll
                    for (int i = 0; i < 4; i++) stsm_x4(sst ^ (i << 5), qf[q * 4 + i][0], qf[q * 4 + i][1], qf[q * 4 + i][2], qf[q * 4 + i][3]);
                }
            __syncwarp();
            uint4* d = reinterpret_cast<uint4*>(&g_kv[0][0]) + oofs;
            const uint32_t src = wst + (lane >> 3) * 128 + (((lane & 7) ^ (lane >> 3)) << 4) + (npend & 1) * 2048;
#pragma unroll
            for (int i = 0; i < 4; i++) d[i * (4 * HD / 8)] = lds128((src + i * 512) ^ ((i & 1) << 6));
            oofs += 8;
            if (--npend == 0) handoff();
        };
        auto round_a = [&](const float* a, int hh) {
            uint4* d = reinterpret_cast<uint4*>(g_part) + oofs;
#pragma unroll
            for (int i = hh * 4; i < hh * 4 + 4; i++) {
                const float* b = a + (i >> 1) * 16 + (i & 1) * 2;
                red_add8(d + (i >> 1) * 4 + (i & 1) * (8 * PG * DM / 8), pack2(b[0], b[1]), pack2(b[4], b[5]), pack2(b[8], b[9]), pack2(b[12], b[13]));
            }
            if (hh) oofs += 16;
        };
        while (true) {
            tc++; TT(0); tc--;
            int code;
            while (true) {
                if (npend == 0) mwait(tfull0 + 8 * (tc & 3), (tc >> 2) & 1);
                if (npend == 0 || UNI(mtest(tfull0 + 8 * (tc & 3), (tc >> 2) & 1))) {
                    code = (int)UNI(lds32(task0 + 4 * (tc & 3)));
                    if (npend == 0 || ((code & 0x80) == 0 && !urgent && UNI(mtest(full0 + 8 * (it & 3), (it >> 2) & 1)))) break;
                }
                round_q();
            }
            if (lane == 0) mbar_arrive_cluster(mapa(tempty0 + 8 * (tc & 3), 0));
            tc++;
            TT(2);
            if (code < 0) break;
            const int type = (code >> 6) & 3;
            TTV(15, code);
#define BTC(type, k)
            if (type == T_CONV) {
                const int m = (code >> 9) & 1;
                BT((tid & 127) == 0, T_CONV, 0, m, 0);
                const int u = 2 * (code & 63) + rank, ch = cw * 4 + warp;
                int lane = tid & 31;
                asm volatile("" : "+r"(lane));
                const float Dv = bf2f(A.ssmD[u * 8 + ch]);
                const int sd = next(), s0 = next(), s1 = next(), s2 = next();
                TT(3);
                const uint32_t e1 = sb0 + s2 * BK_STAGE_BYTES;
                conv_unit(sb0 + s0 * BK_STAGE_BYTES + ch * 4096, sb0 + s1 * BK_STAGE_BYTES + ch * CV_EP, e1 + 64 + ch * CV_EP, e1 + 40960 + ch * 128, sb0 + BULK_STG + ch * 2, Dv, m, lane,
                          [&]() { release(sd); stg_free(); });
                asm volatile("fence.proxy.async.shared::cta;" ::: "memory");
                __syncwarp();
                handoff();
                TT(5);
                wgbar();
                release(s0); release(s1); release(s2);
                __syncwarp();
#pragma unroll
                for (int i = 0; i < 64; i++) qf[i >> 2][i & 3] = 0;
                continue;
            }
            float acc[128];
            {
                int s = next();
                TT(3); BTC(type, 0); BTC(type, 1);
                uint32_t sa = sb0 + s * BK_STAGE_BYTES + cw * 8192, sb = sb0 + s * BK_STAGE_BYTES + 16384;
                wg_fence();
                wgmma_m64n256k16_first(acc, make_desc(sa, 16, 1024), make_desc(sb, 8192, 1024));
#pragma unroll 1
                for (int kb = 0;;) {
#pragma unroll
                    for (int k = 1; k < 4; k++) wgmma_m64n256k16(acc, make_desc(sa + k * 32, 16, 1024), make_desc(sb + k * 2048, 8192, 1024));
                    wg_commit();
                    if (npend) round_q();
                    if (kb) { wg_wait<1>(); release((s - 1) & 3); }
                    if (++kb == 10) break;
                    s = next();
                    sa = sb0 + s * BK_STAGE_BYTES + cw * 8192; sb = sb0 + s * BK_STAGE_BYTES + 16384;
                    wg_fence();
                    wgmma_m64n256k16(acc, make_desc(sa, 16, 1024), make_desc(sb, 8192, 1024));
                }
            }
            wg_wait<0>();
            TT(4);
            release((it - 1) & 3);
            stg_free();
#pragma unroll
            for (int i = 0; i < 16; i++)
#pragma unroll
                for (int e = 0; e < 4; e++) qf[i][e] = pack2(acc[i * 8 + e * 2], acc[i * 8 + e * 2 + 1]);
            {
                const int cd = (int)lds32(task0 + 4 * ((tc - 1) & 3)), lc = (cd >> (rank ? 14 : 9)) & 31, jj = (cd & 256) ? (2 * cd + rank) & 63 : cd & 63;
                const int r0 = cw * 64 + warp * 16;
                if (type == T_KV) {
                    oofs = ((jj >> 4) * S_LEN + (lc & 15) * 128 + r0 + (lane >> 3)) * (HD / 8) + (jj & 15) * 32 + (lane & 7);
                    npend = 4;
                    urgent = URGENT && (lc < 2 || lc >= 16);
                    continue;
                }
                oofs = (((lc >> 4) * PRING + (lc & (PRING - 1))) * 128 + r0 + (lane >> 2)) * (PG * DM / 8) + (jj & (PG - 1)) * (DM / 8) + (lane & 3);
            }
            const float cs = 1.4426950408889634f;
            int lane = tid & 31;
            asm volatile("" : "+r"(lane));
            const int g = lane >> 2, tq = lane & 3;
            const int sg = cw * 2 + (warp >> 1), hs = warp & 1;
            float mt[2][2], sum[2][2];
            {
                const int x0 = next(), x1 = next();
                TT(5);
                float s[2][4][4];
#pragma unroll
                for (int hd = 0; hd < 2; hd++)
#pragma unroll
                    for (int n = 0; n < 4; n++)
#pragma unroll
                        for (int e = 0; e < 4; e++) s[hd][n][e] = 0.f;
                const uint32_t krow = (sg * 32 + (lane & 7) + (lane >> 4) * 8) * 128 + ((((lane >> 3) & 1) ^ (lane & 7)) << 4);
#pragma unroll
                for (int ii = 0; ii < 16; ii++) {
                    const int i = (ii >> 1) + (ii & 1) * 8;
                    const uint32_t kb = sb0 + (i < 12 ? x0 * BK_STAGE_BYTES + (i >> 2) * 16384 : x1 * BK_STAGE_BYTES) + (krow ^ ((i & 3) << 5));
                    const uint4 k0 = ldsm4(kb), k1 = ldsm4(kb + 2048);
                    mma16816(s[i >> 3][0], qf[i][0], qf[i][1], qf[i][2], qf[i][3], k0.x, k0.y);
                    mma16816(s[i >> 3][1], qf[i][0], qf[i][1], qf[i][2], qf[i][3], k0.z, k0.w);
                    mma16816(s[i >> 3][2], qf[i][0], qf[i][1], qf[i][2], qf[i][3], k1.x, k1.y);
                    mma16816(s[i >> 3][3], qf[i][0], qf[i][1], qf[i][2], qf[i][3], k1.z, k1.w);
                }
#pragma unroll
                for (int i = 0; i < 8; i++) sts128(wst + i * 512 + lane * 16, qf[8 + i][0], qf[8 + i][1], qf[8 + i][2], qf[8 + i][3]);
                wgbar();
                release(x0);
                TT(6);
                uint32_t pa[2][4][2];
#pragma unroll
                for (int hd = 0; hd < 2; hd++) {
                    uint32_t mx[2] = {0xff80ff80u, 0xff80ff80u};
#pragma unroll
                    for (int n = 0; n < 4; n++)
#pragma unroll
                        for (int r = 0; r < 2; r++) {
                            const int d = hs * 16 + g + r * 8 - n * 8 - tq * 2;
                            pa[hd][n][r] = rscore(d < 0 ? -INFINITY : s[hd][n][2 * r], d < 1 ? -INFINITY : s[hd][n][2 * r + 1]);
                            mx[r] = bmax2(mx[r], pa[hd][n][r]);
                        }
#pragma unroll
                    for (int r = 0; r < 2; r++) {
                        mx[r] = bmax2(mx[r], __shfl_xor_sync(0xffffffffu, mx[r], 1));
                        mx[r] = bmax2(mx[r], __shfl_xor_sync(0xffffffffu, mx[r], 2));
                        mt[hd][r] = fmaxf(blo(mx[r]), bhi(mx[r])) * cs;
                        sum[hd][r] = 0.f;
                    }
#pragma unroll
                    for (int n = 0; n < 4; n++)
#pragma unroll
                        for (int r = 0; r < 2; r++) {
                            const float p0 = ex2f(fmaf(blo(pa[hd][n][r]), cs, -mt[hd][r])), p1 = ex2f(fmaf(bhi(pa[hd][n][r]), cs, -mt[hd][r]));
                            sum[hd][r] += p0 + p1;
                            pa[hd][n][r] = pack2(p0, p1);
                        }
                }
                const uint32_t vrow = (sg * 32 + (lane & 15)) * 128 + (((lane >> 4) ^ (lane & 7)) << 4);
                int xv = x1;
#pragma unroll
                for (int hd = 0; hd < 2; hd++) {
                    if (hd == 1) xv = next();
#pragma unroll
                    for (int i = 0; i < 8; i++) {
                        const uint32_t vb = sb0 + xv * BK_STAGE_BYTES + (hd == 0 ? 16384 : 0) + (i >> 2) * 16384 + (vrow ^ ((i & 3) << 5));
                        uint4 v0, v1;
                        ldsm_x4_t(v0.x, v0.y, v0.z, v0.w, vb);
                        ldsm_x4_t(v1.x, v1.y, v1.z, v1.w, vb + 2048);
                        float* o = acc + hd * 64 + i * 8;
#pragma unroll
                        for (int e = 0; e < 8; e++) o[e] = 0.f;
                        mma16816(o, pa[hd][0][0], pa[hd][0][1], pa[hd][1][0], pa[hd][1][1], v0.x, v0.y);
                        mma16816(o + 4, pa[hd][0][0], pa[hd][0][1], pa[hd][1][0], pa[hd][1][1], v0.z, v0.w);
                        mma16816(o, pa[hd][2][0], pa[hd][2][1], pa[hd][3][0], pa[hd][3][1], v1.x, v1.y);
                        mma16816(o + 4, pa[hd][2][0], pa[hd][2][1], pa[hd][3][0], pa[hd][3][1], v1.z, v1.w);
                    }
                    wgbar();
                    release(xv);
                }
            }
            TT(7);
            BTC(T_ATT, 0);
            {
                const int xm = next();
                TT(8);
                BTC(T_ATT, 1);
                const uint32_t mb = sb0 + xm * BK_STAGE_BYTES + sg * 8192 + lane * 16;
                float sm[2][2][4];
#pragma unroll
                for (int i = 0; i < 16; i++) (&sm[0][0][0])[i] = 0.f;
#pragma unroll
                for (int q = 0; q < 4; q++) {
                    const uint4 k0 = lds128(mb + q * 512), k1 = lds128(mb + 4096 + q * 512);
                    const uint4 qa = lds128(wst + q * 1024 + lane * 16), qb = lds128(wst + q * 1024 + 512 + lane * 16);
                    mma16816(sm[0][0], qf[2 * q][0], qf[2 * q][1], qf[2 * q][2], qf[2 * q][3], k0.x, k0.y);
                    mma16816(sm[0][1], qf[2 * q + 1][0], qf[2 * q + 1][1], qf[2 * q + 1][2], qf[2 * q + 1][3], k0.z, k0.w);
                    mmau(sm[1][0], qa, k1.x, k1.y);
                    mmau(sm[1][1], qb, k1.z, k1.w);
                }
                float f[2][2];
                uint32_t pm[2][2];
#pragma unroll
                for (int hd = 0; hd < 2; hd++)
#pragma unroll
                    for (int r = 0; r < 2; r++) {
                        const uint32_t w = rscore(sm[hd][0][2 * r] + sm[hd][1][2 * r], sm[hd][0][2 * r + 1] + sm[hd][1][2 * r + 1]);
                        const float s0 = blo(w) * cs, s1 = bhi(w) * cs;
                        float m = fmaxf(s0, s1);
                        m = fmaxf(m, __shfl_xor_sync(0xffffffffu, m, 1));
                        m = fmaxf(fmaxf(m, __shfl_xor_sync(0xffffffffu, m, 2)), mt[hd][r]);
                        const float a = ex2f(mt[hd][r] - m), p0 = ex2f(s0 - m), p1 = ex2f(s1 - m);
                        float t = fmaf(sum[hd][r], a, p0 + p1);
                        t += __shfl_xor_sync(0xffffffffu, t, 1);
                        t += __shfl_xor_sync(0xffffffffu, t, 2);
                        t = rcpf(t);
                        f[hd][r] = a * t;
                        pm[hd][r] = pack2(p0 * t, p1 * t);
                    }
#pragma unroll
                for (int q = 0; q < 8; q++) {
                    const int hd = q >> 2;
                    const uint4 vm = lds128(mb + hd * 4096 + 2048 + (q & 3) * 512);
                    float* o = acc + q * 16;
#pragma unroll
                    for (int e = 0; e < 16; e++) o[e] *= f[hd][(e >> 1) & 1];
                    mma1688(o, pm[hd][0], pm[hd][1], vm.x);
                    mma1688(o + 4, pm[hd][0], pm[hd][1], vm.y);
                    mma1688(o + 8, pm[hd][0], pm[hd][1], vm.z);
                    mma1688(o + 12, pm[hd][0], pm[hd][1], vm.w);
#pragma unroll
                    for (int e = 0; e < 8; e++) qf[q * 2 + (e >> 2)][e & 3] = pack2(o[2 * e], o[2 * e + 1]);
                }
                wgbar();
                release(xm);
            }
            TT(9);
#pragma unroll
            for (int t = 0; t < 10; t++) {
                const int s = next();
                const uint32_t sb = sb0 + s * BK_STAGE_BYTES;
                float* d = acc + ((t >> 1) & 1) * 64;
                wg_fence();
#pragma unroll
                for (int k = 0; k < 8; k++) {
                    const uint64_t db = make_desc(sb + k * 2048, 16384, 1024);
                    if (k == 0 && !(t & 1)) wgmma_rs_m64n128k16_first(d, qf[k], db);
                    else wgmma_rs_m64n128k16(d, qf[(t & 1) * 8 + k], db);
                }
                wg_commit();
                if (t) {
                    wg_wait<1>();
                    release((s - 1) & 3);
                    if (t > 1) round_a(acc + (((t >> 1) & 1) ^ 1) * 64, t & 1);
                }
            }
            wg_wait<0>();
            release((it - 1) & 3);
            TT(10);
#pragma unroll
            for (int i = 0; i < 32; i++) qf[i >> 2][i & 3] = pack2(acc[(i >> 3) * 16 + (i & 4) / 2 + (i & 3) * 4], acc[(i >> 3) * 16 + (i & 4) / 2 + (i & 3) * 4 + 1]);
            npend = 6;
            urgent = URGENT > 1;
        }
    }
    cluster_sync_all();
}

__global__ void __launch_bounds__(256) reset_kernel(const bf16* x, int g0, int ncl) {
    const int lane = threadIdx.x & 31, row = blockIdx.x * 8 + (threadIdx.x >> 5);
    uint32_t r[10];
    ld5<128>(r, x + (size_t)row * DM + lane * 4);
    if (blockIdx.x == 0)
        for (int i = threadIdx.x; i < NFLAG * 2; i += blockDim.x) reinterpret_cast<uint4*>(FLG(i >> 1))[i & 1] = make_uint4(i == g0 ? min(ncl, 32) : (i == g0 + 2 ? max(ncl - 32, 0) : 0), 0, 0, 0);
    for (int i = blockIdx.x * 256 + threadIdx.x; i < 2 * PROWS * PG * DM / 8; i += S_LEN * 32) reinterpret_cast<uint4*>(g_part)[i] = make_uint4(0, 0, 0, 0);
    ln_row(r, r);
    st5(g_h[0] + (size_t)row * DM + lane * 4, r);
    if (blockIdx.x) return;
}

typedef CUresult (*PFN_encodeTiled)(CUtensorMap*, CUtensorMapDataType, cuuint32_t, void*, const cuuint64_t*, const cuuint64_t*,
                                    const cuuint32_t*, const cuuint32_t*, CUtensorMapInterleave, CUtensorMapSwizzle,
                                    CUtensorMapL2promotion, CUtensorMapFloatOOBfill);
static PFN_encodeTiled get_encode() {
    static PFN_encodeTiled fn = nullptr;
    if (!fn) {
        void* p = nullptr;
        cudaDriverEntryPointQueryResult qr;
        cudaGetDriverEntryPoint("cuTensorMapEncodeTiled", &p, cudaEnableDefault, &qr);
        fn = (PFN_encodeTiled)p;
    }
    return fn;
}
static void make_map(CUtensorMap* m, const void* ptr, uint64_t rows, uint64_t cols, uint32_t box_rows) {
    cuuint64_t dims[2] = {cols, rows};
    cuuint64_t strides[1] = {cols * 2};
    cuuint32_t box[2] = {64u, box_rows};
    cuuint32_t es[2] = {1, 1};
    get_encode()(m, CU_TENSOR_MAP_DATA_TYPE_BFLOAT16, 2, const_cast<void*>(ptr), dims, strides, box, es,
                 CU_TENSOR_MAP_INTERLEAVE_NONE, CU_TENSOR_MAP_SWIZZLE_128B, CU_TENSOR_MAP_L2_PROMOTION_L2_128B,
                 CU_TENSOR_MAP_FLOAT_OOB_FILL_NONE);
}
static void make_map3(CUtensorMap* m, const void* ptr) {
    cuuint64_t dims[3] = {64, DM, HD / 64};
    cuuint64_t strides[2] = {HD * 2, 128};
    cuuint32_t box[3] = {64u, 64u, 2u};
    cuuint32_t es[3] = {1, 1, 1};
    get_encode()(m, CU_TENSOR_MAP_DATA_TYPE_BFLOAT16, 3, const_cast<void*>(ptr), dims, strides, box, es,
                 CU_TENSOR_MAP_INTERLEAVE_NONE, CU_TENSOR_MAP_SWIZZLE_128B, CU_TENSOR_MAP_L2_PROMOTION_L2_128B,
                 CU_TENSOR_MAP_FLOAT_OOB_FILL_NONE);
}
#define QA_PRE0 4
#define KV1_E 1
#define KV1_L 16
#define KV0_X 6
#define CONV0_AT 1
#define CONV1_AT 9
static void build_sched(Sched& S, int naux) {
    int n = 0;
    auto ck = [](int f, int t) { return (uint32_t)(f * 32) | (uint32_t)t << 16; };
    auto add = [&](int lm, int type, int la, int ca, int lb, int cb, int ntask, uint32_t soft) {
        S.info[n] = (uint32_t)(type << 6 | lm << 8 | (la * 16 + ca) << 9 | (lb * 16 + cb) << 14);
        S.chk[n * 4] = ck(F_CNT + n, ntask); S.chk[n * 4 + 1] = soft;
        S.chk[n * 4 + 2] = ck(F_H + la * NCHK + ca, H_TGT); S.chk[n * 4 + 3] = ck(F_H + lb * NCHK + cb, H_TGT);
        n++;
    };
    for (int i = 0; i < MAXG * 4; i++) S.chk[i] = ck(F_ZERO, 0);
    for (int i = 0; i < MAXG; i++) S.info[i] = 0;
    S.sbeg[0] = n;
    for (int i = 0; i < NCHK; i++) {
        add(1, T_KV, 1, i, 1, i, 16, i < KV1_E || i >= KV1_L ? ck(F_OP + i, 14) + 4 : ck(F_H + NCHK + i, KV1_N));
        S.chk[n * 4 - 2] = S.chk[n * 4 - 1] = ck(F_CONV + i / 8, CONV_TGT);
    }
    S.sbeg[1] = n;
    auto addqa = [&]() {
    for (int p = 0; p < NCHK + PDIST; p++) {
        const bool h0 = p < NCHK, h1 = p >= PDIST;
        const int la = h0 ? 0 : 1, ca = h0 ? p : p - PDIST, lb = h1 ? 1 : 0, cb = h1 ? p - PDIST : p;
        const int ta = ca * CSEG + CSEG + la * LAG;
        add(!(h0 && h1), T_QA, la, ca, lb, cb, h0 && h1 ? 16 : 8,
            ck(F_PROG, h1 ? ta - QA_PRE : (ta > QA_PRE0 ? ta - QA_PRE0 : 0)));
        S.info[n - 1] |= 3u << 19;
        S.chk[n * 4 - 2] = h0 && ca >= PRING ? ck(F_H + NCHK + ca - PRING + 1, H_TGT) : ck(F_ZERO, 0);
        S.chk[n * 4 - 1] = !h1 ? ck(F_KV + ca, KV_TGT) : (cb >= PRING ? ck(F_OP + NCHK + cb - PRING, 128) + 5 : ck(F_ZERO, 0));
    }
    };
    auto addkv = [&]() {
    for (int i = 0; i < NCHK; i += 2) add(0, T_KV, 0, i, 0, i + 1, 32, ck(F_PROG, 4 * i > KV0_X + 1 ? 4 * i - KV0_X : 1)), S.chk[n * 4 - 2] = S.chk[n * 4 - 1] = ck(F_ZERO, 0);
    };
    addqa();
    S.sbeg[2] = n;
    for (int m = 0; m < 2; m++) {
        add(0, T_CONV, 0, m, 0, m, 40, ck(F_U + m, naux));
        S.chk[n * 4 - 2] = S.chk[n * 4 - 1] = ck(F_CNT + S.sbeg[2] + 2 + (m ? CONV1_AT : CONV0_AT) / 2, 32);
    }
    S.sbeg[3] = n;
    addkv();
    S.sbeg[4] = n;
}

static void launch_all(void* const* d_in, void* d_out) {
    const bf16* x = (const bf16*)d_in[0];
    const bf16* mem0 = (const bf16*)d_in[1];
    const bf16* Wq = (const bf16*)d_in[2];
    const bf16* Wk = (const bf16*)d_in[3];
    const bf16* Wv = (const bf16*)d_in[4];
    const bf16* Wo = (const bf16*)d_in[5];
    static bool inited = false;
    static int nsm = 132;
    static Sched SC;
    bf16 *p_h, *p_kv, *p_u;
    cudaGetSymbolAddress((void**)&p_h, g_h);
    cudaGetSymbolAddress((void**)&p_kv, g_kv);
    cudaGetSymbolAddress((void**)&p_u, g_U);
    if (!inited) {
        inited = true;
        cudaDeviceGetAttribute(&nsm, cudaDevAttrMultiProcessorCount, 0);
        cudaFuncSetAttribute(chain_kernel, cudaFuncAttributeMaxDynamicSharedMemorySize, (int)sizeof(ChainSmem));
        cudaFuncSetAttribute(chain_kernel, cudaFuncAttributeNonPortableClusterSizeAllowed, 1);
        cudaFuncSetAttribute(bulk_kernel, cudaFuncAttributeMaxDynamicSharedMemorySize, BULK_SMEM);
        build_sched(SC, 2 * ((nsm - 64) & ~1));
    }
    const size_t QS = (size_t)S_LEN * HD;
    BulkMaps M;
    make_map(&M.h, p_h, 2 * S_LEN, DM, 64);
    make_map(&M.h2, p_h, 2 * S_LEN, DM, 128);
    make_map3(&M.wq, Wq);
    make_map3(&M.wk, Wk);
    make_map3(&M.wv, Wv);
    make_map(&M.wo, Wo, HD, DM, 128);
    make_map(&M.kv, p_kv, 2 * S_LEN, HD, 128);
    make_map(&M.lu, p_u, DM * 32, 64, 256);
    BulkArgs BA;
    BA.x = x; BA.out = (bf16*)d_out;
    BA.Bk = (const bf16*)d_in[8]; BA.Bv = (const bf16*)d_in[9]; BA.shiftk = (const bf16*)d_in[10];
    BA.ssmk = (const bf16*)d_in[11]; BA.ssmD = (const bf16*)d_in[12];
    ChainArgs ca;
    for (int l = 0; l < 2; l++) {
        make_map(&ca.tk[l], p_kv, S_LEN, HD, 32);
        make_map(&ca.tv[l], p_kv + QS, S_LEN, HD, 32);
    }
    ca.x = x; ca.mem0 = mem0; ca.Wq = Wq; ca.Wk = Wk; ca.Wv = Wv; ca.Wo = Wo; ca.kv_target = KV_TGT;
    cudaStream_t s = cudaStreamPerThread;
    reset_kernel<<<S_LEN / 8, 256, 0, s>>>(x, 2 * (F_CNT + SC.sbeg[3]), (nsm - 64) / 2);
    {
        cudaLaunchConfig_t cfg = {};
        cfg.gridDim = dim3(64); cfg.blockDim = dim3(CHAIN_THREADS); cfg.dynamicSmemBytes = sizeof(ChainSmem); cfg.stream = s;
        cudaLaunchAttribute at[1];
        at[0].id = cudaLaunchAttributeClusterDimension;
        at[0].val.clusterDim.x = CL; at[0].val.clusterDim.y = 1; at[0].val.clusterDim.z = 1;
        cfg.attrs = at; cfg.numAttrs = 1;
        cudaLaunchKernelEx(&cfg, chain_kernel, ca);
    }
    {
        cudaLaunchConfig_t cfg = {};
        cfg.gridDim = dim3((nsm - 64) & ~1); cfg.blockDim = dim3(384); cfg.dynamicSmemBytes = BULK_SMEM; cfg.stream = s;
        cudaLaunchAttribute at[2];
        at[0].id = cudaLaunchAttributeProgrammaticStreamSerialization;
        at[0].val.programmaticStreamSerializationAllowed = 1;
        at[1].id = cudaLaunchAttributeClusterDimension;
        at[1].val.clusterDim.x = 2; at[1].val.clusterDim.y = 1; at[1].val.clusterDim.z = 1;
        cfg.attrs = at; cfg.numAttrs = 2;
        cudaLaunchKernelEx(&cfg, bulk_kernel, M, BA, SC);
    }
}
}

extern "C" void kernel_launch(void* const* d_in, const int* in_sizes, int n_in, void* d_out, int out_size) {
    (void)in_sizes; (void)n_in; (void)out_size;
    if (ws::usable()) ws::launch_all(d_in, d_out);
    else ni::launch_all(d_in, d_out);
}
```

```cpp
#include <cuda_runtime.h>
#include <cuda_bf16.h>
#include <stdint.h>
#include <cuda.h>

typedef __nv_bfloat16 bf16;
namespace ws {
constexpr int S_LEN = 2048, DM = 640, NH = 32, DH = 128, HD = NH * DH, SEG = 32, NSEG = S_LEN / SEG;

__device__ __forceinline__ float bf2f(bf16 v) { return __bfloat162float(v); }
__device__ __forceinline__ float rbf(float v) { return __bfloat162float(__float2bfloat16_rn(v)); }
__device__ __forceinline__ uint32_t pack2(float a, float b) {
    __nv_bfloat162 t = __floats2bfloat162_rn(a, b);
    return *reinterpret_cast<uint32_t*>(&t);
}
__device__ __forceinline__ float blo(uint32_t v) { return __uint_as_float(v << 16); }
__device__ __forceinline__ float bhi(uint32_t v) { return __uint_as_float(v & 0xffff0000u); }
__device__ __forceinline__ uint32_t badd(uint32_t a, uint32_t b) { uint32_t r; asm("add.rn.bf16x2 %0, %1, %2;" : "=r"(r) : "r"(a), "r"(b)); return r; }
__device__ __forceinline__ uint32_t smem_u32(const void* p) { return (uint32_t)__cvta_generic_to_shared(p); }
__device__ __forceinline__ uint4 ldsm4(uint32_t a) {
    uint4 v;
    asm volatile("ldmatrix.sync.aligned.m8n8.x4.shared.b16 {%0,%1,%2,%3}, [%4];" : "=r"(v.x), "=r"(v.y), "=r"(v.z), "=r"(v.w) : "r"(a));
    return v;
}
__device__ __forceinline__ uint4 ldsm4t(uint32_t a) {
    uint4 v;
    asm volatile("ldmatrix.sync.aligned.m8n8.x4.trans.shared.b16 {%0,%1,%2,%3}, [%4];" : "=r"(v.x), "=r"(v.y), "=r"(v.z), "=r"(v.w) : "r"(a));
    return v;
}
__device__ __forceinline__ void stsm4(uint32_t a, uint32_t r0, uint32_t r1, uint32_t r2, uint32_t r3) {
    asm volatile("stmatrix.sync.aligned.m8n8.x4.shared.b16 [%0], {%1,%2,%3,%4};" ::"r"(a), "r"(r0), "r"(r1), "r"(r2), "r"(r3) : "memory");
}
__device__ __forceinline__ void stsm4t(uint32_t a, uint32_t r0, uint32_t r1, uint32_t r2, uint32_t r3) {
    asm volatile("stmatrix.sync.aligned.m8n8.x4.trans.shared.b16 [%0], {%1,%2,%3,%4};" ::"r"(a), "r"(r0), "r"(r1), "r"(r2), "r"(r3) : "memory");
}
__device__ __forceinline__ void mma16816(float* c, uint32_t a0, uint32_t a1, uint32_t a2, uint32_t a3, uint32_t b0, uint32_t b1) {
    asm("mma.sync.aligned.m16n8k16.row.col.f32.bf16.bf16.f32 {%0,%1,%2,%3}, {%4,%5,%6,%7}, {%8,%9}, {%0,%1,%2,%3};"
        : "+f"(c[0]), "+f"(c[1]), "+f"(c[2]), "+f"(c[3]) : "r"(a0), "r"(a1), "r"(a2), "r"(a3), "r"(b0), "r"(b1));
}
__device__ __forceinline__ void mmav(float* c, uint32_t a0, uint32_t a1, uint32_t a2, uint32_t a3, uint32_t b0, uint32_t b1) {
    asm volatile("mma.sync.aligned.m16n8k16.row.col.f32.bf16.bf16.f32 {%0,%1,%2,%3}, {%4,%5,%6,%7}, {%8,%9}, {%0,%1,%2,%3};"
        : "+f"(c[0]), "+f"(c[1]), "+f"(c[2]), "+f"(c[3]) : "r"(a0), "r"(a1), "r"(a2), "r"(a3), "r"(b0), "r"(b1));
}
__device__ __forceinline__ void mmau(float* c, const uint4& a, uint32_t b0, uint32_t b1) { mma16816(c, a.x, a.y, a.z, a.w, b0, b1); }
__device__ __forceinline__ void mma1688(float* c, uint32_t a0, uint32_t a1, uint32_t b0) {
    asm("mma.sync.aligned.m16n8k8.row.col.f32.bf16.bf16.f32 {%0,%1,%2,%3}, {%4,%5}, {%6}, {%0,%1,%2,%3};"
        : "+f"(c[0]), "+f"(c[1]), "+f"(c[2]), "+f"(c[3]) : "r"(a0), "r"(a1), "r"(b0));
}
__device__ __forceinline__ void mmav8(float* c, uint32_t a0, uint32_t a1, uint32_t b0) {
    asm volatile("mma.sync.aligned.m16n8k8.row.col.f32.bf16.bf16.f32 {%0,%1,%2,%3}, {%4,%5}, {%6}, {%0,%1,%2,%3};"
        : "+f"(c[0]), "+f"(c[1]), "+f"(c[2]), "+f"(c[3]) : "r"(a0), "r"(a1), "r"(b0));
}
__device__ __forceinline__ void cp_async16(uint32_t dst, const void* src) { asm volatile("cp.async.cg.shared.global [%0], [%1], 16;" ::"r"(dst), "l"(src)); }
__device__ __forceinline__ void cp_commit() { asm volatile("cp.async.commit_group;"); }
template <int N> __device__ __forceinline__ void cp_wait() { asm volatile("cp.async.wait_group %0;" ::"n"(N)); }
__device__ __forceinline__ uint4 lds128(uint32_t a) {
    uint4 v;
    asm volatile("ld.shared.v4.u32 {%0,%1,%2,%3}, [%4];" : "=r"(v.x), "=r"(v.y), "=r"(v.z), "=r"(v.w) : "r"(a));
    return v;
}
__device__ __forceinline__ uint2 lds64(uint32_t a) {
    uint2 v;
    asm volatile("ld.shared.v2.u32 {%0,%1}, [%2];" : "=r"(v.x), "=r"(v.y) : "r"(a));
    return v;
}
__device__ __forceinline__ uint32_t lds32(uint32_t a) { uint32_t v; asm volatile("ld.shared.u32 %0, [%1];" : "=r"(v) : "r"(a)); return v; }
__device__ __forceinline__ void sts32(uint32_t a, uint32_t x) { asm volatile("st.shared.u32 [%0], %1;" ::"r"(a), "r"(x) : "memory"); }
__device__ __forceinline__ void sts64(uint32_t a, uint32_t x, uint32_t y) { asm volatile("st.shared.v2.u32 [%0], {%1,%2};" ::"r"(a), "r"(x), "r"(y) : "memory"); }
__device__ __forceinline__ void sts128(uint32_t a, uint32_t x, uint32_t y, uint32_t z, uint32_t w) {
    asm volatile("st.shared.v4.u32 [%0], {%1,%2,%3,%4};" ::"r"(a), "r"(x), "r"(y), "r"(z), "r"(w) : "memory");
}
__device__ __forceinline__ uint4 ld_relaxed_v4(const void* p) {
    uint4 v;
    asm volatile("ld.relaxed.gpu.global.v4.u32 {%0,%1,%2,%3}, [%4];" : "=r"(v.x), "=r"(v.y), "=r"(v.z), "=r"(v.w) : "l"(p) : "memory");
    return v;
}
__device__ __forceinline__ uint2 ld_relaxed_v2(const void* p) {
    uint2 v;
    asm volatile("ld.relaxed.gpu.global.v2.u32 {%0,%1}, [%2];" : "=r"(v.x), "=r"(v.y) : "l"(p) : "memory");
    return v;
}
__device__ __forceinline__ void ld7_relaxed(uint4* x, const void* p) {
    asm volatile("ld.relaxed.gpu.global.v4.u32 {%0,%1,%2,%3}, [%28 + 0];\nld.relaxed.gpu.global.v4.u32 {%4,%5,%6,%7}, [%28 + 512];\nld.relaxed.gpu.global.v4.u32 {%8,%9,%10,%11}, [%28 + 1024];\nld.relaxed.gpu.global.v4.u32 {%12,%13,%14,%15}, [%28 + 1536];\nld.relaxed.gpu.global.v4.u32 {%16,%17,%18,%19}, [%28 + 2048];\nld.relaxed.gpu.global.v4.u32 {%20,%21,%22,%23}, [%28 + 2560];\nld.relaxed.gpu.global.v4.u32 {%24,%25,%26,%27}, [%28 + 3072];\n" : "=r"(x[0].x), "=r"(x[0].y), "=r"(x[0].z), "=r"(x[0].w), "=r"(x[1].x), "=r"(x[1].y), "=r"(x[1].z), "=r"(x[1].w), "=r"(x[2].x), "=r"(x[2].y), "=r"(x[2].z), "=r"(x[2].w), "=r"(x[3].x), "=r"(x[3].y), "=r"(x[3].z), "=r"(x[3].w), "=r"(x[4].x), "=r"(x[4].y), "=r"(x[4].z), "=r"(x[4].w), "=r"(x[5].x), "=r"(x[5].y), "=r"(x[5].z), "=r"(x[5].w), "=r"(x[6].x), "=r"(x[6].y), "=r"(x[6].z), "=r"(x[6].w) : "l"(p) : "memory");
}
__device__ __forceinline__ void ld7_relaxed(uint2* x, const void* p) {
    asm volatile("ld.relaxed.gpu.global.v2.u32 {%0,%1}, [%14 + 0];\nld.relaxed.gpu.global.v2.u32 {%2,%3}, [%14 + 512];\nld.relaxed.gpu.global.v2.u32 {%4,%5}, [%14 + 1024];\nld.relaxed.gpu.global.v2.u32 {%6,%7}, [%14 + 1536];\nld.relaxed.gpu.global.v2.u32 {%8,%9}, [%14 + 2048];\nld.relaxed.gpu.global.v2.u32 {%10,%11}, [%14 + 2560];\nld.relaxed.gpu.global.v2.u32 {%12,%13}, [%14 + 3072];\n" : "=r"(x[0].x), "=r"(x[0].y), "=r"(x[1].x), "=r"(x[1].y), "=r"(x[2].x), "=r"(x[2].y), "=r"(x[3].x), "=r"(x[3].y), "=r"(x[4].x), "=r"(x[4].y), "=r"(x[5].x), "=r"(x[5].y), "=r"(x[6].x), "=r"(x[6].y) : "l"(p) : "memory");
}
__device__ __forceinline__ void st_relaxed_v4(void* p, uint32_t a, uint32_t b, uint32_t c, uint32_t d) {
    asm volatile("st.relaxed.gpu.global.v4.u32 [%0], {%1,%2,%3,%4};" ::"l"(p), "r"(a), "r"(b), "r"(c), "r"(d) : "memory");
}
__device__ __forceinline__ void st_relaxed_v2(void* p, uint32_t a, uint32_t b) {
    asm volatile("st.relaxed.gpu.global.v2.u32 [%0], {%1,%2};" ::"l"(p), "r"(a), "r"(b) : "memory");
}
__device__ __forceinline__ uint32_t nz(uint32_t v) { uint32_t r; asm("max.u32 %0, %1, 1;" : "=r"(r) : "r"(v)); return r; }
__device__ __forceinline__ void touch(const void* p) { asm volatile("prefetch.global.L2 [%0];" ::"l"(p) : "memory"); }
__device__ __forceinline__ int ld_relaxed(const int* p) {
    int v;
    asm volatile("ld.relaxed.gpu.global.u32 %0, [%1];" : "=r"(v) : "l"(p) : "memory");
    return v;
}
__device__ __forceinline__ int ld_acquire(const int* p) {
    int v;
    asm volatile("ld.acquire.gpu.global.u32 %0, [%1];" : "=r"(v) : "l"(p) : "memory");
    return v;
}
__device__ __forceinline__ void red_release(int* p, int v) { asm volatile("red.release.gpu.global.add.u32 [%0], %1;" ::"l"(p), "r"(v) : "memory"); }
__device__ __forceinline__ void mbar_init(uint32_t bar, int count) { asm volatile("mbarrier.init.shared::cta.b64 [%0], %1;" ::"r"(bar), "r"(count)); }
__device__ __forceinline__ void mbar_expect_tx(uint32_t bar, uint32_t bytes) {
    asm volatile("mbarrier.arrive.expect_tx.shared::cta.b64 _, [%0], %1;" ::"r"(bar), "r"(bytes) : "memory");
}
__device__ __forceinline__ void mbar_arrive(uint32_t bar) { asm volatile("mbarrier.arrive.shared::cta.b64 _, [%0];" ::"r"(bar) : "memory"); }
__device__ __forceinline__ void mbar_arrive_cluster(uint32_t bar) { asm volatile("mbarrier.arrive.shared::cluster.b64 _, [%0];" ::"r"(bar) : "memory"); }
__device__ __forceinline__ void mslow(uint32_t bar, uint32_t parity) {
    asm volatile(
        "{\n.reg .pred P1;\n.reg .u32 cnt;\n"
        "mov.u32 cnt, 0;\n"
        "LAB_WAIT:\n"
        "mbarrier.try_wait.parity.shared::cta.b64 P1, [%0], %1;\n"
        "@P1 bra DONE;\n"
        "add.u32 cnt, cnt, 1;\n"
        "setp.lt.u32 P1, cnt, 1000000;\n"
        "@P1 bra LAB_WAIT;\n"
        "trap;\n"
        "DONE:\n}\n" ::"r"(bar), "r"(parity) : "memory");
}
__device__ __forceinline__ void mwait(uint32_t bar, uint32_t parity) {
    asm volatile(
        "{\n.reg .pred P1, P2;\n.reg .u32 cnt;\n"
        "mov.u32 cnt, 0;\n"
        "LAB_WAIT:\n"
        "mbarrier.try_wait.parity.shared::cta.b64 P1, [%0], %1;\n"
        "add.u32 cnt, cnt, 1;\n"
        "setp.gt.u32 P2, cnt, 1000000;\n"
        "@P2 trap;\n"
        "@!P1 bra LAB_WAIT;\n"
        "}\n" ::"r"(bar), "r"(parity) : "memory");
}
__device__ __forceinline__ uint32_t mtest(uint32_t bar, uint32_t parity) {
    uint32_t ok;
    asm volatile("{\n.reg .pred P1;\nmbarrier.test_wait.parity.shared::cta.b64 P1, [%1], %2;\nselp.u32 %0, 1, 0, P1;\n}\n" : "=r"(ok) : "r"(bar), "r"(parity) : "memory");
    return ok;
}
__device__ __forceinline__ uint32_t mapa(uint32_t addr, uint32_t rank) {
    uint32_t r;
    asm("mapa.shared::cluster.u32 %0, %1, %2;" : "=r"(r) : "r"(addr), "r"(rank));
    return r;
}
__device__ __forceinline__ void st_async_b32(uint32_t addr, uint32_t a, uint32_t bar) {
    asm volatile("st.async.weak.shared::cluster.mbarrier::complete_tx::bytes.b32 [%0], %1, [%2];" ::"r"(addr), "r"(a), "r"(bar) : "memory");
}
__device__ __forceinline__ void st_async_v2(uint32_t addr, uint32_t a, uint32_t b, uint32_t bar) {
    asm volatile("st.async.weak.shared::cluster.mbarrier::complete_tx::bytes.v2.b32 [%0], {%1,%2}, [%3];" ::"r"(addr), "r"(a), "r"(b), "r"(bar) : "memory");
}
__device__ __forceinline__ void st_async_v4(uint32_t addr, uint32_t a, uint32_t b, uint32_t c, uint32_t d, uint32_t bar) {
    asm volatile("st.async.weak.shared::cluster.mbarrier::complete_tx::bytes.v4.b32 [%0], {%1,%2,%3,%4}, [%5];" ::"r"(addr), "r"(a), "r"(b), "r"(c), "r"(d), "r"(bar) : "memory");
}
__device__ __forceinline__ void st_async_v4p(uint32_t addr, uint32_t a, uint32_t b, uint32_t c, uint32_t d, uint32_t bar) {
    asm volatile("{\n.reg .pred p;\nsetp.ne.u32 p, %5, 0;\n@p st.async.weak.shared::cluster.mbarrier::complete_tx::bytes.v4.b32 [%0], {%1,%2,%3,%4}, [%5];\n}"
                 ::"r"(addr), "r"(a), "r"(b), "r"(c), "r"(d), "r"(bar) : "memory");
}
__device__ __forceinline__ void st_async_v2p(uint32_t addr, uint32_t a, uint32_t b, uint32_t bar) {
    asm volatile("{\n.reg .pred p;\nsetp.ne.u32 p, %3, 0;\n@p st.async.weak.shared::cluster.mbarrier::complete_tx::bytes.v2.b32 [%0], {%1,%2}, [%3];\n}"
                 ::"r"(addr), "r"(a), "r"(b), "r"(bar) : "memory");
}
__device__ __forceinline__ void cluster_arrive() { asm volatile("barrier.cluster.arrive.release.aligned;" ::: "memory"); }
__device__ __forceinline__ void cluster_arrive_relaxed() { asm volatile("barrier.cluster.arrive.relaxed.aligned;" ::: "memory"); }
__device__ __forceinline__ void prefetch_l2(const void* p, uint32_t bytes) { asm volatile("cp.async.bulk.prefetch.L2.global [%0], %1;" ::"l"(p), "r"(bytes) : "memory"); }
__device__ __forceinline__ void cluster_wait() { asm volatile("barrier.cluster.wait.acquire.aligned;" ::: "memory"); }
__device__ __forceinline__ void named_bar(int id, int n) { asm volatile("bar.sync %0, %1;" ::"r"(id), "r"(n) : "memory"); }
__device__ __forceinline__ void named_arrive(int id, int n) { asm volatile("bar.arrive %0, %1;" ::"r"(id), "r"(n) : "memory"); }
__device__ __forceinline__ void fence_async_smem() { asm volatile("fence.proxy.async.shared::cta;" ::: "memory"); }
__device__ __forceinline__ void fence_async_global() { asm volatile("fence.proxy.async.global;" ::: "memory"); }
__device__ __forceinline__ void wg_fence() { asm volatile("wgmma.fence.sync.aligned;" ::: "memory"); }
__device__ __forceinline__ void wg_commit() { asm volatile("wgmma.commit_group.sync.aligned;" ::: "memory"); }
template <int N> __device__ __forceinline__ void wg_wait() { asm volatile("wgmma.wait_group.sync.aligned %0;" ::"n"(N) : "memory"); }
__device__ __forceinline__ float ex2f(float x) { float y; asm("ex2.approx.ftz.f32 %0, %1;" : "=f"(y) : "f"(x)); return y; }
__device__ __forceinline__ float rcpf(float x) { float y; asm("rcp.approx.ftz.f32 %0, %1;" : "=f"(y) : "f"(x)); return y; }
__device__ __forceinline__ uint32_t clk32() { uint32_t c; asm volatile("mov.u32 %0, %clock;" : "=r"(c)); return c; }
__device__ __forceinline__ uint32_t opq(uint32_t x) { uint32_t y; asm volatile("mov.u32 %0, %1;" : "=r"(y) : "r"(x)); return y; }
__device__ __forceinline__ uint64_t mkdesc(uint32_t lo, uint32_t hi) { uint64_t d; asm("mov.b64 %0, {%1,%2};" : "=l"(d) : "r"(lo), "r"(hi)); return d; }
__device__ __forceinline__ void delay(uint32_t n) {
    asm volatile("{\n.reg .pred P;\n.reg .u32 a, b;\nmov.u32 a, %clock;\nadd.u32 a, a, %0;\nDL:\nmov.u32 b, %clock;\nsub.u32 b, b, a;\nsetp.lt.s32 P, b, 0;\n@P bra.uni DL;\n}" ::"r"(n) : "memory");
}
#define UNI(x) __shfl_sync(0xffffffffu, (uint32_t)(x), 0)
__device__ __forceinline__ void wg_n16t(float* d, uint32_t a0, uint32_t a1, uint32_t a2, uint32_t a3, uint64_t db) {
    asm volatile("wgmma.mma_async.sync.aligned.m64n16k16.f32.bf16.bf16 {%0, %1, %2, %3, %4, %5, %6, %7}, {%8, %9, %10, %11}, %12, 1, 1, 1, 1;"
                 : "+f"(d[0]), "+f"(d[1]), "+f"(d[2]), "+f"(d[3]), "+f"(d[4]), "+f"(d[5]), "+f"(d[6]), "+f"(d[7]) : "r"(a0), "r"(a1), "r"(a2), "r"(a3), "l"(db));
}
__device__ __forceinline__ void wg_n16t_first(float* d, uint32_t a0, uint32_t a1, uint32_t a2, uint32_t a3, uint64_t db) {
    asm volatile("wgmma.mma_async.sync.aligned.m64n16k16.f32.bf16.bf16 {%0, %1, %2, %3, %4, %5, %6, %7}, {%8, %9, %10, %11}, %12, 0, 1, 1, 1;"
                 : "=f"(d[0]), "=f"(d[1]), "=f"(d[2]), "=f"(d[3]), "=f"(d[4]), "=f"(d[5]), "=f"(d[6]), "=f"(d[7]) : "r"(a0), "r"(a1), "r"(a2), "r"(a3), "l"(db));
}
__device__ __forceinline__ void wg_n32(float* d, uint32_t a0, uint32_t a1, uint32_t a2, uint32_t a3, uint64_t db) {
    asm volatile("wgmma.mma_async.sync.aligned.m64n32k16.f32.bf16.bf16 {%0, %1, %2, %3, %4, %5, %6, %7, %8, %9, %10, %11, %12, %13, %14, %15}, {%16, %17, %18, %19}, %20, 1, 1, 1, 0;"
                 : "+f"(d[0]), "+f"(d[1]), "+f"(d[2]), "+f"(d[3]), "+f"(d[4]), "+f"(d[5]), "+f"(d[6]), "+f"(d[7]), "+f"(d[8]), "+f"(d[9]), "+f"(d[10]), "+f"(d[11]), "+f"(d[12]), "+f"(d[13]), "+f"(d[14]), "+f"(d[15]) : "r"(a0), "r"(a1), "r"(a2), "r"(a3), "l"(db));
}
__device__ __forceinline__ void wg_n32_first(float* d, uint32_t a0, uint32_t a1, uint32_t a2, uint32_t a3, uint64_t db) {
    asm volatile("wgmma.mma_async.sync.aligned.m64n32k16.f32.bf16.bf16 {%0, %1, %2, %3, %4, %5, %6, %7, %8, %9, %10, %11, %12, %13, %14, %15}, {%16, %17, %18, %19}, %20, 0, 1, 1, 0;"
                 : "=f"(d[0]), "=f"(d[1]), "=f"(d[2]), "=f"(d[3]), "=f"(d[4]), "=f"(d[5]), "=f"(d[6]), "=f"(d[7]), "=f"(d[8]), "=f"(d[9]), "=f"(d[10]), "=f"(d[11]), "=f"(d[12]), "=f"(d[13]), "=f"(d[14]), "=f"(d[15]) : "r"(a0), "r"(a1), "r"(a2), "r"(a3), "l"(db));
}

__device__ __forceinline__ void wg_n16t_sfirst(float* d, uint64_t da, uint64_t db) {
    asm volatile("wgmma.mma_async.sync.aligned.m64n16k16.f32.bf16.bf16 {%0, %1, %2, %3, %4, %5, %6, %7}, %8, %9, 0, 1, 1, 1, 1;"
                 : "=f"(d[0]), "=f"(d[1]), "=f"(d[2]), "=f"(d[3]), "=f"(d[4]), "=f"(d[5]), "=f"(d[6]), "=f"(d[7]) : "l"(da), "l"(db));
}
__device__ __forceinline__ void wg_n32_sfirst(float* d, uint64_t da, uint64_t db) {
    asm volatile("wgmma.mma_async.sync.aligned.m64n32k16.f32.bf16.bf16 {%0, %1, %2, %3, %4, %5, %6, %7, %8, %9, %10, %11, %12, %13, %14, %15}, %16, %17, 0, 1, 1, 1, 0;"
                 : "=f"(d[0]), "=f"(d[1]), "=f"(d[2]), "=f"(d[3]), "=f"(d[4]), "=f"(d[5]), "=f"(d[6]), "=f"(d[7]), "=f"(d[8]), "=f"(d[9]), "=f"(d[10]), "=f"(d[11]), "=f"(d[12]), "=f"(d[13]), "=f"(d[14]), "=f"(d[15]) : "l"(da), "l"(db));
}

__device__ __forceinline__ void wg_n16t_s(float* d, uint64_t da, uint64_t db) {
    asm volatile("wgmma.mma_async.sync.aligned.m64n16k16.f32.bf16.bf16 {%0, %1, %2, %3, %4, %5, %6, %7}, %8, %9, 1, 1, 1, 1, 1;"
                 : "+f"(d[0]), "+f"(d[1]), "+f"(d[2]), "+f"(d[3]), "+f"(d[4]), "+f"(d[5]), "+f"(d[6]), "+f"(d[7]) : "l"(da), "l"(db));
}
__device__ __forceinline__ void wg_n64_sfirst(float* d, uint64_t da, uint64_t db) {
    asm volatile("wgmma.mma_async.sync.aligned.m64n64k16.f32.bf16.bf16 {%0, %1, %2, %3, %4, %5, %6, %7, %8, %9, %10, %11, %12, %13, %14, %15, %16, %17, %18, %19, %20, %21, %22, %23, %24, %25, %26, %27, %28, %29, %30, %31}, %32, %33, 0, 1, 1, 1, 0;"
                 : "=f"(d[0]), "=f"(d[1]), "=f"(d[2]), "=f"(d[3]), "=f"(d[4]), "=f"(d[5]), "=f"(d[6]), "=f"(d[7]), "=f"(d[8]), "=f"(d[9]), "=f"(d[10]), "=f"(d[11]), "=f"(d[12]), "=f"(d[13]), "=f"(d[14]), "=f"(d[15]), "=f"(d[16]), "=f"(d[17]), "=f"(d[18]), "=f"(d[19]), "=f"(d[20]), "=f"(d[21]), "=f"(d[22]), "=f"(d[23]), "=f"(d[24]), "=f"(d[25]), "=f"(d[26]), "=f"(d[27]), "=f"(d[28]), "=f"(d[29]), "=f"(d[30]), "=f"(d[31]) : "l"(da), "l"(db));
}
__device__ __forceinline__ void wg_n64_s(float* d, uint64_t da, uint64_t db) {
    asm volatile("wgmma.mma_async.sync.aligned.m64n64k16.f32.bf16.bf16 {%0, %1, %2, %3, %4, %5, %6, %7, %8, %9, %10, %11, %12, %13, %14, %15, %16, %17, %18, %19, %20, %21, %22, %23, %24, %25, %26, %27, %28, %29, %30, %31}, %32, %33, 1, 1, 1, 1, 0;"
                 : "+f"(d[0]), "+f"(d[1]), "+f"(d[2]), "+f"(d[3]), "+f"(d[4]), "+f"(d[5]), "+f"(d[6]), "+f"(d[7]), "+f"(d[8]), "+f"(d[9]), "+f"(d[10]), "+f"(d[11]), "+f"(d[12]), "+f"(d[13]), "+f"(d[14]), "+f"(d[15]), "+f"(d[16]), "+f"(d[17]), "+f"(d[18]), "+f"(d[19]), "+f"(d[20]), "+f"(d[21]), "+f"(d[22]), "+f"(d[23]), "+f"(d[24]), "+f"(d[25]), "+f"(d[26]), "+f"(d[27]), "+f"(d[28]), "+f"(d[29]), "+f"(d[30]), "+f"(d[31]) : "l"(da), "l"(db));
}
__device__ __forceinline__ void wg_n64(float* d, uint32_t a0, uint32_t a1, uint32_t a2, uint32_t a3, uint64_t db) {
    asm volatile("wgmma.mma_async.sync.aligned.m64n64k16.f32.bf16.bf16 {%0, %1, %2, %3, %4, %5, %6, %7, %8, %9, %10, %11, %12, %13, %14, %15, %16, %17, %18, %19, %20, %21, %22, %23, %24, %25, %26, %27, %28, %29, %30, %31}, {%32, %33, %34, %35}, %36, 1, 1, 1, 0;"
                 : "+f"(d[0]), "+f"(d[1]), "+f"(d[2]), "+f"(d[3]), "+f"(d[4]), "+f"(d[5]), "+f"(d[6]), "+f"(d[7]), "+f"(d[8]), "+f"(d[9]), "+f"(d[10]), "+f"(d[11]), "+f"(d[12]), "+f"(d[13]), "+f"(d[14]), "+f"(d[15]), "+f"(d[16]), "+f"(d[17]), "+f"(d[18]), "+f"(d[19]), "+f"(d[20]), "+f"(d[21]), "+f"(d[22]), "+f"(d[23]), "+f"(d[24]), "+f"(d[25]), "+f"(d[26]), "+f"(d[27]), "+f"(d[28]), "+f"(d[29]), "+f"(d[30]), "+f"(d[31]) : "r"(a0), "r"(a1), "r"(a2), "r"(a3), "l"(db));
}
__device__ __forceinline__ void wg_n64_first(float* d, uint32_t a0, uint32_t a1, uint32_t a2, uint32_t a3, uint64_t db) {
    asm volatile("wgmma.mma_async.sync.aligned.m64n64k16.f32.bf16.bf16 {%0, %1, %2, %3, %4, %5, %6, %7, %8, %9, %10, %11, %12, %13, %14, %15, %16, %17, %18, %19, %20, %21, %22, %23, %24, %25, %26, %27, %28, %29, %30, %31}, {%32, %33, %34, %35}, %36, 0, 1, 1, 0;"
                 : "=f"(d[0]), "=f"(d[1]), "=f"(d[2]), "=f"(d[3]), "=f"(d[4]), "=f"(d[5]), "=f"(d[6]), "=f"(d[7]), "=f"(d[8]), "=f"(d[9]), "=f"(d[10]), "=f"(d[11]), "=f"(d[12]), "=f"(d[13]), "=f"(d[14]), "=f"(d[15]), "=f"(d[16]), "=f"(d[17]), "=f"(d[18]), "=f"(d[19]), "=f"(d[20]), "=f"(d[21]), "=f"(d[22]), "=f"(d[23]), "=f"(d[24]), "=f"(d[25]), "=f"(d[26]), "=f"(d[27]), "=f"(d[28]), "=f"(d[29]), "=f"(d[30]), "=f"(d[31]) : "r"(a0), "r"(a1), "r"(a2), "r"(a3), "l"(db));
}

__device__ __forceinline__ void wg_n32t(float* d, uint32_t a0, uint32_t a1, uint32_t a2, uint32_t a3, uint64_t db) {
    asm volatile("wgmma.mma_async.sync.aligned.m64n32k16.f32.bf16.bf16 {%0, %1, %2, %3, %4, %5, %6, %7, %8, %9, %10, %11, %12, %13, %14, %15}, {%16, %17, %18, %19}, %20, 1, 1, 1, 1;"
                 : "+f"(d[0]), "+f"(d[1]), "+f"(d[2]), "+f"(d[3]), "+f"(d[4]), "+f"(d[5]), "+f"(d[6]), "+f"(d[7]), "+f"(d[8]), "+f"(d[9]), "+f"(d[10]), "+f"(d[11]), "+f"(d[12]), "+f"(d[13]), "+f"(d[14]), "+f"(d[15]) : "r"(a0), "r"(a1), "r"(a2), "r"(a3), "l"(db));
}
__device__ __forceinline__ void wg_n32t_first(float* d, uint32_t a0, uint32_t a1, uint32_t a2, uint32_t a3, uint64_t db) {
    asm volatile("wgmma.mma_async.sync.aligned.m64n32k16.f32.bf16.bf16 {%0, %1, %2, %3, %4, %5, %6, %7, %8, %9, %10, %11, %12, %13, %14, %15}, {%16, %17, %18, %19}, %20, 0, 1, 1, 1;"
                 : "=f"(d[0]), "=f"(d[1]), "=f"(d[2]), "=f"(d[3]), "=f"(d[4]), "=f"(d[5]), "=f"(d[6]), "=f"(d[7]), "=f"(d[8]), "=f"(d[9]), "=f"(d[10]), "=f"(d[11]), "=f"(d[12]), "=f"(d[13]), "=f"(d[14]), "=f"(d[15]) : "r"(a0), "r"(a1), "r"(a2), "r"(a3), "l"(db));
}
__device__ __forceinline__ void wg_n32t_sfirst(float* d, uint64_t da, uint64_t db) {
    asm volatile("wgmma.mma_async.sync.aligned.m64n32k16.f32.bf16.bf16 {%0, %1, %2, %3, %4, %5, %6, %7, %8, %9, %10, %11, %12, %13, %14, %15}, %16, %17, 0, 1, 1, 1, 1;"
                 : "=f"(d[0]), "=f"(d[1]), "=f"(d[2]), "=f"(d[3]), "=f"(d[4]), "=f"(d[5]), "=f"(d[6]), "=f"(d[7]), "=f"(d[8]), "=f"(d[9]), "=f"(d[10]), "=f"(d[11]), "=f"(d[12]), "=f"(d[13]), "=f"(d[14]), "=f"(d[15]) : "l"(da), "l"(db));
}
__device__ __forceinline__ void wg_n32t_s(float* d, uint64_t da, uint64_t db) {
    asm volatile("wgmma.mma_async.sync.aligned.m64n32k16.f32.bf16.bf16 {%0, %1, %2, %3, %4, %5, %6, %7, %8, %9, %10, %11, %12, %13, %14, %15}, %16, %17, 1, 1, 1, 1, 1;"
                 : "+f"(d[0]), "+f"(d[1]), "+f"(d[2]), "+f"(d[3]), "+f"(d[4]), "+f"(d[5]), "+f"(d[6]), "+f"(d[7]), "+f"(d[8]), "+f"(d[9]), "+f"(d[10]), "+f"(d[11]), "+f"(d[12]), "+f"(d[13]), "+f"(d[14]), "+f"(d[15]) : "l"(da), "l"(db));
}

__device__ __forceinline__ void wg_n32_kk(float* d, uint64_t da, uint64_t db) {
    asm volatile("wgmma.mma_async.sync.aligned.m64n32k16.f32.bf16.bf16 {%0, %1, %2, %3, %4, %5, %6, %7, %8, %9, %10, %11, %12, %13, %14, %15}, %16, %17, 1, 1, 1, 0, 0;"
                 : "+f"(d[0]), "+f"(d[1]), "+f"(d[2]), "+f"(d[3]), "+f"(d[4]), "+f"(d[5]), "+f"(d[6]), "+f"(d[7]), "+f"(d[8]), "+f"(d[9]), "+f"(d[10]), "+f"(d[11]), "+f"(d[12]), "+f"(d[13]), "+f"(d[14]), "+f"(d[15]) : "l"(da), "l"(db));
}

}

namespace ws {
#define LAGT 4
constexpr int LAG = LAGT, NT = NSEG + LAG, NCL = 7;
#define P1A 22
#define P1C 10
#define XD 350
#define REG_G 200
#define REG_T 72
#define REG_X 40
template <int N_> struct IC { static constexpr int value = N_; };
#define POST_NS 20
#define OP_NS 20
#define LN0_AHEAD 8
#define TG_STEPS 40
#define NO_X 0
#define WR 4
#define OBK 2
#define WFLY 2
#define H_NS 20
#define LN0_BATCH 1
static_assert(LN0_AHEAD + LN0_BATCH + LAG + 1 <= 16 && (NSEG - LN0_AHEAD) % LN0_BATCH == 0, "ring of the scratch buffers");
constexpr int XRS = 3;
constexpr int O_H = 0, O_MEM = 81920, O_RED = 102400, O_BAR = 110080, O_TAB = O_BAR + 192, O_BT = O_TAB + 128, O_TR = O_BAR + 512, O_X = O_TR + 1024;
constexpr int O_QRY = O_X, O_KEY = O_X + 10240, O_OBA = O_KEY + 10240, O_ST = O_OBA + 4096;
constexpr int O_VT = O_X, O_VM = O_VT + 32768, O_SM = O_VM + 4096, O_PB = O_SM + 3072;
constexpr int O_AS = 228352, O_WO = O_AS - 65536, HEAD_SMEM = O_AS + 4096, O_STG = 40960;
static_assert(O_ST + 8192 <= O_WO && O_PB + 10240 <= O_WO && O_AS % 1024 == 0 && O_STG + 163840 <= O_AS && HEAD_SMEM <= 232448, "smem");
constexpr int B_MEM = 0, B_RED = 64, B_SM = 88, B_ST = 96, B_OB = 104, B_HF = 112, B_HE = 128, B_OTF = 144, B_OTE = 160;

constexpr int F_H = 0, F_O = 128, F_P = 256, F_U = 384, F_CV = 392, F_XL = 398, F_Z = 399, NFLAG = 400;
__device__ int g_flags[NFLAG * 8];
#define FLG(i) (g_flags + (i) * 8)
#define RING 16
__device__ __forceinline__ int rslot(int l, int seg) { return l * RING + (seg & (RING - 1)); }
__device__ uint4 g_ht[2 * RING * 2560];
__device__ uint4 g_ot[2 * RING * 256 * 64];
__device__ uint4 g_pt[2 * RING * 5120];
__device__ uint4 g_Y[80 * S_LEN];
__device__ uint4 g_U[DM * S_LEN / 8];
__device__ bf16 g_x[RING * SEG * DM];
__device__ int g_epoch;
__device__ uint4 g_xc[XRS * 16 * 3 * 8 * 32];
#define GT(cond, i)
#define SC(cond, i)
#define SD(x)
#define TS(i)
#define TV(i, v)

}

namespace ws {
__device__ __forceinline__ uint32_t bmul2(uint32_t a, uint32_t b) { uint32_t r; asm("mul.rn.bf16x2 %0, %1, %2;" : "=r"(r) : "r"(a), "r"(b)); return r; }
__device__ __forceinline__ uint32_t bmax2(uint32_t a, uint32_t b) { uint32_t r; asm("max.bf16x2 %0, %1, %2;" : "=r"(r) : "r"(a), "r"(b)); return r; }
__device__ __forceinline__ void flag_wait(const int* f, int tgt, int ns) {
    int guard = 0;
    while (ld_relaxed(f) < tgt) { if (++guard > 4000000) __trap(); __nanosleep(ns); }
}
template <int STRIDE> __device__ __forceinline__ void ld5(uint32_t* w, const void* p) {
#pragma unroll
    for (int r = 0; r < 5; r++) { const uint2 v = __ldcg(reinterpret_cast<const uint2*>(reinterpret_cast<const char*>(p) + r * STRIDE)); w[2 * r] = v.x; w[2 * r + 1] = v.y; }
}
template <int STRIDE> __device__ __forceinline__ void st5(void* p, const uint32_t* w) {
#pragma unroll
    for (int r = 0; r < 5; r++) *reinterpret_cast<uint2*>(reinterpret_cast<char*>(p) + r * STRIDE) = make_uint2(w[2 * r], w[2 * r + 1]);
}
__device__ __forceinline__ void ln_row(const uint32_t* x, uint32_t* y) {
    const float c = blo(__shfl_sync(0xffffffffu, x[0], 0));
    float s0 = 0.f, s1 = 0.f, q0 = 0.f, q1 = 0.f;
#pragma unroll
    for (int i = 0; i < 10; i++) { const float d0 = blo(x[i]) - c, d1 = bhi(x[i]) - c; s0 += d0; s1 += d1; q0 = fmaf(d0, d0, q0); q1 = fmaf(d1, d1, q1); }
    float s = s0 + s1, q = q0 + q1;
#pragma unroll
    for (int o = 16; o > 0; o >>= 1) { s += __shfl_xor_sync(0xffffffffu, s, o); q += __shfl_xor_sync(0xffffffffu, q, o); }
    s *= 1.0f / DM;
    const float mean = c + s;
    q = fmaxf(fmaf(q, 1.0f / DM, -s * s), 0.f);
    const uint32_t nm = pack2(-mean, -mean);
    float sq;
    asm("sqrt.approx.ftz.f32 %0, %1;" : "=f"(sq) : "f"(rbf(rbf(q) + 1e-5f)));
    const float rd = rcpf(rbf(sq));
#pragma unroll
    for (int i = 0; i < 10; i++) { const uint32_t d = badd(x[i], nm); y[i] = pack2(blo(d) * rd, bhi(d) * rd); }
}
__device__ __forceinline__ void clear_acc(int l, int seg, int tok, int lane) {
    uint4* pz = g_pt + rslot(l, seg) * 5120 + (lane >> 4) * 512 + tok * 16 + (lane & 15);
#pragma unroll
    for (int i = 0; i < 5; i++) pz[i * 1024] = make_uint4(0, 0, 0, 0);
}
__device__ __forceinline__ void put_h(int l, int seg, int tok, int lane, const uint32_t* n) {
    st5<8192>(reinterpret_cast<char*>(g_ht + rslot(l, seg) * 2560) + (lane >> 2) * 1024 + tok * 32 + (((lane & 3) * 8) ^ ((tok & 4) << 2)), n);
}
__device__ __forceinline__ void ln0_rows(const bf16* x, int seg, int cnt, int tok, int lane) {
#pragma unroll 1
    for (int i = 0; i < cnt; i++) {
        uint32_t v[10];
        ld5<256>(v, x + (size_t)((seg + i) * SEG + tok) * DM + lane * 4);
        clear_acc(0, seg + i, tok, lane);
        ln_row(v, v);
        put_h(0, seg + i, tok, lane, v);
    }
    __syncwarp();
    if (lane == 0) {
        red_release(FLG(F_H + seg), 1);
        for (int i = 1; i < cnt; i++) asm volatile("red.relaxed.gpu.global.add.u32 [%0], 1;" ::"l"(FLG(F_H + seg + i)) : "memory");
    }
}
__device__ __forceinline__ void post_row(int l, int seg, int tok, int lane, const bf16* xin, bf16* xout, int ep) {
    uint32_t x[10], y[10], n[10];
    const int row = seg * SEG + tok;
    SC(tr, tb);
    const bool first = seg == 0;
    if (seg == 8 || ((seg & 15) == 0 && seg)) flag_wait(FLG(F_CV + (seg >> 4) + 1), 80 * ep, 50);
    const char* yp = reinterpret_cast<const char*>(g_Y) + ((size_t)(lane >> 1) * S_LEN + row) * 16 + (lane & 1) * 8;
    SC(tr, tb + 1);
    if (!first) ld5<16 * S_LEN * 16>(y, yp);
    bf16* xm = g_x + ((seg & (RING - 1)) * SEG + tok) * DM + lane * 4;
    if (l == 0) {
        ld5<256>(x, xin + (size_t)row * DM + lane * 4);
        clear_acc(1, seg, tok, lane);
    } else {
        flag_wait(seg + 1 < NSEG ? FLG(F_H + 65 + seg) : FLG(F_XL), 32 * ep, 50);
        ld5<256>(x, xm);
    }
    flag_wait(FLG(F_P + l * 64 + seg), 40 * ep, POST_NS);
    SC(tr, tb + 2);
    const uint4* pp = g_pt + rslot(l, seg) * 5120 + (lane >> 4) * 512 + tok * 16 + ((lane & 15) ^ ((tok >> 3) << 1));
    {
        uint4 a[5];
#pragma unroll
        for (int i = 0; i < 5; i++) a[i] = __ldcg(pp + i * 1024);
#pragma unroll
        for (int i = 0; i < 5; i++) {
            x[2 * i] = badd(x[2 * i], pack2(__uint_as_float(a[i].x), __uint_as_float(a[i].y)));
            x[2 * i + 1] = badd(x[2 * i + 1], pack2(__uint_as_float(a[i].z), __uint_as_float(a[i].w)));
        }
    }
    SC(tr && x[0] != 0x12345, tb + 3);
    if (first) { flag_wait(FLG(F_CV), 80 * ep, 50); ld5<16 * S_LEN * 16>(y, yp); }
    ln_row(x, n);
#pragma unroll
    for (int i = 0; i < 10; i++) x[i] = badd(x[i], bmul2(n[i], y[i]));
    SC(tr && x[0] != 0x12345, tb + 4);
    if (l) st5<256>(xout + (size_t)row * DM + lane * 4, x);
    else {
        ln_row(x, n);
        SC(tr && n[0] != 0x12345, tb + 5);
        put_h(1, seg, tok, lane, n);
        __syncwarp();
        if (lane == 0) red_release(FLG(F_H + 64 + seg), 1);
        SC(tr, tb + 6);
        st5<256>(xm, x);
        if (seg == NSEG - 1) { __syncwarp(); if (lane == 0) red_release(FLG(F_XL), 1); }
    }
}
__device__ __forceinline__ void u_piece(const bf16* Bk, const bf16* Bv, const bf16* shiftk, int t0, int cp, uint4* o) {
    uint32_t kk[11], vv[8];
    const uint32_t* pk = reinterpret_cast<const uint32_t*>(Bk + (size_t)t0 * DM) + cp;
    const uint32_t* pv = reinterpret_cast<const uint32_t*>(Bv + (size_t)t0 * DM) + cp;
#pragma unroll
    for (int i = 0; i < 11; i++) kk[i] = (i >= 3 || t0 > 0) ? __ldg(pk + (i - 3) * (DM / 2)) : 0u;
#pragma unroll
    for (int i = 0; i < 8; i++) vv[i] = __ldg(pv + i * (DM / 2));
    const uint4 sh0 = __ldg(reinterpret_cast<const uint4*>(shiftk + cp * 8));
    const uint32_t s0 = __byte_perm(sh0.x, sh0.z, 0x5410), s1 = __byte_perm(sh0.x, sh0.z, 0x7632), s2 = __byte_perm(sh0.y, sh0.w, 0x5410), s3 = __byte_perm(sh0.y, sh0.w, 0x7632);
#pragma unroll
    for (int t = 0; t < 8; t++)
        vv[t] = bmul2(badd(badd(badd(bmul2(kk[t], s3), bmul2(kk[t + 1], s2)), bmul2(kk[t + 2], s1)), bmul2(kk[t + 3], s0)), vv[t]);
#pragma unroll
    for (int c = 0; c < 2; c++) {
        const uint32_t sel = c ? 0x7632 : 0x5410;
        o[c] = make_uint4(__byte_perm(vv[7], vv[6], sel), __byte_perm(vv[5], vv[4], sel), __byte_perm(vv[3], vv[2], sel), __byte_perm(vv[1], vv[0], sel));
    }
}
__device__ __forceinline__ int u_pos(int t0) { return (t0 >> 6) * 8 + ((((t0 ^ 56) & 63) >> 3) ^ ((t0 >> 6) & 7)); }
__device__ __forceinline__ void u_half(const bf16* Bk, const bf16* Bv, const bf16* shiftk, int unit, int lane) {
    const int t0 = (unit / 20) * 16 + (lane & 1) * 8, cp = (unit % 20) * 16 + (lane >> 1);
    uint4 o[2];
    u_piece(Bk, Bv, shiftk, t0, cp, o);
    uint4* d = g_U + (size_t)(cp * 2) * (S_LEN / 8) + u_pos(t0);
    d[0] = o[0]; d[S_LEN / 8] = o[1];
}
constexpr int CV_E = 4224, CV_W = 2 * 4096 + 3 * CV_E + 128, CV_HI = O_X, CV_Y = CV_HI + 4 * CV_W, CV_T = CV_Y + 16384, CV_Z = CV_T + 16384;
static_assert(4 * CV_W <= O_RED && CV_W % 128 == 0 && CV_Z + 128 <= HEAD_SMEM, "conv buffers");
__device__ __forceinline__ void conv_unit(uint32_t ub, uint32_t e0, uint32_t e1, uint32_t zrow, uint32_t tt, uint32_t Dv, int rg, int nq, int lane, uint32_t zero, int tb) {
    const int g7 = 7 - (lane >> 2), tq = lane & 3;
    SC(tb >= 0, tb + 3);
    for (int i = lane; i < 32 * nq + 8; i += 32) {
        const uint4 v = lds128(e0 + i * 16);
        const uint32_t nx = lds32(e0 + i * 16 + 16);
        sts128(e1 + i * 16, __byte_perm(v.x, v.y, 0x5432), __byte_perm(v.y, v.z, 0x5432), __byte_perm(v.z, v.w, 0x5432), __byte_perm(v.w, nx, 0x5432));
    }
    __syncwarp();
    SC(tb >= 0, tb + 4);
    float acc[4][4];
#pragma unroll
    for (int i = 0; i < 16; i++) (&acc[0][0])[i] = 0.f;
    uint32_t wb = (g7 & 1) ? e0 + (1 + g7 + 2 * tq) * 2 : e1 + (g7 + 2 * tq) * 2;
    int row = 8 * rg + (lane & 7);
    auto ldb = [&](uint4* b) {
        const uint32_t x = row < 0 ? zrow : ub + row * 128 + (((lane >> 3) ^ (row & 7)) << 4);
        b[0] = ldsm4(x); b[1] = ldsm4(x ^ 64);
        row--;
    };
    uint4 Q[16], b[2][2];
    Q[15].w = lds32(wb);
    auto ldq = [&](int q, int o) { Q[q].y = lds32(wb + o * 32 + 16); Q[q].w = lds32(wb + o * 32 + 32); };
    auto cpq = [&](int q) { Q[q].x = Q[(q + 15) & 15].w + zero; Q[q].z = Q[q].y + zero; };
#pragma unroll
    for (int q = 0; q < 11; q++) ldq(q, q);
#pragma unroll
    for (int q = 0; q < 7; q++) cpq(q);
    ldb(b[0]);
#pragma unroll 1
    for (int D0 = nq; D0 > 0; D0--) {
#pragma unroll
        for (int d = 0; d < 4; d++) {
            ldb(b[(d + 1) & 1]);
#pragma unroll
            for (int q = 11; q < 15; q++) ldq((4 * d + q) & 15, 4 * d + q);
#pragma unroll
            for (int ks = 0; ks < 4; ks++) {
                const uint4& bb_ = b[d & 1][ks >> 1];
#pragma unroll
                for (int m = 0; m < 4; m++) {
                    const uint4& a = Q[(4 * d + m + ks) & 15];
                    mmav(acc[m], a.x, a.y, a.z, a.w, (ks & 1) ? bb_.z : bb_.x, (ks & 1) ? bb_.w : bb_.y);
                }
                cpq((4 * d + 7 + ks) & 15);
            }
        }
        wb += 512;
    }
    SC(tb >= 0 && acc[0][0] != 1.2345f, tb + 5);
    const uint32_t ua = ub + (8 * rg + (lane & 7)) * 128 + (((lane >> 3) ^ (lane & 7)) << 4);
    const uint4 u0 = ldsm4t(ua), u1 = ldsm4t(ua ^ 64);
    auto y = [&](int m, int hf, uint32_t u) { return badd(pack2(acc[m][2 * hf], acc[m][2 * hf + 1]), bmul2(u, Dv)); };
    stsm4t(tt, y(0, 0, u1.w), y(0, 1, u1.z), y(1, 0, u1.y), y(1, 1, u1.x));
    stsm4t(tt ^ 64, y(2, 0, u0.w), y(2, 1, u0.z), y(3, 0, u0.y), y(3, 1, u0.x));
}
}

namespace ws {
__constant__ unsigned char c_tile[48] = {4, 5, 6, 7, 12, 13, 14, 19, 0, 1, 2, 3, 0, 0, 0, 0, 20, 21, 22, 27, 28, 29, 30, 31, 8, 9, 10, 11, 0, 0, 0, 0,
                                         39, 38, 37, 36, 35, 34, 33, 32, 15, 16, 17, 18, 23, 24, 25, 26};
struct HeadArgs { const bf16 *x, *mem0, *Wq, *Wk, *Wv, *Wo, *Bk, *Bv, *shiftk, *ssmk, *ssmD; bf16* out; int h_target; };

__global__ void __launch_bounds__(512, 1) head_kernel(const __grid_constant__ HeadArgs A) {
    extern __shared__ __align__(1024) unsigned char smem_raw[];
    const int tid = threadIdx.x, warp = __shfl_sync(0xffffffffu, tid >> 5, 0), lane = tid & 31;
    const int cq = blockIdx.x >> 4, r = blockIdx.x & 15;
    const int nh = cq < 4 ? 5 : 4, hi = r / 3, role = r - hi * 3;
    const bool head = r < 3 * nh;
    const int p0 = r >> 1;
    const int h = (cq < 4 ? 5 * cq : 4 * cq + 4) + hi;
    const uint32_t sb = smem_u32(smem_raw), bb = sb + O_BAR;
    GT(tid == 0, 1);
    const int sp = cq < 4 ? cq : 4 * cq + r - 24;
    if (tid == 0) {
        if ((sb & 0xFFFFFFu) != 1024) __trap();
        for (int i = 0; i < 12; i++) mbar_init(bb + i * 8, 1);
        mbar_init(bb + B_ST, role == 2 ? 1 : 5);
        mbar_init(bb + B_OB, 1); mbar_init(bb + B_OB + 64, 1);
        mbar_init(bb + B_HF, 1); mbar_init(bb + B_HF + 8, 1);
        mbar_init(bb + B_HE, 6 * nh);
        mbar_init(bb + B_OTF, head ? 4 : 8); mbar_init(bb + B_OTE, 1); mbar_init(bb + B_OTF + 8, head ? 4 : 8); mbar_init(bb + B_OTE + 16, 1);
        asm volatile("fence.mbarrier_init.release.cluster;" ::: "memory");
        mbar_expect_tx(bb + B_RED, nh * 1280);
        mbar_expect_tx(bb + B_SM, 3072); mbar_expect_tx(bb + B_ST, role == 2 ? 5120 : 4096);
        if (role != 2) { mbar_expect_tx(bb + B_OB, 2048); mbar_expect_tx(bb + B_OB + 64, 2048); }
        mbar_expect_tx(bb + B_HF, 40960); mbar_expect_tx(bb + B_HF + 8, 40960);
    }
    asm volatile("griddepcontrol.launch_dependents;");
    __syncwarp();
    cluster_arrive_relaxed();
    if (warp < 8) {
        asm volatile("setmaxnreg.inc.sync.aligned.u32 %0;" ::"n"(REG_G));
        const int wg = warp >> 2, w4 = warp & 3;
        if (head) {
            uint32_t wa[40][4];
            {
                const int t7 = tid & 127;
                const bf16* W = (role == 2 ? A.Wv + wg * 64 : (wg ? A.Wk : A.Wq) + role * 64) + h * DH + (size_t)(t7 >> 3) * HD + (t7 & 7) * 8;
                const uint32_t so = (t7 >> 3) * 128 + (((t7 & 7) ^ ((t7 >> 3) & 7)) << 4), stg = sb + O_STG + wg * 81920;
                const uint32_t la = stg + ((lane & 7) + (lane >> 4) * 8) * 128 + (((w4 * 2 + ((lane >> 3) & 1)) ^ (lane & 7)) << 4);
                GT(tid == 0, 80);
#pragma unroll
                for (int gi = 0; gi < 8 + WFLY; gi++) {
                    if (gi < 8) {
                        const bf16* Wg = W + (size_t)(((p0 - gi) & 7) * 80) * HD;
#pragma unroll
                        for (int u = 0; u < 5; u++) cp_async16((gi == 0 && u == 0 ? sb + O_AS + wg * 2048 : stg + (gi * 5 + u) * 2048) + so, Wg + (size_t)u * 16 * HD);
                    }
                    cp_commit();
                    if (gi >= WFLY) {
                        cp_wait<WFLY>();
                        named_bar(8 + wg, 128);
#pragma unroll
                        for (int u = 0; u < 5; u++) {
                            const int j = (gi - WFLY) * 5 + u;
                            if (j) { const uint4 v = ldsm4t(la + j * 2048); wa[j][0] = v.x; wa[j][1] = v.y; wa[j][2] = v.z; wa[j][3] = v.w; }
                        }
                    }
                }
                GT(tid == 0, 83);
                cluster_wait();
            }
            named_bar(10, 384);
            GT(tid == 0, 2);
            fence_async_smem();
            named_bar(8 + wg, 128);
            cluster_arrive_relaxed();
            float acc[16];
            const uint32_t ep_q = role == 2 ? sb + O_VM + warp * 512 + (lane ^ ((lane >> 3) & 1)) * 16
                                            : sb + O_QRY + wg * 10240 + ((lane >> 1) & 1) * 5120 + (4 * (lane >> 4) + 2 * ((lane >> 2) & 1) + (lane & 1)) * 128 +
                                                  (((2 * w4 + ((lane >> 3) & 1)) ^ (4 * (lane >> 4) + 2 * ((lane >> 2) & 1) + (lane & 1)) ^ ((lane & 2) << 1)) << 4);
            const uint32_t ep_t = role == 2 ? sb + O_VT + warp * 1024 + ((lane >> 3) & 1) * 512 + (lane >> 4) * 128 + (lane & 7) * 16
                                            : sb + O_QRY + wg * 10240 + (8 + 8 * (lane >> 4) + (lane & 7)) * 128 + (((2 * w4 + ((lane >> 3) & 1)) ^ (lane & 7)) << 4);
                        const int pz = role == 2 ? P1C : P1A;
            const uint32_t ab = (1024 + O_AS + wg * 2048) >> 4;
            uint32_t ok = 1;
            const uint32_t tidk = __shfl_sync(0xffffffffu, tid, lane);
            auto token_gemm = [&](auto ll, const bool pause, const uint32_t vo, const uint32_t nbar, const uint32_t npar, const int t) {
                constexpr int l = decltype(ll)::value;
                constexpr uint32_t hb = ((1024 + O_H + l * 40960) >> 4) | (1u << 16);
                const uint32_t pr = opq(p0);
                if (l) TS(15); else TS(14);
                wg_fence();
#pragma unroll
                for (int j = 0; j < 40; j++) {
                    const uint64_t db = mkdesc(hb + ((pr - j / 5) & 7) * 320 + (j % 5) * 64, 0xC0000010u);
                    if (j == 0) wg_n32_sfirst(acc, mkdesc(ab, 0x40000040u), db);
                    else if (j < TG_STEPS) wg_n32(acc, wa[j][0], wa[j][1], wa[j][2], wa[j][3], db);
                    if (l == 0 && (j + 1 == P1A || j + 1 == P1C)) {
                        if (pause && pz == j + 1) {
                            wg_commit();
                            if (role == 2) mwait(bb + B_OTE, vo >> 14);
                            wg_wait<0>();
                            TS(4);
                            named_arrive(3, 384);
                            named_bar(4, 384);
                            wg_fence();
                        }
                    }
                }
                wg_commit();
                ok = mtest(nbar, npar);
                wg_wait<0>();
                uint32_t pk[8];
#pragma unroll
                for (int i = 0; i < 8; i++) pk[i] = pack2(acc[2 * i], acc[2 * i + 1]);
                if (role == 2) {
                    stsm4(ep_t + l * 8192 + vo, pk[0], pk[1], pk[2], pk[3]);
                    stsm4(ep_t + l * 8192 + vo + 256, pk[4], pk[5], pk[6], pk[7]);
                } else {
                    stsm4t((ep_t ^ (l << 6)) + l * 5120, pk[0], pk[1], pk[2], pk[3]);
                    stsm4t((ep_t ^ (l << 6)) + l * 5120 + 2048, pk[4], pk[5], pk[6], pk[7]);
                }
                asm volatile("{\n.reg .pred p, q;\nsetp.eq.u32 p, %0, 0;\nsetp.eq.u32 q, %1, 0;\n"
                             "@p mbarrier.arrive.expect_tx.shared::cta.b64 _, [%2], %3;\n@q mbarrier.arrive.shared::cluster.b64 _, [%4];\n}"
                             ::"r"(tidk), "r"(tidk & 127), "r"(bb + B_HF + l * 8), "r"(40960), "r"(mapa(bb + B_HE, l)) : "memory");
            };
            GT(tid == 0, 86);
            mwait(bb + B_HF, 0);
            GT(tid == 0, 87);
            token_gemm(IC<0>{}, false, 0, bb + B_MEM, 1, -1);
            GT(tid == 0, 88);
            named_bar(11, 384);
            cluster_wait();
            named_arrive(13, 384);
#pragma unroll 1
            for (int t = 0; t < NT; t++) {
                GT(tid == 0 && blockIdx.x == 98, 100 + t);
                SC(tid == 0 && blockIdx.x == 98, 160 + t);
                TS(0);
                const uint32_t mp = (t & 1) ^ 1;
                const bool tg0 = t + 1 < NSEG, tg1 = t + 1 >= LAG;
                constexpr uint32_t mb = ((1024 + O_MEM) >> 4) | (16u << 16);
#pragma unroll
                for (int G = 0; G < 8; G++) {
                    if (__builtin_expect(!ok, 0)) mwait(bb + B_MEM + G * 8, mp);
                    ok = mtest(G < 7 ? bb + B_MEM + (G + 1) * 8 : bb + B_HF, mp);
                    if (G == 0) { TS(1); wg_fence(); }
                    if (G == 7) TS(2);
                    if (G == 1) TS(8); if (G == 2) TS(9); if (G == 3) TS(10); if (G == 4) TS(11); if (G == 5) TS(12); if (G == 6) TS(13);
#pragma unroll
                    for (int u = 0; u < 5; u++) {
                        const int j = G * 5 + u;
                        const uint64_t db = mkdesc(mb + j * 32, 8);
                        if (j == 0) wg_n16t_sfirst(acc, mkdesc(ab, 0x40000040u), db);
                        else wg_n16t(acc, wa[j][0], wa[j][1], wa[j][2], wa[j][3], db);
                    }
                    wg_commit();
                }
                if (role == 2 && t) named_bar(5, 384);
                if (tidk < 8) mbar_expect_tx(bb + B_MEM + tidk * 8, 2560);
                wg_wait<0>();
                TS(3);
                if (role == 2) sts128(ep_q, pack2(acc[0], acc[1]), pack2(acc[2], acc[3]), pack2(acc[4], acc[5]), pack2(acc[6], acc[7]));
                else stsm4t(ep_q, pack2(acc[0], acc[1]), pack2(acc[2], acc[3]), pack2(acc[4], acc[5]), pack2(acc[6], acc[7]));
                named_arrive(1, 384);
                if (t == NT - 1) break;
                if (tg0) {
                    if (__builtin_expect(!ok, 0)) mwait(bb + B_HF, mp);
                    if (role != 2) named_bar(2, 384);
                    token_gemm(IC<0>{}, true, mp * 16384, tg1 ? bb + B_HF + 8 : bb + B_MEM, tg1 ? (t + 1 - LAG) & 1 : mp ^ 1, t);
                } else {
                    if (role == 2) mwait(bb + B_OTE, mp); else named_bar(2, 384);
                    named_arrive(3, 384); named_bar(4, 384);
                    ok = 0;
                }
                TS(5);
                if (tg1) {
                    if (__builtin_expect(!ok, 0)) mwait(bb + B_HF + 8, (t + 1 - LAG) & 1);
                    token_gemm(IC<1>{}, false, mp * 16384, bb + B_MEM, mp ^ 1, t);
                }
                TS(6);
                named_arrive(13, 384);
            }
        } else {
            cluster_wait(); cluster_arrive_relaxed();
            const int ep = ld_relaxed(&g_epoch) + 1;
            const uint32_t cb = sb + (warp < 4 ? warp * CV_W : CV_HI + (warp - 4) * CV_W), lb = bb + B_MEM + warp * 8;
            auto fetch = [&](int k) {
                const int ps = k / 5, rg = ps ? ps - 1 : 0, ch = (sp * 5 + k - 5 * ps) * 8 + warp;
                if (k == 5 * ps) { flag_wait(FLG(F_U + ps), (ps > 1 ? 20 : (ps ? 32 : 320)) * ep, 50); fence_async_global(); }
                if (lane == 0) {
                    const uint32_t nb = ps ? ps * 1024 : 512;
                    mbar_expect_tx(lb, 2 * nb);
                    asm volatile("cp.async.bulk.shared::cluster.global.mbarrier::complete_tx::bytes [%0], [%1], %2, [%3];" ::"r"(cb + (k & 1) * 4096), "l"(g_U + ch * (S_LEN / 8)), "r"(nb), "r"(lb) : "memory");
                    asm volatile("cp.async.bulk.shared::cluster.global.mbarrier::complete_tx::bytes [%0], [%1], %2, [%3];" ::"r"(cb + 8192 + (k & 1) * CV_E + 128), "l"(A.ssmk + (size_t)ch * S_LEN), "r"(nb), "r"(lb) : "memory");
                }
                __syncwarp();
            };
            sts32(cb + 8192 + lane * 4, 0u); sts32(cb + 8192 + CV_E + lane * 4, 0u);
            if (warp == 0) sts32(sb + CV_Z + lane * 4, 0u);
            uint32_t dv = 0;
            if (lane < 5) {
                prefetch_l2(A.ssmk + (size_t)((sp * 5 + lane) * 8 + warp) * S_LEN, 1024);
                dv = *reinterpret_cast<const unsigned short*>(A.ssmD + (sp * 5 + lane) * 8 + warp) * 0x10001u;
            }
#pragma unroll
            for (int i = 1; i < 5; i++) sts32(cb + 8192 + i * 768 + lane * 4, 0u);
            named_bar(8, 256);
            flag_wait(FLG(F_U), 320 * ep, 50);
            fence_async_global();
            if (lane == 0) mbar_expect_tx(lb, 5120);
            __syncwarp();
            if (lane < 10) {
                const int j = lane >> 1, ch = (sp * 5 + j) * 8 + warp;
                asm volatile("cp.async.bulk.shared::cluster.global.mbarrier::complete_tx::bytes [%0], [%1], %2, [%3];" ::"r"((lane & 1) ? cb + j * 512 : cb + 8192 + j * 768 + 128),
                             "l"((lane & 1) ? (const void*)(g_U + ch * (S_LEN / 8)) : (const void*)(A.ssmk + (size_t)ch * S_LEN)), "r"(512), "r"(lb) : "memory");
            }
            __syncwarp();
#pragma unroll 1
            for (int k = 0; k < 25; k++) {
                const int ps = k / 5, rg = ps ? ps - 1 : 0;
                const uint32_t Dv = __shfl_sync(0xffffffffu, dv, k - 5 * ps);
                const int tb = sp == 0 && tid == 0 && k >= -1 && k < 7 ? 72 + k * 8 : -1;
                SC(tb >= 0, tb);
                if (k == 0 || ps) {
                    mwait(lb, k & 1);
                    SC(tb >= 0, tb + 1);
                    if (ps && k - 5 * ps < 4) { fence_async_smem(); fetch(k + 1); }
                    SC(tb >= 0, tb + 2);
                }
                const uint32_t tt = sb + CV_T + (k & 1) * 8192;
                conv_unit(cb + (ps ? (k & 1) * 4096 : k * 512), cb + 8192 + (ps ? (k & 1) * CV_E : k * 768), cb + 8192 + 2 * CV_E + 64, sb + CV_Z,
                          tt + warp * 1024 + (lane & 7) * 128 + (((lane >> 3) ^ (lane & 7) ^ warp) & 7) * 16, Dv, rg, ps ? 2 * ps : 1, lane, (uint32_t)A.h_target >> 8, tb);
                mwait(bb + B_OTE + (k & 1) * 16, ((k >> 1) & 1) ^ 1);
                named_bar(8, 256);
                {
                    const uint32_t la = tt + (lane & 7) * 1024 + warp * 128 + (((lane >> 3) ^ (lane & 7) ^ warp) & 7) * 16;
                    const uint4 v0 = ldsm4t(la), v1 = ldsm4t(la ^ 64);
                    const uint32_t ya = sb + CV_Y + (k & 1) * 8192 + (warp * 64 + (lane >> 3) * 8 + 7 - (lane & 7)) * 16;
                    stsm4(ya, v0.x, v0.y, v0.z, v0.w);
                    stsm4(ya + 512, v1.x, v1.y, v1.z, v1.w);
                }
                SC(tb >= 0, tb + 6);
                fence_async_smem();
                __syncwarp();
                if (lane == 0) mbar_arrive(bb + B_OTF + (k & 1) * 8);
                if (k - 5 * ps == 4 && k < 24) fetch(k + 1);
                if (k == 0 && lane < 5) prefetch_l2(A.ssmk + (size_t)((sp * 5 + lane) * 8 + warp) * S_LEN + 512, 3072);
            }
            cluster_wait();
        }
    } else if (warp < 12) {
        asm volatile("setmaxnreg.dec.sync.aligned.u32 %0;" ::"n"(REG_T));
        const int w = warp & 3, c = w >> 1, hh = w & 1;
        const uint32_t lane0 = __shfl_sync(0xffffffffu, tid & 31, tid & 31);
        if (head) {
            const int ntile = role == 2 ? 16 : 12;
            auto tile = [&](int i) { return (int)c_tile[role * 16 + i]; };
            const uint32_t wo = sb + O_WO;
            uint32_t mi[5][4];
#pragma unroll
            for (int i = 0; i < 5; i++)
#pragma unroll
                for (int q = 0; q < 4; q++) {
                    const unsigned short* mp = reinterpret_cast<const unsigned short*>(A.mem0) + 2 * q * DM + i * 128 + (tid & 127);
                    mi[i][q] = mp[0] | (uint32_t)mp[DM] << 16;
                }
            cluster_wait();
            named_bar(10, 384);
#pragma unroll
            for (int i = 0; i < 5; i++) {
                const int col = i * 128 + (tid & 127), kk = col >> 4, pr = (kk * 13) >> 6;
                const uint32_t ma = sb + O_MEM + (((p0 - pr) & 7) * 5 + kk - 5 * pr) * 512 + (col & 8) * 32 + (col & 7) * 16;
                sts128(ma, mi[i][0], mi[i][0], mi[i][1], mi[i][1]);
                sts128(ma + 128, mi[i][2], mi[i][2], mi[i][3], mi[i][3]);
            }
            fence_async_smem();
            named_arrive(11, 384);
            for (int i = tid & 127; i < ntile * 256; i += 128) {
                const int ti = i >> 8, p = (i >> 1) & 127, ch = i & 1;
                const int ks = p >> 4, kh = (p >> 3) & 1, e8 = p & 7;
                const int dim = 64 * (ks >> 2) + 16 * (e8 >> 1) + 8 * (e8 & 1) + 2 * (ks & 3) + kh;
                cp_async16(wo + ti * 4096 + p * 32 + ((ch ^ ((p >> 2) & 1)) << 4), A.Wo + (size_t)(h * DH + dim) * DM + tile(ti) * 16 + ch * 8);
            }
            cp_commit();
            if (lane < 8) {
                const int u = 2 * tile(w + 4 * (lane >> 1)) + (lane & 1), ow = u / 5;
                const int sl = u - 5 * ow;
                sts32(sb + O_TAB + w * 32 + lane * 4, mapa(sb + O_RED + (sl >> 1) * 2560 + (sl & 1) * 256 + hi * (sl < 4 ? 512 : 256), ow & 15));
            }
            cluster_arrive_relaxed(); cluster_wait();
            cp_wait<0>();
            named_bar(7, 128);
            const uint32_t wo_a = wo + w * 4096 + ((lane >> 4) * 8 + (lane & 7)) * 32 + ((((lane >> 3) & 1) ^ ((lane >> 2) & 1)) << 4);
            const uint32_t ob_0 = sb + (role == 2 ? O_PB : O_OBA) + (lane >> 4) * 2048 + ((lane >> 3) & 1) * 128 + ((lane & 7) ^ ((lane >> 1) & 4)) * 16;
            const float cs = 0.08838834764831845f * 1.4426950408889634f;
            auto w_frag = [&](auto four, int i) {
                return ldsm4t(wo_a + (i < 16 || decltype(four)::value == 4 ? (i >> 4) * 32768 + (i & 1) * 16384 + ((i >> 1) & 7) * 512 : (i >> 3) * 16384 + (i & 1) * 2048 + ((i >> 1) & 3) * 512));
            };
            auto w_pre = [&](auto four, uint4* wf) {
#pragma unroll
                for (int i = 0; i < 8; i++) wf[i] = w_frag(four, i);
            };
            auto w_run = [&](auto four, auto rem_, uint4* wf, int t, const uint32_t ob_a) {
                constexpr int NTL = decltype(four)::value, NF = 8 * NTL, NP = 2;
                constexpr bool REMOTE = decltype(rem_)::value;
                const uint32_t ln = opq(lane0), l8 = (ln & 2) * 64 + (ln >> 2) * 16 + (ln & 1) * 8, rb = (bb + B_RED) & 0xFFFFFFu;
                auto slot = [](int i) { return i < 8 ? i : 8 - WR + (i - 8) % WR; };
                uint4 obr[8];
#pragma unroll
                for (int k = 0; k < 4; k++) obr[k] = ldsm4(ob_a + k * 256);
#pragma unroll
                for (int p = 0; p < NP; p++) {
                    const bool split = p == 1 && NTL == 3;
                    const int nk = split ? 4 : 8;
                    float d[4][4];
                    uint4 ta;
#pragma unroll
                    for (int i = 0; i < 16; i++) (&d[0][0])[i] = 0.f;
#pragma unroll
                    for (int ks = 0; ks < 8; ks++) {
                        if (ks >= nk) continue;
                        if (p == 0 && ks == OBK) {
                            if (REMOTE) { mwait(bb + B_OB + 64, t & 1); TS(7); }
#pragma unroll
                            for (int k = 4; k < 8; k++) obr[k] = ldsm4(ob_a + k * 256);
                        }
                        if (ks == nk - 2) {
                            if (split) { const uint2 t2 = lds64(sb + O_TAB + w * 32 + 8 + p * 8); ta.x = t2.x; ta.y = t2.y; }
                            else ta = lds128(sb + O_TAB + w * 32 + p * 16);
                        }
#pragma unroll
                        for (int u = 0; u < 2; u++) {
                            const int i = p * 16 + ks * 2 + u;
                            const uint4& o = obr[split && u ? ks + 4 : ks];
                            const uint4& f = wf[slot(i)];
                            mmav(d[2 * u], f.x, f.y, f.z, f.w, o.x, o.y); mmav(d[2 * u + 1], f.x, f.y, f.z, f.w, o.z, o.w);
                            if (i + WR >= 8 && i + WR < NF) wf[slot(i + WR)] = w_frag(four, i + WR);
                        }
                    }
                    if (p) TS(10); else TS(8);
                    if (split) {
#pragma unroll
                        for (int i = 0; i < 4; i++) { d[0][i] += d[2][i]; d[1][i] += d[3][i]; }
                    }
                    st_async_v2(ta.x + l8, pack2(d[0][0], d[0][1]), pack2(d[1][0], d[1][1]), (ta.x & 0xFF000000u) | rb);
                    st_async_v2(ta.y + l8, pack2(d[0][2], d[0][3]), pack2(d[1][2], d[1][3]), (ta.y & 0xFF000000u) | rb);
                    if (!split) {
                        st_async_v2(ta.z + l8, pack2(d[2][0], d[2][1]), pack2(d[3][0], d[3][1]), (ta.z & 0xFF000000u) | rb);
                        st_async_v2(ta.w + l8, pack2(d[2][2], d[2][3]), pack2(d[3][2], d[3][3]), (ta.w & 0xFF000000u) | rb);
                    }
                }
            };
            if (role != 2) {
#pragma unroll 1
                for (int t = 0; t < NT; t++) {
                    const uint32_t lane = opq(lane0);
                    const uint32_t dc = mapa(sb, hi * 3 + 2), dp = mapa(sb, hi * 3 + (role ^ 1));
                    const uint32_t qa = sb + O_QRY + c * 5120 + (lane & 7) * 128;
                    const uint32_t sw = (((lane >> 3) ^ (lane & 7)) << 4) ^ (c << 6);
                    {
                        const uint32_t ka = qa + 10240;
                        const uint32_t kt = sb + O_KEY + c * 5120 + (lane & 15) * 128, kx = (((lane >> 4) ^ (lane & 7)) << 4) ^ (c << 6);
                        const uint32_t sd = dc + O_SM + role * 1536 + c * 768 + lane * 4, sbar = dc + O_BAR + B_SM;
                        const uint32_t ta = sb + O_QRY + c * 5120 + (8 + 16 * hh + ((lane & 15) ^ (role * 8))) * 128;
                        uint4 a[4], f[4];
                        named_bar(13, 384);
#pragma unroll
                        for (int i = 0; i < 4; i++) f[i] = ldsm4(kt + 1024 + hh * 2048 + (kx ^ (i << 5) ^ (hh << 6)));
#pragma unroll
                        for (int i = 0; i < 4; i++) a[i] = ldsm4(ta + (kx ^ (i << 5)));
                        const uint32_t kd = ka + (1 + 2 * hh) * 1024 + sw;
                        uint4 k[5];
                        k[1] = ldsm4(kd); k[2] = ldsm4(kd + 1024);
                        {
                            const uint32_t qh = qa + (sw ^ (hh << 6)), kh = kt + (kx ^ (hh << 6));
                            named_bar(1, 384);
                            const uint4 q0 = ldsm4(qh), g0 = ldsm4(kh), g1 = ldsm4(kh ^ 32), q1 = ldsm4(qh ^ 64);
                            float s0[4] = {0.f, 0.f, 0.f, 0.f}, s1[4] = {0.f, 0.f, 0.f, 0.f}, s2[4] = {0.f, 0.f, 0.f, 0.f}, s3[4] = {0.f, 0.f, 0.f, 0.f};
                            mmav(s0, f[0].x, f[0].y, f[0].z, f[0].w, q0.x, q0.y); mmav(s1, f[1].x, f[1].y, f[1].z, f[1].w, q0.z, q0.w);
                            mmav(s2, g0.x, g0.y, g0.z, g0.w, q0.x, q0.y); mmav(s3, g1.x, g1.y, g1.z, g1.w, q0.z, q0.w);
                            mmav(s0, f[2].x, f[2].y, f[2].z, f[2].w, q1.x, q1.y); mmav(s1, f[3].x, f[3].y, f[3].z, f[3].w, q1.z, q1.w);
                            k[0] = ldsm4(ka + sw); k[3] = ldsm4(ka + 1024 + sw); k[4] = ldsm4(ka + 2048 + sw);
                            st_async_b32(sd + hh * 128, pack2(s2[0] + s3[0], s2[1] + s3[1]), sbar);
                            st_async_b32(sd + 256 + hh * 256, pack2(s0[0] + s1[0], s0[1] + s1[1]), sbar);
                            st_async_b32(sd + 384 + hh * 256, pack2(s0[2] + s1[2], s0[3] + s1[3]), sbar);
                        }
                        TS(1);
                        float u[5][4];
#pragma unroll
                        for (int i = 0; i < 20; i++) (&u[0][0])[i] = 0.f;
                        auto half = [&](auto nn, const uint4& a0, const uint4& a1, bool more) {
                            constexpr int NU = decltype(nn)::value;
                            constexpr int ord[5] = {1, 2, 0, 3, 4};
#pragma unroll
                            for (int i = 0; i < NU; i++) mmav(u[ord[i]], a0.x, a0.y, a0.z, a0.w, k[ord[i]].x, k[ord[i]].y);
#pragma unroll
                            for (int i = 0; i < NU; i++) {
                                const int n = ord[i];
                                mmav(u[n], a1.x, a1.y, a1.z, a1.w, k[n].z, k[n].w);
                                if (more) k[n] = ldsm4(((n == 0 ? ka + sw : (n < 3 ? kd + (n - 1) * 1024 : ka + (n - 2) * 1024 + sw))) ^ 64);
                            }
                        };
                        auto fu = [](float x) { return __float_as_uint(x); };
                        const uint32_t so = O_ST + c * 2048 + hh * 768, td = dp + so, tb = dp + O_BAR + B_ST, lo = sb + so + 4096;
                        if (hh) {
                            half(IC<5>{}, a[0], a[1], true); half(IC<5>{}, a[2], a[3], false);
                            st_async_v4(td + lane * 16, fu(u[0][2]), fu(u[0][3]), fu(u[1][2]), fu(u[1][3]), tb);
                            st_async_v4(td + 512 + lane * 16, fu(u[2][2]), fu(u[2][3]), fu(u[3][2]), fu(u[3][3]), tb);
                            st_async_v2(td + 1024 + lane * 8, fu(u[4][2]), fu(u[4][3]), tb);
                            sts128(lo + lane * 16, fu(u[0][0]), fu(u[0][1]), fu(u[1][0]), fu(u[1][1]));
                            sts128(lo + 512 + lane * 16, fu(u[2][0]), fu(u[2][1]), fu(u[3][0]), fu(u[3][1]));
                            sts64(lo + 1024 + lane * 8, fu(u[4][0]), fu(u[4][1]));
                        } else {
                            half(IC<3>{}, a[0], a[1], true); half(IC<3>{}, a[2], a[3], false);
                            st_async_v4(td + lane * 16, fu(u[0][2]), fu(u[0][3]), fu(u[1][2]), fu(u[1][3]), tb);
                            st_async_v2(td + 512 + lane * 8, fu(u[2][2]), fu(u[2][3]), tb);
                            sts128(lo + lane * 16, fu(u[0][0]), fu(u[0][1]), fu(u[1][0]), fu(u[1][1]));
                            sts64(lo + 512 + lane * 8, fu(u[2][0]), fu(u[2][1]));
                        }
                        if (t < NT - 1) named_arrive(2, 384);
                        __syncwarp();
                        if (lane == 0) mbar_arrive(bb + B_ST);
                        TS(2);
                    }
                    if (t == NT - 1) break;
                    uint4 wf[8];
                    w_pre(IC<3>{}, wf);
                    named_bar(3, 384);
                    mwait(bb + B_OB, t & 1);
                    TS(3);
                    w_run(IC<3>{}, IC<1>{}, wf, t, ob_0);
                    named_arrive(4, 384);
                    if (w == 0 && lane == 0) { mbar_expect_tx(bb + B_OB, 2048); mbar_expect_tx(bb + B_OB + 64, 2048); }
                    TS(5);
                }
            } else {
#pragma unroll 1
                for (int t = 0; t < NT; t++) {
                    const uint32_t lane = opq(lane0);
                    const int g = lane >> 2, tq = lane & 3;
                    const uint32_t vm_a = sb + O_VM + (g * 4 + 2 * (tq & 1) + (c ^ ((g >> 1) & 1))) * 16 + (tq >> 1) * 8;
                    const uint32_t vt_a = sb + O_VT + (t & 1) * 16384 + ((lane >> 3) & 1) * 512 + (lane >> 4) * 128 + (lane & 7) * 16;
                    named_bar(13, 384);
                    uint4 va[4][2];
#pragma unroll
                    for (int i = 0; i < 4; i++) {
                        va[i][0] = ldsm4(vt_a + c * 8192 + (4 * hh + i) * 1024);
                        va[i][1] = ldsm4(vt_a + c * 8192 + (4 * hh + i) * 1024 + 256);
                    }
                    const uint32_t sa = opq(sb + O_SM + c * 768 + 256 + lane * 16), sa2 = opq(sb + O_SM + c * 768 + (lane & 15) * 16 + (lane >> 4) * 1536), vm_b = opq(vm_a + hh * 2048);
                    named_bar(1, 384);
                    if (__builtin_expect(t < NT - 1, 1)) {
                        uint2 vm[4];
#pragma unroll
                        for (int i = 0; i < 4; i++) vm[i] = lds64(vm_b + i * 512);
                        mwait(bb + B_SM, t & 1);
                        TS(1);
                        const uint4 x0 = ldsm4t(sa), y0 = ldsm4t(sa + 1536), x1 = ldsm4t(sa2);
                        float s[10];
                        s[2] = blo(x0.x) + blo(y0.x); s[3] = bhi(x0.x) + bhi(y0.x); s[4] = blo(x0.y) + blo(y0.y); s[5] = bhi(x0.y) + bhi(y0.y);
                        s[6] = blo(x0.z) + blo(y0.z); s[7] = bhi(x0.z) + bhi(y0.z); s[8] = blo(x0.w) + blo(y0.w); s[9] = bhi(x0.w) + bhi(y0.w);
                        s[0] = (blo(x1.x) + blo(x1.y)) + (blo(x1.z) + blo(x1.w)); s[1] = (bhi(x1.x) + bhi(x1.y)) + (bhi(x1.z) + bhi(x1.w));
                        float mx = fmaxf(fmaxf(fmaxf(s[0], s[1]), fmaxf(s[2], s[3])), fmaxf(fmaxf(fmaxf(s[4], s[5]), fmaxf(s[6], s[7])), fmaxf(s[8], s[9])));
                        const float m1 = __shfl_xor_sync(0xffffffffu, mx, 1), m2 = __shfl_xor_sync(0xffffffffu, mx, 2), m3 = __shfl_xor_sync(0xffffffffu, mx, 3);
                        mx = fmaxf(fmaxf(mx, m1), fmaxf(m2, m3)) * -cs;
                        uint32_t pb[5];
#pragma unroll
                        for (int i = 0; i < 5; i++) pb[i] = pack2(ex2f(fmaf(s[2 * i], cs, mx)), ex2f(fmaf(s[2 * i + 1], cs, mx)));
                        TS(9);
                        named_bar(3, 384);
                        float o[5][4];
#pragma unroll
                        for (int i = 0; i < 20; i++) (&o[0][0])[i] = 0.f;
                        const uint32_t one2 = 0x3F803F80u;
                        float z[2][4] = {{0.f, 0.f, 0.f, 0.f}, {0.f, 0.f, 0.f, 0.f}};
                        mmav8(o[4], one2, one2, pb[0]);
                        mmav(z[0], one2, one2, one2, one2, pb[1], pb[2]);
                        mmav(z[1], one2, one2, one2, one2, pb[3], pb[4]);
#pragma unroll
                        for (int i = 0; i < 4; i++) mmav8(o[i], vm[i].x, vm[i].y, pb[0]);
#pragma unroll
                        for (int i = 0; i < 4; i++) mmav(o[i], va[i][0].x, va[i][0].y, va[i][0].z, va[i][0].w, pb[1], pb[2]);
#pragma unroll
                        for (int i = 0; i < 4; i++) mmav(o[i], va[i][1].x, va[i][1].y, va[i][1].z, va[i][1].w, pb[3], pb[4]);
                        o[4][0] += z[0][0] + z[1][0]; o[4][1] += z[0][1] + z[1][1];
                        uint4 wf[8];
                        w_pre(IC<4>{}, wf);
                        const float r0 = rcpf(o[4][0]), r1 = rcpf(o[4][1]);
                        const uint32_t oo = c * 2048 + hh * 1024 + g * 128 + tq * 16 + (g & 1) * 64;
                        uint32_t e0[4], e1[4];
#pragma unroll
                        for (int i = 0; i < 4; i++) { e0[i] = pack2(o[i][0] * r0, o[i][2] * r0); e1[i] = pack2(o[i][1] * r1, o[i][3] * r1); }
                        sts128(sb + O_PB + (~t & 1) * 5120 + oo, e0[0], e0[1], e0[2], e0[3]);
                        sts128(sb + O_PB + (~t & 1) * 5120 + (oo ^ 64), e1[0], e1[1], e1[2], e1[3]);
                        {
                            const uint32_t da = mapa(sb + O_OBA, r - 2) + oo, ba = mapa(bb + B_OB + hh * 64, r - 2);
                            st_async_v4(da, e0[0], e0[1], e0[2], e0[3], ba);
                            st_async_v4(da + 0x01000000u, e0[0], e0[1], e0[2], e0[3], ba + 0x01000000u);
                            st_async_v4(da ^ 64, e1[0], e1[1], e1[2], e1[3], ba);
                            st_async_v4((da ^ 64) + 0x01000000u, e1[0], e1[1], e1[2], e1[3], ba + 0x01000000u);
                        }
                        TS(3);
                        named_bar(7, 128);
                        w_run(IC<4>{}, IC<0>{}, wf, t, ob_0 + (~t & 1) * 5120);
                        named_arrive(4, 384);
                        mwait(bb + B_ST, t & 1);
                        TS(4);
                    } else { mwait(bb + B_SM, t & 1); mwait(bb + B_ST, t & 1); }
                    TS(5);
                    fence_async_smem();
#pragma unroll 1
                    for (int l = t < NSEG ? 0 : 1; l < (t >= LAG ? 2 : 1); l++) {
                        const uint32_t pb_ = ((1024 + O_PB) >> 4) + (t & 1) * 320 + l * 160, va_ = (((1024 + O_VT) >> 4) + (t & 1) * 1024 + l * 512) | (8u << 16);
                        const uint32_t oa = sb + O_VT + (t & 1) * 16384 + l * 8192 + w * 1024 + g * 64 + ((tq ^ (g >> 1)) & 3) * 16;
                        const uint32_t vl = (vm_a ^ ((l ^ c) << 4)) + w * 512;
                        const uint2 a0 = lds64(vl), a1 = lds64(vl + 2048);
                        float d[2][16];
                        wg_fence();
                        wg_n32_first(d[0], a0.x, a0.y, 0u, 0u, mkdesc(pb_, 8));
                        wg_n32_first(d[1], a1.x, a1.y, 0u, 0u, mkdesc(pb_, 8));
#pragma unroll
                        for (int i = 0; i < 4; i++) wg_n32_kk(d[i & 1], mkdesc(va_ + (i & 1) * 256 + (i >> 1) * 16, 32), mkdesc(pb_ + 32 + (i >> 1) * 64 + (32u << 16), 8));
                        wg_commit();
                        if (l) TS(13); else TS(11);
                        wg_wait<0>();
                        if (l) TS(14); else TS(12);
#pragma unroll
                        for (int mt = 0; mt < 2; mt++) {
                            sts128(oa + mt * 4096, pack2(d[mt][0], d[mt][1]), pack2(d[mt][4], d[mt][5]), pack2(d[mt][8], d[mt][9]), pack2(d[mt][12], d[mt][13]));
                            sts128(oa + mt * 4096 + 512, pack2(d[mt][2], d[mt][3]), pack2(d[mt][6], d[mt][7]), pack2(d[mt][10], d[mt][11]), pack2(d[mt][14], d[mt][15]));
                        }
                        if (l == 0) {
                            fence_async_smem();
                            __syncwarp();
                            if (lane == 0) mbar_arrive(bb + B_OTF + 8);
                        }
                    }
                    TS(6);
                    if (w == 0 && lane == 0) { mbar_expect_tx(bb + B_ST, 5120); mbar_expect_tx(bb + B_SM, 3072); }
                    fence_async_smem();
                    __syncwarp();
                    if (lane == 0) mbar_arrive(bb + B_OTF);
                    if (t < NT - 1) named_arrive(5, 384);
                }
            }
        } else {
            cluster_wait(); cluster_arrive_relaxed();
            const int wi = sp * 4 + w, half = wi >> 5, tok = wi & 31, ep = ld_relaxed(&g_epoch) + 1;
            GT(lane == 0, 89);
            if (lane < LN0_AHEAD / 2) prefetch_l2(A.x + (size_t)((half + 2 * lane) * SEG + tok) * DM, 1280);
#pragma unroll 1
            for (int k = -LN0_AHEAD / 2; k < NT; k++) {
                const int s0 = k < 0 ? 2 * k + LN0_AHEAD + half : (half && k % LN0_BATCH == 0 ? k + LN0_AHEAD : NSEG);
                if (s0 < NSEG) { ln0_rows(A.x, s0, k < 0 ? 1 : LN0_BATCH, tok, lane); GT(lane == 0 && k < 0, 30 + s0); }
                if (k == -1 && half) {
#pragma unroll 1
                    for (int u = 320 + tok; u < 640; u += 32) u_half(A.Bk, A.Bv, A.shiftk, u, lane);
                    __syncwarp();
                    if (lane == 0) red_release(FLG(F_U + 1), 1);
                }
                const int n = k - half * LAG;
                if (n >= 0 && n < NSEG && k >= 0) {
                    post_row(half, n, tok, lane, A.x, A.out, ep);
                    GT(lane == 0 && (n & 3) == 0 && k >= 0, 460 + half * 16 + (n >> 2)); GT(lane == 0 && n == 63 && half, 40);
                }
            }
            cluster_wait();
        }
    } else {
        asm volatile("setmaxnreg.dec.sync.aligned.u32 %0;" ::"n"(REG_X));
        cluster_wait();
        const int s = warp - 12;
        const uint32_t lane0 = __shfl_sync(0xffffffffu, tid & 31, tid & 31);
        if (s < 3) {
            cluster_arrive_relaxed();
            GT(lane == 0, 84);
            if (blockIdx.x * 3 + s < 320) {
                u_half(A.Bk, A.Bv, A.shiftk, blockIdx.x * 3 + s, lane);
                GT(lane == 0, 85);
                __syncwarp();
                if (lane == 0) red_release(FLG(F_U), 1);
                GT(lane == 0, 4);
            }
            const int ztgt = 3 * 16 * NCL * (ld_relaxed(&g_epoch) + 1);
#pragma unroll
            for (int i = 0; i < XRS; i++) st_relaxed_v4(g_xc + ((i * 16 + r) * 3 + s) * 256 + cq * 32 + lane, 0, 0, 0, 0);
            __syncwarp();
            if (lane == 0) red_release(FLG(F_Z), 1);
            cluster_wait();
            constexpr uint32_t XSLOT = 16 * 3 * 4096;
            uint32_t xo_ = (r * 3 + s) * 4096;
            if (s == 0) {
                const uint32_t G = lane >> 1, d = ((r + 2 * G) & 15) ^ (lane & 1);
                if (lane < 16) { sts32(sb + O_BT + lane * 8, (d << 24) + G * 2560); sts32(sb + O_BT + lane * 8 + 4, d < 3 * nh ? mapa(bb + B_MEM + G * 8, d) : 0u); }
            }
            while (ld_acquire(FLG(F_Z)) < ztgt) __nanosleep(100);
            named_bar(14, 96);
#pragma unroll 1
            for (int t = 0; t < NT; t++) {
                const uint32_t lane = opq(lane0);
                if (head && role != 2) {
                    auto soft = [&](auto uu, auto vv, int c0, int hh) {
                        constexpr int U = decltype(uu)::value, NV = decltype(vv)::value;
                        const uint32_t dc = mapa(sb, hi * 3 + 2), sa = sb + O_ST + c0 * 2048 + hh * 768;
                        const uint32_t pd = dc + O_PB + (t & 1) * 5120 + c0 * 2560 + (2 * hh + role) * 128 + lane * 4, pbar = dc + O_BAR + B_ST;
                        const int lim = 8 * role + (int)(lane >> 2) - 2 * (int)(lane & 3);
                        auto uf = [](uint32_t x) { return __uint_as_float(x); };
                        mwait(bb + B_ST, t & 1);
                        if (r == 1 && U == 2 && t >= LAG - 1 && t < NT - 1) named_arrive(12, 64);
                        uint32_t z[U][NV];
                        auto zz = [](float x, float y) { const uint32_t w = pack2(x, y); return pack2(blo(w) * 0.08838834764831845f, bhi(w) * 0.08838834764831845f); };
#pragma unroll
                        for (int i = 0; i < U; i++) {
                            const uint4 v = lds128(sa + i * 2048 + lane * 16), w = lds128(sa + i * 2048 + 4096 + lane * 16);
                            z[i][0] = zz(uf(v.x) + uf(w.x), uf(v.y) + uf(w.y));
                            z[i][1] = zz(lim < 0 ? -INFINITY : uf(v.z) + uf(w.z), lim < 1 ? -INFINITY : uf(v.w) + uf(w.w));
                            if (NV == 3) {
                                const uint2 x = lds64(sa + i * 2048 + 512 + lane * 8), y = lds64(sa + i * 2048 + 4608 + lane * 8);
                                z[i][2] = zz(lim < 8 ? -INFINITY : uf(x.x) + uf(y.x), lim < 9 ? -INFINITY : uf(x.y) + uf(y.y));
                            } else {
                                const uint4 x = lds128(sa + 512 + lane * 16), y = lds128(sa + 4608 + lane * 16);
                                const uint2 p = lds64(sa + 1024 + lane * 8), q = lds64(sa + 5120 + lane * 8);
                                z[i][2] = zz(lim < 8 ? -INFINITY : uf(x.x) + uf(y.x), lim < 9 ? -INFINITY : uf(x.y) + uf(y.y));
                                z[i][NV - 2] = zz(uf(x.z) + uf(y.z), uf(x.w) + uf(y.w));
                                z[i][NV - 1] = zz(uf(p.x) + uf(q.x), uf(p.y) + uf(q.y));
                            }
                        }
                        const float l2e = 1.4426950408889634f;
                        float e[U][2 * NV], sum[U];
#pragma unroll
                        for (int i = 0; i < U; i++) {
                            uint32_t zm = bmax2(bmax2(z[i][0], z[i][1]), z[i][2]);
                            if (NV == 5) zm = bmax2(zm, bmax2(z[i][NV - 2], z[i][NV - 1]));
                            zm = bmax2(zm, __shfl_xor_sync(0xffffffffu, zm, 1));
                            zm = bmax2(zm, __shfl_xor_sync(0xffffffffu, zm, 2));
                            const float mx = fmaxf(blo(zm), bhi(zm)) * -l2e;
                            sum[i] = 0.f;
#pragma unroll
                            for (int n = 0; n < NV; n++) { e[i][2 * n] = ex2f(fmaf(blo(z[i][n]), l2e, mx)); e[i][2 * n + 1] = ex2f(fmaf(bhi(z[i][n]), l2e, mx)); }
                            sum[i] = ((e[i][0] + e[i][1]) + (e[i][2] + e[i][3])) + (e[i][4] + e[i][5]);
                            if (NV == 5) sum[i] += (e[i][2 * NV - 4] + e[i][2 * NV - 3]) + (e[i][2 * NV - 2] + e[i][2 * NV - 1]);
                            sum[i] += __shfl_xor_sync(0xffffffffu, sum[i], 1);
                            sum[i] += __shfl_xor_sync(0xffffffffu, sum[i], 2);
                            sum[i] = rcpf(sum[i]);
                        }
#pragma unroll
                        for (int i = 0; i < U; i++)
#pragma unroll
                            for (int n = 0; n < 5; n++)
                                st_async_b32(pd + i * 2560 + (n == 0 ? 0 : (NV == 3 ? n : (n < 3 ? n + 2 : n - 2)) * 512), n < NV ? pack2(e[i][2 * n] * sum[i], e[i][2 * n + 1] * sum[i]) : 0u, pbar);
                    };
                    if (s < 2) soft(IC<1>{}, IC<5>{}, s, 1); else soft(IC<2>{}, IC<3>{}, 0, 0);
                    TS(12);
                    named_bar(14, 96);
                    if (s == 0 && lane == 0) mbar_expect_tx(bb + B_ST, 4096);
                }
                if (t == NT - 1) break;
                uint32_t m0 = 0x80008000u, m1 = 0x80008000u;
                if (t < LAG && cq == 0) {
                    const uint32_t ch = s < 2 ? lane : lane >> 1;
                    const unsigned short* mp = reinterpret_cast<const unsigned short*>(A.mem0) + (((ch >> 3) & 1) * 4 + (s < 2 ? 0 : (lane & 1) * 2)) * DM + (5 * r + 2 * s + (ch >> 4)) * 8 + (ch & 7);
                    m0 = max(mp[0] | (uint32_t)mp[DM] << 16, 1u);
                    if (s < 2) m1 = max(mp[2 * DM] | (uint32_t)mp[3 * DM] << 16, 1u);
                }
                const bool late = t >= LAG;
                auto sum5 = [](uint32_t a, uint32_t b, uint32_t c, uint32_t d, uint32_t e) { return nz(badd(badd(badd(a, b), e), badd(c, d))); };
                auto sum7 = [](uint32_t a, uint32_t b, uint32_t c, uint32_t d, uint32_t e, uint32_t f, uint32_t h_) {
                    return badd(badd(badd(a, b), badd(c, d)), badd(badd(e, f), h_));
                };
                auto min3 = [](uint32_t a, uint32_t b, uint32_t c) { return min(min(a, b), c); };
                auto bcast = [&](auto two, const uint32_t aa, uint32_t x0, uint32_t x1, uint32_t x2, uint32_t x3) {
                    auto send = [&](uint32_t o, uint32_t bar) { if (decltype(two)::value) st_async_v4p(aa + o, x0, x1, x2, x3, bar); else st_async_v2p(aa + o, x0, x1, bar); };
                    uint4 e[5];
                    e[0] = lds128(sb + O_BT);
                    TS(8);
                    send(e[0].x, e[0].y); send(e[0].z, e[0].w);
                    TS(9);
#pragma unroll
                    for (int i = 1; i < 5; i++) e[i] = lds128(sb + O_BT + i * 16);
#pragma unroll
                    for (int i = 1; i < 8; i++) {
                        send(e[(i - 1) % 4 + 1].x, e[(i - 1) % 4 + 1].y); send(e[(i - 1) % 4 + 1].z, e[(i - 1) % 4 + 1].w);
                        if (i < 4) e[i] = lds128(sb + O_BT + (i + 4) * 16);
                    }
                };
                const uint32_t ma = (sb + O_MEM + (5 * (r & 1) + 2 * s) * 256) & 0xFFFFFFu;
                int guard = 0;
                if (s < 2) {
                    const uint32_t ra = sb + O_RED + s * 2560 + lane * 16;
                    uint4* xb = reinterpret_cast<uint4*>(reinterpret_cast<char*>(g_xc) + xo_ + lane * 16);
                    uint4* xo = xb + cq * 32;
                    touch(xo); touch(xb);
                    mwait(bb + B_RED, t & 1);
                    TS(0);
                    uint4 p[5];
#pragma unroll
                    for (int i = 0; i < 5; i++) p[i] = i < 4 || nh == 5 ? lds128(ra + i * 512) : make_uint4(0, 0, 0, 0);
                    const uint32_t u1 = sum5(p[0].y, p[1].y, p[2].y, p[3].y, p[4].y), u3 = sum5(p[0].w, p[1].w, p[2].w, p[3].w, p[4].w);
                    st_relaxed_v4(xo, sum5(p[0].x, p[1].x, p[2].x, p[3].x, p[4].x), late ? u1 : m0, sum5(p[0].z, p[1].z, p[2].z, p[3].z, p[4].z), late ? u3 : m1);
                    TS(1);
                    delay(XD);
                    uint4 x[NCL];
                    while (true) {
                        ld7_relaxed(x, xb);
                        const uint32_t mn = min3(min3(min3(x[0].x, x[0].y, x[0].z), min3(x[0].w, x[1].x, x[1].y), min3(x[1].z, x[1].w, x[2].x)),
                                                 min3(min3(x[2].y, x[2].z, x[2].w), min3(x[3].x, x[3].y, x[3].z), min3(x[3].w, x[4].x, x[4].y)),
                                                 min3(min3(x[4].z, x[4].w, x[5].x), min3(x[5].y, x[5].z, x[5].w), min(min3(x[6].x, x[6].y, x[6].z), x[6].w)));
                        if (NO_X || __all_sync(0xffffffffu, mn != 0)) break;
                        if (++guard > 2000000) __trap();
                    }
                    TS(2);
                    TV(4, guard);
                    bcast(IC<1>{}, ma + lane * 16, sum7(x[0].x, x[1].x, x[2].x, x[3].x, x[4].x, x[5].x, x[6].x), sum7(x[0].y, x[1].y, x[2].y, x[3].y, x[4].y, x[5].y, x[6].y),
                          sum7(x[0].z, x[1].z, x[2].z, x[3].z, x[4].z, x[5].z, x[6].z), sum7(x[0].w, x[1].w, x[2].w, x[3].w, x[4].w, x[5].w, x[6].w));
                } else {
                    const uint32_t ra = sb + O_RED + 5120 + lane * 8;
                    uint2* xb = reinterpret_cast<uint2*>(reinterpret_cast<char*>(g_xc) + xo_ + lane * 8);
                    uint2* xo = xb + cq * 64;
                    touch(xo); touch(xb);
                    mwait(bb + B_RED, t & 1);
                    TS(0);
                    uint2 p[5];
#pragma unroll
                    for (int i = 0; i < 5; i++) p[i] = i < 4 || nh == 5 ? lds64(ra + i * 256) : make_uint2(0, 0);
                    const uint32_t u1 = sum5(p[0].y, p[1].y, p[2].y, p[3].y, p[4].y);
                    st_relaxed_v2(xo, sum5(p[0].x, p[1].x, p[2].x, p[3].x, p[4].x), late ? u1 : m0);
                    if (lane == 0) mbar_expect_tx(bb + B_RED, nh * 1280);
                    TS(1);
                    delay(XD);
                    uint32_t y0, y1;
                    while (true) {
                        uint2 x[NCL];
                        ld7_relaxed(x, xb);
                        const uint32_t mn = min3(min3(min3(x[0].x, x[0].y, x[1].x), min3(x[1].y, x[2].x, x[2].y), min3(x[3].x, x[3].y, x[4].x)), min3(x[4].y, x[5].x, x[5].y), min(x[6].x, x[6].y));
                        y0 = sum7(x[0].x, x[1].x, x[2].x, x[3].x, x[4].x, x[5].x, x[6].x); y1 = sum7(x[0].y, x[1].y, x[2].y, x[3].y, x[4].y, x[5].y, x[6].y);
                        if (NO_X || __all_sync(0xffffffffu, mn != 0)) break;
                        if (++guard > 2000000) __trap();
                    }
                    TS(2);
                    TV(4, guard);
                    bcast(IC<0>{}, ma + lane * 8, y0, y1, 0u, 0u);
                }
                TS(3);
                if (head && role == 2) named_arrive(6, 128);
                xo_ += XSLOT; if (xo_ >= XRS * XSLOT) xo_ -= XRS * XSLOT;
                {
                    const uint32_t zo = xo_ + XSLOT >= XRS * XSLOT ? xo_ + XSLOT - XRS * XSLOT : xo_ + XSLOT;
                    char* zp = reinterpret_cast<char*>(g_xc) + zo + cq * 512 + lane * 16;
                    st_relaxed_v4(zp, 0, 0, 0, 0);
                    if (ld_relaxed_v4(zp).x) __trap();
                }
            }
        } else if (r < 2) {
            const uint16_t mask = (uint16_t)((1u << (3 * nh)) - 1u);
            const int htgt = A.h_target * (ld_relaxed(&g_epoch) + 1);
#pragma unroll 1
            for (int n = 0; n < NSEG; n++) {
                if (n == (r == 0 ? 1 : 0)) { cluster_arrive_relaxed(); cluster_wait(); }
                int guard = 0;
                while (ld_acquire(FLG(F_H + r * 64 + n)) < htgt) { if (++guard > 2000000) __trap(); __nanosleep(H_NS); }
                fence_async_global();
                TS(0);
                if (r == 1) named_bar(12, 64);
                TS(1);
                if (n) mwait(bb + B_HE, (n - 1) & 1);
                TS(2);
                if (lane < 8)
                    asm volatile("cp.async.bulk.shared::cluster.global.mbarrier::complete_tx::bytes.multicast::cluster [%0], [%1], %2, [%3], %4;" ::"r"(sb + O_H + r * 40960 + lane * 5120),
                                 "l"(g_ht + rslot(r, n) * 2560 + lane * 320), "r"(5120), "r"(bb + B_HF + r * 8), "h"(mask) : "memory");
                __syncwarp();
            }
        } else {
            cluster_arrive_relaxed(); cluster_wait();
            if (head && role == 2) {
#pragma unroll 1
                for (int t = 0; t < NT; t++) {
                    auto put = [&](int l, int n) {
                        asm volatile("cp.async.bulk.global.shared::cta.bulk_group [%0], [%1], %2;" ::"l"(g_ot + (rslot(l, n) * 256 + h * 8) * 64), "r"(sb + O_VT + (t & 1) * 16384 + l * 8192), "r"(8192) : "memory");
                        asm volatile("cp.async.bulk.commit_group;" ::: "memory");
                    };
                    auto publish = [&](int l, int n) {
                        asm volatile("cp.async.bulk.wait_group 0;" ::: "memory");
                        fence_async_global();
                        red_release(FLG(F_O + l * 64 + n) + (h >> 3), 1);
                        GT(true, 200 + l * 64 + n);
                    };
                    if (t < NSEG) {
                        mwait(bb + B_OTF + 8, t & 1);
                        TS(0);
                        if (lane == 0) { put(0, t); publish(0, t); }
                        __syncwarp();
                        TS(1);
                    }
                    mwait(bb + B_OTF, t & 1);
                    TS(2);
                    if (t < NT - 1) named_bar(6, 128);
                    TS(3);
                    if (lane == 0) {
                        if (t >= LAG) {
                            put(1, t - LAG);
                            asm volatile("cp.async.bulk.wait_group.read 0;" ::: "memory");
                        }
                        mbar_arrive(bb + B_OTE);
                        TS(8);
                        if (t >= LAG) publish(1, t - LAG);
                        TS(9);
                    }
                    __syncwarp();
                }
            }
            if (!head && lane == 0) {
#pragma unroll 1
                for (int k = 0; k < 25; k++) {
                    const int rg = k / 5, r0 = rg == 1 ? 256 : 0;
                    mwait(bb + B_OTF + (k & 1) * 8, (k >> 1) & 1);
                    asm volatile("cp.async.bulk.global.shared::cta.bulk_group [%0], [%1], %2;" ::"l"(g_Y + (sp * 5 + k - 5 * rg) * S_LEN + (rg ? rg - 1 : 0) * 512 + r0),
                                 "r"(sb + CV_Y + (k & 1) * 8192 + r0 * 16), "r"(rg < 2 ? 4096 : 8192) : "memory");
                    asm volatile("cp.async.bulk.commit_group;" ::: "memory");
                    asm volatile("cp.async.bulk.wait_group 0;" ::: "memory");
                    mbar_arrive(bb + B_OTE + (k & 1) * 16);
                    fence_async_global();
                    red_release(FLG(F_CV + rg), 1);
                    GT(true, 50 + k);
                }
            }
            __syncwarp();
        }
    }
    cluster_arrive_relaxed(); cluster_wait();
    if (blockIdx.x == 0 && tid == 0) atomicAdd(&g_epoch, 1);
}
}

namespace ws {
constexpr int OP_SS = 17;
constexpr int P_RING = 0, P_AS = 131072, P_STG = P_AS + 2 * OP_SS * 2048, P_BAR = P_STG + 16384, OP_SMEM = P_BAR + 256;
constexpr int PB_FULL = 0, PB_EMPTY = 128, PB_SF = 144, PB_SE = 176;
static_assert(OP_SMEM <= 232448, "smem");
#define OP_MIX 1
__host__ __device__ constexpr bool op_ss(int j) { return OP_MIX ? (j % 4 == 0 || j == 63) : j < OP_SS; }
__host__ __device__ constexpr int op_idx(int j) { return OP_MIX ? (op_ss(j) ? (j + 1) / 4 : j - (j + 3) / 4) : (j < OP_SS ? j : j - OP_SS); }
__device__ __forceinline__ int op_rs_step(int i) { return OP_MIX ? i + i / 3 + 1 : OP_SS + i; }
__device__ __forceinline__ int op_ss_step(int i) { return OP_MIX ? (i < 16 ? 4 * i : 63) : i; }

__global__ void __launch_bounds__(384, 1) op_kernel(const bf16* __restrict__ Wo, const bf16* __restrict__ Bk, const bf16* __restrict__ Bv, const bf16* __restrict__ shiftk) {
    extern __shared__ __align__(1024) unsigned char smem_raw[];
    const int tid = threadIdx.x, warp = __shfl_sync(0xffffffffu, tid >> 5, 0), lane = tid & 31;
    const int nb = blockIdx.x % 5, ks = blockIdx.x / 5;
    const uint32_t sb = smem_u32(smem_raw), bb = sb + P_BAR;
    if (tid == 0) {
        if ((sb & 0xFFFFFFu) != 1024) __trap();
        for (int i = 0; i < 16; i++) mbar_init(bb + PB_FULL + i * 8, 1);
        for (int i = 0; i < 2; i++) mbar_init(bb + PB_EMPTY + i * 8, 2);
        for (int i = 0; i < 4; i++) { mbar_init(bb + PB_SF + i * 8, 4); mbar_init(bb + PB_SE + i * 8, 1); }
        asm volatile("fence.mbarrier_init.release.cluster;" ::: "memory");
    }
    GT(tid == 0, 8);
    __syncthreads();
    if (warp < 4) {
        asm volatile("setmaxnreg.dec.sync.aligned.u32 40;");
        if (warp == 0) {
            named_bar(3, 288);
            GT(lane == 0, 3);
            uint32_t it = 0;
            const int otgt = 8 * (ld_relaxed(&g_epoch) + 1);
#pragma unroll 1
            for (int q = 0; q < 2 * NT; q++) {
                const int l = q & 1, n = (q >> 1) - l * LAG;
                if (n < 0 || n >= NSEG) continue;
                int guard = 0;
                while (ld_acquire(FLG(F_O + l * 64 + n) + ks) < otgt) { if (++guard > 4000000) __trap(); __nanosleep(OP_NS); }
                SC(blockIdx.x == 7 && lane == 0 && it == 127, 240);
                fence_async_global();
                SC(blockIdx.x == 7 && lane == 0 && it == 127, 241);
                mwait(bb + PB_EMPTY + (it & 1) * 8, ((it >> 1) & 1) ^ 1);
                if (lane < 8) {
                    const uint32_t fb = bb + PB_FULL + ((it & 1) * 8 + lane) * 8;
                    mbar_expect_tx(fb, 8192);
                    asm volatile("cp.async.bulk.shared::cluster.global.mbarrier::complete_tx::bytes [%0], [%1], %2, [%3];" ::"r"(sb + P_RING + (it & 1) * 65536 + lane * 8192),
                                 "l"(g_ot + (rslot(l, n) * 256 + (ks * 8 + lane) * 8) * 64), "r"(8192), "r"(fb) : "memory");
                }
                __syncwarp();
                SC(blockIdx.x == 7 && lane == 0 && it == 127, 242);
                it++;
            }
        } else if (warp == 3) {
#pragma unroll 1
            for (int rg = 1; rg < 4; rg++) {
#pragma unroll 1
                for (int u = rg * 640 + blockIdx.x; u < rg * 640 + 640; u += 20) u_half(Bk, Bv, shiftk, u, lane);
                __syncwarp();
                if (lane == 0) red_release(FLG(F_U + rg + 1), 1);
                GT(lane == 0 && rg, 4 + rg);
            }
        } else if (lane == 0) {
            const int cw = warp - 1;
            uint32_t it = 0;
#pragma unroll 1
            for (int q = 0; q < 2 * NT; q++) {
                const int l = q & 1, n = (q >> 1) - l * LAG;
                if (n < 0 || n >= NSEG) continue;
                mwait(bb + PB_SF + cw * 8, it & 1);
                SC(blockIdx.x == 7 && cw == 0 && it == 127, 246);
                asm volatile("cp.reduce.async.bulk.global.shared::cta.bulk_group.add.f32 [%0], [%1], %2;" ::"l"(g_pt + (rslot(l, n) * 10 + nb * 2 + cw) * 512), "r"(sb + P_STG + cw * 8192), "r"(8192) : "memory");
                asm volatile("cp.async.bulk.commit_group;" ::: "memory");
                asm volatile("cp.async.bulk.wait_group.read 0;" ::: "memory");
                mbar_arrive(bb + PB_SE + cw * 8);
                asm volatile("cp.async.bulk.wait_group 0;" ::: "memory");
                SC(blockIdx.x == 7 && cw == 0 && it == 127, 247);
                fence_async_global();
                SC(blockIdx.x == 7 && cw == 0 && it == 127, 248);
                red_release(FLG(F_P + l * 64 + n), 1);
                SC(blockIdx.x == 7 && cw == 0 && it == 127, 249);
                GT(true, 330 + l * 64 + n);
                it++;
            }
        }
    } else {
        asm volatile("setmaxnreg.inc.sync.aligned.u32 232;");
        const int cw = (warp >> 2) - 1, w4 = warp & 3, t7 = tid & 127;
        uint32_t wa[64 - OP_SS][4];
        {
            const bf16* W = Wo + (size_t)ks * 1024 * DM + nb * 128 + cw * 64 + (t7 & 7) * 8;
            const uint32_t so = (t7 >> 3) * 128 + (((t7 & 7) ^ ((t7 >> 3) & 7)) << 4);
            const uint32_t stg = sb + P_RING + cw * 65536;
            const uint32_t la = stg + ((lane & 7) + (lane >> 4) * 8) * 128 + (((w4 * 2 + ((lane >> 3) & 1)) ^ (lane & 7)) << 4);
#pragma unroll 4
            for (int i = 0; i < 32; i++) cp_async16(stg + i * 2048 + so, W + (size_t)(op_rs_step(i) * 16 + (t7 >> 3)) * DM);
            cp_commit();
#pragma unroll 1
            for (int i = 0; i < OP_SS; i++) cp_async16(sb + P_AS + cw * OP_SS * 2048 + i * 2048 + so, W + (size_t)(op_ss_step(i) * 16 + (t7 >> 3)) * DM);
            cp_commit();
            cp_wait<1>();
            named_bar(1 + cw, 128);
#pragma unroll
            for (int j = 0; j < 32; j++) { const uint4 v = ldsm4t(la + j * 2048); wa[j][0] = v.x; wa[j][1] = v.y; wa[j][2] = v.z; wa[j][3] = v.w; }
            named_bar(1 + cw, 128);
#pragma unroll 1
            for (int i = 0; i < 32 - OP_SS; i++) cp_async16(stg + i * 2048 + so, W + (size_t)(op_rs_step(32 + i) * 16 + (t7 >> 3)) * DM);
            cp_commit();
            cp_wait<0>();
            named_bar(1 + cw, 128);
#pragma unroll
            for (int j = 0; j < 32 - OP_SS; j++) { const uint4 v = ldsm4t(la + j * 2048); wa[32 + j][0] = v.x; wa[32 + j][1] = v.y; wa[32 + j][2] = v.z; wa[32 + j][3] = v.w; }
            fence_async_smem();
            named_bar(3, 288);
        }
        const uint32_t ab = (1024 + P_AS + cw * OP_SS * 2048) >> 4;
        const uint32_t ea = sb + P_STG + cw * 8192 + (lane & 3) * 2048 + (((2 * w4) ^ (lane & 3)) << 5) + (lane >> 2) * 4;
#pragma unroll 1
        for (uint32_t it = 0; it < 2 * NSEG; it++) {
            float acc[16];
            const uint32_t fb = bb + PB_FULL + (it & 1) * 64, par = (it >> 1) & 1;
            const uint32_t ob = opq(((1024 + P_RING) >> 4) + (it & 1) * 4096);
            uint32_t ok = 0;
#pragma unroll
            for (int j = 0; j < 64; j++) {
                if ((j & 7) == 0) {
                    if (j) wg_commit();
                    if (!ok) mslow(fb + j, par);
                    ok = j < 56 ? mtest(fb + j + 8, par) : mtest(bb + PB_SE + cw * 8, (it & 1) ^ 1);
                    if (j == 0) { SC(blockIdx.x == 7 && tid == 128 && it == 127, 243); wg_fence(); }
                    if (j == 56) SC(blockIdx.x == 7 && tid == 128 && it == 127, 244);
                }
                const uint64_t db = mkdesc(ob + j * 64, 0x80000020u);
                if (j == 0) wg_n32t_sfirst(acc, mkdesc(ab, 0x40000040u), db);
                else if (op_ss(j)) wg_n32t_s(acc, mkdesc(ab + op_idx(j) * 128, 0x40000040u), db);
                else wg_n32t(acc, wa[op_idx(j)][0], wa[op_idx(j)][1], wa[op_idx(j)][2], wa[op_idx(j)][3], db);
            }
            wg_commit();
            if (!ok) mslow(bb + PB_SE + cw * 8, (it & 1) ^ 1);
            wg_wait<0>();
            SC(blockIdx.x == 7 && tid == 128 && it == 127, 245);
            if (t7 == 0) mbar_arrive(bb + PB_EMPTY + (it & 1) * 8);
#pragma unroll
            for (int i = 0; i < 16; i++) sts32((ea ^ ((i & 2) << 4)) + ((i >> 2) * 2 + (i & 1)) * 256, __float_as_uint(acc[i]));
            fence_async_smem();
            __syncwarp();
            if (lane == 0) mbar_arrive(bb + PB_SF + cw * 8);
        }
    }
}
}

namespace ws {
static bool usable() {
    static int ok = -1;
    if (ok < 0) {
        cudaFuncSetAttribute(head_kernel, cudaFuncAttributeMaxDynamicSharedMemorySize, HEAD_SMEM);
        cudaFuncSetAttribute(head_kernel, cudaFuncAttributeNonPortableClusterSizeAllowed, 1);
        cudaFuncSetAttribute(op_kernel, cudaFuncAttributeMaxDynamicSharedMemorySize, OP_SMEM);
        cudaLaunchConfig_t cfg = {};
        cfg.gridDim = dim3(NCL * 16); cfg.blockDim = dim3(512); cfg.dynamicSmemBytes = HEAD_SMEM;
        cudaLaunchAttribute at[1];
        at[0].id = cudaLaunchAttributeClusterDimension;
        at[0].val.clusterDim.x = 16; at[0].val.clusterDim.y = 1; at[0].val.clusterDim.z = 1;
        cfg.attrs = at; cfg.numAttrs = 1;
        int n = 0, nsm = 0;
        cudaDeviceGetAttribute(&nsm, cudaDevAttrMultiProcessorCount, 0);
        ok = cudaOccupancyMaxActiveClusters(&n, head_kernel, &cfg) == cudaSuccess && n >= NCL && nsm >= NCL * 16 + 20;
        (void)cudaGetLastError();
    }
    return ok > 0;
}
static void launch_all(void* const* d_in, void* d_out) {
    HeadArgs A;
    A.x = (const bf16*)d_in[0]; A.mem0 = (const bf16*)d_in[1]; A.Wq = (const bf16*)d_in[2]; A.Wk = (const bf16*)d_in[3]; A.Wv = (const bf16*)d_in[4]; A.Wo = (const bf16*)d_in[5];
    A.Bk = (const bf16*)d_in[8]; A.Bv = (const bf16*)d_in[9]; A.shiftk = (const bf16*)d_in[10]; A.ssmk = (const bf16*)d_in[11]; A.ssmD = (const bf16*)d_in[12];
    A.out = (bf16*)d_out; A.h_target = 32;
    cudaStream_t s = cudaStreamPerThread;
    {
        cudaLaunchConfig_t cfg = {};
        cfg.gridDim = dim3(NCL * 16); cfg.blockDim = dim3(512); cfg.dynamicSmemBytes = HEAD_SMEM; cfg.stream = s;
        cudaLaunchAttribute at[2];
        at[0].id = cudaLaunchAttributeClusterDimension;
        at[0].val.clusterDim.x = 16; at[0].val.clusterDim.y = 1; at[0].val.clusterDim.z = 1;
        at[1].id = cudaLaunchAttributeProgrammaticStreamSerialization;
        at[1].val.programmaticStreamSerializationAllowed = 1;
        cfg.attrs = at; cfg.numAttrs = 1;
        cudaLaunchKernelEx(&cfg, head_kernel, A);
    }
    {
        cudaLaunchConfig_t cfg = {};
        cfg.gridDim = dim3(20); cfg.blockDim = dim3(384); cfg.dynamicSmemBytes = OP_SMEM; cfg.stream = s;
        cudaLaunchAttribute at[1];
        at[0].id = cudaLaunchAttributeProgrammaticStreamSerialization;
        at[0].val.programmaticStreamSerializationAllowed = 1;
        cfg.attrs = at; cfg.numAttrs = 1;
        cudaLaunchKernelEx(&cfg, op_kernel, A.Wo, A.Bk, A.Bv, A.shiftk);
    }
}
}

#undef FLG
#undef GT
#undef H_NS
#undef LAGT
#undef LN0_AHEAD
#undef LN0_BATCH
#undef NO_X
#undef OBK
#undef OP_MIX
#undef OP_NS
#undef P1A
#undef P1C
#undef POST_NS
#undef REG_G
#undef REG_T
#undef REG_X
#undef RING
#undef SC
#undef SD
#undef TG_STEPS
#undef TS
#undef TV
#undef UNI
#undef WFLY
#undef WR
#undef XD
namespace ni {

constexpr int S_LEN = 2048;
constexpr int DM = 640;
constexpr int NH = 32;
constexpr int DH = 128;
constexpr int HD = NH * DH;
constexpr int MEMR = 8;
constexpr int SEG = 32;
constexpr int NSEG = S_LEN / SEG;

__device__ __forceinline__ float bf2f(bf16 v) { return __bfloat162float(v); }
__device__ __forceinline__ bf16 f2bf(float v) { return __float2bfloat16_rn(v); }
__device__ __forceinline__ float rbf(float v) { return __bfloat162float(__float2bfloat16_rn(v)); }
__device__ __forceinline__ uint32_t pack2(float a, float b) {
    __nv_bfloat162 t = __floats2bfloat162_rn(a, b);
    return *reinterpret_cast<uint32_t*>(&t);
}
__device__ __forceinline__ uint32_t smem_u32(const void* p) { return (uint32_t)__cvta_generic_to_shared(p); }
__device__ __forceinline__ void ldsm_x4(uint32_t& r0, uint32_t& r1, uint32_t& r2, uint32_t& r3, uint32_t addr) {
    asm volatile("ldmatrix.sync.aligned.m8n8.x4.shared.b16 {%0,%1,%2,%3}, [%4];"
                 : "=r"(r0), "=r"(r1), "=r"(r2), "=r"(r3) : "r"(addr));
}
__device__ __forceinline__ void ldsm_x2(uint32_t& r0, uint32_t& r1, uint32_t addr) {
    asm volatile("ldmatrix.sync.aligned.m8n8.x2.shared.b16 {%0,%1}, [%2];" : "=r"(r0), "=r"(r1) : "r"(addr));
}
__device__ __forceinline__ void ldsm_x4_t(uint32_t& r0, uint32_t& r1, uint32_t& r2, uint32_t& r3, uint32_t addr) {
    asm volatile("ldmatrix.sync.aligned.m8n8.x4.trans.shared.b16 {%0,%1,%2,%3}, [%4];"
                 : "=r"(r0), "=r"(r1), "=r"(r2), "=r"(r3) : "r"(addr));
}
__device__ __forceinline__ void mma16816(float* c, uint32_t a0, uint32_t a1, uint32_t a2, uint32_t a3,
                                         uint32_t b0, uint32_t b1) {
    asm("mma.sync.aligned.m16n8k16.row.col.f32.bf16.bf16.f32 {%0,%1,%2,%3}, {%4,%5,%6,%7}, {%8,%9}, {%0,%1,%2,%3};"
        : "+f"(c[0]), "+f"(c[1]), "+f"(c[2]), "+f"(c[3])
        : "r"(a0), "r"(a1), "r"(a2), "r"(a3), "r"(b0), "r"(b1));
}
__device__ __forceinline__ void cp_async16(uint32_t dst, const void* src) {
    asm volatile("cp.async.cg.shared.global [%0], [%1], 16;" ::"r"(dst), "l"(src));
}
__device__ __forceinline__ void cp_commit() { asm volatile("cp.async.commit_group;"); }
template <int N> __device__ __forceinline__ void cp_wait() { asm volatile("cp.async.wait_group %0;" ::"n"(N)); }
__device__ __forceinline__ uint4 ld_relaxed_v4(const void* p) {
    uint4 v;
    asm volatile("ld.relaxed.gpu.global.v4.u32 {%0,%1,%2,%3}, [%4];"
                 : "=r"(v.x), "=r"(v.y), "=r"(v.z), "=r"(v.w) : "l"(p) : "memory");
    return v;
}
__device__ __forceinline__ void st_relaxed_v4(void* p, uint32_t a, uint32_t b, uint32_t c, uint32_t d) {
    asm volatile("st.relaxed.gpu.global.v4.u32 [%0], {%1,%2,%3,%4};" ::"l"(p), "r"(a), "r"(b), "r"(c), "r"(d) : "memory");
}
__device__ __forceinline__ int ld_acquire(const int* p) {
    int v;
    asm volatile("ld.acquire.gpu.global.u32 %0, [%1];" : "=r"(v) : "l"(p) : "memory");
    return v;
}
__device__ __forceinline__ void mbar_init(uint32_t bar, int count) {
    asm volatile("mbarrier.init.shared::cta.b64 [%0], %1;" ::"r"(bar), "r"(count));
}
__device__ __forceinline__ void mbar_expect_tx(uint32_t bar, uint32_t bytes) {
    asm volatile("mbarrier.arrive.expect_tx.shared::cta.b64 _, [%0], %1;" ::"r"(bar), "r"(bytes) : "memory");
}
__device__ __forceinline__ void mbar_arrive(uint32_t bar) {
    asm volatile("mbarrier.arrive.shared::cta.b64 _, [%0];" ::"r"(bar) : "memory");
}
constexpr int SPIN_LIMIT = 4000000;
__device__ __forceinline__ void mbar_wait_spin(uint32_t bar, uint32_t parity) {
    uint32_t ok = 0;
    int guard = 0;
    while (!ok && ++guard < SPIN_LIMIT) {
        asm volatile(
            "{\n.reg .pred P1;\n"
            "mbarrier.try_wait.parity.shared::cta.b64 P1, [%1], %2;\n"
            "selp.u32 %0, 1, 0, P1;\n}\n"
            : "=r"(ok) : "r"(bar), "r"(parity) : "memory");
    }
}
__device__ __forceinline__ uint32_t mapa(uint32_t addr, uint32_t rank) {
    uint32_t r;
    asm volatile("mapa.shared::cluster.u32 %0, %1, %2;" : "=r"(r) : "r"(addr), "r"(rank));
    return r;
}
__device__ __forceinline__ void st_async_u32(uint32_t addr, uint32_t v, uint32_t bar) {
    asm volatile("st.async.weak.shared::cluster.mbarrier::complete_tx::bytes.b32 [%0], %1, [%2];" ::"r"(addr), "r"(v), "r"(bar) : "memory");
}
__device__ __forceinline__ void st_async_v2(uint32_t addr, uint32_t a, uint32_t b, uint32_t bar) {
    asm volatile("st.async.weak.shared::cluster.mbarrier::complete_tx::bytes.v2.b32 [%0], {%1,%2}, [%3];" ::"r"(addr), "r"(a), "r"(b), "r"(bar) : "memory");
}
__device__ __forceinline__ void cluster_sync_all() {
    asm volatile("barrier.cluster.arrive.release.aligned;\nbarrier.cluster.wait.acquire.aligned;" ::: "memory");
}
__device__ __forceinline__ void named_bar(int id, int n) { asm volatile("bar.sync %0, %1;" ::"r"(id), "r"(n) : "memory"); }

}

namespace ni {
#define CHAIN_LAG 16
constexpr int CL = 16;
constexpr int OWN = DM / CL;
constexpr int NSRC = CL / 2;
constexpr int NCLU = 64 / CL;
constexpr int CSEG = 4;
constexpr int NCHK = NSEG / CSEG;
constexpr int LAG = CHAIN_LAG;
constexpr int NTICK = NSEG + LAG;

constexpr int F_KV = 0, F_MEM = 32, F_H = 64, F_OP = 96, F_CONV = 128, F_U = 130, F_PROG = 132, F_ZERO = 133, F_CNT = 136;
constexpr int NFLAG = 192;
__device__ int g_flags[NFLAG * 32];
#define FLG(i) (g_flags + (i) * 32)
constexpr int CHAIN_THREADS = 384;
__device__ bf16 g_Y[S_LEN * DM];
__device__ bf16 g_U[DM * S_LEN];
__device__ bf16 g_h[2][S_LEN * DM];
__device__ bf16 g_x[S_LEN * DM];
__device__ bf16 g_kv[2][S_LEN * HD];
#define PRING 4
constexpr int PROWS = PRING * 128, PG = 4;
__device__ bf16 g_part[2 * PROWS * PG * DM];
__device__ uint4 g_kvf[2 * NSEG * NH * 256];
__device__ uint32_t g_xc[2 * 2 * CL * NCLU * 8 * OWN];

#define TVAL(i, v)
#define TSTAMP(i)

#define NRQ 36
#define NRW 8
#define PDQ 4
#define PDW1 0
#define PROBE 2
#define PDW 6
constexpr int NSQ = 60 - NRQ, NSW = 20 - NRW;
__host__ __device__ constexpr bool q_smem(int i) { return ((i + 1) * NSQ) / 60 != (i * NSQ) / 60; }
__host__ __device__ constexpr int q_slot(int i) { return q_smem(i) ? (i * NSQ) / 60 : i - (i * NSQ) / 60; }
__host__ __device__ constexpr int w_tile(int i) { return i < 8 ? ((i & 1) ? 0 : 2) : (i < 16 ? (i & 1) : 1); }
__host__ __device__ constexpr int w_k(int i) { return i < 8 ? i / 2 : (i < 16 ? ((i & 1) ? (i - 8) / 2 : 4 + (i - 8) / 2) : i - 12); }
__host__ __device__ constexpr int w_acc(int i) { return (i >= 16 && (i & 1)) ? 3 : w_tile(i); }
__host__ __device__ constexpr bool w_smem(int i) { return i < PDW || NRW == 0 || ((i - PDW + 1) * NRW) / (20 - PDW) == ((i - PDW) * NRW) / (20 - PDW); }
__host__ __device__ constexpr int w_slot(int i) { return i < PDW ? i : (w_smem(i) ? i - ((i - PDW) * NRW) / (20 - PDW) : ((i - PDW) * NRW) / (20 - PDW)); }
constexpr int O_WQ = 0, O_WW = NSQ * 4096, O_REST = (NSQ + NSW) * 4096;
constexpr int C_TOK = 0, C_MEM = 12288, C_RED = C_MEM + 10240, C_Q = C_RED + 6144, C_K = C_Q + 2048, C_V = C_K + 2048, C_S = C_V + 4096,
              C_BAR = C_S + 3072, C_SIZE = 40960;
constexpr int S_BYTES = 3072 + 4096;
constexpr int B_S = 64, B_R = 72, B_T = 96, B_F = 104;
static_assert(C_BAR + 112 <= C_SIZE, "chain block");
constexpr int O_STB = O_REST - 61440;
static_assert((45 * NSQ) / 60 * 4096 <= O_STB && NSQ <= 32, "staging");
struct ChainSmem { unsigned char b[O_REST + 81920 + 1536]; };
static_assert(sizeof(ChainSmem) <= 232448, "smem");

struct ChainArgs {
    CUtensorMap tk[2], tv[2];
    const bf16 *x, *mem0, *Wq, *Wk, *Wv, *Wo;
    int kv_target;
};
__device__ __forceinline__ uint32_t movmat(uint32_t v) {
    uint32_t r;
    asm volatile("movmatrix.sync.aligned.m8n8.trans.b16 %0, %1;" : "=r"(r) : "r"(v));
    return r;
}
__device__ __forceinline__ void named_arrive(int id, int n) { asm volatile("bar.arrive %0, %1;" ::"r"(id), "r"(n) : "memory"); }
__device__ __forceinline__ void red_release(int* p, int v) { asm volatile("red.release.gpu.global.add.u32 [%0], %1;" ::"l"(p), "r"(v) : "memory"); }

#define CVT(i)
__device__ __forceinline__ uint4 lds128(uint32_t a) {
    uint4 v;
    asm volatile("ld.shared.v4.u32 {%0,%1,%2,%3}, [%4];" : "=r"(v.x), "=r"(v.y), "=r"(v.z), "=r"(v.w) : "r"(a));
    return v;
}
__device__ __forceinline__ uint2 lds64(uint32_t a) {
    uint2 v;
    asm volatile("ld.shared.v2.u32 {%0,%1}, [%2];" : "=r"(v.x), "=r"(v.y) : "r"(a));
    return v;
}
__device__ __forceinline__ uint32_t lds32(uint32_t a) {
    uint32_t v;
    asm volatile("ld.shared.u32 %0, [%1];" : "=r"(v) : "r"(a));
    return v;
}
__device__ __forceinline__ void sts64(uint32_t a, uint32_t x, uint32_t y) { asm volatile("st.shared.v2.u32 [%0], {%1,%2};" ::"r"(a), "r"(x), "r"(y) : "memory"); }
__device__ __forceinline__ void sts128(uint32_t a, uint32_t x, uint32_t y, uint32_t z, uint32_t w) {
    asm volatile("st.shared.v4.u32 [%0], {%1,%2,%3,%4};" ::"r"(a), "r"(x), "r"(y), "r"(z), "r"(w) : "memory");
}
__device__ __forceinline__ void st_async_v4(uint32_t addr, uint32_t a, uint32_t b, uint32_t c, uint32_t d, uint32_t bar) {
    asm volatile("st.async.weak.shared::cluster.mbarrier::complete_tx::bytes.v4.b32 [%0], {%1,%2,%3,%4}, [%5];" ::"r"(addr), "r"(a), "r"(b), "r"(c), "r"(d), "r"(bar) : "memory");
}
__device__ __forceinline__ uint2 ld_relaxed_v2(const void* p) {
    uint2 v;
    asm volatile("ld.relaxed.gpu.global.v2.u32 {%0,%1}, [%2];" : "=r"(v.x), "=r"(v.y) : "l"(p) : "memory");
    return v;
}
__device__ __forceinline__ void st_relaxed_v2(void* p, uint32_t a, uint32_t b) {
    asm volatile("st.relaxed.gpu.global.v2.u32 [%0], {%1,%2};" ::"l"(p), "r"(a), "r"(b) : "memory");
}
__device__ __forceinline__ float blo(uint32_t v) { return __uint_as_float(v << 16); }
__device__ __forceinline__ float bhi(uint32_t v) { return __uint_as_float(v & 0xffff0000u); }
__device__ __forceinline__ uint32_t badd2(uint32_t a, uint32_t b) {
    __nv_bfloat162 r = __hadd2(*reinterpret_cast<__nv_bfloat162*>(&a), *reinterpret_cast<__nv_bfloat162*>(&b));
    return *reinterpret_cast<uint32_t*>(&r);
}
__device__ __forceinline__ void mmau(float* c, const uint4& a, uint32_t b0, uint32_t b1) { mma16816(c, a.x, a.y, a.z, a.w, b0, b1); }

__device__ __forceinline__ void stsm_x4_t(uint32_t a, uint32_t r0, uint32_t r1, uint32_t r2, uint32_t r3) {
    asm volatile("stmatrix.sync.aligned.m8n8.x4.trans.shared.b16 [%0], {%1,%2,%3,%4};" ::"r"(a), "r"(r0), "r"(r1), "r"(r2), "r"(r3) : "memory");
}
__device__ __forceinline__ uint4 ldsm4(uint32_t a) { uint4 v; ldsm_x4(v.x, v.y, v.z, v.w, a); return v; }
__device__ __forceinline__ float ex2f(float x) { float y; asm("ex2.approx.ftz.f32 %0, %1;" : "=f"(y) : "f"(x)); return y; }
__device__ __forceinline__ float rcpf(float x) { float y; asm("rcp.approx.ftz.f32 %0, %1;" : "=f"(y) : "f"(x)); return y; }
#define XD 300
__device__ __forceinline__ void xdelay() {
    uint32_t t0, t1;
    asm volatile("mov.u32 %0, %clock;" : "=r"(t0));
    do { asm volatile("mov.u32 %0, %clock;" : "=r"(t1)); } while (t1 - t0 < XD);
}
template <int V> struct IC { static constexpr int value = V; };
__device__ __forceinline__ uint32_t opq(uint32_t x) { uint32_t y; asm volatile("mov.u32 %0, %1;" : "=r"(y) : "r"(x)); return y; }
#define UNI(x) __shfl_sync(0xffffffffu, (uint32_t)(x), 0)
__device__ __forceinline__ uint32_t mtest(uint32_t bar, uint32_t parity) {
    uint32_t ok;
    asm volatile("{\n.reg .pred P1;\nmbarrier.test_wait.parity.shared::cta.b64 P1, [%1], %2;\nselp.u32 %0, 1, 0, P1;\n}\n" : "=r"(ok) : "r"(bar), "r"(parity) : "memory");
    return ok;
}
__device__ __forceinline__ void mwait(uint32_t bar, uint32_t parity) {
    asm volatile(
        "{\n.reg .pred P1;\n.reg .u32 cnt;\n"
        "mbarrier.try_wait.parity.shared::cta.b64 P1, [%0], %1;\n"
        "@P1 bra DONE;\n"
        "mov.u32 cnt, 0;\n"
        "LAB_WAIT:\n"
        "mbarrier.try_wait.parity.shared::cta.b64 P1, [%0], %1;\n"
        "@P1 bra DONE;\n"
        "add.u32 cnt, cnt, 1;\n"
        "setp.lt.u32 P1, cnt, 4000000;\n"
        "@P1 bra LAB_WAIT;\n"
        "DONE:\n}\n" ::"r"(bar), "r"(parity) : "memory");
}

__global__ void __launch_bounds__(CHAIN_THREADS, 1) chain_kernel(const __grid_constant__ ChainArgs A) {
    extern __shared__ __align__(1024) unsigned char smem_raw[];
    const int tid = threadIdx.x, warp = __shfl_sync(0xffffffffu, tid >> 5, 0), lane = tid & 31;
    const int cq = blockIdx.x / CL, r = blockIdx.x % CL;
    const int h = cq * NSRC + (r >> 1), hf = r & 1;
    const uint32_t sb = smem_u32(smem_raw);
    asm volatile("griddepcontrol.launch_dependents;");
    CVT(0);
    if (warp == 8) {
        if (lane < 8) asm volatile("cp.async.bulk.prefetch.L2.global [%0], %1;" ::"l"(A.x + (size_t)(blockIdx.x * 8 + lane) * 2560), "r"(5120) : "memory");
        asm volatile("cp.async.bulk.prefetch.L2.global [%0], %1;" ::"l"((lane < 16 ? A.Wk : A.Wv) + (size_t)(blockIdx.x * 16 + (lane & 15)) * 2560), "r"(5120) : "memory");
        asm volatile("cp.async.bulk.prefetch.L2.global [%0], %1;" ::"l"((lane < 16 ? A.Wq : A.Wo) + (size_t)(blockIdx.x * 16 + (lane & 15)) * 2560), "r"(5120) : "memory");
    }
    CVT(1);
    if (warp < 8) {
        asm volatile("setmaxnreg.inc.sync.aligned.u32 232;");
        const int j = warp & 3, kh = warp >> 2;
        uint4 wr[NRQ + NRW];
        {
            auto load_round = [&](int gi) {
                const uint32_t buf = sb + ((gi & 1) ? O_STB : O_REST);
#pragma unroll
                for (int it = 0; it < 15; it++) {
                    const int i = tid + it * 256;
                    const int pc = i / 1920, rem = i % 1920, row = rem / 24, ch = rem % 24;
                    const int mat = ch >> 3, pi = ((r >> 1) - (2 * gi + pc)) & 7;
                    const bf16* W = mat == 0 ? A.Wq : (mat == 1 ? A.Wk : A.Wv);
                    cp_async16(buf + pc * 30720 + row * 384 + ((ch ^ (row & 7)) << 4), W + (size_t)(pi * 80 + row) * HD + h * DH + hf * 64 + (ch & 7) * 8);
                }
                cp_commit();
            };
            load_round(0);
            load_round(1);
#pragma unroll
            for (int gi = 0; gi < 4; gi++) {
                cp_wait<1>();
                named_bar(1, 256);
                const uint32_t pb = sb + ((gi & 1) ? O_STB : O_REST) + kh * 30720;
                uint4 tmp[8];
#pragma unroll
                for (int u = 0; u < 5; u++)
#pragma unroll
                    for (int tt = 0; tt < 3; tt++) {
                        const int row = u * 16 + (lane & 7) + (lane >> 4) * 8;
                        const int ch = tt * 8 + j * 2 + ((lane >> 3) & 1);
                        uint4 v;
                        ldsm_x4_t(v.x, v.y, v.z, v.w, pb + row * 384 + ((ch ^ (row & 7)) << 4));
                        const int i = (gi * 5 + u) * 3 + tt;
                        if (q_smem(i)) {
                            if (gi == 3) tmp[q_slot(i) & 7] = v;
                            else sts128(sb + O_WQ + q_slot(i) * 4096 + tid * 16, v.x, v.y, v.z, v.w);
                        } else wr[q_slot(i)] = v;
                    }
                named_bar(1, 256);
                if (gi == 3) {
#pragma unroll
                    for (int i = 45; i < 60; i++)
                        if (q_smem(i)) { const uint4 v = tmp[q_slot(i) & 7]; sts128(sb + O_WQ + q_slot(i) * 4096 + tid * 16, v.x, v.y, v.z, v.w); }
                }
                if (gi < 2) load_round(gi + 2);
                else if (gi == 2) {
                    for (int i = tid; i < 128 * 40; i += 256) {
                        const int row = i / 40, ch = i % 40;
                        cp_async16(sb + O_REST + row * 640 + ((ch ^ (row & 7)) << 4), A.Wo + ((size_t)h * DH + row) * DM + hf * 320 + ch * 8);
                    }
                    cp_commit();
                }
            }
            cp_wait<0>();
            named_bar(1, 256);
#pragma unroll
            for (int i = 0; i < 20; i++) {
                const int tl = w_tile(i), et = (w_k(i) + 4 * (warp & 1)) & 7;
                const int row = et * 16 + (lane & 7) + (lane >> 4) * 8;
                const int ch = (warp >> 1) * 10 + (tl == 2 ? 8 : (warp & 1) * 4 + tl * 2) + ((lane >> 3) & 1);
                uint4 v;
                ldsm_x4_t(v.x, v.y, v.z, v.w, sb + O_REST + row * 640 + ((ch ^ (row & 7)) << 4));
                if (w_smem(i)) sts128(sb + O_WW + w_slot(i) * 4096 + tid * 16, v.x, v.y, v.z, v.w);
                else wr[NRQ + w_slot(i)] = v;
            }
            named_bar(1, 256);
            for (int i = tid; i < 2560; i += 256) {
                const int ks = i >> 6, ln = (i >> 1) & 31, wd = i & 1;
                const int pi = ((r >> 1) - ks / 5) & 7;
                const uint32_t v = *reinterpret_cast<const uint32_t*>(A.mem0 + (ln >> 2) * DM + pi * 80 + (ks % 5) * 16 + wd * 8 + (ln & 3) * 2);
                const int o = ks % 5 == 4 ? ks * 256 + wd * 128 + ln * 4 : i * 4;
                asm volatile("st.shared.u32 [%0], %1;" ::"r"(sb + O_REST + C_MEM + o), "r"(v) : "memory");
                asm volatile("st.shared.u32 [%0], %1;" ::"r"(sb + O_REST + C_SIZE + C_MEM + o), "r"(v) : "memory");
            }
            if (tid < 2) {
                const uint32_t bb = sb + O_REST + tid * C_SIZE + C_BAR;
                for (int i = 0; i < 13; i++) mbar_init(bb + i * 8, 1);
                mbar_init(bb + B_F, 4);
                asm volatile("fence.mbarrier_init.release.cluster;" ::: "memory");
                mbar_expect_tx(bb + B_S, S_BYTES);
                for (int i = 0; i < 3; i++) mbar_expect_tx(bb + B_R + i * 8, 2048);
            }
            asm volatile("fence.proxy.async;" ::: "memory");
        }
        CVT(2);
        cluster_sync_all();
        const uint32_t wq_a = sb + O_WQ + tid * 16;
        const uint32_t cb0 = sb + O_REST;
        const uint32_t qk_a = cb0 + j * 512 + (lane & 7) * 16 + (lane < 16 ? C_Q + (lane >> 3) * 256 + kh * 128 : C_K + kh * 256 + ((lane >> 3) & 1) * 128);
        const uint32_t pd = UNI(mapa(sb, (uint32_t)(r ^ 1)) - sb), sd = UNI(mapa(sb, (uint32_t)r) - sb);
        const uint32_t od = UNI(mapa(sb, (uint32_t)(hf * 8 + warp)) - sb);
        const uint32_t oe = UNI(mapa(sb, (uint32_t)(hf * 8 + (warp & 6))) - sb), oo = UNI(mapa(sb, (uint32_t)(hf * 8 + (warp | 1))) - sb);
        const uint32_t u_mem = UNI(cb0 + C_MEM + kh * 1280), u_bm = UNI(cb0 + C_BAR + kh * 8);
        const uint32_t u_v = UNI(cb0 + C_V + hf * 2048 + j * 512 + kh * 256);
        const uint32_t u_ra = UNI(cb0 + C_RED + (r >> 1) * 256);
        const uint32_t u_ob0 = UNI(cb0 + C_Q + (warp & 1) * 1024), u_ob1 = UNI(cb0 + C_Q + ((warp & 1) ^ 1) * 1024);
        const uint32_t u_role = UNI(warp < 3 ? cb0 + C_S + hf * 1536 + warp * 512 : cb0 + C_V + j * 1024);
        const uint32_t t_tok = cb0 + C_TOK + ((lane & 7) + (lane >> 4) * 8) * 128 +
                               (warp < 3 ? warp * 2048 + ((((lane >> 3) & 1) ^ (lane & 7)) << 4) : 4096 + (j >> 1) * 4096 + ((((j & 1) * 4 + ((lane >> 3) & 1)) ^ (lane & 7)) << 4));
        uint4 qb[PDQ];
#pragma unroll
        for (int s = 0; s < PDQ; s++) qb[s] = lds128(wq_a + s * 4096);
        auto tick = [&](auto cc, const int n) {
            constexpr int c = decltype(cc)::value;
            constexpr uint32_t CO = c * C_SIZE;
            const uint32_t cb = cb0 + CO;
            const uint32_t par = (uint32_t)(n & 1);
            const uint32_t l4 = opq(lane * 4), l8 = l4 * 2, l16 = l4 * 4;
            float acc[3][4];
#pragma unroll
            for (int a = 0; a < 3; a++)
#pragma unroll
                for (int i = 0; i < 4; i++) acc[a][i] = 0.f;
            {
                const uint32_t mb = u_mem + CO + l8;
                uint2 bf[3];
                uint32_t ok = 1;
                auto ldb = [&](int ks) {
                    if (ks == 0) mwait(u_bm + CO, par ^ 1);
                    else if (ks % 5 == 0) { if (!ok) mwait(u_bm + CO + (ks / 5) * 16, par ^ 1); }
                    if (ks % 5 == PROBE && ks < 15) ok = mtest(u_bm + CO + (ks / 5 + 1) * 16, par ^ 1);
                    if (ks % 5 == 4) {
                        bf[ks % 3].x = lds32(u_mem + CO + l4 + (ks / 5) * 2560 + 1024);
                        bf[ks % 3].y = lds32(u_mem + CO + l4 + (ks / 5) * 2560 + 1152);
                    } else bf[ks % 3] = lds64(mb + (ks / 5) * 2560 + (ks % 5) * 256);
                };
                ldb(0);
                TSTAMP(c * 12 + 0);
                ldb(1);
#pragma unroll
                for (int ks = 0; ks < 20; ks++) {
                    if (ks + 2 < 20) ldb(ks + 2);
#pragma unroll
                    for (int tt = 0; tt < 3; tt++) {
                        const int i = ks * 3 + tt;
                        if (q_smem(i)) {
                            const int s = q_slot(i);
                            mmau(acc[tt], qb[s % PDQ], bf[ks % 3].x, bf[ks % 3].y);
                            if (s + PDQ < NSQ) qb[s % PDQ] = lds128(wq_a + (s + PDQ) * 4096);
                        } else mmau(acc[tt], wr[q_slot(i)], bf[ks % 3].x, bf[ks % 3].y);
                    }
                }
            }
            TSTAMP(c * 12 + 1);
            stsm_x4_t(opq(qk_a) + CO, pack2(acc[0][0], acc[0][1]), pack2(acc[0][2], acc[0][3]), pack2(acc[1][0], acc[1][1]), pack2(acc[1][2], acc[1][3]));
            const uint32_t v0 = pack2(acc[2][0], acc[2][1]), v1 = pack2(acc[2][2], acc[2][3]);
            if (n == NSEG - 1) {
                sts64(u_v + CO + l8, v0, v1);
                named_bar(1, 256);
                if (kh == 1 && lane == 0) mbar_arrive(cb + C_BAR + B_F);
#pragma unroll
                for (int s = 0; s < PDQ; s++) qb[s] = lds128(wq_a + s * 4096);
                return;
            }
            named_arrive(1, 384);
            st_async_v2(u_v + CO + l8 + pd, v0, v1, cb + C_BAR + B_S + pd);
            st_async_v2(u_v + CO + l8 + sd, v0, v1, cb + C_BAR + B_S + sd);
            uint4 wb[PDW];
            const uint32_t ww_a = wq_a + (O_WW - O_WQ);
            if (warp < 3) {
                uint4 kb[4];
                const uint32_t t_tk = opq(t_tok);
                mwait(cb + C_BAR + B_T, par);
#pragma unroll
                for (int i = 0; i < 4; i++) kb[i] = ldsm4((t_tk ^ (i << 5)) + CO);
                named_bar(1, 384);
                uint4 qa[4];
#pragma unroll
                for (int i = 0; i < 4; i++) qa[i] = ldsm4(cb + l16 + C_Q + i * 512);
                if (warp == 2) {
#pragma unroll
                    for (int i = 0; i < 4; i++) kb[i] = ldsm4(cb + l16 + C_K + i * 512);
                }
                float s0[4][4], s1[4][4];
#pragma unroll
                for (int i = 0; i < 4; i++) {
#pragma unroll
                    for (int q = 0; q < 4; q++) s0[i][q] = s1[i][q] = 0.f;
                    mmau(s0[i], qa[i], kb[i].x, kb[i].y);
                    mmau(s1[i], qa[i], kb[i].z, kb[i].w);
                }
                const float a0 = ((s0[0][0] + s0[0][2]) + (s0[1][0] + s0[1][2])) + ((s0[2][0] + s0[2][2]) + (s0[3][0] + s0[3][2]));
                const float a1 = ((s0[0][1] + s0[0][3]) + (s0[1][1] + s0[1][3])) + ((s0[2][1] + s0[2][3]) + (s0[3][1] + s0[3][3]));
                const float b0 = ((s1[0][0] + s1[0][2]) + (s1[1][0] + s1[1][2])) + ((s1[2][0] + s1[2][2]) + (s1[3][0] + s1[3][2]));
                const float b1 = ((s1[0][1] + s1[0][3]) + (s1[1][1] + s1[1][3])) + ((s1[2][1] + s1[2][3]) + (s1[3][1] + s1[3][3]));
                const uint32_t so = u_role + CO + l16, bs = cb + C_BAR + B_S;
                const float c0 = warp == 2 ? a0 + b0 : a0, c1 = warp == 2 ? a1 + b1 : a1;
                st_async_v4(so + pd, __float_as_uint(c0), __float_as_uint(c1), __float_as_uint(b0), __float_as_uint(b1), bs + pd);
                st_async_v4(so + sd, __float_as_uint(c0), __float_as_uint(c1), __float_as_uint(b0), __float_as_uint(b1), bs + sd);
                TSTAMP(c * 12 + 2);
#pragma unroll
                for (int s = 0; s < PDW; s++) wb[s] = lds128(ww_a + s * 4096);
            } else if (warp == 3) {
                named_bar(1, 384);
                if (lane < 8) mbar_expect_tx(cb + C_BAR + l8, 1280);
#pragma unroll
                for (int s = 0; s < PDW; s++) wb[s] = lds128(ww_a + s * 4096);
            } else {
                mwait(cb + C_BAR + B_T, par);
                uint4 va[2][2];
                const uint32_t t_tk = opq(t_tok);
#pragma unroll
                for (int e = 0; e < 2; e++)
#pragma unroll
                    for (int k = 0; k < 2; k++)
                        ldsm_x4_t(va[e][k].x, va[e][k].y, va[e][k].z, va[e][k].w, (t_tk ^ (e << 5)) + CO + k * 2048);
#pragma unroll
                for (int s2 = 0; s2 < PDW1; s2++) wb[s2] = lds128(ww_a + s2 * 4096);
                mwait(cb + C_BAR + B_S, par);
                TSTAMP(c * 12 + 3);
                const uint32_t xa = cb + l16 + C_S;
                const uint4 x0 = lds128(xa), y0 = lds128(xa + 1536), x1 = lds128(xa + 512), y1 = lds128(xa + 512 + 1536);
                const uint2 x2 = lds64(xa + 1024), y2 = lds64(xa + 1024 + 1536);
                const uint32_t fv = u_role + CO + l8;
                const float cs = 0.08838834764831845f * 1.4426950408889634f;
                float s[10];
                s[8] = __uint_as_float(x2.x) + __uint_as_float(y2.x); s[9] = __uint_as_float(x2.y) + __uint_as_float(y2.y);
                s[0] = __uint_as_float(x0.x) + __uint_as_float(y0.x); s[1] = __uint_as_float(x0.y) + __uint_as_float(y0.y);
                s[2] = __uint_as_float(x0.z) + __uint_as_float(y0.z); s[3] = __uint_as_float(x0.w) + __uint_as_float(y0.w);
                s[4] = __uint_as_float(x1.x) + __uint_as_float(y1.x); s[5] = __uint_as_float(x1.y) + __uint_as_float(y1.y);
                s[6] = __uint_as_float(x1.z) + __uint_as_float(y1.z); s[7] = __uint_as_float(x1.w) + __uint_as_float(y1.w);
                float mx = fmaxf(fmaxf(fmaxf(s[0], s[1]), fmaxf(s[2], s[3])), fmaxf(fmaxf(fmaxf(s[4], s[5]), fmaxf(s[6], s[7])), fmaxf(s[8], s[9])));
                const float m1 = __shfl_xor_sync(0xffffffffu, mx, 1), m2 = __shfl_xor_sync(0xffffffffu, mx, 2), m3 = __shfl_xor_sync(0xffffffffu, mx, 3);
                const uint2 vm00 = lds64(fv), vm01 = lds64(fv + 256), vm10 = lds64(fv + 512), vm11 = lds64(fv + 768);
                const uint4 vm0 = make_uint4(vm00.x, vm00.y, vm01.x, vm01.y), vm1 = make_uint4(vm10.x, vm10.y, vm11.x, vm11.y);
                mx = fmaxf(fmaxf(mx, m1), fmaxf(m2, m3)) * -cs;
                uint32_t pb[5];
                pb[4] = pack2(ex2f(fmaf(s[8], cs, mx)), ex2f(fmaf(s[9], cs, mx)));
#pragma unroll
                for (int i = 0; i < 4; i++) pb[i] = pack2(ex2f(fmaf(s[2 * i], cs, mx)), ex2f(fmaf(s[2 * i + 1], cs, mx)));
                float o[3][4];
#pragma unroll
                for (int i = 0; i < 4; i++) { o[0][i] = o[1][i] = o[2][i] = 0.f; }
                const uint32_t one2 = 0x3F803F80u;
                mma16816(o[2], one2, one2, one2, one2, pb[4], 0u);
                mmau(o[0], vm0, pb[4], pb[4]);
                mmau(o[1], vm1, pb[4], pb[4]);
                mma16816(o[2], one2, one2, one2, one2, pb[0], pb[1]);
                mmau(o[0], va[0][0], pb[0], pb[1]);
                mmau(o[1], va[1][0], pb[0], pb[1]);
                mma16816(o[2], one2, one2, one2, one2, pb[2], pb[3]);
                mmau(o[0], va[0][1], pb[2], pb[3]);
                mmau(o[1], va[1][1], pb[2], pb[3]);
                const float r0 = rcpf(o[2][0]), r1 = rcpf(o[2][1]);
                stsm_x4_t(cb + l16 + C_Q + j * 512, pack2(o[0][0] * r0, o[0][1] * r1), pack2(o[0][2] * r0, o[0][3] * r1), pack2(o[1][0] * r0, o[1][1] * r1), pack2(o[1][2] * r0, o[1][3] * r1));
                named_arrive(2, 384);
                TSTAMP(c * 12 + 4);
#pragma unroll
                for (int s2 = PDW1; s2 < PDW; s2++) wb[s2] = lds128(ww_a + s2 * 4096);
                if (lane == 0) mbar_arrive(cb + C_BAR + B_F);
                if (warp == 4 && lane == 0) mbar_expect_tx(cb + C_BAR + B_S, S_BYTES);
            }
            named_bar(2, 384);
            TSTAMP(c * 12 + 5);
            {
                uint4 ob[4];
                ob[0] = ldsm4(u_ob0 + CO + l16); ob[1] = ldsm4(u_ob0 + CO + l16 + 512);
                ob[2] = ldsm4(u_ob1 + CO + l16); ob[3] = ldsm4(u_ob1 + CO + l16 + 512);
                float d[4][4];
#pragma unroll
                for (int a = 0; a < 4; a++)
#pragma unroll
                    for (int i = 0; i < 4; i++) d[a][i] = 0.f;
                const uint32_t ra = u_ra + CO + l8, rb = cb + C_BAR + B_R;
#pragma unroll
                for (int i = 0; i < 20; i++) {
                    const int k = w_k(i), ac = w_acc(i);
                    const uint32_t b0 = (k & 1) ? ob[k >> 1].z : ob[k >> 1].x, b1 = (k & 1) ? ob[k >> 1].w : ob[k >> 1].y;
                    if (w_smem(i)) {
                        const int s = w_slot(i);
                        mmau(d[ac], wb[s % PDW], b0, b1);
                        if (s + PDW < NSW) wb[s % PDW] = lds128(ww_a + (s + PDW) * 4096);
                    } else mmau(d[ac], wr[NRQ + w_slot(i)], b0, b1);
                    if (i == 9) {
                        const uint32_t rs = u_ra + CO + l4 + 4096 + (warp & 1) * 128;
                        st_async_u32(rs + oe, pack2(d[2][0], d[2][1]), rb + 16 + oe);
                        st_async_u32(rs + oo, pack2(d[2][2], d[2][3]), rb + 16 + oo);
                    }
                    if (i == 17) st_async_v2(ra + od, pack2(d[0][0], d[0][1]), pack2(d[0][2], d[0][3]), rb + od);
                }
                st_async_v2(ra + 2048 + od, pack2(d[1][0] + d[3][0], d[1][1] + d[3][1]), pack2(d[1][2] + d[3][2], d[1][3] + d[3][3]), rb + 8 + od);
                TSTAMP(c * 12 + 6);
#pragma unroll
                for (int s = 0; s < PDQ; s++) qb[s] = lds128(wq_a + s * 4096);
            }
        };
#pragma unroll 1
        for (int t = 0; t < NTICK; t++) {
            if (t < NSEG) tick(IC<0>{}, t);
            if (t >= LAG) tick(IC<1>{}, t - LAG);
        }
    } else {
        asm volatile("setmaxnreg.dec.sync.aligned.u32 40;");
        const int s = warp - 8;
        cluster_sync_all();
        if (s < 3) {
#pragma unroll 1
            for (int hs = 0; hs < 2 * NTICK; hs++) {
                const int c = hs & 1, t = hs >> 1;
                const int n = t - c * LAG;
                if (n < 0 || n >= NSEG - 1) continue;
                const uint32_t cb = sb + O_REST + c * C_SIZE;
                const uint32_t par = (uint32_t)(n & 1);
                const uint32_t tag = (uint32_t)(n % 13) + 1u;
                uint32_t* xb = g_xc + (size_t)((c * 2 + par) * CL + r) * (NCLU * 320) + s * 128;
                const uint32_t ra = cb + C_RED + s * 2048 + lane * (s < 2 ? 8 : 4);
                mwait(cb + C_BAR + B_R + s * 8, par);
                TSTAMP(c * 12 + 7);
                uint4 p[4];
                if (s < 2) {
#pragma unroll
                    for (int i = 0; i < 4; i++) {
                        const uint2 a = lds64(ra + i * 512), b = lds64(ra + i * 512 + 256);
                        p[i] = make_uint4(a.x, a.y, b.x, b.y);
                    }
                } else {
#pragma unroll
                    for (int i = 0; i < 4; i++) p[i] = make_uint4(lds32(ra + i * 512), lds32(ra + i * 512 + 128), lds32(ra + i * 512 + 256), lds32(ra + i * 512 + 384));
                }
                if (lane == 0) mbar_expect_tx(cb + C_BAR + B_R + s * 8, 2048);
                uint32_t m0, m1;
                if (s < 2) {
                    float f0 = 0.f, f1 = 0.f, f2 = 0.f, f3 = 0.f;
#pragma unroll
                    for (int i = 0; i < 4; i++) {
                        f0 += blo(p[i].x) + blo(p[i].z); f1 += bhi(p[i].x) + bhi(p[i].z);
                        f2 += blo(p[i].y) + blo(p[i].w); f3 += bhi(p[i].y) + bhi(p[i].w);
                    }
                    xb += lane * 4;
                    const uint32_t u0 = (__float_as_uint(f0) & ~0xFu) | tag, u1 = (__float_as_uint(f1) & ~0xFu) | tag;
                    const uint32_t u2 = (__float_as_uint(f2) & ~0xFu) | tag, u3 = (__float_as_uint(f3) & ~0xFu) | tag;
                    st_relaxed_v4(xb + cq * 320, u0, u1, u2, u3);
                    TSTAMP(c * 12 + 8);
                    xdelay();
                    uint4 x[NCLU];
#pragma unroll
                    for (int k = 0; k < NCLU; k++) x[k] = make_uint4(u0, u1, u2, u3);
                    int guard = 0;
                    bool first = true;
                    while (true) {
                        bool ok = true;
#pragma unroll
                        for (int k = 0; k < NCLU; k++) {
                            const bool okk = k == cq || (!first && ((x[k].x ^ tag) | (x[k].y ^ tag) | (x[k].z ^ tag) | (x[k].w ^ tag)) << 28 == 0);
                            if (!okk) { x[k] = ld_relaxed_v4(xb + k * 320); ok = false; }
                        }
                        first = false;
                        if (__all_sync(0xffffffffu, ok) || ++guard > SPIN_LIMIT) break;
                    }
                    TVAL(c * 12 + 11, guard);
                    f0 = f1 = f2 = f3 = 0.f;
#pragma unroll
                    for (int k = 0; k < NCLU; k++) {
                        f0 += __uint_as_float(x[k].x & ~0xFu); f1 += __uint_as_float(x[k].y & ~0xFu);
                        f2 += __uint_as_float(x[k].z & ~0xFu); f3 += __uint_as_float(x[k].w & ~0xFu);
                    }
                    m0 = movmat(pack2(f0, f1)); m1 = movmat(pack2(f2, f3));
                } else {
                    float f0 = 0.f, f1 = 0.f;
#pragma unroll
                    for (int i = 0; i < 4; i++) {
                        f0 += (blo(p[i].x) + blo(p[i].y)) + (blo(p[i].z) + blo(p[i].w));
                        f1 += (bhi(p[i].x) + bhi(p[i].y)) + (bhi(p[i].z) + bhi(p[i].w));
                    }
                    xb += lane * 2;
                    const uint32_t u0 = (__float_as_uint(f0) & ~0xFu) | tag, u1 = (__float_as_uint(f1) & ~0xFu) | tag;
                    st_relaxed_v2(xb + cq * 320, u0, u1);
                    TSTAMP(c * 12 + 8);
                    xdelay();
                    uint2 x[NCLU];
#pragma unroll
                    for (int k = 0; k < NCLU; k++) x[k] = make_uint2(u0, u1);
                    int guard = 0;
                    bool first = true;
                    while (true) {
                        bool ok = true;
#pragma unroll
                        for (int k = 0; k < NCLU; k++) {
                            const bool okk = k == cq || (!first && ((x[k].x ^ tag) | (x[k].y ^ tag)) << 28 == 0);
                            if (!okk) { x[k] = ld_relaxed_v2(xb + k * 320); ok = false; }
                        }
                        first = false;
                        if (__all_sync(0xffffffffu, ok) || ++guard > SPIN_LIMIT) break;
                    }
                    TVAL(c * 12 + 11, guard);
                    f0 = f1 = 0.f;
#pragma unroll
                    for (int k = 0; k < NCLU; k++) { f0 += __uint_as_float(x[k].x & ~0xFu); f1 += __uint_as_float(x[k].y & ~0xFu); }
                    m0 = movmat(pack2(f0, f1)); m1 = 0;
                }
                TSTAMP(c * 12 + 9);
                const uint32_t ma = cb + C_MEM + (s < 2 ? lane * 8 + (hf * 2 + s) * 256 : 1024 + hf * 128 + lane * 4), bm = cb + C_BAR;
                if (s < 2) {
#pragma unroll
                    for (int G = 0; G < 8; G++)
#pragma unroll
                        for (int b = 0; b < 2; b++) {
                            const uint32_t dd = mapa(sb, (uint32_t)(((r + 2 * G) & 15) ^ b)) - sb;
                            st_async_v2(ma + G * 1280 + dd, m0, m1, bm + G * 8 + dd);
                        }
                } else {
#pragma unroll
                    for (int G = 0; G < 8; G++)
#pragma unroll
                        for (int b = 0; b < 2; b++) {
                            const uint32_t dd = mapa(sb, (uint32_t)(((r + 2 * G) & 15) ^ b)) - sb;
                            st_async_u32(ma + G * 1280 + dd, m0, bm + G * 8 + dd);
                        }
                }
                TSTAMP(c * 12 + 10);
            }
        } else {
            auto fetch = [&](int c, int seg) {
                if (lane == 0) {
                    if (seg % CSEG == 0) {
                        int guard = 0;
                        while (ld_acquire(FLG(F_KV + c * NCHK + seg / CSEG)) < A.kv_target && ++guard < SPIN_LIMIT) __nanosleep(64);
                    }
                    asm volatile("fence.proxy.async;" ::: "memory");
                    const uint32_t cb = sb + O_REST + c * C_SIZE;
                    const uint32_t bt = cb + C_BAR + B_T, d = cb + C_TOK;
                    mbar_expect_tx(bt, 12288);
                    const CUtensorMap* mk = &A.tk[c];
                    const CUtensorMap* mv = &A.tv[c];
                    asm volatile("cp.async.bulk.tensor.2d.shared::cluster.global.mbarrier::complete_tx::bytes [%0], [%1, {%3, %4}], [%2];" ::"r"(d),
                                 "l"(mk), "r"(bt), "r"(h * DH + hf * 64), "r"(seg * SEG) : "memory");
#pragma unroll
                    for (int i = 0; i < 2; i++)
                        asm volatile("cp.async.bulk.tensor.2d.shared::cluster.global.mbarrier::complete_tx::bytes [%0], [%1, {%3, %4}], [%2];" ::"r"(d + 4096 + i * 4096),
                                     "l"(mv), "r"(bt), "r"(h * DH + i * 64), "r"(seg * SEG) : "memory");
                }
                __syncwarp();
            };
            fetch(0, 0);
#pragma unroll 1
            for (int hs = 0; hs < 2 * NTICK; hs++) {
                const int c = hs & 1, t = hs >> 1;
                const int n = t - c * LAG;
                if (n < -1 || n >= NSEG) continue;
                if (n >= 0) {
                    const uint32_t cb = sb + O_REST + c * C_SIZE;
                    mwait(cb + C_BAR + B_F, (uint32_t)(n & 1));
                    uint4* fd = g_kvf + (size_t)((c * NSEG + n) * NH + h) * 256 + hf * 64 + lane;
#pragma unroll
                    for (int i = 0; i < 2; i++) {
                        const uint4 k0 = ldsm4(cb + C_K + i * 1024 + lane * 16), k1 = ldsm4(cb + C_K + i * 1024 + 512 + lane * 16);
                        fd[i * 32] = make_uint4(badd2(k0.x, k0.z), badd2(k0.y, k0.w), badd2(k1.x, k1.z), badd2(k1.y, k1.w));
                        const uint32_t va = cb + C_V + hf * 2048 + i * 1024 + lane * 8;
                        const uint2 v0 = lds64(va), v1 = lds64(va + 256), v2 = lds64(va + 512), v3 = lds64(va + 768);
                        fd[128 + i * 32] = make_uint4(badd2(v0.x, v1.x), badd2(v0.y, v1.y), badd2(v2.x, v3.x), badd2(v2.y, v3.y));
                    }
                    if (blockIdx.x == 0 && lane == 0 && (c == 0 || t >= NSEG)) asm volatile("st.relaxed.gpu.global.u32 [%0], %1;" ::"l"(FLG(F_PROG)), "r"(t + 1) : "memory");
                    if ((n % CSEG) == CSEG - 1) {
                        asm volatile("fence.proxy.async;" ::: "memory");
                        __syncwarp();
                        if (lane == 0) { red_release(FLG(F_MEM + c * NCHK + n / CSEG), 1); }
                    }
                }
                if (n + 1 < NSEG - 1) fetch(c, n + 1);
            }
        }
    }
    cluster_sync_all();
}
}

namespace ni {
constexpr int KV_TGT = 32, MEM_TGT = 64, OP_TGT = 16, CONV_TGT = 80, H_TGT = 128;
constexpr int PDIST = (LAG + 3) / 4;
#define QA_PRE 3
#define KV1_W 5
#define KV1_N 16
static_assert(QA_PRE < 4, "inputs of the chunk must be complete");
#define SPLAN 0x102030
#define URGENT 1
#define POST_NS 40

#define ELECT "{\n.reg .pred p;\nelect.sync _|p, 0xffffffff;\n@p "
__device__ __forceinline__ void tma_load_2d(uint32_t dst, const CUtensorMap* map, uint32_t bar, int c0, int c1) {
    asm volatile(ELECT "cp.async.bulk.tensor.2d.shared::cluster.global.mbarrier::complete_tx::bytes [%0], [%1, {%3, %4}], [%2];\n}" ::"r"(dst),
                 "l"(map), "r"(bar), "r"(c0), "r"(c1) : "memory");
}
__device__ __forceinline__ void tma_load_2d_mc(uint32_t dst, const CUtensorMap* map, uint32_t bar, int c0, int c1) {
    asm volatile(ELECT "cp.async.bulk.tensor.2d.shared::cluster.global.mbarrier::complete_tx::bytes.multicast::cluster [%0], [%1, {%3, %4}], [%2], %5;\n}" ::"r"(dst),
                 "l"(map), "r"(bar), "r"(c0), "r"(c1), "h"((unsigned short)3) : "memory");
}
__device__ __forceinline__ void tma_load_3d(uint32_t dst, const CUtensorMap* map, uint32_t bar, int c1, int c2) {
    asm volatile(ELECT "cp.async.bulk.tensor.3d.shared::cluster.global.mbarrier::complete_tx::bytes [%0], [%1, {%5, %3, %4}], [%2];\n}" ::"r"(dst),
                 "l"(map), "r"(bar), "r"(c1), "r"(c2), "r"(0) : "memory");
}
__device__ __forceinline__ void tma_load_3d_mc(uint32_t dst, const CUtensorMap* map, uint32_t bar, int c1, int c2) {
    asm volatile(ELECT "cp.async.bulk.tensor.3d.shared::cluster.global.mbarrier::complete_tx::bytes.multicast::cluster [%0], [%1, {%6, %3, %4}], [%2], %5;\n}" ::"r"(dst),
                 "l"(map), "r"(bar), "r"(c1), "r"(c2), "h"((unsigned short)3), "r"(0) : "memory");
}
__device__ __forceinline__ void bulk_load(uint32_t dst, const void* src, uint32_t bytes, uint32_t bar) {
    asm volatile(ELECT "cp.async.bulk.shared::cluster.global.mbarrier::complete_tx::bytes [%0], [%1], %2, [%3];\n}" ::"r"(dst), "l"(src), "r"(bytes), "r"(bar) : "memory");
}
__device__ __forceinline__ void expect_tx1(uint32_t bar, uint32_t bytes) {
    asm volatile(ELECT "mbarrier.arrive.expect_tx.shared::cta.b64 _, [%0], %1;\n}" ::"r"(bar), "r"(bytes) : "memory");
}
__device__ __forceinline__ void wg_fence() { asm volatile("wgmma.fence.sync.aligned;" ::: "memory"); }
__device__ __forceinline__ void wg_commit() { asm volatile("wgmma.commit_group.sync.aligned;" ::: "memory"); }
template <int N> __device__ __forceinline__ void wg_wait() { asm volatile("wgmma.wait_group.sync.aligned %0;" ::"n"(N) : "memory"); }
__device__ __forceinline__ uint64_t make_desc(uint32_t addr, uint32_t lbo, uint32_t sbo) {
    return (uint64_t)((addr & 0x3FFFF) >> 4) | ((uint64_t)((lbo & 0x3FFFF) >> 4) << 16) |
           ((uint64_t)((sbo & 0x3FFFF) >> 4) << 32) | (1ull << 62);
}
__device__ __forceinline__ void wgmma_m64n256k16(float* d, uint64_t da, uint64_t db) {
    asm volatile("{\n.reg .pred p;\nsetp.ne.b32 p, 1, 0;\n"
                 "wgmma.mma_async.sync.aligned.m64n256k16.f32.bf16.bf16 {%0, %1, %2, %3, %4, %5, %6, %7, %8, %9, %10, %11, %12, %13, %14, %15, %16, %17, %18, %19, %20, %21, %22, %23, %24, %25, %26, %27, %28, %29, %30, %31, %32, %33, %34, %35, %36, %37, %38, %39, %40, %41, %42, %43, %44, %45, %46, %47, %48, %49, %50, %51, %52, %53, %54, %55, %56, %57, %58, %59, %60, %61, %62, %63, %64, %65, %66, %67, %68, %69, %70, %71, %72, %73, %74, %75, %76, %77, %78, %79, %80, %81, %82, %83, %84, %85, %86, %87, %88, %89, %90, %91, %92, %93, %94, %95, %96, %97, %98, %99, %100, %101, %102, %103, %104, %105, %106, %107, %108, %109, %110, %111, %112, %113, %114, %115, %116, %117, %118, %119, %120, %121, %122, %123, %124, %125, %126, %127}, %128, %129, p, 1, 1, 0, 1;\n}\n"
                 : "+f"(d[0]), "+f"(d[1]), "+f"(d[2]), "+f"(d[3]), "+f"(d[4]), "+f"(d[5]), "+f"(d[6]), "+f"(d[7]), "+f"(d[8]), "+f"(d[9]), "+f"(d[10]), "+f"(d[11]), "+f"(d[12]), "+f"(d[13]), "+f"(d[14]), "+f"(d[15]), "+f"(d[16]), "+f"(d[17]), "+f"(d[18]), "+f"(d[19]), "+f"(d[20]), "+f"(d[21]), "+f"(d[22]), "+f"(d[23]), "+f"(d[24]), "+f"(d[25]), "+f"(d[26]), "+f"(d[27]), "+f"(d[28]), "+f"(d[29]), "+f"(d[30]), "+f"(d[31]), "+f"(d[32]), "+f"(d[33]), "+f"(d[34]), "+f"(d[35]), "+f"(d[36]), "+f"(d[37]), "+f"(d[38]), "+f"(d[39]), "+f"(d[40]), "+f"(d[41]), "+f"(d[42]), "+f"(d[43]), "+f"(d[44]), "+f"(d[45]), "+f"(d[46]), "+f"(d[47]), "+f"(d[48]), "+f"(d[49]), "+f"(d[50]), "+f"(d[51]), "+f"(d[52]), "+f"(d[53]), "+f"(d[54]), "+f"(d[55]), "+f"(d[56]), "+f"(d[57]), "+f"(d[58]), "+f"(d[59]), "+f"(d[60]), "+f"(d[61]), "+f"(d[62]), "+f"(d[63]), "+f"(d[64]), "+f"(d[65]), "+f"(d[66]), "+f"(d[67]), "+f"(d[68]), "+f"(d[69]), "+f"(d[70]), "+f"(d[71]), "+f"(d[72]), "+f"(d[73]), "+f"(d[74]), "+f"(d[75]), "+f"(d[76]), "+f"(d[77]), "+f"(d[78]), "+f"(d[79]), "+f"(d[80]), "+f"(d[81]), "+f"(d[82]), "+f"(d[83]), "+f"(d[84]), "+f"(d[85]), "+f"(d[86]), "+f"(d[87]), "+f"(d[88]), "+f"(d[89]), "+f"(d[90]), "+f"(d[91]), "+f"(d[92]), "+f"(d[93]), "+f"(d[94]), "+f"(d[95]), "+f"(d[96]), "+f"(d[97]), "+f"(d[98]), "+f"(d[99]), "+f"(d[100]), "+f"(d[101]), "+f"(d[102]), "+f"(d[103]), "+f"(d[104]), "+f"(d[105]), "+f"(d[106]), "+f"(d[107]), "+f"(d[108]), "+f"(d[109]), "+f"(d[110]), "+f"(d[111]), "+f"(d[112]), "+f"(d[113]), "+f"(d[114]), "+f"(d[115]), "+f"(d[116]), "+f"(d[117]), "+f"(d[118]), "+f"(d[119]), "+f"(d[120]), "+f"(d[121]), "+f"(d[122]), "+f"(d[123]), "+f"(d[124]), "+f"(d[125]), "+f"(d[126]), "+f"(d[127])
                 : "l"(da), "l"(db));
}
__device__ __forceinline__ void wgmma_m64n256k16_first(float* d, uint64_t da, uint64_t db) {
    asm volatile("{\n.reg .pred p;\nsetp.ne.b32 p, 0, 0;\n"
                 "wgmma.mma_async.sync.aligned.m64n256k16.f32.bf16.bf16 {%0, %1, %2, %3, %4, %5, %6, %7, %8, %9, %10, %11, %12, %13, %14, %15, %16, %17, %18, %19, %20, %21, %22, %23, %24, %25, %26, %27, %28, %29, %30, %31, %32, %33, %34, %35, %36, %37, %38, %39, %40, %41, %42, %43, %44, %45, %46, %47, %48, %49, %50, %51, %52, %53, %54, %55, %56, %57, %58, %59, %60, %61, %62, %63, %64, %65, %66, %67, %68, %69, %70, %71, %72, %73, %74, %75, %76, %77, %78, %79, %80, %81, %82, %83, %84, %85, %86, %87, %88, %89, %90, %91, %92, %93, %94, %95, %96, %97, %98, %99, %100, %101, %102, %103, %104, %105, %106, %107, %108, %109, %110, %111, %112, %113, %114, %115, %116, %117, %118, %119, %120, %121, %122, %123, %124, %125, %126, %127}, %128, %129, p, 1, 1, 0, 1;\n}\n"
                 : "=f"(d[0]), "=f"(d[1]), "=f"(d[2]), "=f"(d[3]), "=f"(d[4]), "=f"(d[5]), "=f"(d[6]), "=f"(d[7]), "=f"(d[8]), "=f"(d[9]), "=f"(d[10]), "=f"(d[11]), "=f"(d[12]), "=f"(d[13]), "=f"(d[14]), "=f"(d[15]), "=f"(d[16]), "=f"(d[17]), "=f"(d[18]), "=f"(d[19]), "=f"(d[20]), "=f"(d[21]), "=f"(d[22]), "=f"(d[23]), "=f"(d[24]), "=f"(d[25]), "=f"(d[26]), "=f"(d[27]), "=f"(d[28]), "=f"(d[29]), "=f"(d[30]), "=f"(d[31]), "=f"(d[32]), "=f"(d[33]), "=f"(d[34]), "=f"(d[35]), "=f"(d[36]), "=f"(d[37]), "=f"(d[38]), "=f"(d[39]), "=f"(d[40]), "=f"(d[41]), "=f"(d[42]), "=f"(d[43]), "=f"(d[44]), "=f"(d[45]), "=f"(d[46]), "=f"(d[47]), "=f"(d[48]), "=f"(d[49]), "=f"(d[50]), "=f"(d[51]), "=f"(d[52]), "=f"(d[53]), "=f"(d[54]), "=f"(d[55]), "=f"(d[56]), "=f"(d[57]), "=f"(d[58]), "=f"(d[59]), "=f"(d[60]), "=f"(d[61]), "=f"(d[62]), "=f"(d[63]), "=f"(d[64]), "=f"(d[65]), "=f"(d[66]), "=f"(d[67]), "=f"(d[68]), "=f"(d[69]), "=f"(d[70]), "=f"(d[71]), "=f"(d[72]), "=f"(d[73]), "=f"(d[74]), "=f"(d[75]), "=f"(d[76]), "=f"(d[77]), "=f"(d[78]), "=f"(d[79]), "=f"(d[80]), "=f"(d[81]), "=f"(d[82]), "=f"(d[83]), "=f"(d[84]), "=f"(d[85]), "=f"(d[86]), "=f"(d[87]), "=f"(d[88]), "=f"(d[89]), "=f"(d[90]), "=f"(d[91]), "=f"(d[92]), "=f"(d[93]), "=f"(d[94]), "=f"(d[95]), "=f"(d[96]), "=f"(d[97]), "=f"(d[98]), "=f"(d[99]), "=f"(d[100]), "=f"(d[101]), "=f"(d[102]), "=f"(d[103]), "=f"(d[104]), "=f"(d[105]), "=f"(d[106]), "=f"(d[107]), "=f"(d[108]), "=f"(d[109]), "=f"(d[110]), "=f"(d[111]), "=f"(d[112]), "=f"(d[113]), "=f"(d[114]), "=f"(d[115]), "=f"(d[116]), "=f"(d[117]), "=f"(d[118]), "=f"(d[119]), "=f"(d[120]), "=f"(d[121]), "=f"(d[122]), "=f"(d[123]), "=f"(d[124]), "=f"(d[125]), "=f"(d[126]), "=f"(d[127])
                 : "l"(da), "l"(db));
}
__device__ __forceinline__ void wgmma_rs_m64n128k16(float* d, const uint32_t* a, uint64_t db) {
    asm volatile("{\n.reg .pred p;\nsetp.ne.b32 p, 1, 0;\n"
                 "wgmma.mma_async.sync.aligned.m64n128k16.f32.bf16.bf16 {%0, %1, %2, %3, %4, %5, %6, %7, %8, %9, %10, %11, %12, %13, %14, %15, %16, %17, %18, %19, %20, %21, %22, %23, %24, %25, %26, %27, %28, %29, %30, %31, %32, %33, %34, %35, %36, %37, %38, %39, %40, %41, %42, %43, %44, %45, %46, %47, %48, %49, %50, %51, %52, %53, %54, %55, %56, %57, %58, %59, %60, %61, %62, %63}, {%64, %65, %66, %67}, %68, p, 1, 1, 1;\n}\n"
                 : "+f"(d[0]), "+f"(d[1]), "+f"(d[2]), "+f"(d[3]), "+f"(d[4]), "+f"(d[5]), "+f"(d[6]), "+f"(d[7]), "+f"(d[8]), "+f"(d[9]), "+f"(d[10]), "+f"(d[11]), "+f"(d[12]), "+f"(d[13]), "+f"(d[14]), "+f"(d[15]), "+f"(d[16]), "+f"(d[17]), "+f"(d[18]), "+f"(d[19]), "+f"(d[20]), "+f"(d[21]), "+f"(d[22]), "+f"(d[23]), "+f"(d[24]), "+f"(d[25]), "+f"(d[26]), "+f"(d[27]), "+f"(d[28]), "+f"(d[29]), "+f"(d[30]), "+f"(d[31]), "+f"(d[32]), "+f"(d[33]), "+f"(d[34]), "+f"(d[35]), "+f"(d[36]), "+f"(d[37]), "+f"(d[38]), "+f"(d[39]), "+f"(d[40]), "+f"(d[41]), "+f"(d[42]), "+f"(d[43]), "+f"(d[44]), "+f"(d[45]), "+f"(d[46]), "+f"(d[47]), "+f"(d[48]), "+f"(d[49]), "+f"(d[50]), "+f"(d[51]), "+f"(d[52]), "+f"(d[53]), "+f"(d[54]), "+f"(d[55]), "+f"(d[56]), "+f"(d[57]), "+f"(d[58]), "+f"(d[59]), "+f"(d[60]), "+f"(d[61]), "+f"(d[62]), "+f"(d[63])
                 : "r"(a[0]), "r"(a[1]), "r"(a[2]), "r"(a[3]), "l"(db));
}
__device__ __forceinline__ void wgmma_rs_m64n128k16_first(float* d, const uint32_t* a, uint64_t db) {
    asm volatile("{\n.reg .pred p;\nsetp.ne.b32 p, 0, 0;\n"
                 "wgmma.mma_async.sync.aligned.m64n128k16.f32.bf16.bf16 {%0, %1, %2, %3, %4, %5, %6, %7, %8, %9, %10, %11, %12, %13, %14, %15, %16, %17, %18, %19, %20, %21, %22, %23, %24, %25, %26, %27, %28, %29, %30, %31, %32, %33, %34, %35, %36, %37, %38, %39, %40, %41, %42, %43, %44, %45, %46, %47, %48, %49, %50, %51, %52, %53, %54, %55, %56, %57, %58, %59, %60, %61, %62, %63}, {%64, %65, %66, %67}, %68, p, 1, 1, 1;\n}\n"
                 : "=f"(d[0]), "=f"(d[1]), "=f"(d[2]), "=f"(d[3]), "=f"(d[4]), "=f"(d[5]), "=f"(d[6]), "=f"(d[7]), "=f"(d[8]), "=f"(d[9]), "=f"(d[10]), "=f"(d[11]), "=f"(d[12]), "=f"(d[13]), "=f"(d[14]), "=f"(d[15]), "=f"(d[16]), "=f"(d[17]), "=f"(d[18]), "=f"(d[19]), "=f"(d[20]), "=f"(d[21]), "=f"(d[22]), "=f"(d[23]), "=f"(d[24]), "=f"(d[25]), "=f"(d[26]), "=f"(d[27]), "=f"(d[28]), "=f"(d[29]), "=f"(d[30]), "=f"(d[31]), "=f"(d[32]), "=f"(d[33]), "=f"(d[34]), "=f"(d[35]), "=f"(d[36]), "=f"(d[37]), "=f"(d[38]), "=f"(d[39]), "=f"(d[40]), "=f"(d[41]), "=f"(d[42]), "=f"(d[43]), "=f"(d[44]), "=f"(d[45]), "=f"(d[46]), "=f"(d[47]), "=f"(d[48]), "=f"(d[49]), "=f"(d[50]), "=f"(d[51]), "=f"(d[52]), "=f"(d[53]), "=f"(d[54]), "=f"(d[55]), "=f"(d[56]), "=f"(d[57]), "=f"(d[58]), "=f"(d[59]), "=f"(d[60]), "=f"(d[61]), "=f"(d[62]), "=f"(d[63])
                 : "r"(a[0]), "r"(a[1]), "r"(a[2]), "r"(a[3]), "l"(db));
}

struct BulkMaps { CUtensorMap h, h2, wq, wk, wv, wo, kv, lu; };
struct BulkArgs {
    const bf16 *x, *ssmk, *ssmD, *Bk, *Bv, *shiftk;
    bf16* out;
};
enum { T_KV = 0, T_QA, T_CONV, T_ATT, T_POST, T_LN0 };
constexpr int MAXG = 52, SENT = MAXG - 1;
struct Sched { uint32_t chk[MAXG * 4]; uint32_t info[MAXG]; int sbeg[8]; };

constexpr int BK_STAGES = 4, BK_STAGE_BYTES = 49152, TSLOTS = 4;
struct BulkSmemTail {
    unsigned long long full[BK_STAGES], empty[BK_STAGES], tfull[TSLOTS], tempty[TSLOTS], sfull[4], sempty[4];
    int task[TSLOTS];
    uint32_t tab[MAXG * 5];
};
constexpr int BULK_STG = BK_STAGES * BK_STAGE_BYTES;
constexpr int BULK_TAIL = BULK_STG + 32768;
constexpr int BULK_SMEM = BULK_TAIL + (int)sizeof(BulkSmemTail);
static_assert(BULK_SMEM <= 232448, "bulk smem");
#define PACE 0
#define REG_C 224
#define REG_P 56

#define BT(lead, type, l, c, k)
#define TT(k)
#define FT(k)
#define TTV(k, v)
__device__ __forceinline__ void tma_store_2d(const CUtensorMap* map, uint32_t src, int c0, int c1) {
    asm volatile("cp.async.bulk.tensor.2d.global.shared::cta.bulk_group [%0, {%2, %3}], [%1];" ::"l"(map), "r"(src), "r"(c0), "r"(c1) : "memory");
}
__device__ __forceinline__ void bulk_commit() { asm volatile("cp.async.bulk.commit_group;" ::: "memory"); }
template <int N> __device__ __forceinline__ void bulk_wait_read() { asm volatile("cp.async.bulk.wait_group.read %0;" ::"n"(N) : "memory"); }
template <int N> __device__ __forceinline__ void bulk_wait() { asm volatile("cp.async.bulk.wait_group %0;" ::"n"(N) : "memory"); }
__device__ __forceinline__ void mbar_arrive_cluster(uint32_t bar) {
    asm volatile("mbarrier.arrive.shared::cluster.b64 _, [%0];" ::"r"(bar) : "memory");
}
__device__ __forceinline__ void stsm_x4(uint32_t addr, uint32_t r0, uint32_t r1, uint32_t r2, uint32_t r3) {
    asm volatile("stmatrix.sync.aligned.m8n8.x4.shared.b16 [%0], {%1,%2,%3,%4};" ::"r"(addr), "r"(r0), "r"(r1), "r"(r2), "r"(r3) : "memory");
}
__device__ __forceinline__ void mma1688(float* c, uint32_t a0, uint32_t a1, uint32_t b0) {
    asm("mma.sync.aligned.m16n8k8.row.col.f32.bf16.bf16.f32 {%0,%1,%2,%3}, {%4,%5}, {%6}, {%0,%1,%2,%3};"
        : "+f"(c[0]), "+f"(c[1]), "+f"(c[2]), "+f"(c[3]) : "r"(a0), "r"(a1), "r"(b0));
}
__device__ __forceinline__ int ld_relaxed(const int* p) {
    int v;
    asm volatile("ld.relaxed.gpu.global.u32 %0, [%1];" : "=r"(v) : "l"(p) : "memory");
    return v;
}
__device__ __forceinline__ void flag_wait(const int* f, int tgt, int ns) {
    int guard = 0;
    while (ld_relaxed(f) < tgt && ++guard < 4000000) __nanosleep(ns);
}
__device__ __forceinline__ void fence_async() { asm volatile("fence.proxy.async.global;" ::: "memory"); }
__device__ __forceinline__ uint32_t bmul2(uint32_t a, uint32_t b) { uint32_t r; asm("mul.rn.bf16x2 %0, %1, %2;" : "=r"(r) : "r"(a), "r"(b)); return r; }
__device__ __forceinline__ uint32_t bsum2(uint32_t a, uint32_t b) { uint32_t r; asm("add.rn.bf16x2 %0, %1, %2;" : "=r"(r) : "r"(a), "r"(b)); return r; }
__device__ __forceinline__ uint32_t bmax2(uint32_t a, uint32_t b) { uint32_t r; asm("max.bf16x2 %0, %1, %2;" : "=r"(r) : "r"(a), "r"(b)); return r; }
__device__ __forceinline__ uint32_t rscore(float a, float b) {
    const uint32_t u = pack2(a, b);
    return pack2(blo(u) * 0.08838834764831845f, bhi(u) * 0.08838834764831845f);
}
template <int STRIDE> __device__ __forceinline__ void ld5(uint32_t* w, const bf16* p) {
#pragma unroll
    for (int r = 0; r < 5; r++) { const uint2 v = __ldcg(reinterpret_cast<const uint2*>(p + r * STRIDE)); w[2 * r] = v.x; w[2 * r + 1] = v.y; }
}
__device__ __forceinline__ void st5(bf16* p, const uint32_t* w) {
#pragma unroll
    for (int r = 0; r < 5; r++) *reinterpret_cast<uint2*>(p + r * 128) = make_uint2(w[2 * r], w[2 * r + 1]);
}
__device__ __forceinline__ void ln_row(const uint32_t* x, uint32_t* y) {
    float s = 0.f;
#pragma unroll
    for (int i = 0; i < 10; i++) s += blo(x[i]) + bhi(x[i]);
#pragma unroll
    for (int o = 16; o > 0; o >>= 1) s += __shfl_xor_sync(0xffffffffu, s, o);
    const float mean = s * (1.0f / DM);
    float q = 0.f;
#pragma unroll
    for (int i = 0; i < 10; i++) { const float d0 = blo(x[i]) - mean, d1 = bhi(x[i]) - mean; q = fmaf(d0, d0, q); q = fmaf(d1, d1, q); }
#pragma unroll
    for (int o = 16; o > 0; o >>= 1) q += __shfl_xor_sync(0xffffffffu, q, o);
    const uint32_t nm = pack2(-mean, -mean);
    float sq;
    asm("sqrt.approx.ftz.f32 %0, %1;" : "=f"(sq) : "f"(rbf(rbf(q * (1.0f / DM)) + 1e-5f)));
    const float rd = rcpf(rbf(sq));
#pragma unroll
    for (int i = 0; i < 10; i++) { const uint32_t d = bsum2(x[i], nm); y[i] = pack2(blo(d) * rd, bhi(d) * rd); }
}
__device__ __forceinline__ void red_add8(uint4* p, uint32_t a, uint32_t b, uint32_t c, uint32_t d) {
    asm volatile("red.relaxed.gpu.global.add.noftz.v4.bf16x2 [%0], {%1,%2,%3,%4};" ::"l"(p), "r"(a), "r"(b), "r"(c), "r"(d) : "memory");
}
__device__ __forceinline__ void part_sum(const uint4& v, const uint4& w, int lane, uint32_t& x0, uint32_t& x1) {
    float t[8];
    t[0] = blo(v.x) + blo(w.x); t[1] = bhi(v.x) + bhi(w.x); t[2] = blo(v.y) + blo(w.y); t[3] = bhi(v.y) + bhi(w.y);
    t[4] = blo(v.z) + blo(w.z); t[5] = bhi(v.z) + bhi(w.z); t[6] = blo(v.w) + blo(w.w); t[7] = bhi(v.w) + bhi(w.w);
#pragma unroll
    for (int i = 0; i < 4; i++) t[i] = (lane < 16 ? t[i] : t[4 + i]) + __shfl_xor_sync(0xffffffffu, lane < 16 ? t[4 + i] : t[i], 16);
    const uint32_t r0 = pack2(t[0], t[1]), r1 = pack2(t[2], t[3]);
    const uint32_t ex = __shfl_xor_sync(0xffffffffu, (lane & 1) ? r0 : r1, 1);
    x0 = (lane & 1) ? ex : r0; x1 = (lane & 1) ? r1 : ex;
}
__device__ __forceinline__ void post_row(int l, int row, int lane, const bf16* xin, bf16* xout) {
    uint32_t x[10], y[10], n[10];
    const int cl = (lane & 12) * 8 + (lane >> 4) * 16 + (lane & 1) * 8 + (lane & 2) * 2;
    uint4* pp = reinterpret_cast<uint4*>(g_part + (size_t)(l * PROWS + (row & (PROWS - 1))) * (PG * DM)) + (lane & 15) + (lane >> 4) * 80;
    int* f = FLG(F_OP + l * NCHK + (row >> 7));
    flag_wait(FLG(F_CONV + (row >> 10)), CONV_TGT, 200);
    ld5<128>(x, xin + (size_t)row * DM + cl);
    flag_wait(f + 4, OP_TGT, POST_NS);
    {
        uint4 v[10];
#pragma unroll
        for (int i = 0; i < 10; i++) v[i] = __ldcg(pp + (i >> 1) * 16 + (i & 1) * 160);
#pragma unroll
        for (int r = 0; r < 5; r++) {
            uint32_t s0, s1;
            part_sum(v[2 * r], v[2 * r + 1], lane, s0, s1);
            if (r == 1) ld5<16 * S_LEN * 8>(y, g_Y + ((size_t)(cl >> 3) * S_LEN + (row ^ ((row >> 6) & 7))) * 8 + (cl & 4));
            x[2 * r] = bsum2(x[2 * r], s0); x[2 * r + 1] = bsum2(x[2 * r + 1], s1);
        }
    }
    ln_row(x, n);
#pragma unroll
    for (int i = 0; i < 10; i++) x[i] = bsum2(x[i], bmul2(n[i], y[i]));
    if (l == 0) {
        ln_row(x, n);
        st5(g_h[1] + (size_t)row * DM + cl, n);
        __syncwarp();
        if (lane == 0) red_release(FLG(F_H + NCHK + (row >> 7)), 1);
    }
#pragma unroll
    for (int i = 0; i < 10; i++) pp[(i >> 1) * 16 + (i & 1) * 160] = make_uint4(0, 0, 0, 0);
    st5(xout + (size_t)row * DM + cl, x);
    __syncwarp();
    if (l && lane == 0) red_release(f + 5, 1);
}
__device__ __forceinline__ void u_unit(const bf16* Bk, const bf16* Bv, const bf16* shiftk, int unit, int lane) {
    const int t0 = (unit / 10) * 16, cp = (unit % 10) * 32 + lane;
    uint32_t kk[19], vv[16];
    const uint32_t* pk = reinterpret_cast<const uint32_t*>(Bk + (size_t)t0 * DM) + cp;
    const uint32_t* pv = reinterpret_cast<const uint32_t*>(Bv + (size_t)t0 * DM) + cp;
#pragma unroll
    for (int i = 0; i < 19; i++) kk[i] = (i >= 3 || t0 > 0) ? __ldg(pk + (i - 3) * (DM / 2)) : 0u;
#pragma unroll
    for (int i = 0; i < 16; i++) vv[i] = __ldg(pv + i * (DM / 2));
    const uint4 sh0 = __ldg(reinterpret_cast<const uint4*>(shiftk + cp * 8));
    const uint32_t s0 = __byte_perm(sh0.x, sh0.z, 0x5410), s1 = __byte_perm(sh0.x, sh0.z, 0x7632), s2 = __byte_perm(sh0.y, sh0.w, 0x5410), s3 = __byte_perm(sh0.y, sh0.w, 0x7632);
#pragma unroll
    for (int t = 0; t < 16; t++)
        vv[t] = bmul2(bsum2(bsum2(bsum2(bmul2(kk[t], s3), bmul2(kk[t + 1], s2)), bmul2(kk[t + 2], s1)), bmul2(kk[t + 3], s0)), vv[t]);
    uint4* d = reinterpret_cast<uint4*>(g_U + (size_t)(cp * 2) * S_LEN + (t0 ^ 48));
#pragma unroll
    for (int c = 0; c < 2; c++) {
        const uint32_t sel = c ? 0x7632 : 0x5410;
#pragma unroll
        for (int hh = 0; hh < 2; hh++)
            d[c * (S_LEN / 8) + hh] = make_uint4(__byte_perm(vv[15 - hh * 8], vv[14 - hh * 8], sel), __byte_perm(vv[13 - hh * 8], vv[12 - hh * 8], sel),
                                                 __byte_perm(vv[11 - hh * 8], vv[10 - hh * 8], sel), __byte_perm(vv[9 - hh * 8], vv[8 - hh * 8], sel));
    }
}
constexpr int CV_EP = 4224;
template <class F> __device__ __forceinline__ void conv_unit(uint32_t ub, uint32_t e0, uint32_t e1, uint32_t zrow, uint32_t yt, float Dv, int m, int lane, F&& nearly_done) {
    const int g = lane >> 2, tq = lane & 3;
    asm volatile("st.shared.u32 [%0], %1;" ::"r"(e0 + lane * 4), "r"(0) : "memory");
    asm volatile("st.shared.u32 [%0], %1;" ::"r"(zrow + lane * 4), "r"(0) : "memory");
    __syncwarp();
    for (int i = lane; i < CV_EP / 16; i += 32) {
        const uint4 v = lds128(e0 + i * 16);
        const uint32_t nx = i + 1 < CV_EP / 16 ? lds32(e0 + i * 16 + 16) : 0u;
        sts128(e1 + i * 16, __byte_perm(v.x, v.y, 0x5432), __byte_perm(v.y, v.z, 0x5432), __byte_perm(v.z, v.w, 0x5432), __byte_perm(v.w, nx, 0x5432));
    }
    __syncwarp();
    float acc[8][4];
#pragma unroll
    for (int n = 0; n < 8; n++)
#pragma unroll
        for (int i = 0; i < 4; i++) acc[n][i] = 0.f;
    uint32_t wb = (g & 1) ? e0 + (1 + g + 2 * tq) * 2 : e1 + (g + 2 * tq) * 2;
    uint32_t W[16], a[4][4], an[4][4];
    int row = m * 16 + (lane & 15);
    auto lda = [&](uint32_t (*d)[4]) {
        const uint32_t x = row < 0 ? zrow : ub + row * 128 + (((lane >> 4) ^ (row & 7)) << 4);
#pragma unroll
        for (int ks = 0; ks < 4; ks++) ldsm_x4(d[ks][0], d[ks][1], d[ks][2], d[ks][3], x ^ (ks << 5));
        row--;
    };
#pragma unroll
    for (int i = 0; i < 16; i++) W[i] = lds32(wb + i * 16);
    lda(a);
    const int nD = m == 0 ? 16 : 32;
#pragma unroll 2
    for (int D = 0; D < nD; D++) {
        uint32_t Wn[8];
        wb += 128;
        if (D == nD - 6) nearly_done();
        lda(an);
#pragma unroll
        for (int i = 0; i < 8; i++) Wn[i] = lds32(wb + 128 + i * 16);
#pragma unroll
        for (int ks = 0; ks < 4; ks++)
#pragma unroll
            for (int n = 0; n < 8; n++) mma16816(acc[n], a[ks][0], a[ks][1], a[ks][2], a[ks][3], W[2 * ks + n], W[2 * ks + n + 1]);
#pragma unroll
        for (int i = 0; i < 8; i++) { W[i] = W[i + 8]; W[i + 8] = Wn[i]; }
#pragma unroll
        for (int ks = 0; ks < 4; ks++)
#pragma unroll
            for (int i = 0; i < 4; i++) a[ks][i] = an[ks][i];
    }
#pragma unroll
    for (int n = 0; n < 8; n++)
#pragma unroll
        for (int r = 0; r < 2; r++) {
            const int a_ = g + r * 8, b_ = n * 8 + tq * 2;
            const int ar = m * 16 + a_, p = 62 - b_;
            const uint32_t kv = lds32(ub + ar * 128 + (((p >> 3) ^ (ar & 7)) << 4) + (p & 7) * 2);
            const float y0 = rbf(acc[n][2 * r]) + rbf(bhi(kv) * Dv), y1 = rbf(acc[n][2 * r + 1]) + rbf(blo(kv) * Dv);
            const uint32_t pk = pack2(y0, y1);
            asm volatile("st.shared.u16 [%0], %1;" ::"r"(yt + ((a_ * 64 + b_) ^ g) * 16), "h"((unsigned short)(pk & 0xffff)) : "memory");
            asm volatile("st.shared.u16 [%0], %1;" ::"r"(yt + ((a_ * 64 + b_ + 1) ^ g) * 16), "h"((unsigned short)(pk >> 16)) : "memory");
        }
}

__global__ void __launch_bounds__(384, 1) bulk_kernel(const __grid_constant__ BulkMaps M, const __grid_constant__ BulkArgs A,
                                                      const __grid_constant__ Sched SC) {
    extern __shared__ __align__(1024) unsigned char smem_raw[];
    const uint32_t sb0 = smem_u32(smem_raw);
    const uint32_t full0 = sb0 + BULK_TAIL, empty0 = full0 + 32, tfull0 = full0 + 64, tempty0 = full0 + 96, sfull = full0 + 128, sempty = full0 + 160,
                   task0 = full0 + 192, tab0 = full0 + 208;
    const int tid = threadIdx.x, wid = __shfl_sync(0xffffffffu, tid >> 5, 0), lane = tid & 31;
    const int rank = blockIdx.x & 1;
    if (tid == 0) {
        for (int i = 0; i < BK_STAGES; i++) { mbar_init(full0 + 8 * i, 1); mbar_init(empty0 + 8 * i, 4); }
        for (int i = 0; i < TSLOTS; i++) { mbar_init(tfull0 + 8 * i, 1); mbar_init(tempty0 + 8 * i, 19); }
        for (int i = 0; i < 4; i++) { mbar_init(sfull + 8 * i, 8); mbar_init(sempty + 8 * i, 1); }
        asm volatile("fence.mbarrier_init.release.cluster;" ::: "memory");
        if (rank == 1) for (int i = 0; i < TSLOTS; i++) mbar_expect_tx(tfull0 + 8 * i, 4);
        BT(true, T_LN0, 0, 0, 0);
    }
    if (tid < MAXG * 5) asm volatile("st.shared.u32 [%0], %1;" ::"r"(tab0 + tid * 4), "r"(SC.chk[tid]) : "memory");
    cluster_sync_all();
    uint32_t tc = 0, it = 0;
    if (wid < 4) {
        asm volatile("setmaxnreg.dec.sync.aligned.u32 %0;" ::"n"(REG_P));
        if (wid == 0) {
            int head = SC.sbeg[lane >> 3];
            const int hend = SC.sbeg[(lane >> 3) + 1];
            uint32_t chk = 0; int pv = (blockIdx.x >> 1) & 31, grp = (SC.sbeg[3] + (blockIdx.x >> 6)) << 2 | 3, ncode = 0, code = 3 << 6 | 2, guard = 0;
            auto acquire = [&](uint32_t bytes) -> uint32_t {
                const uint32_t s = it & 3;
                mwait(empty0 + 8 * s, ((it >> 2) & 1) ^ 1);
                it++;
                expect_tx1(full0 + 8 * s, bytes);
                return s;
            };
            auto uwait = [&](const int* f, int tgt) {
                int g2 = 0;
                while ((int)UNI(ld_relaxed(f)) < tgt && ++g2 < 4000000) __nanosleep(32);
                fence_async();
            };
#pragma unroll 1
            while (true) {
                const int type = (code >> 6) & 3;
                const int iend = type == T_KV ? 10 : (type == T_QA ? 24 : 31);
                const int jj = code & 63, g0 = (jj & 15) * 4, lc = (code >> 9) & 31;
                const bool lm = (code >> 8) & 1;
                const CUtensorMap* mb = type == T_QA ? &M.wq : (jj < 16 ? &M.wk : &M.wv);
                bool have = false, ok = (code >> 14) & 1;
                int imem = 16;
#pragma unroll 1
                for (int i = type < T_CONV ? 0 : (type == T_CONV ? 24 : 28 + jj); i < iend; i++) {
                    const int sd = (type < T_CONV ? SPLAN : 0x1230) >> 4 * min(iend - i, 7) & 15;
                    if (rank == 0 && sd) {
                        if (sd == 1) {
                            if (type == T_CONV) mwait(empty0 + 8 * (it & 3), ((it >> 2) & 1) ^ 1);
                            const int gi = head + ((lane >> 2) & 1);
                            chk = lds32(tab0 + ((gi < hend ? gi : SENT) * 4 + (lane & 3)) * 4);
                            pv = ld_relaxed(g_flags + (chk & 0xffff));
                        } else if (sd == 2) {
                            const int tgt = (int)(chk >> 16);
                            const uint32_t b = (__ballot_sync(0xffffffffu, (lane & 3) == 0 ? pv < tgt : pv >= tgt) >> (lane & 24)) & 0xff;
                            const uint32_t cand = (b & 1) ? b & 15 : b >> 4;
                            head += (b & 1) ? 0 : ((b & 16) ? 1 : 2);
                            if (head > hend || guard > 4000000) head = hend;
                            const uint32_t req = lane >= 24 ? 1 : 15;
                            grp = (int)__reduce_min_sync(0xffffffffu, (cand & req) == req ? ((uint32_t)head << 2 | (cand ^ req) >> 2 | ((cand ^ req) & 2 ? 0 : 256)) : (head < hend ? 1000u : 1004u));
                            if (grp < 1000) grp &= 255;
                            if (grp < 1000) asm volatile("{\n.reg .pred p;\nsetp.eq.u32 p, %2, 0;\n@p atom.relaxed.gpu.global.inc.u32 %0, [%1], 0x7fffffff;\n}" : "+r"(pv) : "l"(FLG(F_CNT + (grp >> 2))), "r"(lane) : "memory");
                        } else {
                            if (grp < 1000) {
                                const int tk = (int)UNI(pv);
                                have = tk < (int)(UNI(lds32(tab0 + (grp >> 2) * 16)) >> 16);
                                ncode = (int)UNI(lds32(tab0 + MAXG * 16 + (grp & ~3))) | (grp & 3) << 19 | tk;
                            } else if (grp == 1004) { have = true; ncode = -1; }
                            if (have) {
                                const uint32_t o = (tc & 3) * 4;
                                mwait(tempty0 + 2 * o, ((tc >> 2) & 1) ^ 1);
                                asm volatile(ELECT "st.shared.u32 [%0], %1;\n@p mbarrier.arrive.shared::cta.b64 _, [%2];\n"
                                             "@p st.async.weak.shared::cluster.mbarrier::complete_tx::bytes.b32 [%3], %1, [%4];\n}"
                                             ::"r"(task0 + o), "r"(ncode), "r"(tfull0 + 2 * o), "r"(mapa(task0 + o, 1)), "r"(mapa(tfull0 + 2 * o, 1)) : "memory");
                            }
                        }
                    }
                    if (i >= 28) continue;
                    if (i == 8 && type == T_QA) pv = ld_relaxed(FLG((lane & 1 ? F_MEM : F_KV) + lc));
                    if (i == 10) {
                        const uint32_t b = __ballot_sync(0xffffffffu, pv >= (lane & 1 ? MEM_TGT : KV_TGT));
                        if (b & 2) imem = 13;
                        if (!(b & 1)) uwait(FLG(F_KV + lc), KV_TGT);
                        fence_async();
                    }
                    const uint32_t s = acquire(i < 12 ? 49152 : (i == 24 || i == 27 ? 0 : 32768));
                    const uint32_t sa = sb0 + s * BK_STAGE_BYTES, fb = full0 + 8 * s;
                    if (i == 0) TT(3);
                    if (i < 10) {
                        if (lm) {
                            tma_load_3d(sa + 16384, mb, fb, i * 64, g0);
                            tma_load_3d(sa + 32768, mb, fb, i * 64, g0 + 2);
                        } else tma_load_3d_mc(sa + 16384 + rank * 16384, mb, fb, i * 64, g0 + rank * 2);
                        int d = 0;
                        if (!ok) {
                            d = 1;
                            if (i == 3) {
                                uwait(FLG(F_H + lc), H_TGT);
                                ok = true;
                                d = -3;
                                TT(4);
                            }
                        }
#pragma unroll 1
                        for (; d <= 0; d++) {
                            const uint32_t s2 = (s + d) & 3;
                            if (lm) tma_load_2d_mc(sb0 + s2 * BK_STAGE_BYTES + rank * 8192, &M.h, full0 + 8 * s2, (i + d) * 64, lc * 128 + rank * 64);
                            else tma_load_2d(sb0 + s2 * BK_STAGE_BYTES, &M.h2, full0 + 8 * s2, (i + d) * 64, lc * 128);
                        }
                    } else if (i < 13) {
#pragma unroll 1
                        for (int k = 0, bx = (i - 10) * 3; k < 3 && bx < 8; k++, bx++)
                            tma_load_2d(sa + k * 16384, &M.kv, fb, (g0 + (bx & 3)) * 64, (bx >> 2) * S_LEN + (lc & 15) * 128);
                    } else if (i < 24) {
                        const int cn = ((i - 14) >> 1) * 128, ck = g0 * 64 + (i & 1) * 128;
                        if (i > 13) {
                            if (lm) { tma_load_2d(sa, &M.wo, fb, cn, ck); tma_load_2d(sa + 16384, &M.wo, fb, cn + 64, ck); }
                            else tma_load_2d_mc(sa + rank * 16384, &M.wo, fb, cn + rank * 64, ck);
                        }
                        if (i == imem) {
                            TT(5);
                            if (i == 16) uwait(FLG(F_MEM + lc), MEM_TGT);
                            const uint32_t s2 = (s + (i >> 4)) & 3;
#pragma unroll 1
                            for (int k = 0; k < 4; k++)
                                bulk_load(sb0 + s2 * BK_STAGE_BYTES + k * 8192, g_kvf + (size_t)((lc * CSEG + k) * NH + jj * 2) * 256, 8192, full0 + 8 * s2);
                            TT(6);
                        }
                    } else if (i == 25) {
                        tma_load_2d(sa, &M.lu, fb, 0, (2 * jj + rank) * 256);
                    } else if (i == 26) {
#pragma unroll 1
                        for (int k = 0; k < 8; k++)
                            bulk_load(sa + k * CV_EP + 128, A.ssmk + (size_t)((2 * jj + rank) * 8 + k) * S_LEN, 4096, fb);
                    }
                }
                if (type != 3) TT(7);
                if (rank == 0) {
                    if (!have) {
                        if (type == 3) { guard++; __nanosleep(64); }
                        code = 3 << 6;
                        continue;
                    }
                } else {
                    const uint32_t o = (tc & 3) * 4;
                    mwait(tfull0 + 2 * o, (tc >> 2) & 1);
                    ncode = (int)UNI(lds32(task0 + o));
                    asm volatile(ELECT "mbarrier.arrive.expect_tx.shared::cta.b64 _, [%0], 4;\n@p mbarrier.arrive.shared::cluster.b64 _, [%1];\n}" ::"r"(tfull0 + 2 * o), "r"(mapa(tempty0 + 2 * o, 0)) : "memory");
                    __syncwarp();
                }
                tc++;
                if (ncode < 0) break;
                TT(0); TTV(15, ncode);
                code = ((ncode & 256) ? (2 * ncode + rank) & 63 : ncode & 63) | (ncode & 0x1c0) | ((ncode >> (rank ? 14 : 9)) & 31) << 9 | ((ncode >> (19 + rank)) & 1) << 14;
                fence_async();
            }
        } else if (wid == 1) {
            if (lane < 8) asm volatile("prefetch.tensormap [%0];" ::"l"(&M.h + lane) : "memory");
            __syncwarp();
            if (lane == 0) {
                uint32_t rc = 0;
                while (true) {
                    mwait(tfull0 + 8 * (tc & 3), (tc >> 2) & 1);
                    const int code = (int)lds32(task0 + 4 * (tc & 3));
                    mbar_arrive_cluster(mapa(tempty0 + 8 * (tc & 3), 0));
                    tc++;
                    if (code < 0) break;
                    const int type = (code >> 6) & 3;
                    const int lc = (code >> (rank ? 14 : 9)) & 31;
                    mwait(sfull + 8 * (rc & 3), (rc >> 2) & 1);
                    if (type == T_CONV) {
                        asm volatile("cp.async.bulk.global.shared::cta.bulk_group [%0], [%1], %2;" ::"l"(g_Y + (size_t)((2 * (code & 63) + rank) * S_LEN + lc * 1024) * 8), "r"(sb0 + BULK_STG), "r"(16384) : "memory");
                        bulk_commit();
                        bulk_wait<0>();
                    }
                    mbar_arrive(sempty + 8 * (rc & 3));
                    rc++;
                    FT(0);
                    red_release(type == T_QA ? FLG(F_OP + lc) + 4 : FLG((type == T_KV ? F_KV : F_CONV) + lc), 1);
                    FT(1);
                    BT(true, type, lc >> 4, lc & 15, 2);
                }
            }
        } else {
            const int nw = 2 * gridDim.x, idx = (wid - 2) * gridDim.x + blockIdx.x;
#pragma unroll 1
            for (int hh = 0; hh < 2; hh++) {
#pragma unroll 1
                for (int u = hh * 640 + idx; u < hh * 640 + 640; u += nw) u_unit(A.Bk, A.Bv, A.shiftk, u, lane);
                __syncwarp();
                if (lane == 0) red_release(FLG(F_U + hh), 1);
                BT(lane == 0, T_LN0, hh, 0, 2);
            }
#pragma unroll 1
            for (int q = 0; q < 2 * (NCHK + PDIST); q++) {
                const int l = q & 1, c = (q >> 1) - l * PDIST;
                if (c < 0 || c >= NCHK) continue;
#pragma unroll 1
                for (int rr = idx; rr < 128; rr += nw) post_row(l, c * 128 + rr, lane, l ? g_x : A.x, l ? A.out : g_x);
                BT(lane == 0, T_POST, l, c, 2);
            }
        }
    } else {
        asm volatile("setmaxnreg.inc.sync.aligned.u32 %0;" ::"n"(REG_C));
        const int cw = (wid >> 2) - 1, warp = wid & 3;
        const uint32_t wst = sb0 + BULK_STG + (cw * 4 + warp) * 4096;
        uint32_t rc = 0;
        int npend = 0;
        bool urgent = false;
        uint32_t oofs = 0;
        uint32_t qf[16][4];
        auto release = [&](int s) { if ((tid & 127) == 0) { mbar_arrive(empty0 + 8 * s); mbar_arrive_cluster(mapa(empty0 + 8 * s, rank ^ 1)); } };
        auto next = [&]() -> int { const int s = it & 3; mwait(full0 + 8 * s, (it >> 2) & 1); it++; return s; };
        auto wgbar = [&]() { if (cw == 0) named_bar(2, 128); else named_bar(3, 128); };
        auto handoff = [&]() {
            mwait(sempty + 8 * (rc & 3), ((rc >> 2) & 1) ^ 1);
            asm volatile(ELECT "mbarrier.arrive.shared::cta.b64 _, [%0];\n}" ::"r"(sfull + 8 * (rc & 3)) : "memory");
            rc++;
        };
        auto stg_free = [&]() { mwait(sempty + 8 * ((rc - 1) & 3), ((rc - 1) >> 2) & 1); };
        auto round_q = [&]() {
            if (npend > 4) {
                uint4* d = reinterpret_cast<uint4*>(g_part) + oofs;
                if (npend == 6) {
#pragma unroll
                    for (int i = 0; i < 4; i++) red_add8(d + (i >> 1) * 4 + (i & 1) * (8 * PG * DM / 8), qf[i][0], qf[i][1], qf[i][2], qf[i][3]);
                    npend = 5;
                } else {
#pragma unroll
                    for (int i = 4; i < 8; i++) red_add8(d + (i >> 1) * 4 + (i & 1) * (8 * PG * DM / 8), qf[i][0], qf[i][1], qf[i][2], qf[i][3]);
                    npend = 0;
                    handoff();
                }
                return;
            }
            const uint32_t sst = wst + (lane & 15) * 128 + (((lane >> 4) ^ (lane & 7)) << 4) + (npend & 1) * 2048;
#pragma unroll
            for (int q = 0; q < 4; q++)
                if (npend == 4 - q) {
#pragma unroll
                    for (int i = 0; i < 4; i++) stsm_x4(sst ^ (i << 5), qf[q * 4 + i][0], qf[q * 4 + i][1], qf[q * 4 + i][2], qf[q * 4 + i][3]);
                }
            __syncwarp();
            uint4* d = reinterpret_cast<uint4*>(&g_kv[0][0]) + oofs;
            const uint32_t src = wst + (lane >> 3) * 128 + (((lane & 7) ^ (lane >> 3)) << 4) + (npend & 1) * 2048;
#pragma unroll
            for (int i = 0; i < 4; i++) d[i * (4 * HD / 8)] = lds128((src + i * 512) ^ ((i & 1) << 6));
            oofs += 8;
            if (--npend == 0) handoff();
        };
        auto round_a = [&](const float* a, int hh) {
            uint4* d = reinterpret_cast<uint4*>(g_part) + oofs;
#pragma unroll
            for (int i = hh * 4; i < hh * 4 + 4; i++) {
                const float* b = a + (i >> 1) * 16 + (i & 1) * 2;
                red_add8(d + (i >> 1) * 4 + (i & 1) * (8 * PG * DM / 8), pack2(b[0], b[1]), pack2(b[4], b[5]), pack2(b[8], b[9]), pack2(b[12], b[13]));
            }
            if (hh) oofs += 16;
        };
        while (true) {
            tc++; TT(0); tc--;
            int code;
            while (true) {
                if (npend == 0) mwait(tfull0 + 8 * (tc & 3), (tc >> 2) & 1);
                if (npend == 0 || UNI(mtest(tfull0 + 8 * (tc & 3), (tc >> 2) & 1))) {
                    code = (int)UNI(lds32(task0 + 4 * (tc & 3)));
                    if (npend == 0 || ((code & 0x80) == 0 && !urgent && UNI(mtest(full0 + 8 * (it & 3), (it >> 2) & 1)))) break;
                }
                round_q();
            }
            if (lane == 0) mbar_arrive_cluster(mapa(tempty0 + 8 * (tc & 3), 0));
            tc++;
            TT(2);
            if (code < 0) break;
            const int type = (code >> 6) & 3;
            TTV(15, code);
#define BTC(type, k)
            if (type == T_CONV) {
                const int m = (code >> 9) & 1;
                BT((tid & 127) == 0, T_CONV, 0, m, 0);
                const int u = 2 * (code & 63) + rank, ch = cw * 4 + warp;
                int lane = tid & 31;
                asm volatile("" : "+r"(lane));
                const float Dv = bf2f(A.ssmD[u * 8 + ch]);
                const int sd = next(), s0 = next(), s1 = next(), s2 = next();
                TT(3);
                const uint32_t e1 = sb0 + s2 * BK_STAGE_BYTES;
                conv_unit(sb0 + s0 * BK_STAGE_BYTES + ch * 4096, sb0 + s1 * BK_STAGE_BYTES + ch * CV_EP, e1 + 64 + ch * CV_EP, e1 + 40960 + ch * 128, sb0 + BULK_STG + ch * 2, Dv, m, lane,
                          [&]() { release(sd); stg_free(); });
                asm volatile("fence.proxy.async.shared::cta;" ::: "memory");
                __syncwarp();
                handoff();
                TT(5);
                wgbar();
                release(s0); release(s1); release(s2);
                __syncwarp();
#pragma unroll
                for (int i = 0; i < 64; i++) qf[i >> 2][i & 3] = 0;
                continue;
            }
            float acc[128];
            {
                int s = next();
                TT(3); BTC(type, 0); BTC(type, 1);
                uint32_t sa = sb0 + s * BK_STAGE_BYTES + cw * 8192, sb = sb0 + s * BK_STAGE_BYTES + 16384;
                wg_fence();
                wgmma_m64n256k16_first(acc, make_desc(sa, 16, 1024), make_desc(sb, 8192, 1024));
#pragma unroll 1
                for (int kb = 0;;) {
#pragma unroll
                    for (int k = 1; k < 4; k++) wgmma_m64n256k16(acc, make_desc(sa + k * 32, 16, 1024), make_desc(sb + k * 2048, 8192, 1024));
                    wg_commit();
                    if (npend) round_q();
                    if (kb) { wg_wait<1>(); release((s - 1) & 3); }
                    if (++kb == 10) break;
                    s = next();
                    sa = sb0 + s * BK_STAGE_BYTES + cw * 8192; sb = sb0 + s * BK_STAGE_BYTES + 16384;
                    wg_fence();
                    wgmma_m64n256k16(acc, make_desc(sa, 16, 1024), make_desc(sb, 8192, 1024));
                }
            }
            wg_wait<0>();
            TT(4);
            release((it - 1) & 3);
            stg_free();
#pragma unroll
            for (int i = 0; i < 16; i++)
#pragma unroll
                for (int e = 0; e < 4; e++) qf[i][e] = pack2(acc[i * 8 + e * 2], acc[i * 8 + e * 2 + 1]);
            {
                const int cd = (int)lds32(task0 + 4 * ((tc - 1) & 3)), lc = (cd >> (rank ? 14 : 9)) & 31, jj = (cd & 256) ? (2 * cd + rank) & 63 : cd & 63;
                const int r0 = cw * 64 + warp * 16;
                if (type == T_KV) {
                    oofs = ((jj >> 4) * S_LEN + (lc & 15) * 128 + r0 + (lane >> 3)) * (HD / 8) + (jj & 15) * 32 + (lane & 7);
                    npend = 4;
                    urgent = URGENT && (lc < 2 || lc >= 16);
                    continue;
                }
                oofs = (((lc >> 4) * PRING + (lc & (PRING - 1))) * 128 + r0 + (lane >> 2)) * (PG * DM / 8) + (jj & (PG - 1)) * (DM / 8) + (lane & 3);
            }
            const float cs = 1.4426950408889634f;
            int lane = tid & 31;
            asm volatile("" : "+r"(lane));
            const int g = lane >> 2, tq = lane & 3;
            const int sg = cw * 2 + (warp >> 1), hs = warp & 1;
            float mt[2][2], sum[2][2];
            {
                const int x0 = next(), x1 = next();
                TT(5);
                float s[2][4][4];
#pragma unroll
                for (int hd = 0; hd < 2; hd++)
#pragma unroll
                    for (int n = 0; n < 4; n++)
#pragma unroll
                        for (int e = 0; e < 4; e++) s[hd][n][e] = 0.f;
                const uint32_t krow = (sg * 32 + (lane & 7) + (lane >> 4) * 8) * 128 + ((((lane >> 3) & 1) ^ (lane & 7)) << 4);
#pragma unroll
                for (int ii = 0; ii < 16; ii++) {
                    const int i = (ii >> 1) + (ii & 1) * 8;
                    const uint32_t kb = sb0 + (i < 12 ? x0 * BK_STAGE_BYTES + (i >> 2) * 16384 : x1 * BK_STAGE_BYTES) + (krow ^ ((i & 3) << 5));
                    const uint4 k0 = ldsm4(kb), k1 = ldsm4(kb + 2048);
                    mma16816(s[i >> 3][0], qf[i][0], qf[i][1], qf[i][2], qf[i][3], k0.x, k0.y);
                    mma16816(s[i >> 3][1], qf[i][0], qf[i][1], qf[i][2], qf[i][3], k0.z, k0.w);
                    mma16816(s[i >> 3][2], qf[i][0], qf[i][1], qf[i][2], qf[i][3], k1.x, k1.y);
                    mma16816(s[i >> 3][3], qf[i][0], qf[i][1], qf[i][2], qf[i][3], k1.z, k1.w);
                }
#pragma unroll
                for (int i = 0; i < 8; i++) sts128(wst + i * 512 + lane * 16, qf[8 + i][0], qf[8 + i][1], qf[8 + i][2], qf[8 + i][3]);
                wgbar();
                release(x0);
                TT(6);
                uint32_t pa[2][4][2];
#pragma unroll
                for (int hd = 0; hd < 2; hd++) {
                    uint32_t mx[2] = {0xff80ff80u, 0xff80ff80u};
#pragma unroll
                    for (int n = 0; n < 4; n++)
#pragma unroll
                        for (int r = 0; r < 2; r++) {
                            const int d = hs * 16 + g + r * 8 - n * 8 - tq * 2;
                            pa[hd][n][r] = rscore(d < 0 ? -INFINITY : s[hd][n][2 * r], d < 1 ? -INFINITY : s[hd][n][2 * r + 1]);
                            mx[r] = bmax2(mx[r], pa[hd][n][r]);
                        }
#pragma unroll
                    for (int r = 0; r < 2; r++) {
                        mx[r] = bmax2(mx[r], __shfl_xor_sync(0xffffffffu, mx[r], 1));
                        mx[r] = bmax2(mx[r], __shfl_xor_sync(0xffffffffu, mx[r], 2));
                        mt[hd][r] = fmaxf(blo(mx[r]), bhi(mx[r])) * cs;
                        sum[hd][r] = 0.f;
                    }
#pragma unroll
                    for (int n = 0; n < 4; n++)
#pragma unroll
                        for (int r = 0; r < 2; r++) {
                            const float p0 = ex2f(fmaf(blo(pa[hd][n][r]), cs, -mt[hd][r])), p1 = ex2f(fmaf(bhi(pa[hd][n][r]), cs, -mt[hd][r]));
                            sum[hd][r] += p0 + p1;
                            pa[hd][n][r] = pack2(p0, p1);
                        }
                }
                const uint32_t vrow = (sg * 32 + (lane & 15)) * 128 + (((lane >> 4) ^ (lane & 7)) << 4);
                int xv = x1;
#pragma unroll
                for (int hd = 0; hd < 2; hd++) {
                    if (hd == 1) xv = next();
#pragma unroll
                    for (int i = 0; i < 8; i++) {
                        const uint32_t vb = sb0 + xv * BK_STAGE_BYTES + (hd == 0 ? 16384 : 0) + (i >> 2) * 16384 + (vrow ^ ((i & 3) << 5));
                        uint4 v0, v1;
                        ldsm_x4_t(v0.x, v0.y, v0.z, v0.w, vb);
                        ldsm_x4_t(v1.x, v1.y, v1.z, v1.w, vb + 2048);
                        float* o = acc + hd * 64 + i * 8;
#pragma unroll
                        for (int e = 0; e < 8; e++) o[e] = 0.f;
                        mma16816(o, pa[hd][0][0], pa[hd][0][1], pa[hd][1][0], pa[hd][1][1], v0.x, v0.y);
                        mma16816(o + 4, pa[hd][0][0], pa[hd][0][1], pa[hd][1][0], pa[hd][1][1], v0.z, v0.w);
                        mma16816(o, pa[hd][2][0], pa[hd][2][1], pa[hd][3][0], pa[hd][3][1], v1.x, v1.y);
                        mma16816(o + 4, pa[hd][2][0], pa[hd][2][1], pa[hd][3][0], pa[hd][3][1], v1.z, v1.w);
                    }
                    wgbar();
                    release(xv);
                }
            }
            TT(7);
            BTC(T_ATT, 0);
            {
                const int xm = next();
                TT(8);
                BTC(T_ATT, 1);
                const uint32_t mb = sb0 + xm * BK_STAGE_BYTES + sg * 8192 + lane * 16;
                float sm[2][2][4];
#pragma unroll
                for (int i = 0; i < 16; i++) (&sm[0][0][0])[i] = 0.f;
#pragma unroll
                for (int q = 0; q < 4; q++) {
                    const uint4 k0 = lds128(mb + q * 512), k1 = lds128(mb + 4096 + q * 512);
                    const uint4 qa = lds128(wst + q * 1024 + lane * 16), qb = lds128(wst + q * 1024 + 512 + lane * 16);
                    mma16816(sm[0][0], qf[2 * q][0], qf[2 * q][1], qf[2 * q][2], qf[2 * q][3], k0.x, k0.y);
                    mma16816(sm[0][1], qf[2 * q + 1][0], qf[2 * q + 1][1], qf[2 * q + 1][2], qf[2 * q + 1][3], k0.z, k0.w);
                    mmau(sm[1][0], qa, k1.x, k1.y);
                    mmau(sm[1][1], qb, k1.z, k1.w);
                }
                float f[2][2];
                uint32_t pm[2][2];
#pragma unroll
                for (int hd = 0; hd < 2; hd++)
#pragma unroll
                    for (int r = 0; r < 2; r++) {
                        const uint32_t w = rscore(sm[hd][0][2 * r] + sm[hd][1][2 * r], sm[hd][0][2 * r + 1] + sm[hd][1][2 * r + 1]);
                        const float s0 = blo(w) * cs, s1 = bhi(w) * cs;
                        float m = fmaxf(s0, s1);
                        m = fmaxf(m, __shfl_xor_sync(0xffffffffu, m, 1));
                        m = fmaxf(fmaxf(m, __shfl_xor_sync(0xffffffffu, m, 2)), mt[hd][r]);
                        const float a = ex2f(mt[hd][r] - m), p0 = ex2f(s0 - m), p1 = ex2f(s1 - m);
                        float t = fmaf(sum[hd][r], a, p0 + p1);
                        t += __shfl_xor_sync(0xffffffffu, t, 1);
                        t += __shfl_xor_sync(0xffffffffu, t, 2);
                        t = rcpf(t);
                        f[hd][r] = a * t;
                        pm[hd][r] = pack2(p0 * t, p1 * t);
                    }
#pragma unroll
                for (int q = 0; q < 8; q++) {
                    const int hd = q >> 2;
                    const uint4 vm = lds128(mb + hd * 4096 + 2048 + (q & 3) * 512);
                    float* o = acc + q * 16;
#pragma unroll
                    for (int e = 0; e < 16; e++) o[e] *= f[hd][(e >> 1) & 1];
                    mma1688(o, pm[hd][0], pm[hd][1], vm.x);
                    mma1688(o + 4, pm[hd][0], pm[hd][1], vm.y);
                    mma1688(o + 8, pm[hd][0], pm[hd][1], vm.z);
                    mma1688(o + 12, pm[hd][0], pm[hd][1], vm.w);
#pragma unroll
                    for (int e = 0; e < 8; e++) qf[q * 2 + (e >> 2)][e & 3] = pack2(o[2 * e], o[2 * e + 1]);
                }
                wgbar();
                release(xm);
            }
            TT(9);
#pragma unroll
            for (int t = 0; t < 10; t++) {
                const int s = next();
                const uint32_t sb = sb0 + s * BK_STAGE_BYTES;
                float* d = acc + ((t >> 1) & 1) * 64;
                wg_fence();
#pragma unroll
                for (int k = 0; k < 8; k++) {
                    const uint64_t db = make_desc(sb + k * 2048, 16384, 1024);
                    if (k == 0 && !(t & 1)) wgmma_rs_m64n128k16_first(d, qf[k], db);
                    else wgmma_rs_m64n128k16(d, qf[(t & 1) * 8 + k], db);
                }
                wg_commit();
                if (t) {
                    wg_wait<1>();
                    release((s - 1) & 3);
                    if (t > 1) round_a(acc + (((t >> 1) & 1) ^ 1) * 64, t & 1);
                }
            }
            wg_wait<0>();
            release((it - 1) & 3);
            TT(10);
#pragma unroll
            for (int i = 0; i < 32; i++) qf[i >> 2][i & 3] = pack2(acc[(i >> 3) * 16 + (i & 4) / 2 + (i & 3) * 4], acc[(i >> 3) * 16 + (i & 4) / 2 + (i & 3) * 4 + 1]);
            npend = 6;
            urgent = URGENT > 1;
        }
    }
    cluster_sync_all();
}

__global__ void __launch_bounds__(256) reset_kernel(const bf16* x, int g0, int ncl) {
    const int lane = threadIdx.x & 31, row = blockIdx.x * 8 + (threadIdx.x >> 5);
    uint32_t r[10];
    ld5<128>(r, x + (size_t)row * DM + lane * 4);
    if (blockIdx.x == 0)
        for (int i = threadIdx.x; i < NFLAG * 2; i += blockDim.x) reinterpret_cast<uint4*>(FLG(i >> 1))[i & 1] = make_uint4(i == g0 ? min(ncl, 32) : (i == g0 + 2 ? max(ncl - 32, 0) : 0), 0, 0, 0);
    for (int i = blockIdx.x * 256 + threadIdx.x; i < 2 * PROWS * PG * DM / 8; i += S_LEN * 32) reinterpret_cast<uint4*>(g_part)[i] = make_uint4(0, 0, 0, 0);
    ln_row(r, r);
    st5(g_h[0] + (size_t)row * DM + lane * 4, r);
    if (blockIdx.x) return;
}

typedef CUresult (*PFN_encodeTiled)(CUtensorMap*, CUtensorMapDataType, cuuint32_t, void*, const cuuint64_t*, const cuuint64_t*,
                                    const cuuint32_t*, const cuuint32_t*, CUtensorMapInterleave, CUtensorMapSwizzle,
                                    CUtensorMapL2promotion, CUtensorMapFloatOOBfill);
static PFN_encodeTiled get_encode() {
    static PFN_encodeTiled fn = nullptr;
    if (!fn) {
        void* p = nullptr;
        cudaDriverEntryPointQueryResult qr;
        cudaGetDriverEntryPoint("cuTensorMapEncodeTiled", &p, cudaEnableDefault, &qr);
        fn = (PFN_encodeTiled)p;
    }
    return fn;
}
static void make_map(CUtensorMap* m, const void* ptr, uint64_t rows, uint64_t cols, uint32_t box_rows) {
    cuuint64_t dims[2] = {cols, rows};
    cuuint64_t strides[1] = {cols * 2};
    cuuint32_t box[2] = {64u, box_rows};
    cuuint32_t es[2] = {1, 1};
    get_encode()(m, CU_TENSOR_MAP_DATA_TYPE_BFLOAT16, 2, const_cast<void*>(ptr), dims, strides, box, es,
                 CU_TENSOR_MAP_INTERLEAVE_NONE, CU_TENSOR_MAP_SWIZZLE_128B, CU_TENSOR_MAP_L2_PROMOTION_L2_128B,
                 CU_TENSOR_MAP_FLOAT_OOB_FILL_NONE);
}
static void make_map3(CUtensorMap* m, const void* ptr) {
    cuuint64_t dims[3] = {64, DM, HD / 64};
    cuuint64_t strides[2] = {HD * 2, 128};
    cuuint32_t box[3] = {64u, 64u, 2u};
    cuuint32_t es[3] = {1, 1, 1};
    get_encode()(m, CU_TENSOR_MAP_DATA_TYPE_BFLOAT16, 3, const_cast<void*>(ptr), dims, strides, box, es,
                 CU_TENSOR_MAP_INTERLEAVE_NONE, CU_TENSOR_MAP_SWIZZLE_128B, CU_TENSOR_MAP_L2_PROMOTION_L2_128B,
                 CU_TENSOR_MAP_FLOAT_OOB_FILL_NONE);
}
#define QA_PRE0 4
#define KV1_E 1
#define KV1_L 16
#define KV0_X 6
#define CONV0_AT 1
#define CONV1_AT 9
static void build_sched(Sched& S, int naux) {
    int n = 0;
    auto ck = [](int f, int t) { return (uint32_t)(f * 32) | (uint32_t)t << 16; };
    auto add = [&](int lm, int type, int la, int ca, int lb, int cb, int ntask, uint32_t soft) {
        S.info[n] = (uint32_t)(type << 6 | lm << 8 | (la * 16 + ca) << 9 | (lb * 16 + cb) << 14);
        S.chk[n * 4] = ck(F_CNT + n, ntask); S.chk[n * 4 + 1] = soft;
        S.chk[n * 4 + 2] = ck(F_H + la * NCHK + ca, H_TGT); S.chk[n * 4 + 3] = ck(F_H + lb * NCHK + cb, H_TGT);
        n++;
    };
    for (int i = 0; i < MAXG * 4; i++) S.chk[i] = ck(F_ZERO, 0);
    for (int i = 0; i < MAXG; i++) S.info[i] = 0;
    S.sbeg[0] = n;
    for (int i = 0; i < NCHK; i++) {
        add(1, T_KV, 1, i, 1, i, 16, i < KV1_E || i >= KV1_L ? ck(F_OP + i, 14) + 4 : ck(F_H + NCHK + i, KV1_N));
        S.chk[n * 4 - 2] = S.chk[n * 4 - 1] = ck(F_CONV + i / 8, CONV_TGT);
    }
    S.sbeg[1] = n;
    auto addqa = [&]() {
    for (int p = 0; p < NCHK + PDIST; p++) {
        const bool h0 = p < NCHK, h1 = p >= PDIST;
        const int la = h0 ? 0 : 1, ca = h0 ? p : p - PDIST, lb = h1 ? 1 : 0, cb = h1 ? p - PDIST : p;
        const int ta = ca * CSEG + CSEG + la * LAG;
        add(!(h0 && h1), T_QA, la, ca, lb, cb, h0 && h1 ? 16 : 8,
            ck(F_PROG, h1 ? ta - QA_PRE : (ta > QA_PRE0 ? ta - QA_PRE0 : 0)));
        S.info[n - 1] |= 3u << 19;
        S.chk[n * 4 - 2] = h0 && ca >= PRING ? ck(F_H + NCHK + ca - PRING + 1, H_TGT) : ck(F_ZERO, 0);
        S.chk[n * 4 - 1] = !h1 ? ck(F_KV + ca, KV_TGT) : (cb >= PRING ? ck(F_OP + NCHK + cb - PRING, 128) + 5 : ck(F_ZERO, 0));
    }
    };
    auto addkv = [&]() {
    for (int i = 0; i < NCHK; i += 2) add(0, T_KV, 0, i, 0, i + 1, 32, ck(F_PROG, 4 * i > KV0_X + 1 ? 4 * i - KV0_X : 1)), S.chk[n * 4 - 2] = S.chk[n * 4 - 1] = ck(F_ZERO, 0);
    };
    addqa();
    S.sbeg[2] = n;
    for (int m = 0; m < 2; m++) {
        add(0, T_CONV, 0, m, 0, m, 40, ck(F_U + m, naux));
        S.chk[n * 4 - 2] = S.chk[n * 4 - 1] = ck(F_CNT + S.sbeg[2] + 2 + (m ? CONV1_AT : CONV0_AT) / 2, 32);
    }
    S.sbeg[3] = n;
    addkv();
    S.sbeg[4] = n;
}

static void launch_all(void* const* d_in, void* d_out) {
    const bf16* x = (const bf16*)d_in[0];
    const bf16* mem0 = (const bf16*)d_in[1];
    const bf16* Wq = (const bf16*)d_in[2];
    const bf16* Wk = (const bf16*)d_in[3];
    const bf16* Wv = (const bf16*)d_in[4];
    const bf16* Wo = (const bf16*)d_in[5];
    static bool inited = false;
    static int nsm = 132;
    static Sched SC;
    bf16 *p_h, *p_kv, *p_u;
    cudaGetSymbolAddress((void**)&p_h, g_h);
    cudaGetSymbolAddress((void**)&p_kv, g_kv);
    cudaGetSymbolAddress((void**)&p_u, g_U);
    if (!inited) {
        inited = true;
        cudaDeviceGetAttribute(&nsm, cudaDevAttrMultiProcessorCount, 0);
        cudaFuncSetAttribute(chain_kernel, cudaFuncAttributeMaxDynamicSharedMemorySize, (int)sizeof(ChainSmem));
        cudaFuncSetAttribute(chain_kernel, cudaFuncAttributeNonPortableClusterSizeAllowed, 1);
        cudaFuncSetAttribute(bulk_kernel, cudaFuncAttributeMaxDynamicSharedMemorySize, BULK_SMEM);
        build_sched(SC, 2 * ((nsm - 64) & ~1));
    }
    const size_t QS = (size_t)S_LEN * HD;
    BulkMaps M;
    make_map(&M.h, p_h, 2 * S_LEN, DM, 64);
    make_map(&M.h2, p_h, 2 * S_LEN, DM, 128);
    make_map3(&M.wq, Wq);
    make_map3(&M.wk, Wk);
    make_map3(&M.wv, Wv);
    make_map(&M.wo, Wo, HD, DM, 128);
    make_map(&M.kv, p_kv, 2 * S_LEN, HD, 128);
    make_map(&M.lu, p_u, DM * 32, 64, 256);
    BulkArgs BA;
    BA.x = x; BA.out = (bf16*)d_out;
    BA.Bk = (const bf16*)d_in[8]; BA.Bv = (const bf16*)d_in[9]; BA.shiftk = (const bf16*)d_in[10];
    BA.ssmk = (const bf16*)d_in[11]; BA.ssmD = (const bf16*)d_in[12];
    ChainArgs ca;
    for (int l = 0; l < 2; l++) {
        make_map(&ca.tk[l], p_kv, S_LEN, HD, 32);
        make_map(&ca.tv[l], p_kv + QS, S_LEN, HD, 32);
    }
    ca.x = x; ca.mem0 = mem0; ca.Wq = Wq; ca.Wk = Wk; ca.Wv = Wv; ca.Wo = Wo; ca.kv_target = KV_TGT;
    cudaStream_t s = cudaStreamPerThread;
    reset_kernel<<<S_LEN / 8, 256, 0, s>>>(x, 2 * (F_CNT + SC.sbeg[3]), (nsm - 64) / 2);
    {
        cudaLaunchConfig_t cfg = {};
        cfg.gridDim = dim3(64); cfg.blockDim = dim3(CHAIN_THREADS); cfg.dynamicSmemBytes = sizeof(ChainSmem); cfg.stream = s;
        cudaLaunchAttribute at[1];
        at[0].id = cudaLaunchAttributeClusterDimension;
        at[0].val.clusterDim.x = CL; at[0].val.clusterDim.y = 1; at[0].val.clusterDim.z = 1;
        cfg.attrs = at; cfg.numAttrs = 1;
        cudaLaunchKernelEx(&cfg, chain_kernel, ca);
    }
    {
        cudaLaunchConfig_t cfg = {};
        cfg.gridDim = dim3((nsm - 64) & ~1); cfg.blockDim = dim3(384); cfg.dynamicSmemBytes = BULK_SMEM; cfg.stream = s;
        cudaLaunchAttribute at[2];
        at[0].id = cudaLaunchAttributeProgrammaticStreamSerialization;
        at[0].val.programmaticStreamSerializationAllowed = 1;
        at[1].id = cudaLaunchAttributeClusterDimension;
        at[1].val.clusterDim.x = 2; at[1].val.clusterDim.y = 1; at[1].val.clusterDim.z = 1;
        cfg.attrs = at; cfg.numAttrs = 2;
        cudaLaunchKernelEx(&cfg, bulk_kernel, M, BA, SC);
    }
}
}

extern "C" void kernel_launch(void* const* d_in, const int* in_sizes, int n_in, void* d_out, int out_size) {
    (void)in_sizes; (void)n_in; (void)out_size;
    if (ws::usable()) ws::launch_all(d_in, d_out);
    else ni::launch_all(d_in, d_out);
}
```
